```python
import torch

def _softmax(x, axis=-1):
    return torch.softmax(x, dim=axis)
def _gelu(x):
    return torch.nn.functional.gelu(x, approximate="tanh")
def _silu(x):
    return torch.nn.functional.silu(x)
def _sigmoid(x):
    return torch.sigmoid(x)
def _layernorm(x, axis=-1, eps=1e-5):
    m = x.mean(dim=axis, keepdim=True)
    v = x.var(dim=axis, keepdim=True, unbiased=False)
    return (x - m) / torch.sqrt(v + eps)
def _scatter_add(tgt, idx, src, axis=0):
    return tgt.clone().index_add_(axis, idx, src)
def _segment_sum(src, seg, n):
    out = torch.zeros((n,) + src.shape[1:], dtype=src.dtype)
    return out.index_add_(0, seg, src)
def _pad(x, pw):
    flat = tuple(v for pair in reversed(pw) for v in pair)
    return torch.nn.functional.pad(x, flat)

kernel_name = 'interleave_layers__sliding_local_dilated__mixer_token_mlp__prompt'

def setup_inputs():

    _w = (lambda a: (lambda t: t.to(torch.bfloat16) if t.is_floating_point() else t)(torch.as_tensor(a)))
    def _A_setup():
        B, S, D = 1, 2048, 1024
        return {
            "x": _w((lambda *s: torch.randn(*s, dtype=torch.bfloat16) * 0.05)(B, S, D)),
            "wqkv": _w((lambda *s: torch.randn(*s, dtype=torch.bfloat16) * 0.05)(D, 3 * D)),
            "wo": _w((lambda *s: torch.randn(*s, dtype=torch.bfloat16) * 0.05)(D, D)),
        }
    _A_in = _A_setup()

    def _B_setup():
        B, S, D, F = 1, 2048, 1024, 3584
        return {
            "x": _w((lambda *s: torch.randn(*s, dtype=torch.bfloat16) * 0.05)(B, S, D)),
            "w1": _w((lambda *s: torch.randn(*s, dtype=torch.bfloat16) * 1.6)(S, F) * (S ** -0.5)),
            "b1": _w((lambda *s: torch.randn(*s, dtype=torch.bfloat16) * 1.6)(F) * 0.02),
            "w2": _w((lambda *s: torch.randn(*s, dtype=torch.bfloat16) * 1.6)(F, S) * (F ** -0.5)),
            "b2": _w((lambda *s: torch.randn(*s, dtype=torch.bfloat16) * 1.6)(S) * 0.02),
        }
    _B_in = _B_setup()

    return {
        "A_x": _A_in["x"],
        "A_wqkv": _A_in["wqkv"],
        "A_wo": _A_in["wo"],
        "B_x": _B_in["x"],
        "B_w1": _B_in["w1"],
        "B_b1": _B_in["b1"],
        "B_w2": _B_in["w2"],
        "B_b2": _B_in["b2"],
    }

def reference(A_x, A_wqkv, A_wo, B_x, B_w1, B_b1, B_w2, B_b2):
    def _A_ref(x, wqkv, wo):
        B, S, D = x.shape
        H = 32; Dh = D // H
        W, dil = 8, 2
        qkv = (lambda x, *d: x.permute(*d))((x @ wqkv).reshape(B, S, 3, H, Dh), 2, 0, 3, 1, 4)
        q, k, v = qkv[0], qkv[1], qkv[2]
        scale = Dh ** -0.5
        pos = torch.arange(S)
        off = torch.arange(W) * dil
        idx = pos[:, None] - off[None, :]
        mask = idx >= 0
        idx_c = torch.where(mask, idx, 0).reshape(-1)
        kg = k[:, :, idx_c, :].reshape(B, H, S, W, Dh)
        vg = v[:, :, idx_c, :].reshape(B, H, S, W, Dh)
        logits = torch.einsum("bhsd,bhswd->bhsw", q, kg) * scale
        logits = torch.where(mask[None, None, :, :], logits, -1e9)
        attn = _softmax(logits, axis=-1)
        o = torch.einsum("bhsw,bhswd->bhsd", attn, vg)
        return (lambda x, *d: x.permute(*d))(o, 0, 2, 1, 3).reshape(B, S, D) @ wo

    def _B_ref(x, w1, b1, w2, b2):
        B, S, D = x.shape
        h = _layernorm(x, axis=-1)
        u = torch.einsum("bsd,sf->bdf", h, w1) + b1
        u = _gelu(u)
        y = torch.einsum("bdf,fs->bds", u, w2) + b2
        return (lambda x, *d: x.permute(*d))(y, 0, 2, 1)

    x = A_x
    x = x + _A_ref(_layernorm(x, axis=-1), A_wqkv, A_wo)
    x = x + _B_ref(_layernorm(x, axis=-1), B_w1, B_b1, B_w2, B_b2)
    x = x + _A_ref(_layernorm(x, axis=-1), A_wqkv, A_wo)
    x = x + _B_ref(_layernorm(x, axis=-1), B_w1, B_b1, B_w2, B_b2)
    return x
```

```cpp
#include <cuda_runtime.h>
#include <cuda_bf16.h>
#include <cuda.h>
#include <stdint.h>

namespace {

typedef __nv_bfloat16 bf16;
constexpr int S_ = 2048, D_ = 1024, F_ = 3584;

constexpr uint32_t OFF_STG  = 163840;
constexpr uint32_t OFF_XCH  = OFF_STG + 16384;
constexpr uint32_t OFF_STAT = OFF_STG + 28672;
constexpr uint32_t OFF_X    = 196608;
constexpr uint32_t OFF_BAR  = 229376;
constexpr uint32_t OFF_CS   = OFF_BAR + 512;
constexpr uint32_t OFF_B1   = OFF_CS + 1536;
constexpr uint32_t SMEM_BYTES = OFF_B1 + 896;
constexpr int F1 = 0, E1 = 4, F2 = 8, E2 = 13, F3 = 18, E3 = 22, F4 = 26, E4 = 32;
constexpr int JOB = 38;
constexpr int RD = 48;
constexpr int XF = 54, STD = 55;
constexpr int NB_WG = 1  , NB_BOTH = 3, NB_ORDA = 4, NB_ORDB = 5, NB_P1 = 6, NB_P2 = 7;

__device__ __forceinline__ uint32_t slot1(int p) { return p * 40960; }
__device__ __forceinline__ uint32_t slot2(int p) { return p * 32768; }
__device__ __forceinline__ uint32_t slot3(int p) { return ((p + 2) & 3) * 49152; }
__device__ __forceinline__ uint32_t slot4(int p) { return (p < 2 ? p + 4 : p - 2) * 32768; }

__device__ __align__(1024) uint8_t gXB[16 * 16 * 16384];
__device__ __align__(1024) uint8_t gOB[16 * 16 * 16384];
__device__ __align__(1024) uint8_t gHB[8 * 32 * 16384];
__device__ __align__(1024) uint8_t gUB[8 * 56 * 16384];
__device__ __align__(1024) uint4   gST[4][16][8][128];
__device__ __align__(1024) uint4   gHalo[4][16][8][16][32];
__device__ __align__(1024) uint2   gCS[16][3072];
__device__ __align__(1024) unsigned long long gFlag[2][4][16][16];
__device__ uint32_t gEpoch;
#define TS(k)

struct Params {
  CUtensorMap x0, wqkv, wo, w1, w1h, w2, out;
  const bf16 *wqkv_p, *b1, *b2;
};

template <int TA, int TB> __device__ __forceinline__ void wgmma_128(float (&d)[64], uint64_t da, uint64_t db) {
  asm volatile("wgmma.mma_async.sync.aligned.m64n128k16.f32.bf16.bf16 {"
  "%0, %1, %2, %3, %4, %5, %6, %7, %8, %9, %10, %11, %12, %13, %14, %15, "
  "%16, %17, %18, %19, %20, %21, %22, %23, %24, %25, %26, %27, %28, %29, %30, %31, "
  "%32, %33, %34, %35, %36, %37, %38, %39, %40, %41, %42, %43, %44, %45, %46, %47, "
  "%48, %49, %50, %51, %52, %53, %54, %55, %56, %57, %58, %59, %60, %61, %62, %63"
  "}, %64, %65, 1, 1, 1, %66, %67;\n"
  : "+f"(d[0]), "+f"(d[1]), "+f"(d[2]), "+f"(d[3]), "+f"(d[4]), "+f"(d[5]), "+f"(d[6]), "+f"(d[7]),
    "+f"(d[8]), "+f"(d[9]), "+f"(d[10]), "+f"(d[11]), "+f"(d[12]), "+f"(d[13]), "+f"(d[14]), "+f"(d[15]),
    "+f"(d[16]), "+f"(d[17]), "+f"(d[18]), "+f"(d[19]), "+f"(d[20]), "+f"(d[21]), "+f"(d[22]), "+f"(d[23]),
    "+f"(d[24]), "+f"(d[25]), "+f"(d[26]), "+f"(d[27]), "+f"(d[28]), "+f"(d[29]), "+f"(d[30]), "+f"(d[31]),
    "+f"(d[32]), "+f"(d[33]), "+f"(d[34]), "+f"(d[35]), "+f"(d[36]), "+f"(d[37]), "+f"(d[38]), "+f"(d[39]),
    "+f"(d[40]), "+f"(d[41]), "+f"(d[42]), "+f"(d[43]), "+f"(d[44]), "+f"(d[45]), "+f"(d[46]), "+f"(d[47]),
    "+f"(d[48]), "+f"(d[49]), "+f"(d[50]), "+f"(d[51]), "+f"(d[52]), "+f"(d[53]), "+f"(d[54]), "+f"(d[55]),
    "+f"(d[56]), "+f"(d[57]), "+f"(d[58]), "+f"(d[59]), "+f"(d[60]), "+f"(d[61]), "+f"(d[62]), "+f"(d[63])
  : "l"(da), "l"(db), "n"(TA), "n"(TB));
}
template <int TA, int TB> __device__ __forceinline__ void wgmma_192(float (&d)[96], uint64_t da, uint64_t db) {
  asm volatile("wgmma.mma_async.sync.aligned.m64n192k16.f32.bf16.bf16 {"
  "%0, %1, %2, %3, %4, %5, %6, %7, %8, %9, %10, %11, %12, %13, %14, %15, "
  "%16, %17, %18, %19, %20, %21, %22, %23, %24, %25, %26, %27, %28, %29, %30, %31, "
  "%32, %33, %34, %35, %36, %37, %38, %39, %40, %41, %42, %43, %44, %45, %46, %47, "
  "%48, %49, %50, %51, %52, %53, %54, %55, %56, %57, %58, %59, %60, %61, %62, %63, "
  "%64, %65, %66, %67, %68, %69, %70, %71, %72, %73, %74, %75, %76, %77, %78, %79, "
  "%80, %81, %82, %83, %84, %85, %86, %87, %88, %89, %90, %91, %92, %93, %94, %95"
  "}, %96, %97, 1, 1, 1, %98, %99;\n"
  : "+f"(d[0]), "+f"(d[1]), "+f"(d[2]), "+f"(d[3]), "+f"(d[4]), "+f"(d[5]), "+f"(d[6]), "+f"(d[7]),
    "+f"(d[8]), "+f"(d[9]), "+f"(d[10]), "+f"(d[11]), "+f"(d[12]), "+f"(d[13]), "+f"(d[14]), "+f"(d[15]),
    "+f"(d[16]), "+f"(d[17]), "+f"(d[18]), "+f"(d[19]), "+f"(d[20]), "+f"(d[21]), "+f"(d[22]), "+f"(d[23]),
    "+f"(d[24]), "+f"(d[25]), "+f"(d[26]), "+f"(d[27]), "+f"(d[28]), "+f"(d[29]), "+f"(d[30]), "+f"(d[31]),
    "+f"(d[32]), "+f"(d[33]), "+f"(d[34]), "+f"(d[35]), "+f"(d[36]), "+f"(d[37]), "+f"(d[38]), "+f"(d[39]),
    "+f"(d[40]), "+f"(d[41]), "+f"(d[42]), "+f"(d[43]), "+f"(d[44]), "+f"(d[45]), "+f"(d[46]), "+f"(d[47]),
    "+f"(d[48]), "+f"(d[49]), "+f"(d[50]), "+f"(d[51]), "+f"(d[52]), "+f"(d[53]), "+f"(d[54]), "+f"(d[55]),
    "+f"(d[56]), "+f"(d[57]), "+f"(d[58]), "+f"(d[59]), "+f"(d[60]), "+f"(d[61]), "+f"(d[62]), "+f"(d[63]),
    "+f"(d[64]), "+f"(d[65]), "+f"(d[66]), "+f"(d[67]), "+f"(d[68]), "+f"(d[69]), "+f"(d[70]), "+f"(d[71]),
    "+f"(d[72]), "+f"(d[73]), "+f"(d[74]), "+f"(d[75]), "+f"(d[76]), "+f"(d[77]), "+f"(d[78]), "+f"(d[79]),
    "+f"(d[80]), "+f"(d[81]), "+f"(d[82]), "+f"(d[83]), "+f"(d[84]), "+f"(d[85]), "+f"(d[86]), "+f"(d[87]),
    "+f"(d[88]), "+f"(d[89]), "+f"(d[90]), "+f"(d[91]), "+f"(d[92]), "+f"(d[93]), "+f"(d[94]), "+f"(d[95])
  : "l"(da), "l"(db), "n"(TA), "n"(TB));
}
template <int TA, int TB> __device__ __forceinline__ void wgmma_192z(float (&d)[96], uint64_t da, uint64_t db) {
  asm volatile("wgmma.mma_async.sync.aligned.m64n192k16.f32.bf16.bf16 {"
  "%0, %1, %2, %3, %4, %5, %6, %7, %8, %9, %10, %11, %12, %13, %14, %15, "
  "%16, %17, %18, %19, %20, %21, %22, %23, %24, %25, %26, %27, %28, %29, %30, %31, "
  "%32, %33, %34, %35, %36, %37, %38, %39, %40, %41, %42, %43, %44, %45, %46, %47, "
  "%48, %49, %50, %51, %52, %53, %54, %55, %56, %57, %58, %59, %60, %61, %62, %63, "
  "%64, %65, %66, %67, %68, %69, %70, %71, %72, %73, %74, %75, %76, %77, %78, %79, "
  "%80, %81, %82, %83, %84, %85, %86, %87, %88, %89, %90, %91, %92, %93, %94, %95"
  "}, %96, %97, 0, 1, 1, %98, %99;\n"
  : "=f"(d[0]), "=f"(d[1]), "=f"(d[2]), "=f"(d[3]), "=f"(d[4]), "=f"(d[5]), "=f"(d[6]), "=f"(d[7]),
    "=f"(d[8]), "=f"(d[9]), "=f"(d[10]), "=f"(d[11]), "=f"(d[12]), "=f"(d[13]), "=f"(d[14]), "=f"(d[15]),
    "=f"(d[16]), "=f"(d[17]), "=f"(d[18]), "=f"(d[19]), "=f"(d[20]), "=f"(d[21]), "=f"(d[22]), "=f"(d[23]),
    "=f"(d[24]), "=f"(d[25]), "=f"(d[26]), "=f"(d[27]), "=f"(d[28]), "=f"(d[29]), "=f"(d[30]), "=f"(d[31]),
    "=f"(d[32]), "=f"(d[33]), "=f"(d[34]), "=f"(d[35]), "=f"(d[36]), "=f"(d[37]), "=f"(d[38]), "=f"(d[39]),
    "=f"(d[40]), "=f"(d[41]), "=f"(d[42]), "=f"(d[43]), "=f"(d[44]), "=f"(d[45]), "=f"(d[46]), "=f"(d[47]),
    "=f"(d[48]), "=f"(d[49]), "=f"(d[50]), "=f"(d[51]), "=f"(d[52]), "=f"(d[53]), "=f"(d[54]), "=f"(d[55]),
    "=f"(d[56]), "=f"(d[57]), "=f"(d[58]), "=f"(d[59]), "=f"(d[60]), "=f"(d[61]), "=f"(d[62]), "=f"(d[63]),
    "=f"(d[64]), "=f"(d[65]), "=f"(d[66]), "=f"(d[67]), "=f"(d[68]), "=f"(d[69]), "=f"(d[70]), "=f"(d[71]),
    "=f"(d[72]), "=f"(d[73]), "=f"(d[74]), "=f"(d[75]), "=f"(d[76]), "=f"(d[77]), "=f"(d[78]), "=f"(d[79]),
    "=f"(d[80]), "=f"(d[81]), "=f"(d[82]), "=f"(d[83]), "=f"(d[84]), "=f"(d[85]), "=f"(d[86]), "=f"(d[87]),
    "=f"(d[88]), "=f"(d[89]), "=f"(d[90]), "=f"(d[91]), "=f"(d[92]), "=f"(d[93]), "=f"(d[94]), "=f"(d[95])
  : "l"(da), "l"(db), "n"(TA), "n"(TB));
}
template <int TA, int TB> __device__ __forceinline__ void wgmma_224(float (&d)[112], uint64_t da, uint64_t db) {
  asm volatile("wgmma.mma_async.sync.aligned.m64n224k16.f32.bf16.bf16 {"
  "%0, %1, %2, %3, %4, %5, %6, %7, %8, %9, %10, %11, %12, %13, %14, %15, "
  "%16, %17, %18, %19, %20, %21, %22, %23, %24, %25, %26, %27, %28, %29, %30, %31, "
  "%32, %33, %34, %35, %36, %37, %38, %39, %40, %41, %42, %43, %44, %45, %46, %47, "
  "%48, %49, %50, %51, %52, %53, %54, %55, %56, %57, %58, %59, %60, %61, %62, %63, "
  "%64, %65, %66, %67, %68, %69, %70, %71, %72, %73, %74, %75, %76, %77, %78, %79, "
  "%80, %81, %82, %83, %84, %85, %86, %87, %88, %89, %90, %91, %92, %93, %94, %95, "
  "%96, %97, %98, %99, %100, %101, %102, %103, %104, %105, %106, %107, %108, %109, %110, %111"
  "}, %112, %113, 1, 1, 1, %114, %115;\n"
  : "+f"(d[0]), "+f"(d[1]), "+f"(d[2]), "+f"(d[3]), "+f"(d[4]), "+f"(d[5]), "+f"(d[6]), "+f"(d[7]),
    "+f"(d[8]), "+f"(d[9]), "+f"(d[10]), "+f"(d[11]), "+f"(d[12]), "+f"(d[13]), "+f"(d[14]), "+f"(d[15]),
    "+f"(d[16]), "+f"(d[17]), "+f"(d[18]), "+f"(d[19]), "+f"(d[20]), "+f"(d[21]), "+f"(d[22]), "+f"(d[23]),
    "+f"(d[24]), "+f"(d[25]), "+f"(d[26]), "+f"(d[27]), "+f"(d[28]), "+f"(d[29]), "+f"(d[30]), "+f"(d[31]),
    "+f"(d[32]), "+f"(d[33]), "+f"(d[34]), "+f"(d[35]), "+f"(d[36]), "+f"(d[37]), "+f"(d[38]), "+f"(d[39]),
    "+f"(d[40]), "+f"(d[41]), "+f"(d[42]), "+f"(d[43]), "+f"(d[44]), "+f"(d[45]), "+f"(d[46]), "+f"(d[47]),
    "+f"(d[48]), "+f"(d[49]), "+f"(d[50]), "+f"(d[51]), "+f"(d[52]), "+f"(d[53]), "+f"(d[54]), "+f"(d[55]),
    "+f"(d[56]), "+f"(d[57]), "+f"(d[58]), "+f"(d[59]), "+f"(d[60]), "+f"(d[61]), "+f"(d[62]), "+f"(d[63]),
    "+f"(d[64]), "+f"(d[65]), "+f"(d[66]), "+f"(d[67]), "+f"(d[68]), "+f"(d[69]), "+f"(d[70]), "+f"(d[71]),
    "+f"(d[72]), "+f"(d[73]), "+f"(d[74]), "+f"(d[75]), "+f"(d[76]), "+f"(d[77]), "+f"(d[78]), "+f"(d[79]),
    "+f"(d[80]), "+f"(d[81]), "+f"(d[82]), "+f"(d[83]), "+f"(d[84]), "+f"(d[85]), "+f"(d[86]), "+f"(d[87]),
    "+f"(d[88]), "+f"(d[89]), "+f"(d[90]), "+f"(d[91]), "+f"(d[92]), "+f"(d[93]), "+f"(d[94]), "+f"(d[95]),
    "+f"(d[96]), "+f"(d[97]), "+f"(d[98]), "+f"(d[99]), "+f"(d[100]), "+f"(d[101]), "+f"(d[102]), "+f"(d[103]),
    "+f"(d[104]), "+f"(d[105]), "+f"(d[106]), "+f"(d[107]), "+f"(d[108]), "+f"(d[109]), "+f"(d[110]), "+f"(d[111])
  : "l"(da), "l"(db), "n"(TA), "n"(TB));
}
template <int TA, int TB> __device__ __forceinline__ void wgmma_224z(float (&d)[112], uint64_t da, uint64_t db) {
  asm volatile("wgmma.mma_async.sync.aligned.m64n224k16.f32.bf16.bf16 {"
  "%0, %1, %2, %3, %4, %5, %6, %7, %8, %9, %10, %11, %12, %13, %14, %15, "
  "%16, %17, %18, %19, %20, %21, %22, %23, %24, %25, %26, %27, %28, %29, %30, %31, "
  "%32, %33, %34, %35, %36, %37, %38, %39, %40, %41, %42, %43, %44, %45, %46, %47, "
  "%48, %49, %50, %51, %52, %53, %54, %55, %56, %57, %58, %59, %60, %61, %62, %63, "
  "%64, %65, %66, %67, %68, %69, %70, %71, %72, %73, %74, %75, %76, %77, %78, %79, "
  "%80, %81, %82, %83, %84, %85, %86, %87, %88, %89, %90, %91, %92, %93, %94, %95, "
  "%96, %97, %98, %99, %100, %101, %102, %103, %104, %105, %106, %107, %108, %109, %110, %111"
  "}, %112, %113, 0, 1, 1, %114, %115;\n"
  : "=f"(d[0]), "=f"(d[1]), "=f"(d[2]), "=f"(d[3]), "=f"(d[4]), "=f"(d[5]), "=f"(d[6]), "=f"(d[7]),
    "=f"(d[8]), "=f"(d[9]), "=f"(d[10]), "=f"(d[11]), "=f"(d[12]), "=f"(d[13]), "=f"(d[14]), "=f"(d[15]),
    "=f"(d[16]), "=f"(d[17]), "=f"(d[18]), "=f"(d[19]), "=f"(d[20]), "=f"(d[21]), "=f"(d[22]), "=f"(d[23]),
    "=f"(d[24]), "=f"(d[25]), "=f"(d[26]), "=f"(d[27]), "=f"(d[28]), "=f"(d[29]), "=f"(d[30]), "=f"(d[31]),
    "=f"(d[32]), "=f"(d[33]), "=f"(d[34]), "=f"(d[35]), "=f"(d[36]), "=f"(d[37]), "=f"(d[38]), "=f"(d[39]),
    "=f"(d[40]), "=f"(d[41]), "=f"(d[42]), "=f"(d[43]), "=f"(d[44]), "=f"(d[45]), "=f"(d[46]), "=f"(d[47]),
    "=f"(d[48]), "=f"(d[49]), "=f"(d[50]), "=f"(d[51]), "=f"(d[52]), "=f"(d[53]), "=f"(d[54]), "=f"(d[55]),
    "=f"(d[56]), "=f"(d[57]), "=f"(d[58]), "=f"(d[59]), "=f"(d[60]), "=f"(d[61]), "=f"(d[62]), "=f"(d[63]),
    "=f"(d[64]), "=f"(d[65]), "=f"(d[66]), "=f"(d[67]), "=f"(d[68]), "=f"(d[69]), "=f"(d[70]), "=f"(d[71]),
    "=f"(d[72]), "=f"(d[73]), "=f"(d[74]), "=f"(d[75]), "=f"(d[76]), "=f"(d[77]), "=f"(d[78]), "=f"(d[79]),
    "=f"(d[80]), "=f"(d[81]), "=f"(d[82]), "=f"(d[83]), "=f"(d[84]), "=f"(d[85]), "=f"(d[86]), "=f"(d[87]),
    "=f"(d[88]), "=f"(d[89]), "=f"(d[90]), "=f"(d[91]), "=f"(d[92]), "=f"(d[93]), "=f"(d[94]), "=f"(d[95]),
    "=f"(d[96]), "=f"(d[97]), "=f"(d[98]), "=f"(d[99]), "=f"(d[100]), "=f"(d[101]), "=f"(d[102]), "=f"(d[103]),
    "=f"(d[104]), "=f"(d[105]), "=f"(d[106]), "=f"(d[107]), "=f"(d[108]), "=f"(d[109]), "=f"(d[110]), "=f"(d[111])
  : "l"(da), "l"(db), "n"(TA), "n"(TB));
}

__device__ __forceinline__ uint32_t smem_u32(const void* p) { return (uint32_t)__cvta_generic_to_shared(p); }
__device__ __forceinline__ void mbar_init(uint32_t bar, uint32_t cnt) { asm volatile("mbarrier.init.shared::cta.b64 [%0], %1;" ::"r"(bar), "r"(cnt) : "memory"); }
__device__ __forceinline__ void mbar_expect(uint32_t bar, uint32_t bytes) { asm volatile("mbarrier.arrive.expect_tx.shared::cta.b64 _, [%0], %1;" ::"r"(bar), "r"(bytes) : "memory"); }
__device__ __forceinline__ void mbar_arrive(uint32_t bar) { asm volatile("mbarrier.arrive.shared::cta.b64 _, [%0];" ::"r"(bar) : "memory"); }
__device__ __forceinline__ void mbar_arrive_cl(uint32_t cbar) { asm volatile("mbarrier.arrive.shared::cluster.b64 _, [%0];" ::"r"(cbar) : "memory"); }
__device__ __forceinline__ uint32_t mapa(uint32_t a, uint32_t cta) { uint32_t r; asm("mapa.shared::cluster.u32 %0, %1, %2;" : "=r"(r) : "r"(a), "r"(cta)); return r; }
__device__ __forceinline__ void mbar_wait(uint32_t bar, uint32_t parity) {
  asm volatile("{\n.reg .pred p;\n.reg .u32 n;\nmov.u32 n, 0;\n"
    "LAB_WAIT:\n"
    "mbarrier.try_wait.parity.shared::cta.b64 p, [%0], %1;\n"
    "@p bra LAB_DONE;\n"
    "add.u32 n, n, 1;\n"
    "setp.lt.u32 p, n, 2000000;\n"
    "@p bra LAB_WAIT;\n"
    "trap;\n"
    "LAB_DONE:\n}\n" ::"r"(bar), "r"(parity) : "memory");
}
constexpr uint32_t SPIN_MAX = 2000000;
__device__ __forceinline__ void tma2d(uint32_t dst, const CUtensorMap* m, uint32_t bar, int c0, int c1) {
  asm volatile("cp.async.bulk.tensor.2d.shared::cluster.global.mbarrier::complete_tx::bytes [%0], [%1, {%3, %4}], [%2];"
    ::"r"(dst), "l"(m), "r"(bar), "r"(c0), "r"(c1) : "memory");
}
__device__ __forceinline__ void tma2d_mc(uint32_t dst, const CUtensorMap* m, uint32_t bar, int c0, int c1) {
  asm volatile("cp.async.bulk.tensor.2d.shared::cluster.global.mbarrier::complete_tx::bytes.multicast::cluster [%0], [%1, {%3, %4}], [%2], %5;"
    ::"r"(dst), "l"(m), "r"(bar), "r"(c0), "r"(c1), "h"((uint16_t)3) : "memory");
}
__device__ __forceinline__ void tma3d(uint32_t dst, const CUtensorMap* m, uint32_t bar, int c0, int c1, int c2) {
  asm volatile("cp.async.bulk.tensor.3d.shared::cluster.global.mbarrier::complete_tx::bytes [%0], [%1, {%3, %4, %5}], [%2];"
    ::"r"(dst), "l"(m), "r"(bar), "r"(c0), "r"(c1), "r"(c2) : "memory");
}
__device__ __forceinline__ void tma3d_mc(uint32_t dst, const CUtensorMap* m, uint32_t bar, int c0, int c1, int c2) {
  asm volatile("cp.async.bulk.tensor.3d.shared::cluster.global.mbarrier::complete_tx::bytes.multicast::cluster [%0], [%1, {%3, %4, %5}], [%2], %6;"
    ::"r"(dst), "l"(m), "r"(bar), "r"(c0), "r"(c1), "r"(c2), "h"((uint16_t)3) : "memory");
}
__device__ __forceinline__ void tma2d_store(const CUtensorMap* m, uint32_t src, int c0, int c1) {
  asm volatile("cp.async.bulk.tensor.2d.global.shared::cta.bulk_group [%0, {%2, %3}], [%1];" ::"l"(m), "r"(src), "r"(c0), "r"(c1) : "memory");
}
__device__ __forceinline__ void bulk_ld(uint32_t dst, const void* src, uint32_t bytes, uint32_t bar) {
  asm volatile("cp.async.bulk.shared::cluster.global.mbarrier::complete_tx::bytes [%0], [%1], %2, [%3];" ::"r"(dst), "l"(src), "r"(bytes), "r"(bar) : "memory");
}
__device__ __forceinline__ void bulk_ld_mc(uint32_t dst, const void* src, uint32_t bytes, uint32_t bar) {
  asm volatile("cp.async.bulk.shared::cluster.global.mbarrier::complete_tx::bytes.multicast::cluster [%0], [%1], %2, [%3], %4;"
    ::"r"(dst), "l"(src), "r"(bytes), "r"(bar), "h"((uint16_t)3) : "memory");
}
__device__ __forceinline__ void bulk_st(void* dst, uint32_t src, uint32_t bytes) {
  asm volatile("cp.async.bulk.global.shared::cta.bulk_group [%0], [%1], %2;" ::"l"(dst), "r"(src), "r"(bytes) : "memory");
}
__device__ __forceinline__ void bulk_s2s(uint32_t cdst, uint32_t src, uint32_t bytes, uint32_t cbar) {
  asm volatile("cp.async.bulk.shared::cluster.shared::cta.mbarrier::complete_tx::bytes [%0], [%1], %2, [%3];" ::"r"(cdst), "r"(src), "r"(bytes), "r"(cbar) : "memory");
}
__device__ __forceinline__ void bulk_commit() { asm volatile("cp.async.bulk.commit_group;" ::: "memory"); }
__device__ __forceinline__ void bulk_wait0() { asm volatile("cp.async.bulk.wait_group 0;" ::: "memory"); }
__device__ __forceinline__ void fence_async_smem() { asm volatile("fence.proxy.async.shared::cta;" ::: "memory"); }
__device__ __forceinline__ void wg_fence() { asm volatile("wgmma.fence.sync.aligned;" ::: "memory"); }
__device__ __forceinline__ void wg_commit() { asm volatile("wgmma.commit_group.sync.aligned;" ::: "memory"); }
template <int N> __device__ __forceinline__ void wg_wait() { asm volatile("wgmma.wait_group.sync.aligned %0;" ::"n"(N) : "memory"); }
template <int R> __device__ __forceinline__ void reg_alloc() { asm volatile("setmaxnreg.inc.sync.aligned.u32 %0;" ::"n"(R)); }
template <int R> __device__ __forceinline__ void reg_dealloc() { asm volatile("setmaxnreg.dec.sync.aligned.u32 %0;" ::"n"(R)); }
__device__ __forceinline__ void cluster_sync() { asm volatile("barrier.cluster.arrive.release;\nbarrier.cluster.wait.acquire;" ::: "memory"); }
template <int ID> __device__ __forceinline__ void nb_sync(int n) { asm volatile("barrier.sync %0, %1;" ::"n"(ID), "r"(n) : "memory"); }
template <int ID> __device__ __forceinline__ void nb_arrive(int n) { asm volatile("barrier.arrive %0, %1;" ::"n"(ID), "r"(n) : "memory"); }
__device__ __forceinline__ int fresh_tid() { int t; asm volatile("mov.u32 %0, %%tid.x;" : "=r"(t)); return t; }
struct True { static constexpr bool value = true; };
struct False { static constexpr bool value = false; };
template <int N> __device__ __forceinline__ void fence_regs(float (&d)[N]) {
#pragma unroll
  for (int i = 0; i < N; i++) asm volatile("" : "+f"(d[i])::"memory");
}
__device__ __forceinline__ uint64_t mkdesc(uint32_t addr, uint32_t lbo, uint32_t sbo) {
  return (uint64_t)((addr & 0x3FFFF) >> 4) | ((uint64_t)(lbo >> 4) << 16) | ((uint64_t)(sbo >> 4) << 32) | (1ull << 62);
}
__device__ __forceinline__ uint32_t pack2(float lo, float hi) { uint32_t r; asm("cvt.rn.bf16x2.f32 %0, %1, %2;" : "=r"(r) : "f"(hi), "f"(lo)); return r; }
__device__ __forceinline__ float bf_lo(uint32_t v) { return __uint_as_float(v << 16); }
__device__ __forceinline__ float bf_hi(uint32_t v) { return __uint_as_float(v & 0xffff0000u); }
__device__ __forceinline__ void stsm4(uint32_t a, uint32_t r0, uint32_t r1, uint32_t r2, uint32_t r3) {
  asm volatile("stmatrix.sync.aligned.m8n8.x4.shared.b16 [%0], {%1, %2, %3, %4};" ::"r"(a), "r"(r0), "r"(r1), "r"(r2), "r"(r3) : "memory");
}
__device__ __forceinline__ void stsm4t(uint32_t a, uint32_t r0, uint32_t r1, uint32_t r2, uint32_t r3) {
  asm volatile("stmatrix.sync.aligned.m8n8.x4.trans.shared.b16 [%0], {%1, %2, %3, %4};" ::"r"(a), "r"(r0), "r"(r1), "r"(r2), "r"(r3) : "memory");
}
__device__ __forceinline__ void ldsm4(uint32_t a, uint32_t& r0, uint32_t& r1, uint32_t& r2, uint32_t& r3) {
  asm volatile("ldmatrix.sync.aligned.m8n8.x4.shared.b16 {%0, %1, %2, %3}, [%4];" : "=r"(r0), "=r"(r1), "=r"(r2), "=r"(r3) : "r"(a) : "memory");
}
__device__ __forceinline__ uint32_t movm(uint32_t a) { uint32_t d; asm volatile("movmatrix.sync.aligned.m8n8.trans.b16 %0, %1;" : "=r"(d) : "r"(a)); return d; }
__device__ __forceinline__ void mma16816(float (&c)[4], uint32_t a0, uint32_t a1, uint32_t a2, uint32_t a3, uint32_t b0, uint32_t b1) {
  asm volatile("mma.sync.aligned.m16n8k16.row.col.f32.bf16.bf16.f32 {%0, %1, %2, %3}, {%4, %5, %6, %7}, {%8, %9}, {%0, %1, %2, %3};"
    : "+f"(c[0]), "+f"(c[1]), "+f"(c[2]), "+f"(c[3]) : "r"(a0), "r"(a1), "r"(a2), "r"(a3), "r"(b0), "r"(b1));
}
__device__ __forceinline__ void sts128(uint32_t a, uint32_t r0, uint32_t r1, uint32_t r2, uint32_t r3) {
  asm volatile("st.shared.v4.b32 [%0], {%1, %2, %3, %4};" ::"r"(a), "r"(r0), "r"(r1), "r"(r2), "r"(r3) : "memory");
}
__device__ __forceinline__ void lds128(uint32_t a, uint32_t& r0, uint32_t& r1, uint32_t& r2, uint32_t& r3) {
  asm volatile("ld.shared.v4.b32 {%0, %1, %2, %3}, [%4];" : "=r"(r0), "=r"(r1), "=r"(r2), "=r"(r3) : "r"(a) : "memory");
}
__device__ __forceinline__ float2 lds64f(uint32_t a) { float2 v; asm volatile("ld.shared.v2.f32 {%0, %1}, [%2];" : "=f"(v.x), "=f"(v.y) : "r"(a) : "memory"); return v; }
__device__ __forceinline__ void sts64f(uint32_t a, float x, float y) { asm volatile("st.shared.v2.f32 [%0], {%1, %2};" ::"r"(a), "f"(x), "f"(y) : "memory"); }
__device__ __forceinline__ float lds32f(uint32_t a) { float v; asm volatile("ld.shared.f32 %0, [%1];" : "=f"(v) : "r"(a) : "memory"); return v; }
__device__ __forceinline__ void sts32f(uint32_t a, float x) { asm volatile("st.shared.f32 [%0], %1;" ::"r"(a), "f"(x) : "memory"); }
__device__ __forceinline__ void ll_st2(uint4* p, uint32_t a, uint32_t b, uint32_t tag) {
  asm volatile("{\n.reg .b64 x, y;\nmov.b64 x, {%1, %3};\nmov.b64 y, {%2, %3};\nst.relaxed.gpu.global.v2.b64 [%0], {x, y};\n}\n" ::"l"(p), "r"(a), "r"(b), "r"(tag) : "memory");
}
__device__ __forceinline__ uint32_t ll_ld2(const uint4* p, uint32_t& a, uint32_t& b, uint32_t tag) {
  uint32_t t0, t1;
  asm volatile("{\n.reg .b64 x, y;\nld.relaxed.gpu.global.v2.b64 {x, y}, [%4];\nmov.b64 {%0, %1}, x;\nmov.b64 {%2, %3}, y;\n}\n" : "=r"(a), "=r"(t0), "=r"(b), "=r"(t1) : "l"(p) : "memory");
  return (t0 ^ tag) | (t1 ^ tag);
}
__device__ __forceinline__ void ll_st1(uint2* p, uint32_t a, uint32_t tag) {
  asm volatile("{\n.reg .b64 x;\nmov.b64 x, {%1, %2};\nst.relaxed.gpu.global.b64 [%0], x;\n}\n" ::"l"(p), "r"(a), "r"(tag) : "memory");
}
__device__ __forceinline__ uint32_t ll_ld1(const uint2* p, uint32_t& a, uint32_t tag) {
  uint32_t t0;
  asm volatile("{\n.reg .b64 x;\nld.relaxed.gpu.global.b64 x, [%2];\nmov.b64 {%0, %1}, x;\n}\n" : "=r"(a), "=r"(t0) : "l"(p) : "memory");
  return t0 ^ tag;
}
typedef unsigned long long u64;
__device__ __forceinline__ void flag_set(u64* p, u64 bit) { asm volatile("red.release.gpu.global.xor.b64 [%0], %1;" ::"l"(p), "l"(bit) : "memory"); }
__device__ __forceinline__ void flag_wait(const u64* p, u64 inv, u64 need, u64& ready) {
  if ((ready & need) == need) return;
  uint32_t n = 0;
  do {
    asm volatile("ld.acquire.gpu.global.b64 %0, [%1];" : "=l"(ready) : "l"(p) : "memory");
    ready ^= inv;
  } while ((ready & need) != need && ++n < SPIN_MAX);
  asm volatile("fence.proxy.async.global;" ::: "memory");
}
__device__ __forceinline__ bool elect_one() {
  uint32_t p;
  asm volatile("{\n.reg .pred P;\nelect.sync _|P, 0xffffffff;\nselp.u32 %0, 1, 0, P;\n}\n" : "=r"(p));
  return p;
}
__device__ __forceinline__ float gelu_tanh(float x) {
  float t = x * x;
  float p = fmaf(t, 0.0356774081f, 0.7978845608f);
  float y = x * p, th;
  asm("tanh.approx.f32 %0, %1;" : "=f"(th) : "f"(y));
  float hx = 0.5f * x;
  return fmaf(hx, th, hx);
}
__device__ __forceinline__ float ex2(float x) { float y; asm("ex2.approx.ftz.f32 %0, %1;" : "=f"(y) : "f"(x)); return y; }

__device__ __forceinline__ void stats_exchange(uint4 (*buf)[128], int j, int row, float sum, float sq, uint32_t tag, float& mean, float& var) {
  ll_st2(&buf[j][row], __float_as_uint(sum), __float_as_uint(sq), tag);
  uint32_t a[8], b[8], n = 0, bad;
  do {
    bad = 0;
#pragma unroll
    for (int k = 0; k < 8; k++) bad |= ll_ld2(&buf[k][row], a[k], b[k], tag);
  } while (bad && ++n < SPIN_MAX);
  float s = 0.f, q = 0.f;
#pragma unroll
  for (int k = 0; k < 8; k++) { s += __uint_as_float(a[k]); q += __uint_as_float(b[k]); }
  mean = s * (1.f / D_);
  var = fmaxf(fmaf(-mean, mean, q * (1.f / D_)), 0.f);
}

__device__ __forceinline__ void attn_probs(const uint32_t* q0, const uint32_t* q1,
                                           const uint32_t* k0, const uint32_t* k1, const uint32_t* k2, const uint32_t* k3,
                                           float sc0, float sc1, bool first, bool e, bool zneg, uint32_t (&pr)[6]) {
  float s[4][4];
#pragma unroll
  for (int n = 0; n < 4; n++) {
    const uint32_t* k = n == 0 ? k0 : n == 1 ? k1 : n == 2 ? k2 : k3;
    s[n][0] = s[n][1] = s[n][2] = s[n][3] = 0.f;
    mma16816(s[n], q0[0], q1[0], q0[1], q1[1], k[0], k[1]);
    mma16816(s[n], q0[2], q1[2], q0[3], q1[3], k[2], k[3]);
  }
  const float MASKED = -1.0e9f * 1.4426950409f;
  float a0 = (e ? s[1][1] : s[1][0]) * sc0;
  float b0 = (zneg ? (e ? s[0][1] : s[0][0]) : (e ? s[2][1] : s[2][0])) * sc0;
  float a1 = (e ? s[2][3] : s[2][2]) * sc1;
  float b1 = (zneg ? (e ? s[1][3] : s[1][2]) : (e ? s[3][3] : s[3][2])) * sc1;
  if (first) { a0 = MASKED; if (zneg) { b0 = MASKED; b1 = MASKED; } }
  float m0 = fmaxf(a0, b0), m1 = fmaxf(a1, b1);
  m0 = fmaxf(m0, __shfl_xor_sync(0xffffffffu, m0, 1)); m1 = fmaxf(m1, __shfl_xor_sync(0xffffffffu, m1, 1));
  m0 = fmaxf(m0, __shfl_xor_sync(0xffffffffu, m0, 2)); m1 = fmaxf(m1, __shfl_xor_sync(0xffffffffu, m1, 2));
  a0 = ex2(a0 - m0); b0 = ex2(b0 - m0); a1 = ex2(a1 - m1); b1 = ex2(b1 - m1);
  float l0 = a0 + b0, l1 = a1 + b1;
  l0 += __shfl_xor_sync(0xffffffffu, l0, 1); l1 += __shfl_xor_sync(0xffffffffu, l1, 1);
  l0 += __shfl_xor_sync(0xffffffffu, l0, 2); l1 += __shfl_xor_sync(0xffffffffu, l1, 2);
  l0 = __fdividef(1.f, l0); l1 = __fdividef(1.f, l1);
  const int sh = e ? 16 : 0;
  uint32_t pa0 = pack2(a0 * l0, 0.f) << sh, pb0 = pack2(b0 * l0, 0.f) << sh;
  uint32_t pa1 = pack2(a1 * l1, 0.f) << sh, pb1 = pack2(b1 * l1, 0.f) << sh;
  pr[0] = zneg ? pb0 : 0u; pr[1] = pa0; pr[2] = zneg ? 0u : pb0;
  pr[3] = zneg ? pb1 : 0u; pr[4] = pa1; pr[5] = zneg ? 0u : pb1;
}
__device__ __forceinline__ void attn_pv(const uint32_t (&pr)[6], const uint32_t* v0, const uint32_t* v1, const uint32_t* v2, const uint32_t* v3, float (&o)[4][4]) {
#pragma unroll
  for (int dt = 0; dt < 4; dt++) {
    o[dt][0] = o[dt][1] = o[dt][2] = o[dt][3] = 0.f;
    mma16816(o[dt], pr[0], 0u, pr[1], pr[3], v0[dt], v1[dt]);
    mma16816(o[dt], pr[2], pr[4], 0u, pr[5], v2[dt], v3[dt]);
  }
}
#define PAUSE1 5
#define PAUSE2 1

__global__ void __cluster_dims__(2, 1, 1) __launch_bounds__(384, 1) fused_kernel(const __grid_constant__ Params P) {
  extern __shared__ __align__(1024) uint8_t smem_raw[];
  const uint32_t sb = smem_u32(smem_raw);
  const uint32_t bars = sb + OFF_BAR;
  const int tid = threadIdx.x;
  const int wu = __shfl_sync(0xffffffffu, tid >> 5, 0), wg = wu >> 2;
  const int r = blockIdx.x & 1, cl = blockIdx.x >> 1;
  int grp, slt;
  if (cl < 4) { grp = 0; slt = 4 + cl; }
  else if (cl < 36) { grp = (cl - 4) & 7; slt = (cl - 4) >> 3; }
  else { grp = 1 + (cl - 36) % 7; slt = 4 + (cl - 36) / 7; }
#define MAP 0
  const int m = grp, j = slt;
  const int i = 2 * m + r;
  auto BAR = [&](int k) { return bars + 8 * k; };

  if (tid == 0) {
    for (int k = 0; k < 4; k++) { mbar_init(BAR(F1 + k), 1); mbar_init(BAR(E1 + k), 2); mbar_init(BAR(F3 + k), 1); mbar_init(BAR(E3 + k), 4); }
    for (int k = 0; k < 5; k++) { mbar_init(BAR(F2 + k), 1); mbar_init(BAR(E2 + k), 2); }
    for (int k = 0; k < 6; k++) { mbar_init(BAR(F4 + k), 1); mbar_init(BAR(E4 + k), 4); }
    for (int k = 0; k < 10; k++) mbar_init(BAR(JOB + k), k < 4 ? 4 : 8);
    for (int k = 0; k < 6; k++) mbar_init(BAR(RD + k), 2);
    mbar_init(BAR(XF), 1); mbar_init(BAR(STD), 1);
    asm volatile("fence.mbarrier_init.release.cluster;" ::: "memory");
  }
  uint32_t tag;
  asm volatile("ld.relaxed.gpu.global.u32 %0, [%1];" : "=r"(tag) : "l"(&gEpoch) : "memory");
  tag += 1;
  TS(0);
  cluster_sync();

  if (wg == 2) {
    reg_dealloc<40>();
    const u64 inv = (tag & 1) ? 0ull : ~0ull;
    auto kb1 = [&](int n) { const int h = n >= 9, t = n - 2 - 7 * h; return n < 2 ? 2 * j + n : 2 * (t + (t >= j)) + h; };
    auto kb3 = [&](int n) { const int h = n >= 18, t = n - 4 - 14 * h; return n < 4 ? 2 * (i ^ (n >> 1)) + (n & 1) : 2 * ((2 * m + 2 + t) & 15) + h; };
    if (wu == 8) {
      if (elect_one()) {
#pragma unroll 1
        for (int L = 0; L < 2; L++) {
#pragma unroll 1
          for (int n = 0; n < 32; n++) {
            const int p = n & 3, nn = n & 15;
            if (n >= 4) mbar_wait(BAR(E1 + p), ((n >> 2) - 1) & 1);
            else if (L) mbar_wait(BAR(E4 + (n == 3 ? 0 : n + 3)), n == 3);
            mbar_expect(BAR(F1 + p), nn < 2 ? 24576 : 40960);
            tma3d_mc(sb + slot1(p) + 16384 + r * 12288, &P.wqkv, BAR(F1 + p), 128 * j + 64 * (n >> 4), kb1(nn) * 64 + 32 * r, 0);
          }
          int p = 0; uint32_t par = L ? 0x1e : 0;
#pragma unroll 1
          for (int n = 0; n < 16; n++) {
            if (n >= 5) { mbar_wait(BAR(E2 + p), (par >> p) & 1); par ^= 1u << p; }
            else if (n < 4) mbar_wait(BAR(E1 + n), 1);
            mbar_expect(BAR(F2 + p), 32768);
            tma2d_mc(sb + slot2(p) + 16384 + r * 8192, &P.wo, BAR(F2 + p), 128 * j + 64 * r, (2 * (n & 7) + (n >> 3)) * 64);
            if (++p == 5) p = 0;
          }
#pragma unroll 1
          for (int n = 0; n < 32; n++) {
            const int p = n & 3, kb = kb3(n);
            if (n >= 4) mbar_wait(BAR(E3 + p), ((n >> 2) - 1) & 1);
            else if (n == 0) mbar_wait(BAR(E2 + 4), L);
            else if (n == 1) mbar_wait(BAR(E2 + 0), 1);
            mbar_expect(BAR(F3 + p), n < 2 ? 32768 : 49152);
            tma3d(sb + slot3(p) + 16384, &P.w1, BAR(F3 + p), 0, kb * 64, 7 * m + 4 * r);
            tma3d(sb + slot3(p) + 40960, &P.w1h, BAR(F3 + p), 0, kb * 64, 14 * m + 6 + r);
          }
#pragma unroll 1
          for (int n = 0; n < 6; n++) {
            if (n < 3) mbar_wait(BAR(E3 + n), 1);
            else if (n == 4) mbar_wait(BAR(E3 + 3), 1);
            mbar_expect(BAR(F4 + n), n < 3 ? 16384 : n == 3 ? 24576 : 32768);
            tma3d(sb + slot4(n), &P.w2, BAR(F4 + n), 0, (7 * m + (n < 3 ? 4 * r + n : n == 3 ? 3 : n - 4 * r)) * 64, 2 * i);
          }
          p = 0; par = L ? 0x3c : 0;
          auto g4w = [&](int kb) {
            mbar_wait(BAR(E4 + p), (par >> p) & 1); par ^= 1u << p;
            mbar_expect(BAR(F4 + p), 32768);
            tma3d(sb + slot4(p), &P.w2, BAR(F4 + p), 0, kb * 64, 2 * i);
            if (++p == 6) p = 0;
          };
#pragma unroll 1
          for (int c = 0; c < 3; c++)
#pragma unroll 1
            for (int t = 0; t < 14; t++) { const int ii = (2 * m + 2 + t) & 15; g4w(7 * (ii >> 1) + 4 * (ii & 1) + c); }
#pragma unroll 1
          for (int t = 1; t < 9; t++) g4w(t < 8 ? 7 * ((m + t) & 7) + 3 : 7 * m + 6 - 4 * r);
        }
      }
    } else if (wu == 9) {
      if (elect_one()) {
        mbar_expect(BAR(XF), 32768);
        tma2d(sb + OFF_X, &P.x0, BAR(XF), 128 * j, 128 * i);
        tma2d(sb + OFF_X + 16384, &P.x0, BAR(XF), 128 * j + 64, 128 * i);
#pragma unroll 1
        for (int L = 0; L < 2; L++) {
          u64 ready = 0;
#pragma unroll 1
          for (int n = 2; n < 32; n++) {
            const int p = n & 3, nn = n & 15, kb = kb1(nn);
            if (nn < 2) continue;
            if (n >= 4) mbar_wait(BAR(E1 + p), ((n >> 2) - 1) & 1);
            else if (L) mbar_wait(BAR(E4 + (n == 3 ? 0 : n + 3)), n == 3);
            if (L) {
              flag_wait(gFlag[0][0][i], inv, 1ull << kb, ready);
              bulk_ld(sb + slot1(p), gXB + (i * 16 + kb) * 16384, 16384, BAR(F1 + p));
            } else tma2d(sb + slot1(p), &P.x0, BAR(F1 + p), kb * 64, 128 * i);
          }
          ready = 0;
          int p = 0; uint32_t par = L ? 0x1e : 0;
#pragma unroll 1
          for (int n = 0; n < 16; n++) {
            const int hp = 2 * (n & 7) + (n >> 3);
            if (n >= 5) { mbar_wait(BAR(E2 + p), (par >> p) & 1); par ^= 1u << p; }
            else if (n < 4) mbar_wait(BAR(E1 + n), 1);
            flag_wait(gFlag[L][1][i], inv, 1ull << hp, ready);
            bulk_ld(sb + slot2(p), gOB + (i * 16 + hp) * 16384, 16384, BAR(F2 + p));
            if (++p == 5) p = 0;
          }
          ready = 0;
#pragma unroll 1
          for (int n = 4; n < 32; n++) {
            const int p = n & 3, kb = kb3(n);
            if (n < 6) mbar_wait(BAR(RD + n - 4), L);
            mbar_wait(BAR(E3 + p), ((n >> 2) - 1) & 1);
            flag_wait(gFlag[L][2][j], inv, 1ull << kb, ready);
            bulk_ld_mc(sb + slot3(p) + r * 8192, gHB + (j * 32 + kb) * 16384 + r * 8192, 8192, BAR(F3 + p));
          }
          ready = 0; p = 0; par = L ? 0x3c : 0;
          auto g4a = [&](int kb, u64 need, bool mc) {
            mbar_wait(BAR(E4 + p), (par >> p) & 1); par ^= 1u << p;
            flag_wait(gFlag[L][3][j], inv, need, ready);
            const uint8_t* src = gUB + (j * 56 + kb) * 16384;
            if (mc) bulk_ld_mc(sb + slot4(p) + 16384 + r * 8192, src + r * 8192, 8192, BAR(F4 + p));
            else bulk_ld(sb + slot4(p) + 16384, src, 16384, BAR(F4 + p));
            if (++p == 6) p = 0;
          };
#pragma unroll 1
          for (int c = 0; c < 3; c++)
#pragma unroll 1
            for (int t = 0; t < 14; t++) {
              const int ii = (2 * m + 2 + t) & 15;
              if (c == 0 && t < 4) mbar_wait(BAR(RD + 2 + t), L);
              g4a(7 * (ii >> 1) + 4 * (ii & 1) + c, 1ull << (16 * c + ii), true);
            }
#pragma unroll 1
          for (int t = 1; t < 8; t++) { const int mm = (m + t) & 7; g4a(7 * mm + 3, 3ull << (48 + 2 * mm), true); }
          g4a(7 * m + 6 - 4 * r, 1ull << (32 + (i ^ 1)), false);
        }
      }
    } else {
      if (elect_one()) {
        const int h = wu - 10;
        const uint32_t rs = mapa(sb, r ^ 1), rb = rs + OFF_BAR;
        auto drained = [&](int k) { mbar_arrive(BAR(RD + k)); mbar_arrive_cl(rb + 8 * (RD + k)); };
#pragma unroll 1
        for (int L = 0; L < 2; L++) {
          mbar_wait(BAR(JOB + h), L);
          bulk_st(gOB + (i * 16 + 2 * j + h) * 16384, sb + OFF_STG, 16384);
          bulk_commit(); bulk_wait0();
          if (h == 0) mbar_arrive(BAR(STD));
          flag_set(gFlag[L][1][i], 1ull << (2 * j + h));
          mbar_wait(BAR(JOB + 2 + h), L);
          bulk_st(gHB + (j * 32 + 2 * i + h) * 16384, sb + slot3(h), 16384);
          bulk_commit();
          mbar_wait(BAR(E2 + 0), 1);
          bulk_s2s(rs + slot3(2 + h), sb + slot3(h), 16384, rb + 8 * (F3 + 2 + h));
          bulk_wait0(); drained(h);
          flag_set(gFlag[L][2][j], 1ull << (2 * i + h));
          mbar_wait(BAR(JOB + 4 + h), L);
          bulk_st(gUB + (j * 56 + 7 * m + 4 * r + h) * 16384, sb + slot4(h) + 16384, 16384);
          bulk_commit();
          mbar_wait(BAR(E3 + 3), 1);
          bulk_s2s(rs + slot4(4 + h) + 16384, sb + slot4(h) + 16384, 16384, rb + 8 * (F4 + 4 + h));
          bulk_wait0(); drained(2 + h);
          flag_set(gFlag[L][3][j], 1ull << (16 * h + i));
          mbar_wait(BAR(JOB + 6 + h), L);
          if (h == 0) bulk_st(gUB + (j * 56 + 7 * m + 4 * r + 2) * 16384, sb + slot4(2) + 16384, 16384);
          else
            for (int a = 0; a < 2; a++) {
              const uint32_t o = a * 8192 + r * 4096;
              bulk_s2s(rs + slot4(3) + 16384 + o, sb + slot4(3) + 16384 + o, 4096, rb + 8 * (F4 + 3));
              bulk_st(gUB + (j * 56 + 7 * m + 3) * 16384 + o, sb + slot4(3) + 16384 + o, 4096);
            }
          bulk_commit(); bulk_wait0(); drained(4 + h);
          flag_set(gFlag[L][3][j], 1ull << (32 + 16 * h + i));
          mbar_wait(BAR(JOB + 8 + h), L);
          if (L == 0) {
            bulk_st(gXB + (i * 16 + 2 * j + h) * 16384, sb + OFF_X + h * 16384, 16384);
            bulk_commit(); bulk_wait0();
            flag_set(gFlag[0][0][i], 1ull << (2 * j + h));
          } else {
            tma2d_store(&P.out, sb + OFF_X + h * 16384, 128 * j + 64 * h, 128 * i);
            bulk_commit(); bulk_wait0();
          }
        }
        if (blockIdx.x == 0 && h == 0) asm volatile("st.relaxed.gpu.global.u32 [%0], %1;" ::"l"(&gEpoch), "r"(tag) : "memory");
      }
    }
    __syncwarp();
    cluster_sync();
  } else {
    reg_alloc<232>();
    const uint32_t rbars = mapa(bars, tid & 1);
    const bool relp = (tid & 127) < 2;
    auto release = [&](int k) { if (relp) mbar_arrive_cl(rbars + 8 * k); };
    auto job_done = [&](int k) { fence_async_smem(); __syncwarp(); if ((fresh_tid() & 31) == 0) mbar_arrive(BAR(JOB + k)); };
#define GEOM const int t7 = fresh_tid() & 127, lane = t7 & 31, w = t7 >> 5, g = lane >> 2, q = lane & 3, \
                       lr = lane & 15, lt = lane >> 4, l7 = lane & 7; (void)w; (void)g; (void)q; (void)lr; (void)lt; (void)l7

#pragma unroll 1
    for (int L = 0; L < 2; L++) {
      if (L == 0) mbar_wait(BAR(XF), 0);
      if (wg == 1) {
        GEOM;
        float sum = 0.f, sq = 0.f;
#pragma unroll
        for (int c = 0; c < 16; c++) {
          uint32_t v[4];
          lds128(sb + OFF_X + (c >> 3) * 16384 + t7 * 128 + (((c & 7) ^ l7) << 4), v[0], v[1], v[2], v[3]);
#pragma unroll
          for (int k = 0; k < 4; k++) { float a = bf_lo(v[k]), b = bf_hi(v[k]); sum += a + b; sq = fmaf(a, a, fmaf(b, b, sq)); }
        }
        float mean, var;
        stats_exchange(gST[2 * L][i], j, t7, sum, sq, tag, mean, var);
        sts64f(sb + OFF_STAT + t7 * 8, mean, rsqrtf(var + 1e-5f));
        TS(29 + 32 * L);
        if (L == 0) {
          float cs[3][8];
#pragma unroll
          for (int p = 0; p < 3; p++)
#pragma unroll
            for (int k = 0; k < 8; k++) cs[p][k] = 0.f;
          const bf16* wp = P.wqkv_p + (size_t)(64 * i + (t7 >> 4)) * 3072 + 128 * j + (t7 & 15) * 8;
#pragma unroll
          for (int rr = 0; rr < 8; rr++)
#pragma unroll
            for (int p = 0; p < 3; p++) {
              uint4 v = __ldg((const uint4*)(wp + (size_t)rr * 8 * 3072 + p * 1024));
              cs[p][0] += bf_lo(v.x); cs[p][1] += bf_hi(v.x); cs[p][2] += bf_lo(v.y); cs[p][3] += bf_hi(v.y);
              cs[p][4] += bf_lo(v.z); cs[p][5] += bf_hi(v.z); cs[p][6] += bf_lo(v.w); cs[p][7] += bf_hi(v.w);
            }
#pragma unroll
          for (int p = 0; p < 3; p++)
#pragma unroll
            for (int k = 0; k < 8; k++) {
              float v = cs[p][k] + __shfl_xor_sync(0xffffffffu, cs[p][k], 16);
              if (lane < 16) sts32f(sb + OFF_STG + (w * 384 + p * 128 + lane * 8 + k) * 4, v);
            }
          for (int c = t7; c < 224; c += 128) {
            const int f = c < 192 ? 64 * (7 * m + 4 * r) + c : 64 * (7 * m + 3) + 32 * r + c - 192;
            sts32f(sb + OFF_B1 + c * 4, __bfloat162float(P.b1[f]));
          }
          nb_sync<NB_WG + 1>(128);
#pragma unroll
          for (int p = 0; p < 3; p++) {
            float v = 0.f;
#pragma unroll
            for (int k = 0; k < 4; k++) v += lds32f(sb + OFF_STG + (k * 384 + p * 128 + t7) * 4);
            ll_st1(&gCS[i][p * 1024 + 128 * j + t7], __float_as_uint(v), tag);
          }
#pragma unroll
          for (int p = 0; p < 3; p++) {
            uint32_t a[16], n = 0, bad;
            do {
              bad = 0;
#pragma unroll
              for (int k = 0; k < 16; k++) bad |= ll_ld1(&gCS[k][p * 1024 + 128 * j + t7], a[k], tag);
            } while (bad && ++n < SPIN_MAX);
            float v = 0.f;
#pragma unroll
            for (int k = 0; k < 16; k++) v += __uint_as_float(a[k]);
            sts32f(sb + OFF_CS + ((t7 >> 6) * 192 + p * 64 + (t7 & 63)) * 4, v);
          }
        }
        TS(30 + 32 * L);
        nb_sync<NB_ORDA>(256);
      }
      TS(1 + 32 * L);
      {
        float acc[2][96];
        auto g1_issue = [&](uint32_t a, uint32_t st, auto first) {
          const uint64_t da = mkdesc(a, 16, 2048), db = mkdesc(st + 16384, 4096, 1024);
          wg_fence();
#pragma unroll
          for (int kk = 0; kk < 4; kk++) {
            const uint64_t b = db + (((kk >> 1) * 12288 + (kk & 1) * 2048) >> 4);
            if (first.value && kk == 0) { wgmma_192z<0, 1>(acc[0], da, b); wgmma_192z<0, 1>(acc[1], da + 64, b); }
            else { wgmma_192<0, 1>(acc[0], da + kk * 2, b); wgmma_192<0, 1>(acc[1], da + kk * 2 + 64, b); }
          }
          wg_commit();
        };
        mbar_wait(BAR(F1), 0);
        g1_issue(sb + OFF_X, sb + slot1(0), True{});
#pragma unroll 1
        for (int n = 1; n < 16; n++) {
          const int p = n & 3;
          mbar_wait(BAR(F1 + p), (n >> 2) & 1);
          const uint32_t st = sb + slot1(p);
          g1_issue(n == 1 ? sb + OFF_X + 16384 : st, st, False{});
          if (n == 15 && wg == 0) nb_sync<NB_ORDA>(256);
          if (n == PAUSE1 && wg == 1) nb_arrive<NB_P1>(256);
          wg_wait<1>();
          release(E1 + ((n - 1) & 3));
          if (n == PAUSE1 && wg == 1) nb_sync<NB_P2>(256);
        }
        wg_wait<0>();
        release(E1 + 3);
        fence_regs(acc[0]); fence_regs(acc[1]);
        TS(2 + 32 * L);
        GEOM;
        float mean[4], rstd[4];
#pragma unroll
        for (int o = 0; o < 4; o++) { float2 v = lds64f(sb + OFF_STAT + (32 * w + 8 * o + g) * 8); mean[o] = -v.x; rstd[o] = v.y; }
        uint32_t Q[4][8], K[4][8], V[4][8];
#pragma unroll
        for (int t = 23; t >= 0; t--) {
          const float2 cs = lds64f(sb + OFF_CS + (wg * 192 + 8 * t + 2 * q) * 4);
#pragma unroll
          for (int o = 0; o < 4; o++) {
            float v0 = fmaf(mean[o], cs.x, acc[o & 1][4 * t + 2 * (o >> 1)]);
            float v1 = fmaf(mean[o], cs.y, acc[o & 1][4 * t + 2 * (o >> 1) + 1]);
            if (t >= 8) { v0 *= rstd[o]; v1 *= rstd[o]; }
            const uint32_t pk = pack2(v0, v1);
            if (t < 8) Q[o][t] = pk; else if (t < 16) K[o][t - 8] = pk; else V[o][t - 16] = movm(pk);
          }
          if (t == 8) {
            if (wg == 1) mbar_wait(BAR(STD), L);
            if (w < 3) {
              const uint32_t a = sb + OFF_XCH + w * 4096 + lane * 16;
#pragma unroll
              for (int c = 0; c < 2; c++) {
                sts128(a + (0 + c) * 512, K[2][4 * c], K[2][4 * c + 1], K[2][4 * c + 2], K[2][4 * c + 3]);
                sts128(a + (2 + c) * 512, K[3][4 * c], K[3][4 * c + 1], K[3][4 * c + 2], K[3][4 * c + 3]);
                sts128(a + (4 + c) * 512, V[2][4 * c], V[2][4 * c + 1], V[2][4 * c + 2], V[2][4 * c + 3]);
                sts128(a + (6 + c) * 512, V[3][4 * c], V[3][4 * c + 1], V[3][4 * c + 2], V[3][4 * c + 3]);
              }
            } else if (i < 15) {
              uint4* hp = &gHalo[2 * L + wg][i][j][0][lane];
#pragma unroll
              for (int c = 0; c < 4; c++) {
                ll_st2(hp + (0 + c) * 32, K[2][2 * c], K[2][2 * c + 1], tag);
                ll_st2(hp + (4 + c) * 32, K[3][2 * c], K[3][2 * c + 1], tag);
                ll_st2(hp + (8 + c) * 32, V[2][2 * c], V[2][2 * c + 1], tag);
                ll_st2(hp + (12 + c) * 32, V[3][2 * c], V[3][2 * c + 1], tag);
              }
            }
          }
        }
        TS(28 + 32 * L);
        if (wg == 0) nb_sync<NB_WG>(128); else { nb_sync<NB_WG + 1>(128); nb_arrive<NB_ORDB>(256); }
        uint32_t KH[2][8], VH[2][8];
        if (w > 0) {
          const uint32_t a = sb + OFF_XCH + (w - 1) * 4096 + lane * 16;
#pragma unroll
          for (int c = 0; c < 2; c++) {
            lds128(a + (0 + c) * 512, KH[0][4 * c], KH[0][4 * c + 1], KH[0][4 * c + 2], KH[0][4 * c + 3]);
            lds128(a + (2 + c) * 512, KH[1][4 * c], KH[1][4 * c + 1], KH[1][4 * c + 2], KH[1][4 * c + 3]);
            lds128(a + (4 + c) * 512, VH[0][4 * c], VH[0][4 * c + 1], VH[0][4 * c + 2], VH[0][4 * c + 3]);
            lds128(a + (6 + c) * 512, VH[1][4 * c], VH[1][4 * c + 1], VH[1][4 * c + 2], VH[1][4 * c + 3]);
          }
        } else if (i > 0) {
          const uint4* hp = &gHalo[2 * L + wg][i - 1][j][0][lane];
          uint32_t n = 0, bad;
          do {
            bad = 0;
#pragma unroll
            for (int c = 0; c < 4; c++) {
              bad |= ll_ld2(hp + (0 + c) * 32, KH[0][2 * c], KH[0][2 * c + 1], tag);
              bad |= ll_ld2(hp + (4 + c) * 32, KH[1][2 * c], KH[1][2 * c + 1], tag);
              bad |= ll_ld2(hp + (8 + c) * 32, VH[0][2 * c], VH[0][2 * c + 1], tag);
              bad |= ll_ld2(hp + (12 + c) * 32, VH[1][2 * c], VH[1][2 * c + 1], tag);
            }
          } while (bad && ++n < SPIN_MAX);
          __syncwarp();
        } else {
#pragma unroll
          for (int c = 0; c < 8; c++) KH[0][c] = KH[1][c] = VH[0][c] = VH[1][c] = 0u;
        }
        const bool e = g & 1, zneg = (g >> 1) < q, first = (i == 0) && (w == 0);
        const float qs = 0.17677669530f * 1.4426950409f;
        TS(11 + 32 * L);
        nb_sync<NB_P1>(256);
        TS(12 + 32 * L);
        float o[4][4][4];
        {
          uint32_t pr[4][6];
#pragma unroll
          for (int hh = 0; hh < 2; hh++) {
            attn_probs(&Q[0][4 * hh], &Q[1][4 * hh], &KH[0][4 * hh], &KH[1][4 * hh], &K[0][4 * hh], &K[1][4 * hh], rstd[0] * qs, rstd[1] * qs, first, e, zneg, pr[hh]);
            attn_probs(&Q[2][4 * hh], &Q[3][4 * hh], &K[0][4 * hh], &K[1][4 * hh], &K[2][4 * hh], &K[3][4 * hh], rstd[2] * qs, rstd[3] * qs, false, e, zneg, pr[2 + hh]);
          }
#pragma unroll
          for (int hh = 0; hh < 2; hh++) {
            attn_pv(pr[hh], &VH[0][4 * hh], &VH[1][4 * hh], &V[0][4 * hh], &V[1][4 * hh], o[hh]);
            attn_pv(pr[2 + hh], &V[0][4 * hh], &V[1][4 * hh], &V[2][4 * hh], &V[3][4 * hh], o[2 + hh]);
          }
        }
#pragma unroll
        for (int u = 0; u < 4; u++)
#pragma unroll
          for (int dt = 0; dt < 4; dt += 2)
            stsm4(sb + OFF_STG + (32 * w + 16 * (u >> 1) + lr) * 128 + (((4 * (u & 1) + dt + lt) ^ l7) << 4),
                  pack2(o[u][dt][0], o[u][dt][1]), pack2(o[u][dt][2], o[u][dt][3]), pack2(o[u][dt + 1][0], o[u][dt + 1][1]), pack2(o[u][dt + 1][2], o[u][dt + 1][3]));
        nb_arrive<NB_P2>(256);
        job_done(wg);
        TS(3 + 32 * L);
      }
      if (wg == 0) {
        float acc[2][64];
        GEOM;
#pragma unroll
        for (int mb = 0; mb < 2; mb++)
#pragma unroll
          for (int t = 0; t < 16; t += 2) {
            uint32_t v0, v1, v2, v3;
            ldsm4(sb + OFF_X + (t >> 3) * 16384 + (64 * mb + 16 * w + lr) * 128 + ((((t & 7) + lt) ^ l7) << 4), v0, v1, v2, v3);
            acc[mb][4 * t + 0] = bf_lo(v0); acc[mb][4 * t + 1] = bf_hi(v0); acc[mb][4 * t + 2] = bf_lo(v1); acc[mb][4 * t + 3] = bf_hi(v1);
            acc[mb][4 * t + 4] = bf_lo(v2); acc[mb][4 * t + 5] = bf_hi(v2); acc[mb][4 * t + 6] = bf_lo(v3); acc[mb][4 * t + 7] = bf_hi(v3);
          }
        fence_regs(acc[0]); fence_regs(acc[1]);
        nb_sync<NB_ORDB>(256);
        TS(4 + 32 * L);
        int p = 0, pp = 0; uint32_t par = L ? 0x1e : 0;
#pragma unroll 1
        for (int n = 0; n < 16; n++) {
          mbar_wait(BAR(F2 + p), (par >> p) & 1);
          par ^= 1u << p;
          const uint32_t st = sb + slot2(p);
          const uint64_t da = mkdesc(st, 16, 1024), db = mkdesc(st + 16384, 8192, 1024);
          wg_fence();
#pragma unroll
          for (int kk = 0; kk < 4; kk++) {
            wgmma_128<0, 1>(acc[0], da + kk * 2, db + kk * 128);
            wgmma_128<0, 1>(acc[1], da + kk * 2 + 512, db + kk * 128);
          }
          wg_commit();
          if (n == PAUSE2) nb_arrive<NB_P1>(256);
          wg_wait<1>();
          if (n > 0) release(E2 + pp);
          if (n == PAUSE2) nb_sync<NB_P2>(256);
          pp = p; if (++p == 5) p = 0;
        }
        wg_wait<0>();
        release(E2 + 0);
        fence_regs(acc[0]); fence_regs(acc[1]);
        TS(5 + 32 * L);
        float sum[4], sq[4];
#pragma unroll
        for (int o = 0; o < 4; o++) {
          float s0 = 0.f, s1 = 0.f, q0 = 0.f, q1 = 0.f;
#pragma unroll
          for (int t = 0; t < 16; t++) {
            const float a = acc[o >> 1][4 * t + 2 * (o & 1)], b = acc[o >> 1][4 * t + 2 * (o & 1) + 1];
            s0 += a; s1 += b; q0 = fmaf(a, a, q0); q1 = fmaf(b, b, q1);
          }
          sum[o] = s0 + s1; sq[o] = q0 + q1;
        }
        {
          const bool h2 = q & 2, h1 = q & 1;
          float s0 = (h2 ? sum[2] : sum[0]) + __shfl_xor_sync(0xffffffffu, h2 ? sum[0] : sum[2], 2);
          float s1 = (h2 ? sum[3] : sum[1]) + __shfl_xor_sync(0xffffffffu, h2 ? sum[1] : sum[3], 2);
          float q0 = (h2 ? sq[2] : sq[0]) + __shfl_xor_sync(0xffffffffu, h2 ? sq[0] : sq[2], 2);
          float q1 = (h2 ? sq[3] : sq[1]) + __shfl_xor_sync(0xffffffffu, h2 ? sq[1] : sq[3], 2);
          sum[0] = (h1 ? s1 : s0) + __shfl_xor_sync(0xffffffffu, h1 ? s0 : s1, 1);
          sq[0] = (h1 ? q1 : q0) + __shfl_xor_sync(0xffffffffu, h1 ? q0 : q1, 1);
        }
        uint4 (*stb)[128] = gST[2 * L + 1][i];
        ll_st2(&stb[j][t7], __float_as_uint(sum[0]), __float_as_uint(sq[0]), tag);
        TS(13 + 32 * L);
#pragma unroll
        for (int mb = 0; mb < 2; mb++)
#pragma unroll
          for (int t = 0; t < 16; t += 2)
            stsm4(sb + OFF_X + (t >> 3) * 16384 + (64 * mb + 16 * w + lr) * 128 + ((((t & 7) + lt) ^ l7) << 4),
                  pack2(acc[mb][4 * t], acc[mb][4 * t + 1]), pack2(acc[mb][4 * t + 2], acc[mb][4 * t + 3]),
                  pack2(acc[mb][4 * t + 4], acc[mb][4 * t + 5]), pack2(acc[mb][4 * t + 6], acc[mb][4 * t + 7]));
        TS(14 + 32 * L);
        float rr, mr;
        {
          uint32_t a[8], b[8], n = 0, bad;
          do {
            bad = 0;
#pragma unroll
            for (int k = 0; k < 8; k++) bad |= ll_ld2(&stb[k][t7], a[k], b[k], tag);
          } while (bad && ++n < SPIN_MAX);
          __syncwarp();
          float s = 0.f, qq = 0.f;
#pragma unroll
          for (int k = 0; k < 8; k++) { s += __uint_as_float(a[k]); qq += __uint_as_float(b[k]); }
          const float mean = s * (1.f / D_);
          const float var = fmaxf(fmaf(-mean, mean, qq * (1.f / D_)), 0.f);
          const float r1 = rsqrtf(var + 1e-5f);
          rr = r1 * rsqrtf(fmaf(var * r1, r1, 1e-5f));
          mr = -mean * rr;
        }
        TS(15 + 32 * L);
#pragma unroll
        for (int o = 0; o < 4; o++) { sum[o] = __shfl_sync(0xffffffffu, rr, (lane & 28) + o); sq[o] = __shfl_sync(0xffffffffu, mr, (lane & 28) + o); }
#pragma unroll
        for (int mb = 0; mb < 2; mb++) {
#pragma unroll
          for (int t = 0; t < 16; t += 2) {
            const float r0 = sum[2 * mb], m0 = sq[2 * mb], r1 = sum[2 * mb + 1], m1 = sq[2 * mb + 1];
            stsm4(sb + slot3(mb) + (t >> 3) * 8192 + (16 * w + lr) * 128 + ((((t & 7) + lt) ^ l7) << 4),
                  pack2(fmaf(acc[mb][4 * t], r0, m0), fmaf(acc[mb][4 * t + 1], r0, m0)),
                  pack2(fmaf(acc[mb][4 * t + 2], r1, m1), fmaf(acc[mb][4 * t + 3], r1, m1)),
                  pack2(fmaf(acc[mb][4 * t + 4], r0, m0), fmaf(acc[mb][4 * t + 5], r0, m0)),
                  pack2(fmaf(acc[mb][4 * t + 6], r1, m1), fmaf(acc[mb][4 * t + 7], r1, m1)));
          }
          job_done(2 + mb);
        }
      }
      nb_sync<NB_BOTH>(256);
      TS(6 + 32 * L);
      float acc3[112], acc4[64];
      auto g3_issue = [&](int p, auto first) {
        const uint32_t st = sb + slot3(p);
        const uint64_t da = mkdesc(st + wg * 8192, 8192, 1024), db = mkdesc(st + 16384, 8192, 1024);
        wg_fence();
#pragma unroll
        for (int kk = 0; kk < 4; kk++) {
          if (first.value && kk == 0) wgmma_224z<1, 1>(acc3, da, db);
          else wgmma_224<1, 1>(acc3, da + kk * 128, db + kk * 128);
        }
        wg_commit();
      };
      mbar_wait(BAR(F3 + 0), 0); g3_issue(0, True{});
      mbar_wait(BAR(F3 + 1), 0); g3_issue(1, False{}); wg_wait<1>();
      mbar_wait(BAR(F3 + 2), 0); release(E3 + 0); g3_issue(2, False{}); wg_wait<1>();
      mbar_wait(BAR(F3 + 3), 0); release(E3 + 1); g3_issue(3, False{});
      {
        GEOM;
        const int row = 128 * i + 64 * wg + 16 * w + g;
        const float c0 = __bfloat162float(P.b2[row]), c1 = __bfloat162float(P.b2[row + 8]);
#pragma unroll
        for (int t = 0; t < 16; t += 2) {
          uint32_t v0, v1, v2, v3;
          ldsm4(sb + OFF_X + (t >> 3) * 16384 + (64 * wg + 16 * w + lr) * 128 + ((((t & 7) + lt) ^ l7) << 4), v0, v1, v2, v3);
          acc4[4 * t + 0] = bf_lo(v0) + c0; acc4[4 * t + 1] = bf_hi(v0) + c0; acc4[4 * t + 2] = bf_lo(v1) + c1; acc4[4 * t + 3] = bf_hi(v1) + c1;
          acc4[4 * t + 4] = bf_lo(v2) + c0; acc4[4 * t + 5] = bf_hi(v2) + c0; acc4[4 * t + 6] = bf_lo(v3) + c1; acc4[4 * t + 7] = bf_hi(v3) + c1;
        }
        fence_regs(acc4);
      }
      wg_wait<1>(); release(E3 + 2);
#pragma unroll 1
      for (int n = 4; n < 32; n++) {
        const int p = n & 3;
        mbar_wait(BAR(F3 + p), (n >> 2) & 1);
        g3_issue(p, False{});
        wg_wait<1>();
        release(E3 + ((n - 1) & 3));
      }
      wg_wait<0>();
      release(E3 + 3);
      fence_regs(acc3);
      TS(7 + 32 * L);
      auto g4_issue = [&](int p) {
        const uint32_t st = sb + slot4(p);
        const uint64_t da = mkdesc(st + wg * 8192, 8192, 1024), db = mkdesc(st + 16384, 8192, 1024);
        wg_fence();
#pragma unroll
        for (int kk = 0; kk < 4; kk++) wgmma_128<1, 1>(acc4, da + kk * 128, db + kk * 128);
        wg_commit();
      };
      uint32_t par = L ? 0x3c : 0;
      GEOM;
#pragma unroll
      for (int c = 0; c < 4; c++) {
        if (c != 1) mbar_wait(BAR(E3 + (c == 0 ? 1 : c)), 1);
        const uint32_t ua = sb + slot4(c) + 16384 + wg * 8192 + ((c == 3 ? 32 * r : 0) + 8 * lt + l7) * 128 + (((2 * w + ((lane >> 3) & 1)) ^ l7) << 4);
#pragma unroll
        for (int t = 8 * c; t < (c == 3 ? 28 : 8 * c + 8); t += 2) {
          const float2 ba = lds64f(sb + OFF_B1 + (8 * t + 2 * q) * 4), bb = lds64f(sb + OFF_B1 + (8 * t + 8 + 2 * q) * 4);
          stsm4t(ua + (t & 7) * 1024,
                 pack2(gelu_tanh(acc3[4 * t] + ba.x), gelu_tanh(acc3[4 * t + 1] + ba.y)),
                 pack2(gelu_tanh(acc3[4 * t + 2] + ba.x), gelu_tanh(acc3[4 * t + 3] + ba.y)),
                 pack2(gelu_tanh(acc3[4 * t + 4] + bb.x), gelu_tanh(acc3[4 * t + 5] + bb.y)),
                 pack2(gelu_tanh(acc3[4 * t + 6] + bb.x), gelu_tanh(acc3[4 * t + 7] + bb.y)));
        }
        TS(16 + 3 * c + 32 * L);
        job_done(4 + c);
        nb_sync<NB_BOTH>(256);
        TS(17 + 3 * c + 32 * L);
        mbar_wait(BAR(F4 + c), (par >> c) & 1);
        TS(18 + 3 * c + 32 * L);
        g4_issue(c);
      }
      TS(8 + 32 * L);
      wg_wait<1>();
      mbar_wait(BAR(F4 + 4), (par >> 4) & 1);
      mbar_wait(BAR(F4 + 5), (par >> 5) & 1);
      release(E4 + 0); release(E4 + 1); release(E4 + 2);
      par ^= 0xf;
      {
        int p = 4, pp = 3;
#pragma unroll 1
        for (int n = 4; n < 56; n++) {
          mbar_wait(BAR(F4 + p), (par >> p) & 1);
          par ^= 1u << p;
          g4_issue(p);
          wg_wait<1>();
          release(E4 + pp);
          pp = p; if (++p == 6) p = 0;
        }
      }
      wg_wait<0>();
      release(E4 + 1);
      fence_regs(acc4);
      TS(9 + 32 * L);
#pragma unroll
      for (int t = 0; t < 16; t += 2) {
        stsm4(sb + OFF_X + (t >> 3) * 16384 + (64 * wg + 16 * w + lr) * 128 + ((((t & 7) + lt) ^ l7) << 4),
              pack2(acc4[4 * t], acc4[4 * t + 1]), pack2(acc4[4 * t + 2], acc4[4 * t + 3]),
              pack2(acc4[4 * t + 4], acc4[4 * t + 5]), pack2(acc4[4 * t + 6], acc4[4 * t + 7]));
        if ((t & 7) == 6) job_done(8 + (t >> 3));
      }
      nb_sync<NB_BOTH>(256);
      TS(10 + 32 * L);
    }
    cluster_sync();
    TS(63);
  }
}

typedef CUresult (*EncodeFn)(CUtensorMap*, CUtensorMapDataType, cuuint32_t, void*, const cuuint64_t*, const cuuint64_t*, const cuuint32_t*,
                             const cuuint32_t*, CUtensorMapInterleave, CUtensorMapSwizzle, CUtensorMapL2promotion, CUtensorMapFloatOOBfill);

void make_map(EncodeFn enc, CUtensorMap* mp, const void* base, int rank, cuuint64_t d0, cuuint64_t d1, cuuint64_t d2, cuuint64_t s1, cuuint64_t s2,
              cuuint32_t b0, cuuint32_t b1, cuuint32_t b2) {
  cuuint64_t dims[3] = {d0, d1, d2}, strides[2] = {s1, s2};
  cuuint32_t box[3] = {b0, b1, b2}, es[3] = {1, 1, 1};
  CUresult res = enc(mp, CU_TENSOR_MAP_DATA_TYPE_BFLOAT16, rank, const_cast<void*>(base), dims, strides, box, es, CU_TENSOR_MAP_INTERLEAVE_NONE,
                     CU_TENSOR_MAP_SWIZZLE_128B, CU_TENSOR_MAP_L2_PROMOTION_L2_128B, CU_TENSOR_MAP_FLOAT_OOB_FILL_NONE);
  (void)res;
}

}

extern "C" void kernel_launch(void* const* d_in, const int* in_sizes, int n_in, void* d_out, int out_size) {
  (void)in_sizes; (void)n_in; (void)out_size;
  static EncodeFn enc = nullptr;
  if (!enc) {
    void* fn = nullptr;
    cudaDriverEntryPointQueryResult qr;
    cudaGetDriverEntryPoint("cuTensorMapEncodeTiled", &fn, cudaEnableDefault, &qr);
    enc = (EncodeFn)fn;
    cudaFuncSetAttribute(fused_kernel, cudaFuncAttributeMaxDynamicSharedMemorySize, SMEM_BYTES);
  }
  Params P;
  make_map(enc, &P.x0, d_in[0], 2, D_, S_, 1, D_ * 2, 0, 64, 128, 1);
  make_map(enc, &P.wqkv, d_in[1], 3, D_, D_, 3, 3 * D_ * 2, D_ * 2, 64, 32, 3);
  make_map(enc, &P.wo, d_in[2], 2, D_, D_, 1, D_ * 2, 0, 64, 64, 1);
  make_map(enc, &P.w1, d_in[4], 3, 64, S_, F_ / 64, F_ * 2, 128, 64, 64, 3);
  make_map(enc, &P.w1h, d_in[4], 3, 32, S_, F_ / 32, F_ * 2, 64, 64, 64, 1);
  make_map(enc, &P.w2, d_in[6], 3, 64, F_, S_ / 64, S_ * 2, 128, 64, 64, 2);
  make_map(enc, &P.out, d_out, 2, D_, S_, 1, D_ * 2, 0, 64, 128, 1);
  P.wqkv_p = (const bf16*)d_in[1];
  P.b1 = (const bf16*)d_in[5];
  P.b2 = (const bf16*)d_in[7];
  fused_kernel<<<128, 384, SMEM_BYTES>>>(P);
}
```

```cpp
#include <cuda_runtime.h>
#include <cuda_bf16.h>
#include <cuda.h>
#include <stdint.h>

namespace {

typedef __nv_bfloat16 bf16;
constexpr int S_ = 2048, D_ = 1024, F_ = 3584;

constexpr uint32_t OFF_STG  = 163840;
constexpr uint32_t OFF_X    = 196608;
constexpr uint32_t OFF_BAR  = 229376;
constexpr uint32_t OFF_CS   = OFF_BAR + 512;
constexpr uint32_t OFF_B1   = OFF_CS + 1536;
constexpr uint32_t SMEM_BYTES = OFF_B1 + 896 + 128;
constexpr int F1 = 0, E1 = 4, F2 = 8, E2 = 13, F3 = 18, E3 = 22, F4 = 26, E4 = 32;
constexpr int JOB = 38;
constexpr int RD = 48;
constexpr int XF = 54, STD = 56, STAT = 58, SEQ = 59, CSJ = 61;
constexpr int NB_BOTH = 1;

__device__ __forceinline__ uint32_t slot1(int p) { return p * 40960; }
__device__ __forceinline__ uint32_t slot2(int p) { return p * 32768; }
__device__ __forceinline__ uint32_t slot3(int p) { return ((p + 2) & 3) * 49152; }
__device__ __forceinline__ uint32_t slot4(int p) { return (p < 2 ? p + 4 : p - 2) * 32768; }

__device__ __align__(1024) uint8_t gXB[16 * 16 * 16384];
__device__ __align__(1024) uint8_t gOB[16 * 16 * 16384];
__device__ __align__(1024) uint8_t gHB[8 * 32 * 16384];
__device__ __align__(1024) uint8_t gUB[8 * 56 * 16384];
__device__ __align__(1024) uint4   gST[2][16][8][128];
__device__ __align__(1024) uint4   gHalo[4][16][8][16][32];
__device__ __align__(1024) uint4   gCS[8][16][64];
__device__ __align__(1024) unsigned long long gFlag[2][4][16][16];
__device__ uint32_t gEpoch;
#define TS(k)

struct Params {
  CUtensorMap x0, wqkv, wo, w1, w1h, w2, out;
  const bf16 *wqkv_p, *b1, *b2;
};

template <int TA, int TB> __device__ __forceinline__ void wgmma_128(float (&d)[64], uint64_t da, uint64_t db) {
  asm volatile("wgmma.mma_async.sync.aligned.m64n128k16.f32.bf16.bf16 {"
  "%0, %1, %2, %3, %4, %5, %6, %7, %8, %9, %10, %11, %12, %13, %14, %15, "
  "%16, %17, %18, %19, %20, %21, %22, %23, %24, %25, %26, %27, %28, %29, %30, %31, "
  "%32, %33, %34, %35, %36, %37, %38, %39, %40, %41, %42, %43, %44, %45, %46, %47, "
  "%48, %49, %50, %51, %52, %53, %54, %55, %56, %57, %58, %59, %60, %61, %62, %63"
  "}, %64, %65, 1, 1, 1, %66, %67;\n"
  : "+f"(d[0]), "+f"(d[1]), "+f"(d[2]), "+f"(d[3]), "+f"(d[4]), "+f"(d[5]), "+f"(d[6]), "+f"(d[7]),
    "+f"(d[8]), "+f"(d[9]), "+f"(d[10]), "+f"(d[11]), "+f"(d[12]), "+f"(d[13]), "+f"(d[14]), "+f"(d[15]),
    "+f"(d[16]), "+f"(d[17]), "+f"(d[18]), "+f"(d[19]), "+f"(d[20]), "+f"(d[21]), "+f"(d[22]), "+f"(d[23]),
    "+f"(d[24]), "+f"(d[25]), "+f"(d[26]), "+f"(d[27]), "+f"(d[28]), "+f"(d[29]), "+f"(d[30]), "+f"(d[31]),
    "+f"(d[32]), "+f"(d[33]), "+f"(d[34]), "+f"(d[35]), "+f"(d[36]), "+f"(d[37]), "+f"(d[38]), "+f"(d[39]),
    "+f"(d[40]), "+f"(d[41]), "+f"(d[42]), "+f"(d[43]), "+f"(d[44]), "+f"(d[45]), "+f"(d[46]), "+f"(d[47]),
    "+f"(d[48]), "+f"(d[49]), "+f"(d[50]), "+f"(d[51]), "+f"(d[52]), "+f"(d[53]), "+f"(d[54]), "+f"(d[55]),
    "+f"(d[56]), "+f"(d[57]), "+f"(d[58]), "+f"(d[59]), "+f"(d[60]), "+f"(d[61]), "+f"(d[62]), "+f"(d[63])
  : "l"(da), "l"(db), "n"(TA), "n"(TB));
}
template <int TA, int TB> __device__ __forceinline__ void wgmma_192(float (&d)[96], uint64_t da, uint64_t db) {
  asm volatile("wgmma.mma_async.sync.aligned.m64n192k16.f32.bf16.bf16 {"
  "%0, %1, %2, %3, %4, %5, %6, %7, %8, %9, %10, %11, %12, %13, %14, %15, "
  "%16, %17, %18, %19, %20, %21, %22, %23, %24, %25, %26, %27, %28, %29, %30, %31, "
  "%32, %33, %34, %35, %36, %37, %38, %39, %40, %41, %42, %43, %44, %45, %46, %47, "
  "%48, %49, %50, %51, %52, %53, %54, %55, %56, %57, %58, %59, %60, %61, %62, %63, "
  "%64, %65, %66, %67, %68, %69, %70, %71, %72, %73, %74, %75, %76, %77, %78, %79, "
  "%80, %81, %82, %83, %84, %85, %86, %87, %88, %89, %90, %91, %92, %93, %94, %95"
  "}, %96, %97, 1, 1, 1, %98, %99;\n"
  : "+f"(d[0]), "+f"(d[1]), "+f"(d[2]), "+f"(d[3]), "+f"(d[4]), "+f"(d[5]), "+f"(d[6]), "+f"(d[7]),
    "+f"(d[8]), "+f"(d[9]), "+f"(d[10]), "+f"(d[11]), "+f"(d[12]), "+f"(d[13]), "+f"(d[14]), "+f"(d[15]),
    "+f"(d[16]), "+f"(d[17]), "+f"(d[18]), "+f"(d[19]), "+f"(d[20]), "+f"(d[21]), "+f"(d[22]), "+f"(d[23]),
    "+f"(d[24]), "+f"(d[25]), "+f"(d[26]), "+f"(d[27]), "+f"(d[28]), "+f"(d[29]), "+f"(d[30]), "+f"(d[31]),
    "+f"(d[32]), "+f"(d[33]), "+f"(d[34]), "+f"(d[35]), "+f"(d[36]), "+f"(d[37]), "+f"(d[38]), "+f"(d[39]),
    "+f"(d[40]), "+f"(d[41]), "+f"(d[42]), "+f"(d[43]), "+f"(d[44]), "+f"(d[45]), "+f"(d[46]), "+f"(d[47]),
    "+f"(d[48]), "+f"(d[49]), "+f"(d[50]), "+f"(d[51]), "+f"(d[52]), "+f"(d[53]), "+f"(d[54]), "+f"(d[55]),
    "+f"(d[56]), "+f"(d[57]), "+f"(d[58]), "+f"(d[59]), "+f"(d[60]), "+f"(d[61]), "+f"(d[62]), "+f"(d[63]),
    "+f"(d[64]), "+f"(d[65]), "+f"(d[66]), "+f"(d[67]), "+f"(d[68]), "+f"(d[69]), "+f"(d[70]), "+f"(d[71]),
    "+f"(d[72]), "+f"(d[73]), "+f"(d[74]), "+f"(d[75]), "+f"(d[76]), "+f"(d[77]), "+f"(d[78]), "+f"(d[79]),
    "+f"(d[80]), "+f"(d[81]), "+f"(d[82]), "+f"(d[83]), "+f"(d[84]), "+f"(d[85]), "+f"(d[86]), "+f"(d[87]),
    "+f"(d[88]), "+f"(d[89]), "+f"(d[90]), "+f"(d[91]), "+f"(d[92]), "+f"(d[93]), "+f"(d[94]), "+f"(d[95])
  : "l"(da), "l"(db), "n"(TA), "n"(TB));
}
template <int TA, int TB> __device__ __forceinline__ void wgmma_192z(float (&d)[96], uint64_t da, uint64_t db) {
  asm volatile("wgmma.mma_async.sync.aligned.m64n192k16.f32.bf16.bf16 {"
  "%0, %1, %2, %3, %4, %5, %6, %7, %8, %9, %10, %11, %12, %13, %14, %15, "
  "%16, %17, %18, %19, %20, %21, %22, %23, %24, %25, %26, %27, %28, %29, %30, %31, "
  "%32, %33, %34, %35, %36, %37, %38, %39, %40, %41, %42, %43, %44, %45, %46, %47, "
  "%48, %49, %50, %51, %52, %53, %54, %55, %56, %57, %58, %59, %60, %61, %62, %63, "
  "%64, %65, %66, %67, %68, %69, %70, %71, %72, %73, %74, %75, %76, %77, %78, %79, "
  "%80, %81, %82, %83, %84, %85, %86, %87, %88, %89, %90, %91, %92, %93, %94, %95"
  "}, %96, %97, 0, 1, 1, %98, %99;\n"
  : "=f"(d[0]), "=f"(d[1]), "=f"(d[2]), "=f"(d[3]), "=f"(d[4]), "=f"(d[5]), "=f"(d[6]), "=f"(d[7]),
    "=f"(d[8]), "=f"(d[9]), "=f"(d[10]), "=f"(d[11]), "=f"(d[12]), "=f"(d[13]), "=f"(d[14]), "=f"(d[15]),
    "=f"(d[16]), "=f"(d[17]), "=f"(d[18]), "=f"(d[19]), "=f"(d[20]), "=f"(d[21]), "=f"(d[22]), "=f"(d[23]),
    "=f"(d[24]), "=f"(d[25]), "=f"(d[26]), "=f"(d[27]), "=f"(d[28]), "=f"(d[29]), "=f"(d[30]), "=f"(d[31]),
    "=f"(d[32]), "=f"(d[33]), "=f"(d[34]), "=f"(d[35]), "=f"(d[36]), "=f"(d[37]), "=f"(d[38]), "=f"(d[39]),
    "=f"(d[40]), "=f"(d[41]), "=f"(d[42]), "=f"(d[43]), "=f"(d[44]), "=f"(d[45]), "=f"(d[46]), "=f"(d[47]),
    "=f"(d[48]), "=f"(d[49]), "=f"(d[50]), "=f"(d[51]), "=f"(d[52]), "=f"(d[53]), "=f"(d[54]), "=f"(d[55]),
    "=f"(d[56]), "=f"(d[57]), "=f"(d[58]), "=f"(d[59]), "=f"(d[60]), "=f"(d[61]), "=f"(d[62]), "=f"(d[63]),
    "=f"(d[64]), "=f"(d[65]), "=f"(d[66]), "=f"(d[67]), "=f"(d[68]), "=f"(d[69]), "=f"(d[70]), "=f"(d[71]),
    "=f"(d[72]), "=f"(d[73]), "=f"(d[74]), "=f"(d[75]), "=f"(d[76]), "=f"(d[77]), "=f"(d[78]), "=f"(d[79]),
    "=f"(d[80]), "=f"(d[81]), "=f"(d[82]), "=f"(d[83]), "=f"(d[84]), "=f"(d[85]), "=f"(d[86]), "=f"(d[87]),
    "=f"(d[88]), "=f"(d[89]), "=f"(d[90]), "=f"(d[91]), "=f"(d[92]), "=f"(d[93]), "=f"(d[94]), "=f"(d[95])
  : "l"(da), "l"(db), "n"(TA), "n"(TB));
}
template <int TA, int TB> __device__ __forceinline__ void wgmma_224(float (&d)[112], uint64_t da, uint64_t db) {
  asm volatile("wgmma.mma_async.sync.aligned.m64n224k16.f32.bf16.bf16 {"
  "%0, %1, %2, %3, %4, %5, %6, %7, %8, %9, %10, %11, %12, %13, %14, %15, "
  "%16, %17, %18, %19, %20, %21, %22, %23, %24, %25, %26, %27, %28, %29, %30, %31, "
  "%32, %33, %34, %35, %36, %37, %38, %39, %40, %41, %42, %43, %44, %45, %46, %47, "
  "%48, %49, %50, %51, %52, %53, %54, %55, %56, %57, %58, %59, %60, %61, %62, %63, "
  "%64, %65, %66, %67, %68, %69, %70, %71, %72, %73, %74, %75, %76, %77, %78, %79, "
  "%80, %81, %82, %83, %84, %85, %86, %87, %88, %89, %90, %91, %92, %93, %94, %95, "
  "%96, %97, %98, %99, %100, %101, %102, %103, %104, %105, %106, %107, %108, %109, %110, %111"
  "}, %112, %113, 1, 1, 1, %114, %115;\n"
  : "+f"(d[0]), "+f"(d[1]), "+f"(d[2]), "+f"(d[3]), "+f"(d[4]), "+f"(d[5]), "+f"(d[6]), "+f"(d[7]),
    "+f"(d[8]), "+f"(d[9]), "+f"(d[10]), "+f"(d[11]), "+f"(d[12]), "+f"(d[13]), "+f"(d[14]), "+f"(d[15]),
    "+f"(d[16]), "+f"(d[17]), "+f"(d[18]), "+f"(d[19]), "+f"(d[20]), "+f"(d[21]), "+f"(d[22]), "+f"(d[23]),
    "+f"(d[24]), "+f"(d[25]), "+f"(d[26]), "+f"(d[27]), "+f"(d[28]), "+f"(d[29]), "+f"(d[30]), "+f"(d[31]),
    "+f"(d[32]), "+f"(d[33]), "+f"(d[34]), "+f"(d[35]), "+f"(d[36]), "+f"(d[37]), "+f"(d[38]), "+f"(d[39]),
    "+f"(d[40]), "+f"(d[41]), "+f"(d[42]), "+f"(d[43]), "+f"(d[44]), "+f"(d[45]), "+f"(d[46]), "+f"(d[47]),
    "+f"(d[48]), "+f"(d[49]), "+f"(d[50]), "+f"(d[51]), "+f"(d[52]), "+f"(d[53]), "+f"(d[54]), "+f"(d[55]),
    "+f"(d[56]), "+f"(d[57]), "+f"(d[58]), "+f"(d[59]), "+f"(d[60]), "+f"(d[61]), "+f"(d[62]), "+f"(d[63]),
    "+f"(d[64]), "+f"(d[65]), "+f"(d[66]), "+f"(d[67]), "+f"(d[68]), "+f"(d[69]), "+f"(d[70]), "+f"(d[71]),
    "+f"(d[72]), "+f"(d[73]), "+f"(d[74]), "+f"(d[75]), "+f"(d[76]), "+f"(d[77]), "+f"(d[78]), "+f"(d[79]),
    "+f"(d[80]), "+f"(d[81]), "+f"(d[82]), "+f"(d[83]), "+f"(d[84]), "+f"(d[85]), "+f"(d[86]), "+f"(d[87]),
    "+f"(d[88]), "+f"(d[89]), "+f"(d[90]), "+f"(d[91]), "+f"(d[92]), "+f"(d[93]), "+f"(d[94]), "+f"(d[95]),
    "+f"(d[96]), "+f"(d[97]), "+f"(d[98]), "+f"(d[99]), "+f"(d[100]), "+f"(d[101]), "+f"(d[102]), "+f"(d[103]),
    "+f"(d[104]), "+f"(d[105]), "+f"(d[106]), "+f"(d[107]), "+f"(d[108]), "+f"(d[109]), "+f"(d[110]), "+f"(d[111])
  : "l"(da), "l"(db), "n"(TA), "n"(TB));
}

__device__ __forceinline__ uint32_t smem_u32(const void* p) { return (uint32_t)__cvta_generic_to_shared(p); }
__device__ __forceinline__ void mbar_init(uint32_t bar, uint32_t cnt) { asm volatile("mbarrier.init.shared::cta.b64 [%0], %1;" ::"r"(bar), "r"(cnt) : "memory"); }
__device__ __forceinline__ void mbar_expect(uint32_t bar, uint32_t bytes) { asm volatile("mbarrier.arrive.expect_tx.shared::cta.b64 _, [%0], %1;" ::"r"(bar), "r"(bytes) : "memory"); }
__device__ __forceinline__ void mbar_arrive(uint32_t bar) { asm volatile("mbarrier.arrive.shared::cta.b64 _, [%0];" ::"r"(bar) : "memory"); }
__device__ __forceinline__ void mbar_arrive_cl(uint32_t cbar) { asm volatile("mbarrier.arrive.shared::cluster.b64 _, [%0];" ::"r"(cbar) : "memory"); }
__device__ __forceinline__ uint32_t mapa(uint32_t a, uint32_t cta) { uint32_t r; asm("mapa.shared::cluster.u32 %0, %1, %2;" : "=r"(r) : "r"(a), "r"(cta)); return r; }
__device__ __forceinline__ void mbar_wait(uint32_t bar, uint32_t parity) {
  asm volatile("{\n.reg .pred p;\n.reg .u32 n;\nmov.u32 n, 0;\n"
    "LAB_WAIT:\n"
    "mbarrier.try_wait.parity.shared::cta.b64 p, [%0], %1;\n"
    "@p bra LAB_DONE;\n"
    "add.u32 n, n, 1;\n"
    "setp.lt.u32 p, n, 2000000;\n"
    "@p bra LAB_WAIT;\n"
    "trap;\n"
    "LAB_DONE:\n}\n" ::"r"(bar), "r"(parity) : "memory");
}
constexpr uint32_t SPIN_MAX = 2000000;
__device__ __forceinline__ void tma2d(uint32_t dst, const CUtensorMap* m, uint32_t bar, int c0, int c1) {
  asm volatile("cp.async.bulk.tensor.2d.shared::cluster.global.mbarrier::complete_tx::bytes [%0], [%1, {%3, %4}], [%2];"
    ::"r"(dst), "l"(m), "r"(bar), "r"(c0), "r"(c1) : "memory");
}
__device__ __forceinline__ void tma2d_mc(uint32_t dst, const CUtensorMap* m, uint32_t bar, int c0, int c1) {
  asm volatile("cp.async.bulk.tensor.2d.shared::cluster.global.mbarrier::complete_tx::bytes.multicast::cluster [%0], [%1, {%3, %4}], [%2], %5;"
    ::"r"(dst), "l"(m), "r"(bar), "r"(c0), "r"(c1), "h"((uint16_t)3) : "memory");
}
__device__ __forceinline__ void tma3d(uint32_t dst, const CUtensorMap* m, uint32_t bar, int c0, int c1, int c2) {
  asm volatile("cp.async.bulk.tensor.3d.shared::cluster.global.mbarrier::complete_tx::bytes [%0], [%1, {%3, %4, %5}], [%2];"
    ::"r"(dst), "l"(m), "r"(bar), "r"(c0), "r"(c1), "r"(c2) : "memory");
}
__device__ __forceinline__ void tma3d_mc(uint32_t dst, const CUtensorMap* m, uint32_t bar, int c0, int c1, int c2) {
  asm volatile("cp.async.bulk.tensor.3d.shared::cluster.global.mbarrier::complete_tx::bytes.multicast::cluster [%0], [%1, {%3, %4, %5}], [%2], %6;"
    ::"r"(dst), "l"(m), "r"(bar), "r"(c0), "r"(c1), "r"(c2), "h"((uint16_t)3) : "memory");
}
__device__ __forceinline__ void tma2d_store(const CUtensorMap* m, uint32_t src, int c0, int c1) {
  asm volatile("cp.async.bulk.tensor.2d.global.shared::cta.bulk_group [%0, {%2, %3}], [%1];" ::"l"(m), "r"(src), "r"(c0), "r"(c1) : "memory");
}
__device__ __forceinline__ void bulk_ld(uint32_t dst, const void* src, uint32_t bytes, uint32_t bar) {
  asm volatile("cp.async.bulk.shared::cluster.global.mbarrier::complete_tx::bytes [%0], [%1], %2, [%3];" ::"r"(dst), "l"(src), "r"(bytes), "r"(bar) : "memory");
}
__device__ __forceinline__ void bulk_ld_mc(uint32_t dst, const void* src, uint32_t bytes, uint32_t bar) {
  asm volatile("cp.async.bulk.shared::cluster.global.mbarrier::complete_tx::bytes.multicast::cluster [%0], [%1], %2, [%3], %4;"
    ::"r"(dst), "l"(src), "r"(bytes), "r"(bar), "h"((uint16_t)3) : "memory");
}
__device__ __forceinline__ void bulk_commit() { asm volatile("cp.async.bulk.commit_group;" ::: "memory"); }
__device__ __forceinline__ void bulk_wait0() { asm volatile("cp.async.bulk.wait_group 0;" ::: "memory"); }
__device__ __forceinline__ void fence_async_smem() { asm volatile("fence.proxy.async.shared::cta;" ::: "memory"); }
__device__ __forceinline__ void wg_fence() { asm volatile("wgmma.fence.sync.aligned;" ::: "memory"); }
__device__ __forceinline__ void wg_commit() { asm volatile("wgmma.commit_group.sync.aligned;" ::: "memory"); }
template <int N> __device__ __forceinline__ void wg_wait() { asm volatile("wgmma.wait_group.sync.aligned %0;" ::"n"(N) : "memory"); }
template <int R> __device__ __forceinline__ void reg_alloc() { asm volatile("setmaxnreg.inc.sync.aligned.u32 %0;" ::"n"(R)); }
template <int R> __device__ __forceinline__ void reg_dealloc() { asm volatile("setmaxnreg.dec.sync.aligned.u32 %0;" ::"n"(R)); }
__device__ __forceinline__ void cluster_sync() { asm volatile("barrier.cluster.arrive.release;\nbarrier.cluster.wait.acquire;" ::: "memory"); }
__device__ __forceinline__ void cluster_exit() { asm volatile("barrier.cluster.arrive.relaxed;\nbarrier.cluster.wait;" ::: "memory"); }
template <int ID> __device__ __forceinline__ void nb_sync(int n) { asm volatile("barrier.sync %0, %1;" ::"n"(ID), "r"(n) : "memory"); }
template <int ID> __device__ __forceinline__ void nb_arrive(int n) { asm volatile("barrier.arrive %0, %1;" ::"n"(ID), "r"(n) : "memory"); }
__device__ __forceinline__ int fresh_tid() { int t; asm volatile("mov.u32 %0, %%tid.x;" : "=r"(t)); return t; }
struct True { static constexpr bool value = true; };
struct False { static constexpr bool value = false; };
template <int N> __device__ __forceinline__ void fence_regs(float (&d)[N]) {
#pragma unroll
  for (int i = 0; i < N; i++) asm volatile("" : "+f"(d[i])::"memory");
}
__device__ __forceinline__ uint64_t mkdesc(uint32_t addr, uint32_t lbo, uint32_t sbo) {
  return (uint64_t)((addr & 0x3FFFF) >> 4) | ((uint64_t)(lbo >> 4) << 16) | ((uint64_t)(sbo >> 4) << 32) | (1ull << 62);
}
__device__ __forceinline__ uint32_t pack2(float lo, float hi) { uint32_t r; asm("cvt.rn.bf16x2.f32 %0, %1, %2;" : "=r"(r) : "f"(hi), "f"(lo)); return r; }
__device__ __forceinline__ float bf_lo(uint32_t v) { return __uint_as_float(v << 16); }
__device__ __forceinline__ float bf_hi(uint32_t v) { return __uint_as_float(v & 0xffff0000u); }
__device__ __forceinline__ void stsm4(uint32_t a, uint32_t r0, uint32_t r1, uint32_t r2, uint32_t r3) {
  asm volatile("stmatrix.sync.aligned.m8n8.x4.shared.b16 [%0], {%1, %2, %3, %4};" ::"r"(a), "r"(r0), "r"(r1), "r"(r2), "r"(r3) : "memory");
}
__device__ __forceinline__ void stsm4t(uint32_t a, uint32_t r0, uint32_t r1, uint32_t r2, uint32_t r3) {
  asm volatile("stmatrix.sync.aligned.m8n8.x4.trans.shared.b16 [%0], {%1, %2, %3, %4};" ::"r"(a), "r"(r0), "r"(r1), "r"(r2), "r"(r3) : "memory");
}
__device__ __forceinline__ void ldsm4(uint32_t a, uint32_t& r0, uint32_t& r1, uint32_t& r2, uint32_t& r3) {
  asm volatile("ldmatrix.sync.aligned.m8n8.x4.shared.b16 {%0, %1, %2, %3}, [%4];" : "=r"(r0), "=r"(r1), "=r"(r2), "=r"(r3) : "r"(a) : "memory");
}
__device__ __forceinline__ uint32_t movm(uint32_t a) { uint32_t d; asm volatile("movmatrix.sync.aligned.m8n8.trans.b16 %0, %1;" : "=r"(d) : "r"(a)); return d; }
__device__ __forceinline__ void mma16816(float (&c)[4], uint32_t a0, uint32_t a1, uint32_t a2, uint32_t a3, uint32_t b0, uint32_t b1) {
  asm volatile("mma.sync.aligned.m16n8k16.row.col.f32.bf16.bf16.f32 {%0, %1, %2, %3}, {%4, %5, %6, %7}, {%8, %9}, {%0, %1, %2, %3};"
    : "+f"(c[0]), "+f"(c[1]), "+f"(c[2]), "+f"(c[3]) : "r"(a0), "r"(a1), "r"(a2), "r"(a3), "r"(b0), "r"(b1));
}
__device__ __forceinline__ void sts128(uint32_t a, uint32_t r0, uint32_t r1, uint32_t r2, uint32_t r3) {
  asm volatile("st.shared.v4.b32 [%0], {%1, %2, %3, %4};" ::"r"(a), "r"(r0), "r"(r1), "r"(r2), "r"(r3) : "memory");
}
__device__ __forceinline__ void lds128(uint32_t a, uint32_t& r0, uint32_t& r1, uint32_t& r2, uint32_t& r3) {
  asm volatile("ld.shared.v4.b32 {%0, %1, %2, %3}, [%4];" : "=r"(r0), "=r"(r1), "=r"(r2), "=r"(r3) : "r"(a) : "memory");
}
__device__ __forceinline__ float2 lds64f(uint32_t a) { float2 v; asm volatile("ld.shared.v2.f32 {%0, %1}, [%2];" : "=f"(v.x), "=f"(v.y) : "r"(a) : "memory"); return v; }
__device__ __forceinline__ void sts64f(uint32_t a, float x, float y) { asm volatile("st.shared.v2.f32 [%0], {%1, %2};" ::"r"(a), "f"(x), "f"(y) : "memory"); }
__device__ __forceinline__ float lds32f(uint32_t a) { float v; asm volatile("ld.shared.f32 %0, [%1];" : "=f"(v) : "r"(a) : "memory"); return v; }
__device__ __forceinline__ void sts32f(uint32_t a, float x) { asm volatile("st.shared.f32 [%0], %1;" ::"r"(a), "f"(x) : "memory"); }
__device__ __forceinline__ void ll_st2(uint4* p, uint32_t a, uint32_t b, uint32_t tag) {
  asm volatile("{\n.reg .b64 x, y;\nmov.b64 x, {%1, %3};\nmov.b64 y, {%2, %3};\nst.relaxed.gpu.global.v2.b64 [%0], {x, y};\n}\n" ::"l"(p), "r"(a), "r"(b), "r"(tag) : "memory");
}
__device__ __forceinline__ uint32_t ll_ld2(const uint4* p, uint32_t& a, uint32_t& b, uint32_t tag) {
  uint32_t t0, t1;
  asm volatile("{\n.reg .b64 x, y;\nld.relaxed.gpu.global.v2.b64 {x, y}, [%4];\nmov.b64 {%0, %1}, x;\nmov.b64 {%2, %3}, y;\n}\n" : "=r"(a), "=r"(t0), "=r"(b), "=r"(t1) : "l"(p) : "memory");
  return (t0 ^ tag) | (t1 ^ tag);
}
__device__ __forceinline__ void ll_st3(uint4* p, uint32_t a, uint32_t b, uint32_t c, uint32_t tag) {
  asm volatile("{\n.reg .b64 x, y;\n.reg .b128 z;\nmov.b64 x, {%1, %2};\nmov.b64 y, {%3, %4};\nmov.b128 z, {x, y};\nst.relaxed.gpu.global.b128 [%0], z;\n}\n"
    ::"l"(p), "r"(a), "r"(b), "r"(c), "r"(tag) : "memory");
}
__device__ __forceinline__ uint32_t ll_ld3(const uint4* p, uint32_t& a, uint32_t& b, uint32_t& c, uint32_t tag) {
  uint32_t t;
  asm volatile("{\n.reg .b64 x, y;\n.reg .b128 z;\nld.relaxed.gpu.global.b128 z, [%4];\nmov.b128 {x, y}, z;\nmov.b64 {%0, %1}, x;\nmov.b64 {%2, %3}, y;\n}\n"
    : "=r"(a), "=r"(b), "=r"(c), "=r"(t) : "l"(p) : "memory");
  return t ^ tag;
}
__device__ __forceinline__ void warp_store(uint8_t* dst, uint32_t src, int bytes) {
#pragma unroll 1
  for (int o = 0; o < bytes; o += 2048) {
    uint4 v[4];
#pragma unroll
    for (int k = 0; k < 4; k++) lds128(src + o + k * 512, v[k].x, v[k].y, v[k].z, v[k].w);
#pragma unroll
    for (int k = 0; k < 4; k++) asm volatile("st.global.v4.b32 [%0], {%1, %2, %3, %4};" ::"l"(dst + o + k * 512), "r"(v[k].x), "r"(v[k].y), "r"(v[k].z), "r"(v[k].w) : "memory");
  }
  __syncwarp();
}
__device__ __forceinline__ void warp_send(uint32_t cdst, uint32_t src, int bytes, uint32_t cbar) {
#pragma unroll 1
  for (int o = 0; o < bytes; o += 2048) {
    uint4 v[4];
#pragma unroll
    for (int k = 0; k < 4; k++) lds128(src + o + k * 512, v[k].x, v[k].y, v[k].z, v[k].w);
#pragma unroll
    for (int k = 0; k < 4; k++)
      asm volatile("st.async.weak.shared::cluster.mbarrier::complete_tx::bytes.v4.b32 [%0], {%1, %2, %3, %4}, [%5];"
        ::"r"(cdst + o + k * 512), "r"(v[k].x), "r"(v[k].y), "r"(v[k].z), "r"(v[k].w), "r"(cbar) : "memory");
  }
  __syncwarp();
}
typedef unsigned long long u64;
__device__ __forceinline__ void flag_set(u64* p, u64 bit) { asm volatile("red.release.gpu.global.xor.b64 [%0], %1;" ::"l"(p), "l"(bit) : "memory"); }
__device__ __forceinline__ void flag_wait(const u64* p, u64 inv, u64 need, u64& ready) {
  if ((ready & need) == need) return;
  uint32_t n = 0;
  do {
    asm volatile("ld.acquire.gpu.global.b64 %0, [%1];" : "=l"(ready) : "l"(p) : "memory");
    ready ^= inv;
  } while ((ready & need) != need && ++n < SPIN_MAX);
  asm volatile("fence.proxy.async.global;" ::: "memory");
}
__device__ __forceinline__ bool elect_one() {
  uint32_t p;
  asm volatile("{\n.reg .pred P;\nelect.sync _|P, 0xffffffff;\nselp.u32 %0, 1, 0, P;\n}\n" : "=r"(p));
  return p;
}
__device__ __forceinline__ float gelu_half(float hx) {
  const float y = hx * fmaf(hx * hx, 8.f * 0.0356774081f, 2.f * 0.7978845608f);
  float th;
  asm("tanh.approx.f32 %0, %1;" : "=f"(th) : "f"(y));
  return fmaf(hx, th, hx);
}
__device__ __forceinline__ float ex2(float x) { float y; asm("ex2.approx.ftz.f32 %0, %1;" : "=f"(y) : "f"(x)); return y; }

template <int NP>
__device__ __forceinline__ void stats_gather(const uint4* p, uint32_t tag, float& mean, float& var) {
  uint32_t a[NP / 2], b[NP / 2], n = 0, bad;
  do {
    bad = 0;
#pragma unroll
    for (int k = 0; k < NP / 2; k++) bad |= ll_ld2(p + k * 128, a[k], b[k], tag);
  } while (bad && ++n < SPIN_MAX);
  __syncwarp();
  float s = 0.f, q = 0.f;
#pragma unroll
  for (int k = 0; k < NP / 2; k++) { s += __uint_as_float(a[k]); q += __uint_as_float(b[k]); }
  s += __shfl_xor_sync(0xffffffffu, s, 2); q += __shfl_xor_sync(0xffffffffu, q, 2);
  mean = s * (1.f / D_);
  var = fmaxf(fmaf(-mean, mean, q * (1.f / D_)), 0.f);
}

__device__ __forceinline__ void attn_probs(const uint32_t* q0, const uint32_t* q1,
                                           const uint32_t* k0, const uint32_t* k1, const uint32_t* k2, const uint32_t* k3,
                                           float sc0, float sc1, bool first, bool e, bool zneg, uint32_t (&pr)[6]) {
  float s[4][4];
#pragma unroll
  for (int n = 0; n < 4; n++) {
    const uint32_t* k = n == 0 ? k0 : n == 1 ? k1 : n == 2 ? k2 : k3;
    s[n][0] = s[n][1] = s[n][2] = s[n][3] = 0.f;
    mma16816(s[n], q0[0], q1[0], q0[1], q1[1], k[0], k[1]);
    mma16816(s[n], q0[2], q1[2], q0[3], q1[3], k[2], k[3]);
  }
  const float MASKED = -1.0e9f * 1.4426950409f;
  float a0 = (e ? s[1][1] : s[1][0]) * sc0;
  float b0 = (zneg ? (e ? s[0][1] : s[0][0]) : (e ? s[2][1] : s[2][0])) * sc0;
  float a1 = (e ? s[2][3] : s[2][2]) * sc1;
  float b1 = (zneg ? (e ? s[1][3] : s[1][2]) : (e ? s[3][3] : s[3][2])) * sc1;
  if (first) { a0 = MASKED; if (zneg) { b0 = MASKED; b1 = MASKED; } }
  float m0 = fmaxf(a0, b0), m1 = fmaxf(a1, b1);
  m0 = fmaxf(m0, __shfl_xor_sync(0xffffffffu, m0, 1)); m1 = fmaxf(m1, __shfl_xor_sync(0xffffffffu, m1, 1));
  m0 = fmaxf(m0, __shfl_xor_sync(0xffffffffu, m0, 2)); m1 = fmaxf(m1, __shfl_xor_sync(0xffffffffu, m1, 2));
  a0 = ex2(a0 - m0); b0 = ex2(b0 - m0); a1 = ex2(a1 - m1); b1 = ex2(b1 - m1);
  float l0 = a0 + b0, l1 = a1 + b1;
  l0 += __shfl_xor_sync(0xffffffffu, l0, 1); l1 += __shfl_xor_sync(0xffffffffu, l1, 1);
  l0 += __shfl_xor_sync(0xffffffffu, l0, 2); l1 += __shfl_xor_sync(0xffffffffu, l1, 2);
  asm("rcp.approx.ftz.f32 %0, %0;" : "+f"(l0)); asm("rcp.approx.ftz.f32 %0, %0;" : "+f"(l1));
  const int sh = e ? 16 : 0;
  uint32_t pa0 = pack2(a0 * l0, 0.f) << sh, pb0 = pack2(b0 * l0, 0.f) << sh;
  uint32_t pa1 = pack2(a1 * l1, 0.f) << sh, pb1 = pack2(b1 * l1, 0.f) << sh;
  pr[0] = zneg ? pb0 : 0u; pr[1] = pa0; pr[2] = zneg ? 0u : pb0;
  pr[3] = zneg ? pb1 : 0u; pr[4] = pa1; pr[5] = zneg ? 0u : pb1;
}
__device__ __forceinline__ void attn_pv(const uint32_t (&pr)[6], const uint32_t* vh, const uint32_t* v, float (&o)[4][4]) {
#pragma unroll
  for (int dt = 0; dt < 4; dt++) {
    o[dt][0] = o[dt][1] = o[dt][2] = o[dt][3] = 0.f;
    mma16816(o[dt], pr[0], 0u, pr[1], pr[3], vh[2 * dt], vh[2 * dt + 1]);
    mma16816(o[dt], pr[2], pr[4], 0u, pr[5], v[2 * dt], v[2 * dt + 1]);
  }
}

__global__ void __cluster_dims__(2, 1, 1) __launch_bounds__(384, 1) fused_kernel(const __grid_constant__ Params P) {
  extern __shared__ __align__(1024) uint8_t smem_raw[];
  const uint32_t sb = smem_u32(smem_raw);
  const uint32_t bars = sb + OFF_BAR;
  const int tid = threadIdx.x;
  const int wu = __shfl_sync(0xffffffffu, tid >> 5, 0), wg = wu >> 2;
  const int r = blockIdx.x & 1, cl = blockIdx.x >> 1;
  int grp, slt;
  if (cl < 4) { grp = 0; slt = 4 + cl; }
  else if (cl < 36) { grp = (cl - 4) & 7; slt = (cl - 4) >> 3; }
  else { grp = 1 + (cl - 36) % 7; slt = 4 + (cl - 36) / 7; }
#define MAP 0
  const int m = grp, j = slt;
  const int i = 2 * m + r;
  auto BAR = [&](int k) { return bars + 8 * k; };

  if (tid == 0) {
    for (int k = 0; k < 4; k++) { mbar_init(BAR(F1 + k), 1); mbar_init(BAR(E1 + k), 4); mbar_init(BAR(F3 + k), 1); mbar_init(BAR(E3 + k), 4); }
    for (int k = 0; k < 5; k++) { mbar_init(BAR(F2 + k), 1); mbar_init(BAR(E2 + k), 4); }
    for (int k = 0; k < 6; k++) { mbar_init(BAR(F4 + k), 1); mbar_init(BAR(E4 + k), 4); }
    for (int k = 0; k < 10; k++) mbar_init(BAR(JOB + k), (k >> 1) == 1 ? 4 : 8);
    for (int k = 0; k < 6; k++) mbar_init(BAR(RD + k), k < 2 ? 4 : 2);
    for (int k = 0; k < 2; k++) { mbar_init(BAR(XF + k), 1); mbar_init(BAR(STD + k), 1); mbar_init(BAR(SEQ + k), 1); }
    mbar_init(BAR(STAT), 2); mbar_init(BAR(CSJ), 8);
    asm volatile("fence.mbarrier_init.release.cluster;" ::: "memory");
    fence_async_smem();
    for (int h = 0; h < 2; h++) {
      mbar_expect(BAR(XF + h), 16384);
      tma2d(sb + OFF_X + h * 16384, &P.x0, BAR(XF + h), 128 * j + 64 * h, 128 * i);
    }
  }
  uint32_t tag;
  asm volatile("ld.relaxed.gpu.global.u32 %0, [%1];" : "=r"(tag) : "l"(&gEpoch) : "memory");
  tag += 1;
  TS(0);
  cluster_sync();

  if (wg == 2) {
    reg_dealloc<40>();
    const u64 inv = (tag & 1) ? 0ull : ~0ull;
    auto kb1 = [&](int n) { const int h = n >= 9, t = n - 2 - 7 * h; return n < 2 ? 2 * j + n : 2 * (t + (t >= j)) + h; };
    auto kb3 = [&](int n) { const int h = n >= 18, t = n - 4 - 14 * h; return n < 4 ? 2 * (i ^ (n >> 1)) + (n & 1) : 2 * ((2 * m + 2 + t) & 15) + h; };
    auto kb4 = [&](int c, int t) { const int ii = (2 * m + 2 + t) & 15; return 7 * (ii >> 1) + 4 * (ii & 1) + c; };
    if (wu == 8) {
      if (elect_one()) {
#pragma unroll 1
        for (int L = 0; L < 2; L++) {
#pragma unroll 1
          for (int u = 0; u < 32; u++) {
            const int v = (L && u >= 2 && u < 18) ? (u < 4 ? u + 14 : u - 2) : u;
            const int p = u & 3, ab = v >> 4, nn = v & 15;
            if (u >= 4) mbar_wait(BAR(E1 + p), ((u >> 2) - 1) & 1);
            else if (L) mbar_wait(BAR(E4 + (u == 3 ? 0 : u + 3)), u == 3);
            mbar_expect(BAR(F1 + p), nn < 2 ? 24576 : 40960);
            tma3d_mc(sb + slot1(p) + 16384 + r * 12288, &P.wqkv, BAR(F1 + p), 128 * j + 64 * ab, kb1(nn) * 64 + 32 * r, 0);
          }
          int p = 0; uint32_t par = L ? 0x1e : 0;
#pragma unroll 1
          for (int n = 0; n < 16; n++) {
            if (n >= 5) { mbar_wait(BAR(E2 + p), (par >> p) & 1); par ^= 1u << p; }
            else if (n < 4) mbar_wait(BAR(E1 + n), 1);
            mbar_expect(BAR(F2 + p), 32768);
            tma2d_mc(sb + slot2(p) + 16384 + r * 8192, &P.wo, BAR(F2 + p), 128 * j + 64 * r, (2 * (n & 7) + (n >> 3)) * 64);
            if (++p == 5) p = 0;
          }
#pragma unroll 1
          for (int u = 0; u < 32; u++) {
            const int n = u < 2 ? u ^ 1 : u, p = n & 3, kb = kb3(n);
            if (n >= 4) mbar_wait(BAR(E3 + p), ((n >> 2) - 1) & 1);
            else if (n == 1) mbar_wait(BAR(STD + 1), L);
            else if (n == 0) mbar_wait(BAR(E2 + 4), L);
            else if (n == 2) { mbar_wait(BAR(E2 + 0), 1); mbar_wait(BAR(JOB + 2), L); }
            mbar_expect(BAR(F3 + p), n < 2 ? 32768 : 49152);
            tma3d(sb + slot3(p) + 16384, &P.w1, BAR(F3 + p), 0, kb * 64, 7 * m + 4 * r);
            tma3d(sb + slot3(p) + 40960, &P.w1h, BAR(F3 + p), 0, kb * 64, 14 * m + 6 + r);
          }
#pragma unroll 1
          for (int n = 0; n < 6; n++) {
            if (n < 3) mbar_wait(BAR(E3 + n), 1);
            else if (n == 4) mbar_wait(BAR(E3 + 3), 1);
            mbar_expect(BAR(F4 + n), n < 3 ? 16384 : 32768);
            tma3d(sb + slot4(n), &P.w2, BAR(F4 + n), 0, (n < 3 ? 7 * m + 4 * r + n : 7 * ((m + n - 3) & 7) + 3) * 64, 2 * i);
          }
          p = 0; par = L ? 0x3c : 0;
          auto g4w = [&](int kb) {
            mbar_wait(BAR(E4 + p), (par >> p) & 1); par ^= 1u << p;
            mbar_expect(BAR(F4 + p), 32768);
            tma3d(sb + slot4(p), &P.w2, BAR(F4 + p), 0, kb * 64, 2 * i);
            if (++p == 6) p = 0;
          };
#pragma unroll 1
          for (int t = 3; t < 8; t++) g4w(7 * ((m + t) & 7) + 3);
#pragma unroll 1
          for (int c = 0; c < 3; c++)
#pragma unroll 1
            for (int t = 0; t < 15; t++) g4w(t < 14 ? kb4(c, t) : 7 * m + 4 - 4 * r + c);
        }
      }
    } else if (wu == 9) {
      if (elect_one()) {
#pragma unroll 1
        for (int L = 0; L < 2; L++) {
          u64 ready = 0;
#pragma unroll 1
          for (int u = 2 + 2 * L; u < 32; u++) {
            const int p = u & 3, nn = (L && u < 18 ? u - 2 : u) & 15, kb = kb1(nn);
            if (nn < 2) continue;
            if (L && u < 8) mbar_wait(BAR(F1 + p), 0);
            else if (u >= 4) mbar_wait(BAR(E1 + p), ((u >> 2) - 1) & 1);
            if (L) {
              flag_wait(gFlag[0][0][i], inv, 1ull << kb, ready);
              bulk_ld(sb + slot1(p), gXB + (i * 16 + kb) * 16384, 16384, BAR(F1 + p));
            } else tma2d(sb + slot1(p), &P.x0, BAR(F1 + p), kb * 64, 128 * i);
          }
          ready = 0;
          int p = 0; uint32_t par = L ? 0x1e : 0;
#pragma unroll 1
          for (int n = 0; n < 16; n++) {
            const int hp = 2 * (n & 7) + (n >> 3);
            if (n >= 5) { mbar_wait(BAR(E2 + p), (par >> p) & 1); par ^= 1u << p; }
            else if (n < 4) mbar_wait(BAR(E1 + n), 1);
            flag_wait(gFlag[L][1][i], inv, 1ull << hp, ready);
            bulk_ld(sb + slot2(p), gOB + (i * 16 + hp) * 16384, 16384, BAR(F2 + p));
            if (++p == 5) p = 0;
          }
          ready = 0;
#pragma unroll 1
          for (int n = 4; n < 32; n++) {
            const int p = n & 3, kb = kb3(n);
            if (n < 6) mbar_wait(BAR(RD + n - 4), L);
            mbar_wait(BAR(E3 + p), ((n >> 2) - 1) & 1);
            flag_wait(gFlag[L][2][j], inv, 1ull << kb, ready);
            bulk_ld_mc(sb + slot3(p) + r * 8192, gHB + (j * 32 + kb) * 16384 + r * 8192, 8192, BAR(F3 + p));
          }
          ready = 0; p = 3; par = L ? 0x3c : 0;
          auto g4a = [&](int kb, u64 need, bool mc) {
            flag_wait(gFlag[L][3][j], inv, need, ready);
            const uint8_t* src = gUB + (j * 56 + kb) * 16384;
            if (mc) bulk_ld_mc(sb + slot4(p) + 16384 + r * 8192, src + r * 8192, 8192, BAR(F4 + p));
            else bulk_ld(sb + slot4(p) + 16384, src, 16384, BAR(F4 + p));
            if (++p == 6) p = 0;
          };
          mbar_wait(BAR(E3 + 3), 1);
          mbar_wait(BAR(RD + 5), L);
#pragma unroll 1
          for (int t = 0; t < 8; t++) {
            const int mm = (m + t) & 7;
            if (t >= 3) { if (t < 6) mbar_wait(BAR(RD + t - 1), L); mbar_wait(BAR(E4 + p), (par >> p) & 1); par ^= 1u << p; }
            g4a(7 * mm + 3, 3ull << (48 + 2 * mm), true);
          }
#pragma unroll 1
          for (int c = 0; c < 3; c++)
#pragma unroll 1
            for (int t = 0; t < 15; t++) {
              mbar_wait(BAR(E4 + p), (par >> p) & 1); par ^= 1u << p;
              if (t < 14) g4a(kb4(c, t), 1ull << (16 * c + ((2 * m + 2 + t) & 15)), true);
              else g4a(7 * m + 4 - 4 * r + c, 1ull << (16 * c + (i ^ 1)), false);
            }
        }
      }
    } else {
      const int h = wu - 10;
      int lane = tid & 31, z = 0;
#define FRESH asm volatile("" : "+r"(lane), "+r"(z))
      const uint32_t rs = mapa(sb, r ^ 1), rb = rs + OFF_BAR;
      auto signal = [&](int k) { if (lane == 0) mbar_arrive(BAR(k)); };
      auto drained = [&](int k) { if (lane == 0) { mbar_arrive(BAR(RD + k)); mbar_arrive_cl(rb + 8 * (RD + k)); } };
      auto publish = [&](u64* f, int bit) { if (lane == 0) flag_set(f + z, 1ull << (bit + z)); __syncwarp(); };
      for (int c = 32 * h + lane; c < 224; c += 64)
        sts32f(sb + OFF_B1 + c * 4, 0.5f * __bfloat162float(P.b1[c < 192 ? 64 * (7 * m + 4 * r) + c : 64 * (7 * m + 3) + 32 * r + c - 192]));
      mbar_wait(BAR(XF), 0); mbar_wait(BAR(XF + 1), 0);
#pragma unroll 1
      for (int L = 0; L < 2; L++) {
        FRESH;
#pragma unroll 1
        for (int k = 0; k < 2; k++) {
          const int row = 64 * h + 32 * k + lane;
          float s0 = 0.f, s1 = 0.f, q0 = 0.f, q1 = 0.f;
#pragma unroll 2
          for (int c = 0; c < 16; c++) {
            uint32_t v[4];
            lds128(sb + OFF_X + (c >> 3) * 16384 + row * 128 + (((c ^ lane) & 7) << 4), v[0], v[1], v[2], v[3]);
#pragma unroll
            for (int e = 0; e < 4; e++) { const float a = bf_lo(v[e]), b = bf_hi(v[e]); s0 += a; s1 += b; q0 = fmaf(a, a, q0); q1 = fmaf(b, b, q1); }
          }
          ll_st2(&gST[L][i][j][row], __float_as_uint(s0 + s1), __float_as_uint(q0 + q1), 2 * tag);
        }
        FRESH;
        if (L == 0) {
          mbar_wait(BAR(CSJ), 0);
          float c0 = 0.f, c1 = 0.f, c2 = 0.f;
          const uint32_t a = sb + OFF_STG + 2048 + (32 * h + lane) * 4;
#pragma unroll 4
          for (int k = 0; k < 32; k++) { c0 += lds32f(a + k * 768); c1 += lds32f(a + k * 768 + 256); c2 += lds32f(a + k * 768 + 512); }
          ll_st3(&gCS[j][i][32 * h + lane], __float_as_uint(c0), __float_as_uint(c1), __float_as_uint(c2), tag);
        }
#pragma unroll 1
        for (int k = 0; k < 2; k++) {
          const int row = 64 * h + 32 * k + lane;
          float s = 0.f, q = 0.f;
#pragma unroll 1
          for (int b4 = 0; b4 < 8; b4 += 4) {
            uint32_t a[4], b[4], n = 0, bad;
            do {
              bad = 0;
#pragma unroll
              for (int e = 0; e < 4; e++) bad |= ll_ld2(&gST[L][i][b4 + e][row], a[e], b[e], 2 * tag);
            } while (bad && ++n < SPIN_MAX);
#pragma unroll
            for (int e = 0; e < 4; e++) { s += __uint_as_float(a[e]); q += __uint_as_float(b[e]); }
          }
          const float mean = s * (1.f / D_);
          sts64f(sb + OFF_STG + row * 8, -mean, rsqrtf(fmaxf(fmaf(-mean, mean, q * (1.f / D_)), 0.f) + 1e-5f));
        }
        FRESH;
        if (L == 0) {
#pragma unroll 1
          for (int ab = 0; ab < 2; ab++) {
            float c0 = 0.f, c1 = 0.f, c2 = 0.f;
#pragma unroll 1
            for (int b4 = 0; b4 < 8; b4 += 4) {
              uint32_t a[4], b[4], c[4], n = 0, bad;
              do {
                bad = 0;
#pragma unroll
                for (int e = 0; e < 4; e++) bad |= ll_ld3(&gCS[j][2 * (b4 + e) + ab][32 * h + lane], a[e], b[e], c[e], tag);
              } while (bad && ++n < SPIN_MAX);
#pragma unroll
              for (int e = 0; e < 4; e++) { c0 += __uint_as_float(a[e]); c1 += __uint_as_float(b[e]); c2 += __uint_as_float(c[e]); }
            }
            const uint32_t a = sb + OFF_CS + (ab * 192 + 32 * h + lane) * 4;
            sts32f(a, c0); sts32f(a + 256, c1); sts32f(a + 512, c2);
          }
        }
        __syncwarp();
        signal(STAT);
        FRESH;
        mbar_wait(BAR(JOB + h), L);
        warp_store(gOB + (i * 16 + 2 * j + h) * 16384 + lane * 16, sb + lane * 16 + OFF_STG, 16384);
        signal(STD + h);
        publish(gFlag[L][1][i], 2 * j + h);
        FRESH;
        mbar_wait(BAR(JOB + 2), L);
        if (h == 0) {
          warp_store(gHB + (j * 32 + 2 * i) * 16384 + lane * 16, sb + lane * 16 + slot3(0), 16384);
          signal(SEQ); drained(0);
          publish(gFlag[L][2][j], 2 * i);
          mbar_wait(BAR(JOB + 3), L);
          warp_store(gHB + (j * 32 + 2 * i + 1) * 16384 + lane * 16, sb + lane * 16 + slot3(1), 16384);
          drained(1);
          publish(gFlag[L][2][j], 2 * i + 1);
        } else {
          mbar_wait(BAR(E2 + 0), 1);
          mbar_wait(BAR(SEQ), L);
          warp_send(rs + lane * 16 + slot3(2), sb + lane * 16 + slot3(0), 16384, rb + 8 * (F3 + 2));
          drained(0);
          mbar_wait(BAR(JOB + 3), L);
          warp_send(rs + lane * 16 + slot3(3), sb + lane * 16 + slot3(1), 16384, rb + 8 * (F3 + 3));
          drained(1);
        }
        FRESH;
        if (h == 0) {
          mbar_wait(BAR(JOB + 7), L);
#pragma unroll 1
          for (int a = 0; a < 2; a++)
            warp_store(gUB + (j * 56 + 7 * m + 3) * 16384 + a * 8192 + r * 4096 + lane * 16, sb + lane * 16 + slot4(5) + 16384 + a * 8192 + r * 4096, 4096);
          drained(5);
          publish(gFlag[L][3][j], 48 + i);
        }
#pragma unroll 1
        for (int c = 1 - h; c < 3; c += 2) {
          mbar_wait(BAR(JOB + 4 + c), L);
          warp_store(gUB + (j * 56 + 7 * m + 4 * r + c) * 16384 + lane * 16, sb + lane * 16 + slot4(c) + 16384, 16384);
          drained(2 + c);
          publish(gFlag[L][3][j], 16 * c + i);
        }
        FRESH;
        mbar_wait(BAR(JOB + 8 + h), L);
        if (L == 0) {
          if (h) mbar_wait(BAR(SEQ + 1), 0);
          warp_store(gXB + (i * 16 + 2 * j + h) * 16384 + lane * 16, sb + lane * 16 + OFF_X + h * 16384, 16384);
          if (h == 0) signal(SEQ + 1);
          publish(gFlag[0][0][i], 2 * j + h);
          mbar_wait(BAR(JOB + 9), 0);
        } else if (lane == 0) {
          tma2d_store(&P.out, sb + OFF_X + h * 16384, 128 * j + 64 * h, 128 * i);
          bulk_commit(); bulk_wait0();
        }
      }
      if (blockIdx.x == 0 && h == 0 && lane == 0) asm volatile("st.relaxed.gpu.global.u32 [%0], %1;" ::"l"(&gEpoch), "r"(tag) : "memory");
    }
    __syncwarp();
    cluster_exit();
  } else {
    reg_alloc<232>();
    const uint32_t rbars = mapa(bars, tid & 1);
    const bool relp = (tid & 127) < 2;
    auto release = [&](int k) { if (relp) mbar_arrive_cl(rbars + 8 * k); };
    auto signal = [&](int k) { __syncwarp(); if ((fresh_tid() & 31) == 0) mbar_arrive(BAR(k)); };
#define GEOM const int t7 = fresh_tid() & 127, lane = t7 & 31, w = t7 >> 5, g = lane >> 2, q = lane & 3, \
                       lr = lane & 15, lt = lane >> 4, l7 = lane & 7; (void)w; (void)g; (void)q; (void)lr; (void)lt; (void)l7

#pragma unroll 1
    for (int L = 0; L < 2; L++) {
      float acca[96], accb[96], xa[64];
      float nmean0, nmean1, rstd0, rstd1;
      uint32_t Q[2][8], K[2][8], V[16];
      auto g1_issue = [&](float (&acc)[96], uint32_t a, uint32_t st, auto first) {
        const uint64_t da = mkdesc(a + wg * 8192, 16, 1024), db = mkdesc(st + 16384, 4096, 1024);
        wg_fence();
#pragma unroll
        for (int kk = 0; kk < 4; kk++) {
          const uint64_t b = db + (((kk >> 1) * 12288 + (kk & 1) * 2048) >> 4);
          if (first.value && kk == 0) wgmma_192z<0, 1>(acc, da, b); else wgmma_192<0, 1>(acc, da + kk * 2, b);
        }
        wg_commit();
      };
      auto g1_loop = [&](float (&acc)[96], int u0, int u1, int urel) {
#pragma unroll 1
        for (int u = u0; u < u1; u++) {
          const int p = u & 3;
          mbar_wait(BAR(F1 + p), (u >> 2) & 1);
          g1_issue(acc, sb + slot1(p), sb + slot1(p), False{});
          wg_wait<1>();
          if (u > urel) release(E1 + ((u - 1) & 3));
        }
      };
      auto fold = [&](float (&acc)[96], int ab) {
        GEOM;
        const uint32_t ca = sb + OFF_CS + (ab * 192 + 2 * q) * 4;
        float2 cq[8];
#pragma unroll
        for (int t = 23; t >= 8; t--) {
          const float2 cs = lds64f(ca + 32 * t);
          if (t < 16) cq[t - 8] = lds64f(ca + 32 * (t - 8));
          const uint32_t p0 = pack2(fmaf(nmean0, cs.x, acc[4 * t]) * rstd0, fmaf(nmean0, cs.y, acc[4 * t + 1]) * rstd0);
          const uint32_t p1 = pack2(fmaf(nmean1, cs.x, acc[4 * t + 2]) * rstd1, fmaf(nmean1, cs.y, acc[4 * t + 3]) * rstd1);
          if (t < 16) { K[0][t - 8] = p0; K[1][t - 8] = p1; }
          else { V[2 * (t - 16)] = movm(p0); V[2 * (t - 16) + 1] = movm(p1); }
        }
        if (wu < 7) {
          const uint32_t a = sb + OFF_STG + (wu + 1) * 2048 + lane * 16;
#pragma unroll
          for (int c = 0; c < 4; c++) {
            sts128(a + c * 512, K[c >> 1][4 * (c & 1)], K[c >> 1][4 * (c & 1) + 1], K[c >> 1][4 * (c & 1) + 2], K[c >> 1][4 * (c & 1) + 3]);
            sts128(a + 16384 + c * 512, V[4 * c], V[4 * c + 1], V[4 * c + 2], V[4 * c + 3]);
          }
        } else if (i < 15) {
          uint4* hp = &gHalo[2 * L + ab][i][j][0][lane];
#pragma unroll
          for (int c = 0; c < 8; c++) {
            ll_st2(hp + c * 32, K[c >> 2][2 * (c & 3)], K[c >> 2][2 * (c & 3) + 1], tag);
            ll_st2(hp + (8 + c) * 32, V[2 * c], V[2 * c + 1], tag);
          }
        }
#pragma unroll
        for (int t = 0; t < 8; t++) {
          Q[0][t] = pack2(fmaf(nmean0, cq[t].x, acc[4 * t]), fmaf(nmean0, cq[t].y, acc[4 * t + 1]));
          Q[1][t] = pack2(fmaf(nmean1, cq[t].x, acc[4 * t + 2]), fmaf(nmean1, cq[t].y, acc[4 * t + 3]));
        }
      };
      auto attend = [&](int ab, auto drain) {
        GEOM;
        nb_sync<NB_BOTH>(256);
        const uint32_t xa_ = sb + OFF_STG + wu * 2048 + lane * 16;
        if (wu == 0) {
          uint32_t hb[32];
          if (i > 0) {
            const uint4* hp = &gHalo[2 * L + ab][i - 1][j][0][lane];
            uint32_t n = 0, bad;
            do {
              bad = 0;
#pragma unroll
              for (int c = 0; c < 16; c++) bad |= ll_ld2(hp + c * 32, hb[2 * c], hb[2 * c + 1], tag);
            } while (bad && ++n < SPIN_MAX);
          } else {
#pragma unroll
            for (int c = 0; c < 32; c++) hb[c] = 0u;
          }
#pragma unroll
          for (int c = 0; c < 8; c++) sts128(xa_ + (c >> 2) * 16384 + (c & 3) * 512, hb[4 * c], hb[4 * c + 1], hb[4 * c + 2], hb[4 * c + 3]);
          __syncwarp();
        }
        uint32_t KH[2][8], VH[16];
#pragma unroll
        for (int c = 0; c < 4; c++) {
          lds128(xa_ + c * 512, KH[c >> 1][4 * (c & 1)], KH[c >> 1][4 * (c & 1) + 1], KH[c >> 1][4 * (c & 1) + 2], KH[c >> 1][4 * (c & 1) + 3]);
          lds128(xa_ + 16384 + c * 512, VH[4 * c], VH[4 * c + 1], VH[4 * c + 2], VH[4 * c + 3]);
        }
        TS(11 + ab + 32 * L);
        drain();
        const bool e = g & 1, zneg = (g >> 1) < q, first = (i == 0) && (wu == 0);
        const float qs = 0.17677669530f * 1.4426950409f;
        uint32_t pr[2][6];
#pragma unroll
        for (int hh = 0; hh < 2; hh++)
          attn_probs(&Q[0][4 * hh], &Q[1][4 * hh], &KH[0][4 * hh], &KH[1][4 * hh], &K[0][4 * hh], &K[1][4 * hh], rstd0 * qs, rstd1 * qs, first, e, zneg, pr[hh]);
        float o[2][4][4];
#pragma unroll
        for (int hh = 0; hh < 2; hh++) attn_pv(pr[hh], &VH[8 * hh], &V[8 * hh], o[hh]);
#pragma unroll
        for (int hh = 0; hh < 2; hh++)
#pragma unroll
          for (int dt = 0; dt < 4; dt += 2)
            stsm4(sb + OFF_STG + (16 * wu + lr) * 128 + (((4 * hh + dt + lt) ^ l7) << 4),
                  pack2(o[hh][dt][0], o[hh][dt][1]), pack2(o[hh][dt][2], o[hh][dt][3]), pack2(o[hh][dt + 1][0], o[hh][dt + 1][1]), pack2(o[hh][dt + 1][2], o[hh][dt + 1][3]));
        signal(JOB + ab);
        nb_sync<NB_BOTH>(256);
      };

      if (L == 0) mbar_wait(BAR(XF), 0);
      TS(1 + 32 * L);
      mbar_wait(BAR(F1), 0);     g1_issue(acca, sb + OFF_X, sb + slot1(0), True{});
      if (L == 0) mbar_wait(BAR(XF + 1), 0);
      mbar_wait(BAR(F1 + 1), 0); g1_issue(acca, sb + OFF_X + 16384, sb + slot1(1), False{});
      wg_wait<1>(); release(E1 + 0);
      auto g1_bhead = [&](int p) {
        mbar_wait(BAR(F1 + p), 0);     g1_issue(accb, sb + OFF_X, sb + slot1(p), True{});
        wg_wait<1>(); release(E1 + ((p + 3) & 3));
        mbar_wait(BAR(F1 + p + 1), 0); g1_issue(accb, sb + OFF_X + 16384, sb + slot1(p + 1), False{});
        wg_wait<1>(); release(E1 + p);
      };
      if (L == 0) {
        uint4 wv[12];
        GEOM;
        const bf16* wp = P.wqkv_p + (size_t)(128 * m + 16 * wg + (t7 >> 3)) * 3072 + 128 * j + 64 * r + l7 * 8;
#pragma unroll
        for (int k = 0; k < 12; k++)
          asm volatile("ld.global.nc.v4.u32 {%0, %1, %2, %3}, [%4];" : "=r"(wv[k].x), "=r"(wv[k].y), "=r"(wv[k].z), "=r"(wv[k].w)
                       : "l"(wp + (size_t)(k & 3) * 32 * 3072 + (k >> 2) * 1024));
        g1_loop(acca, 2, 5, 0);
        const uint32_t ca = sb + OFF_STG + 2048 + (16 * wg + (t7 >> 3)) * 768 + l7 * 32;
#pragma unroll
        for (int p = 0; p < 3; p++) {
          float cs[8];
#pragma unroll
          for (int k = 0; k < 4; k++) {
            const uint4 v = wv[4 * p + k];
            const float t[8] = {bf_lo(v.x), bf_hi(v.x), bf_lo(v.y), bf_hi(v.y), bf_lo(v.z), bf_hi(v.z), bf_lo(v.w), bf_hi(v.w)};
#pragma unroll
            for (int e = 0; e < 8; e++) cs[e] = k ? cs[e] + t[e] : t[e];
          }
          sts128(ca + p * 256, __float_as_uint(cs[0]), __float_as_uint(cs[1]), __float_as_uint(cs[2]), __float_as_uint(cs[3]));
          sts128(ca + p * 256 + 16, __float_as_uint(cs[4]), __float_as_uint(cs[5]), __float_as_uint(cs[6]), __float_as_uint(cs[7]));
        }
        signal(CSJ);
        TS(17);
        g1_loop(acca, 5, 16, 0);
        wg_wait<0>();
        fence_regs(acca);
        g1_bhead(0);
      } else {
        g1_bhead(2);
        TS(49);
        g1_loop(acca, 4, 18, 0);
      }
      {
        GEOM;
        mbar_wait(BAR(STAT), L);
        const float2 s0 = lds64f(sb + OFF_STG + (16 * wu + g) * 8), s1 = lds64f(sb + OFF_STG + (16 * wu + g + 8) * 8);
        nmean0 = s0.x; rstd0 = s0.y; nmean1 = s1.x; rstd1 = s1.y;
      }
      wg_wait<0>(); release(E1 + 1);
      fence_regs(acca);
      TS(2 + 32 * L);
      fold(acca, 0);
      TS(28 + 32 * L);
      g1_loop(accb, 18, 22, 18);
      attend(0, [&]() { wg_wait<0>(); release(E1 + 1); });
      TS(3 + 32 * L);
      g1_loop(accb, 22, 25, 22);
      {
        GEOM;
#pragma unroll
        for (int t = 0; t < 16; t += 2) {
          uint32_t v0, v1, v2, v3;
          ldsm4(sb + OFF_X + (t >> 3) * 16384 + (16 * wu + lr) * 128 + ((((t & 7) + lt) ^ l7) << 4), v0, v1, v2, v3);
          xa[4 * t + 0] = bf_lo(v0); xa[4 * t + 1] = bf_hi(v0); xa[4 * t + 2] = bf_lo(v1); xa[4 * t + 3] = bf_hi(v1);
          xa[4 * t + 4] = bf_lo(v2); xa[4 * t + 5] = bf_hi(v2); xa[4 * t + 6] = bf_lo(v3); xa[4 * t + 7] = bf_hi(v3);
        }
        fence_regs(xa);
      }
      g1_loop(accb, 25, 32, 0);
      mbar_wait(BAR(STD), L);
      wg_wait<0>(); release(E1 + 3);
      fence_regs(accb);
      TS(4 + 32 * L);
      fold(accb, 1);
      TS(29 + 32 * L);
      {
        auto g2_issue = [&](int p) {
          const uint32_t st = sb + slot2(p);
          const uint64_t da = mkdesc(st + wg * 8192, 16, 1024), db = mkdesc(st + 16384, 8192, 1024);
          wg_fence();
#pragma unroll
          for (int kk = 0; kk < 4; kk++) wgmma_128<0, 1>(xa, da + kk * 2, db + kk * 128);
          wg_commit();
        };
        uint32_t par = L ? 0x1e : 0;
        mbar_wait(BAR(F2 + 0), par & 1); g2_issue(0);
        mbar_wait(BAR(F2 + 1), (par >> 1) & 1); g2_issue(1);
        par ^= 3;
        attend(1, [&]() { wg_wait<0>(); release(E2 + 0); release(E2 + 1); });
        TS(30 + 32 * L);
        int p = 2, pp = 0;
#pragma unroll 1
        for (int n = 2; n < 16; n++) {
          mbar_wait(BAR(F2 + p), (par >> p) & 1);
          par ^= 1u << p;
          g2_issue(p);
          wg_wait<1>();
          if (n > 2) release(E2 + pp);
          pp = p; if (++p == 5) p = 0;
        }
        wg_wait<0>();
        release(E2 + 0);
        fence_regs(xa);
      }
      TS(5 + 32 * L);
      float acc3[112];
      {
        GEOM;
        float s0 = 0.f, s1 = 0.f, s2 = 0.f, s3 = 0.f, q0 = 0.f, q1 = 0.f, q2 = 0.f, q3 = 0.f;
#pragma unroll
        for (int t = 0; t < 16; t++) {
          s0 += xa[4 * t]; s1 += xa[4 * t + 1]; s2 += xa[4 * t + 2]; s3 += xa[4 * t + 3];
          q0 = fmaf(xa[4 * t], xa[4 * t], q0); q1 = fmaf(xa[4 * t + 1], xa[4 * t + 1], q1);
          q2 = fmaf(xa[4 * t + 2], xa[4 * t + 2], q2); q3 = fmaf(xa[4 * t + 3], xa[4 * t + 3], q3);
        }
        s0 += s1; s2 += s3; q0 += q1; q2 += q3;
        const bool h1 = q & 1;
        float sm = (h1 ? s2 : s0) + __shfl_xor_sync(0xffffffffu, h1 ? s0 : s2, 1);
        float sq = (h1 ? q2 : q0) + __shfl_xor_sync(0xffffffffu, h1 ? q0 : q2, 1);
        sm += __shfl_xor_sync(0xffffffffu, sm, 2); sq += __shfl_xor_sync(0xffffffffu, sq, 2);
        const int row = 16 * wu + g + 8 * (q & 1);
        if (q < 2) ll_st2(&gST[L][i][j][row], __float_as_uint(sm), __float_as_uint(sq), 2 * tag + 1);
        TS(13 + 32 * L);
#pragma unroll
        for (int t = 0; t < 28; t++) {
          const float2 b = lds64f(sb + OFF_B1 + (8 * t + 2 * q) * 4);
          acc3[4 * t] = b.x; acc3[4 * t + 1] = b.y; acc3[4 * t + 2] = b.x; acc3[4 * t + 3] = b.y;
        }
        fence_regs(acc3);
        TS(14 + 32 * L);
        float mean, var;
        stats_gather<8>(&gST[L][i][4 * (q >> 1)][row], 2 * tag + 1, mean, var);
        const float ra = rsqrtf(var + 1e-5f);
        const float rr = 0.5f * ra * rsqrtf(fmaf(var * ra, ra, 1e-5f));
        const float mr = -mean * rr;
        const float orr = __shfl_xor_sync(0xffffffffu, rr, 1), omr = __shfl_xor_sync(0xffffffffu, mr, 1);
        const float r0 = h1 ? orr : rr, m0 = h1 ? omr : mr, r1 = h1 ? rr : orr, m1 = h1 ? mr : omr;
        TS(15 + 32 * L);
        mbar_wait(BAR(E2 + 4), L);
        const uint32_t ha = sb + slot3(wg) + (16 * w + lr) * 128;
#pragma unroll
        for (int t = 0; t < 16; t += 2)
          stsm4(ha + (t >> 3) * 8192 + ((((t & 7) + lt) ^ l7) << 4),
                pack2(fmaf(xa[4 * t], r0, m0), fmaf(xa[4 * t + 1], r0, m0)), pack2(fmaf(xa[4 * t + 2], r1, m1), fmaf(xa[4 * t + 3], r1, m1)),
                pack2(fmaf(xa[4 * t + 4], r0, m0), fmaf(xa[4 * t + 5], r0, m0)), pack2(fmaf(xa[4 * t + 6], r1, m1), fmaf(xa[4 * t + 7], r1, m1)));
        signal(JOB + 2 + wg);
        fence_async_smem();
        nb_sync<NB_BOTH>(256);
      }
      TS(6 + 32 * L);
      auto g3_issue = [&](int p) {
        const uint32_t st = sb + slot3(p);
        const uint64_t da = mkdesc(st + wg * 8192, 8192, 1024), db = mkdesc(st + 16384, 8192, 1024);
        wg_fence();
#pragma unroll
        for (int kk = 0; kk < 4; kk++) wgmma_224<1, 1>(acc3, da + kk * 128, db + kk * 128);
        wg_commit();
      };
      mbar_wait(BAR(F3 + 0), 0); g3_issue(0);
      mbar_wait(BAR(F3 + 1), 0); g3_issue(1);
      {
        GEOM;
        const int row = 128 * i + 16 * wu + g;
        const float c0 = __bfloat162float(P.b2[row]), c1 = __bfloat162float(P.b2[row + 8]);
#pragma unroll
        for (int t = 0; t < 16; t++) { xa[4 * t] += c0; xa[4 * t + 1] += c0; xa[4 * t + 2] += c1; xa[4 * t + 3] += c1; }
        fence_regs(xa);
      }
      wg_wait<1>(); release(E3 + 0);
      mbar_wait(BAR(F3 + 2), 0); fence_async_smem(); g3_issue(2); wg_wait<1>(); release(E3 + 1);
      mbar_wait(BAR(F3 + 3), 0); fence_async_smem(); g3_issue(3); wg_wait<1>(); release(E3 + 2);
      TS(31 + 32 * L);
#pragma unroll 1
      for (int n = 4; n < 32; n++) {
        const int p = n & 3;
        mbar_wait(BAR(F3 + p), (n >> 2) & 1);
        g3_issue(p);
        wg_wait<1>();
        release(E3 + ((n - 1) & 3));
      }
      wg_wait<0>();
      release(E3 + 3);
      fence_regs(acc3);
      TS(7 + 32 * L);
      auto g4_issue = [&](int p) {
        const uint32_t st = sb + slot4(p);
        const uint64_t da = mkdesc(st + wg * 8192, 8192, 1024), db = mkdesc(st + 16384, 8192, 1024);
        wg_fence();
#pragma unroll
        for (int kk = 0; kk < 4; kk++) wgmma_128<1, 1>(xa, da + kk * 128, db + kk * 128);
        wg_commit();
      };
      uint32_t par = L ? 0x3c : 0;
      {
        GEOM;
        const uint32_t ua = sb + 16384 + wg * 8192 + (8 * lt + l7) * 128 + (((2 * w + ((lane >> 3) & 1)) ^ l7) << 4);
#pragma unroll
        for (int cc = 0; cc < 4; cc++) {
          const int c = (cc + 3) & 3;
          uint32_t u[16];
#pragma unroll
          for (int k = 0; k < (c == 3 ? 8 : 16); k++) u[k] = pack2(gelu_half(acc3[32 * c + 2 * k]), gelu_half(acc3[32 * c + 2 * k + 1]));
          if (c >= 2) mbar_wait(BAR(E3 + (c == 3 ? 1 : 2)), 1);
#pragma unroll
          for (int k = 0; k < (c == 3 ? 2 : 4); k++)
            stsm4t(ua + (c == 3 ? slot4(5) + 4096 * r : slot4(c)) + k * 2048, u[4 * k], u[4 * k + 1], u[4 * k + 2], u[4 * k + 3]);
          signal(JOB + 4 + c);
          TS(16 + 3 * c + 32 * L);
          if (c < 3) {
            fence_async_smem();
            nb_sync<NB_BOTH>(256);
            mbar_wait(BAR(F4 + c), (par >> c) & 1);
            TS(18 + 3 * c + 32 * L);
            g4_issue(c);
          }
        }
      }
      wg_wait<1>();
      release(E4 + 0); release(E4 + 1);
      par ^= 0x7;
      TS(8 + 32 * L);
      {
        int p = 3, pp = 2;
#pragma unroll 1
        for (int n = 3; n < 56; n++) {
          mbar_wait(BAR(F4 + p), (par >> p) & 1);
          if (n == 3) TS(27 + 32 * L);
          par ^= 1u << p;
          g4_issue(p);
          wg_wait<1>();
          release(E4 + pp);
          pp = p; if (++p == 6) p = 0;
        }
      }
      wg_wait<0>();
      release(E4 + 1);
      fence_regs(xa);
      TS(9 + 32 * L);
      {
        GEOM;
#pragma unroll
        for (int t = 0; t < 16; t += 2) {
          stsm4(sb + OFF_X + (t >> 3) * 16384 + (16 * wu + lr) * 128 + ((((t & 7) + lt) ^ l7) << 4),
                pack2(xa[4 * t], xa[4 * t + 1]), pack2(xa[4 * t + 2], xa[4 * t + 3]),
                pack2(xa[4 * t + 4], xa[4 * t + 5]), pack2(xa[4 * t + 6], xa[4 * t + 7]));
          if ((t & 7) == 6) { if (L) fence_async_smem(); signal(JOB + 8 + (t >> 3)); }
        }
        fence_async_smem();
        nb_sync<NB_BOTH>(256);
      }
      TS(10 + 32 * L);
    }
    cluster_exit();
    TS(32);
  }
}

typedef CUresult (*EncodeFn)(CUtensorMap*, CUtensorMapDataType, cuuint32_t, void*, const cuuint64_t*, const cuuint64_t*, const cuuint32_t*,
                             const cuuint32_t*, CUtensorMapInterleave, CUtensorMapSwizzle, CUtensorMapL2promotion, CUtensorMapFloatOOBfill);

void make_map(EncodeFn enc, CUtensorMap* mp, const void* base, int rank, cuuint64_t d0, cuuint64_t d1, cuuint64_t d2, cuuint64_t s1, cuuint64_t s2,
              cuuint32_t b0, cuuint32_t b1, cuuint32_t b2) {
  cuuint64_t dims[3] = {d0, d1, d2}, strides[2] = {s1, s2};
  cuuint32_t box[3] = {b0, b1, b2}, es[3] = {1, 1, 1};
  CUresult res = enc(mp, CU_TENSOR_MAP_DATA_TYPE_BFLOAT16, rank, const_cast<void*>(base), dims, strides, box, es, CU_TENSOR_MAP_INTERLEAVE_NONE,
                     CU_TENSOR_MAP_SWIZZLE_128B, CU_TENSOR_MAP_L2_PROMOTION_L2_128B, CU_TENSOR_MAP_FLOAT_OOB_FILL_NONE);
  (void)res;
}

}

extern "C" void kernel_launch(void* const* d_in, const int* in_sizes, int n_in, void* d_out, int out_size) {
  (void)in_sizes; (void)n_in; (void)out_size;
  static EncodeFn enc = nullptr;
  if (!enc) {
    void* fn = nullptr;
    cudaDriverEntryPointQueryResult qr;
    cudaGetDriverEntryPoint("cuTensorMapEncodeTiled", &fn, cudaEnableDefault, &qr);
    enc = (EncodeFn)fn;
    cudaFuncSetAttribute(fused_kernel, cudaFuncAttributeMaxDynamicSharedMemorySize, SMEM_BYTES);
  }
  Params P;
  make_map(enc, &P.x0, d_in[0], 2, D_, S_, 1, D_ * 2, 0, 64, 128, 1);
  make_map(enc, &P.wqkv, d_in[1], 3, D_, D_, 3, 3 * D_ * 2, D_ * 2, 64, 32, 3);
  make_map(enc, &P.wo, d_in[2], 2, D_, D_, 1, D_ * 2, 0, 64, 64, 1);
  make_map(enc, &P.w1, d_in[4], 3, 64, S_, F_ / 64, F_ * 2, 128, 64, 64, 3);
  make_map(enc, &P.w1h, d_in[4], 3, 32, S_, F_ / 32, F_ * 2, 64, 64, 64, 1);
  make_map(enc, &P.w2, d_in[6], 3, 64, F_, S_ / 64, S_ * 2, 128, 64, 64, 2);
  make_map(enc, &P.out, d_out, 2, D_, S_, 1, D_ * 2, 0, 64, 128, 1);
  P.wqkv_p = (const bf16*)d_in[1];
  P.b1 = (const bf16*)d_in[5];
  P.b2 = (const bf16*)d_in[7];
  fused_kernel<<<128, 384, SMEM_BYTES>>>(P);
}
```

```cpp
#include <cuda_runtime.h>
#include <cuda_bf16.h>
#include <cuda.h>
#include <stdint.h>

namespace {

typedef __nv_bfloat16 bf16;
constexpr int S_ = 2048, D_ = 1024, F_ = 3584;

constexpr uint32_t OFF_STG  = 163840;
constexpr uint32_t OFF_X    = 196608;
constexpr uint32_t OFF_BAR  = 229376;
constexpr uint32_t OFF_CS   = OFF_BAR + 512;
constexpr uint32_t OFF_B1   = OFF_CS + 1536;
constexpr uint32_t SMEM_BYTES = OFF_B1 + 896 + 128;
constexpr int F1 = 0, E1 = 4, F2 = 8, E2 = 13, F3 = 18, E3 = 22, F4 = 26, E4 = 32;
constexpr int JOB = 38;
constexpr int RD = 48;
constexpr int XF = 54, STD = 56, STAT = 58, FOLD = 59, CSJ = 61, HALO = 62;
constexpr int NB_BOTH = 1, NB_HELP = 2;

__device__ __forceinline__ uint32_t slot1(int p) { return p * 40960; }
__device__ __forceinline__ uint32_t slot2(int p) { return p * 32768; }
__device__ __forceinline__ uint32_t slot3(int p) { return ((p + 2) & 3) * 49152; }
__device__ __forceinline__ uint32_t slot4(int p) { return (p < 2 ? p + 4 : p - 2) * 32768; }

__device__ __align__(1024) uint8_t gXB[16 * 16 * 16384];
__device__ __align__(1024) uint8_t gOB[16 * 16 * 16384];
__device__ __align__(1024) uint8_t gHB[8 * 32 * 16384];
__device__ __align__(1024) uint8_t gUB[8 * 56 * 16384];
__device__ __align__(1024) uint2   gST[2][16][8][8][16];
__device__ __align__(1024) uint4   gHalo[2][16][8][12][32];
__device__ __align__(1024) uint32_t gAck[2][16][8][2][8];
__device__ __align__(1024) uint4   gCS[8][16][64];
__device__ __align__(1024) uint32_t gFlag[2][7][16][32];
__device__ uint32_t gEpoch;
#define TS(k)
#define TS2(k)

#define KB(k)
#define ST(k)
struct Params {
  CUtensorMap x0, wqkv, wo, w1, w1h, w2, out;
  const bf16 *wqkv_p, *b1, *b2;
  uint32_t zero;
};

template <int TA, int TB> __device__ __forceinline__ void wgmma_128(float (&d)[64], uint64_t da, uint64_t db) {
  asm volatile("wgmma.mma_async.sync.aligned.m64n128k16.f32.bf16.bf16 {"
  "%0, %1, %2, %3, %4, %5, %6, %7, %8, %9, %10, %11, %12, %13, %14, %15, "
  "%16, %17, %18, %19, %20, %21, %22, %23, %24, %25, %26, %27, %28, %29, %30, %31, "
  "%32, %33, %34, %35, %36, %37, %38, %39, %40, %41, %42, %43, %44, %45, %46, %47, "
  "%48, %49, %50, %51, %52, %53, %54, %55, %56, %57, %58, %59, %60, %61, %62, %63"
  "}, %64, %65, 1, 1, 1, %66, %67;\n"
  : "+f"(d[0]), "+f"(d[1]), "+f"(d[2]), "+f"(d[3]), "+f"(d[4]), "+f"(d[5]), "+f"(d[6]), "+f"(d[7]),
    "+f"(d[8]), "+f"(d[9]), "+f"(d[10]), "+f"(d[11]), "+f"(d[12]), "+f"(d[13]), "+f"(d[14]), "+f"(d[15]),
    "+f"(d[16]), "+f"(d[17]), "+f"(d[18]), "+f"(d[19]), "+f"(d[20]), "+f"(d[21]), "+f"(d[22]), "+f"(d[23]),
    "+f"(d[24]), "+f"(d[25]), "+f"(d[26]), "+f"(d[27]), "+f"(d[28]), "+f"(d[29]), "+f"(d[30]), "+f"(d[31]),
    "+f"(d[32]), "+f"(d[33]), "+f"(d[34]), "+f"(d[35]), "+f"(d[36]), "+f"(d[37]), "+f"(d[38]), "+f"(d[39]),
    "+f"(d[40]), "+f"(d[41]), "+f"(d[42]), "+f"(d[43]), "+f"(d[44]), "+f"(d[45]), "+f"(d[46]), "+f"(d[47]),
    "+f"(d[48]), "+f"(d[49]), "+f"(d[50]), "+f"(d[51]), "+f"(d[52]), "+f"(d[53]), "+f"(d[54]), "+f"(d[55]),
    "+f"(d[56]), "+f"(d[57]), "+f"(d[58]), "+f"(d[59]), "+f"(d[60]), "+f"(d[61]), "+f"(d[62]), "+f"(d[63])
  : "l"(da), "l"(db), "n"(TA), "n"(TB));
}
template <int TA, int TB> __device__ __forceinline__ void wgmma_192(float (&d)[96], uint64_t da, uint64_t db) {
  asm volatile("wgmma.mma_async.sync.aligned.m64n192k16.f32.bf16.bf16 {"
  "%0, %1, %2, %3, %4, %5, %6, %7, %8, %9, %10, %11, %12, %13, %14, %15, "
  "%16, %17, %18, %19, %20, %21, %22, %23, %24, %25, %26, %27, %28, %29, %30, %31, "
  "%32, %33, %34, %35, %36, %37, %38, %39, %40, %41, %42, %43, %44, %45, %46, %47, "
  "%48, %49, %50, %51, %52, %53, %54, %55, %56, %57, %58, %59, %60, %61, %62, %63, "
  "%64, %65, %66, %67, %68, %69, %70, %71, %72, %73, %74, %75, %76, %77, %78, %79, "
  "%80, %81, %82, %83, %84, %85, %86, %87, %88, %89, %90, %91, %92, %93, %94, %95"
  "}, %96, %97, 1, 1, 1, %98, %99;\n"
  : "+f"(d[0]), "+f"(d[1]), "+f"(d[2]), "+f"(d[3]), "+f"(d[4]), "+f"(d[5]), "+f"(d[6]), "+f"(d[7]),
    "+f"(d[8]), "+f"(d[9]), "+f"(d[10]), "+f"(d[11]), "+f"(d[12]), "+f"(d[13]), "+f"(d[14]), "+f"(d[15]),
    "+f"(d[16]), "+f"(d[17]), "+f"(d[18]), "+f"(d[19]), "+f"(d[20]), "+f"(d[21]), "+f"(d[22]), "+f"(d[23]),
    "+f"(d[24]), "+f"(d[25]), "+f"(d[26]), "+f"(d[27]), "+f"(d[28]), "+f"(d[29]), "+f"(d[30]), "+f"(d[31]),
    "+f"(d[32]), "+f"(d[33]), "+f"(d[34]), "+f"(d[35]), "+f"(d[36]), "+f"(d[37]), "+f"(d[38]), "+f"(d[39]),
    "+f"(d[40]), "+f"(d[41]), "+f"(d[42]), "+f"(d[43]), "+f"(d[44]), "+f"(d[45]), "+f"(d[46]), "+f"(d[47]),
    "+f"(d[48]), "+f"(d[49]), "+f"(d[50]), "+f"(d[51]), "+f"(d[52]), "+f"(d[53]), "+f"(d[54]), "+f"(d[55]),
    "+f"(d[56]), "+f"(d[57]), "+f"(d[58]), "+f"(d[59]), "+f"(d[60]), "+f"(d[61]), "+f"(d[62]), "+f"(d[63]),
    "+f"(d[64]), "+f"(d[65]), "+f"(d[66]), "+f"(d[67]), "+f"(d[68]), "+f"(d[69]), "+f"(d[70]), "+f"(d[71]),
    "+f"(d[72]), "+f"(d[73]), "+f"(d[74]), "+f"(d[75]), "+f"(d[76]), "+f"(d[77]), "+f"(d[78]), "+f"(d[79]),
    "+f"(d[80]), "+f"(d[81]), "+f"(d[82]), "+f"(d[83]), "+f"(d[84]), "+f"(d[85]), "+f"(d[86]), "+f"(d[87]),
    "+f"(d[88]), "+f"(d[89]), "+f"(d[90]), "+f"(d[91]), "+f"(d[92]), "+f"(d[93]), "+f"(d[94]), "+f"(d[95])
  : "l"(da), "l"(db), "n"(TA), "n"(TB));
}
template <int TA, int TB> __device__ __forceinline__ void wgmma_192z(float (&d)[96], uint64_t da, uint64_t db) {
  asm volatile("wgmma.mma_async.sync.aligned.m64n192k16.f32.bf16.bf16 {"
  "%0, %1, %2, %3, %4, %5, %6, %7, %8, %9, %10, %11, %12, %13, %14, %15, "
  "%16, %17, %18, %19, %20, %21, %22, %23, %24, %25, %26, %27, %28, %29, %30, %31, "
  "%32, %33, %34, %35, %36, %37, %38, %39, %40, %41, %42, %43, %44, %45, %46, %47, "
  "%48, %49, %50, %51, %52, %53, %54, %55, %56, %57, %58, %59, %60, %61, %62, %63, "
  "%64, %65, %66, %67, %68, %69, %70, %71, %72, %73, %74, %75, %76, %77, %78, %79, "
  "%80, %81, %82, %83, %84, %85, %86, %87, %88, %89, %90, %91, %92, %93, %94, %95"
  "}, %96, %97, 0, 1, 1, %98, %99;\n"
  : "=f"(d[0]), "=f"(d[1]), "=f"(d[2]), "=f"(d[3]), "=f"(d[4]), "=f"(d[5]), "=f"(d[6]), "=f"(d[7]),
    "=f"(d[8]), "=f"(d[9]), "=f"(d[10]), "=f"(d[11]), "=f"(d[12]), "=f"(d[13]), "=f"(d[14]), "=f"(d[15]),
    "=f"(d[16]), "=f"(d[17]), "=f"(d[18]), "=f"(d[19]), "=f"(d[20]), "=f"(d[21]), "=f"(d[22]), "=f"(d[23]),
    "=f"(d[24]), "=f"(d[25]), "=f"(d[26]), "=f"(d[27]), "=f"(d[28]), "=f"(d[29]), "=f"(d[30]), "=f"(d[31]),
    "=f"(d[32]), "=f"(d[33]), "=f"(d[34]), "=f"(d[35]), "=f"(d[36]), "=f"(d[37]), "=f"(d[38]), "=f"(d[39]),
    "=f"(d[40]), "=f"(d[41]), "=f"(d[42]), "=f"(d[43]), "=f"(d[44]), "=f"(d[45]), "=f"(d[46]), "=f"(d[47]),
    "=f"(d[48]), "=f"(d[49]), "=f"(d[50]), "=f"(d[51]), "=f"(d[52]), "=f"(d[53]), "=f"(d[54]), "=f"(d[55]),
    "=f"(d[56]), "=f"(d[57]), "=f"(d[58]), "=f"(d[59]), "=f"(d[60]), "=f"(d[61]), "=f"(d[62]), "=f"(d[63]),
    "=f"(d[64]), "=f"(d[65]), "=f"(d[66]), "=f"(d[67]), "=f"(d[68]), "=f"(d[69]), "=f"(d[70]), "=f"(d[71]),
    "=f"(d[72]), "=f"(d[73]), "=f"(d[74]), "=f"(d[75]), "=f"(d[76]), "=f"(d[77]), "=f"(d[78]), "=f"(d[79]),
    "=f"(d[80]), "=f"(d[81]), "=f"(d[82]), "=f"(d[83]), "=f"(d[84]), "=f"(d[85]), "=f"(d[86]), "=f"(d[87]),
    "=f"(d[88]), "=f"(d[89]), "=f"(d[90]), "=f"(d[91]), "=f"(d[92]), "=f"(d[93]), "=f"(d[94]), "=f"(d[95])
  : "l"(da), "l"(db), "n"(TA), "n"(TB));
}
template <int TA, int TB> __device__ __forceinline__ void wgmma_224(float (&d)[112], uint64_t da, uint64_t db) {
  asm volatile("wgmma.mma_async.sync.aligned.m64n224k16.f32.bf16.bf16 {"
  "%0, %1, %2, %3, %4, %5, %6, %7, %8, %9, %10, %11, %12, %13, %14, %15, "
  "%16, %17, %18, %19, %20, %21, %22, %23, %24, %25, %26, %27, %28, %29, %30, %31, "
  "%32, %33, %34, %35, %36, %37, %38, %39, %40, %41, %42, %43, %44, %45, %46, %47, "
  "%48, %49, %50, %51, %52, %53, %54, %55, %56, %57, %58, %59, %60, %61, %62, %63, "
  "%64, %65, %66, %67, %68, %69, %70, %71, %72, %73, %74, %75, %76, %77, %78, %79, "
  "%80, %81, %82, %83, %84, %85, %86, %87, %88, %89, %90, %91, %92, %93, %94, %95, "
  "%96, %97, %98, %99, %100, %101, %102, %103, %104, %105, %106, %107, %108, %109, %110, %111"
  "}, %112, %113, 1, 1, 1, %114, %115;\n"
  : "+f"(d[0]), "+f"(d[1]), "+f"(d[2]), "+f"(d[3]), "+f"(d[4]), "+f"(d[5]), "+f"(d[6]), "+f"(d[7]),
    "+f"(d[8]), "+f"(d[9]), "+f"(d[10]), "+f"(d[11]), "+f"(d[12]), "+f"(d[13]), "+f"(d[14]), "+f"(d[15]),
    "+f"(d[16]), "+f"(d[17]), "+f"(d[18]), "+f"(d[19]), "+f"(d[20]), "+f"(d[21]), "+f"(d[22]), "+f"(d[23]),
    "+f"(d[24]), "+f"(d[25]), "+f"(d[26]), "+f"(d[27]), "+f"(d[28]), "+f"(d[29]), "+f"(d[30]), "+f"(d[31]),
    "+f"(d[32]), "+f"(d[33]), "+f"(d[34]), "+f"(d[35]), "+f"(d[36]), "+f"(d[37]), "+f"(d[38]), "+f"(d[39]),
    "+f"(d[40]), "+f"(d[41]), "+f"(d[42]), "+f"(d[43]), "+f"(d[44]), "+f"(d[45]), "+f"(d[46]), "+f"(d[47]),
    "+f"(d[48]), "+f"(d[49]), "+f"(d[50]), "+f"(d[51]), "+f"(d[52]), "+f"(d[53]), "+f"(d[54]), "+f"(d[55]),
    "+f"(d[56]), "+f"(d[57]), "+f"(d[58]), "+f"(d[59]), "+f"(d[60]), "+f"(d[61]), "+f"(d[62]), "+f"(d[63]),
    "+f"(d[64]), "+f"(d[65]), "+f"(d[66]), "+f"(d[67]), "+f"(d[68]), "+f"(d[69]), "+f"(d[70]), "+f"(d[71]),
    "+f"(d[72]), "+f"(d[73]), "+f"(d[74]), "+f"(d[75]), "+f"(d[76]), "+f"(d[77]), "+f"(d[78]), "+f"(d[79]),
    "+f"(d[80]), "+f"(d[81]), "+f"(d[82]), "+f"(d[83]), "+f"(d[84]), "+f"(d[85]), "+f"(d[86]), "+f"(d[87]),
    "+f"(d[88]), "+f"(d[89]), "+f"(d[90]), "+f"(d[91]), "+f"(d[92]), "+f"(d[93]), "+f"(d[94]), "+f"(d[95]),
    "+f"(d[96]), "+f"(d[97]), "+f"(d[98]), "+f"(d[99]), "+f"(d[100]), "+f"(d[101]), "+f"(d[102]), "+f"(d[103]),
    "+f"(d[104]), "+f"(d[105]), "+f"(d[106]), "+f"(d[107]), "+f"(d[108]), "+f"(d[109]), "+f"(d[110]), "+f"(d[111])
  : "l"(da), "l"(db), "n"(TA), "n"(TB));
}

__device__ __forceinline__ uint32_t smem_u32(const void* p) { return (uint32_t)__cvta_generic_to_shared(p); }
__device__ __forceinline__ void mbar_init(uint32_t bar, uint32_t cnt) { asm volatile("mbarrier.init.shared::cta.b64 [%0], %1;" ::"r"(bar), "r"(cnt) : "memory"); }
__device__ __forceinline__ void mbar_expect(uint32_t bar, uint32_t bytes) { asm volatile("mbarrier.arrive.expect_tx.shared::cta.b64 _, [%0], %1;" ::"r"(bar), "r"(bytes) : "memory"); }
__device__ __forceinline__ void mbar_arrive(uint32_t bar) { asm volatile("mbarrier.arrive.shared::cta.b64 _, [%0];" ::"r"(bar) : "memory"); }
__device__ __forceinline__ void mbar_arrive_cl(uint32_t cbar) { asm volatile("mbarrier.arrive.shared::cluster.b64 _, [%0];" ::"r"(cbar) : "memory"); }
__device__ __forceinline__ uint32_t mapa(uint32_t a, uint32_t cta) { uint32_t r; asm("mapa.shared::cluster.u32 %0, %1, %2;" : "=r"(r) : "r"(a), "r"(cta)); return r; }
__device__ __forceinline__ void mbar_wait(uint32_t bar, uint32_t parity) {
  asm volatile("{\n.reg .pred p;\n.reg .u32 n;\nmov.u32 n, 0;\n"
    "LAB_WAIT:\n"
    "mbarrier.try_wait.parity.shared::cta.b64 p, [%0], %1;\n"
    "@p bra LAB_DONE;\n"
    "add.u32 n, n, 1;\n"
    "setp.lt.u32 p, n, 2000000;\n"
    "@p bra LAB_WAIT;\n"
    "trap;\n"
    "LAB_DONE:\n}\n" ::"r"(bar), "r"(parity) : "memory");
}
constexpr uint32_t SPIN_MAX = 2000000;
__device__ __forceinline__ void tma2d(uint32_t dst, const CUtensorMap* m, uint32_t bar, int c0, int c1) {
  asm volatile("cp.async.bulk.tensor.2d.shared::cluster.global.mbarrier::complete_tx::bytes [%0], [%1, {%3, %4}], [%2];"
    ::"r"(dst), "l"(m), "r"(bar), "r"(c0), "r"(c1) : "memory");
}
__device__ __forceinline__ void tma2d_mc(uint32_t dst, const CUtensorMap* m, uint32_t bar, int c0, int c1) {
  asm volatile("cp.async.bulk.tensor.2d.shared::cluster.global.mbarrier::complete_tx::bytes.multicast::cluster [%0], [%1, {%3, %4}], [%2], %5;"
    ::"r"(dst), "l"(m), "r"(bar), "r"(c0), "r"(c1), "h"((uint16_t)3) : "memory");
}
__device__ __forceinline__ void tma3d(uint32_t dst, const CUtensorMap* m, uint32_t bar, int c0, int c1, int c2) {
  asm volatile("cp.async.bulk.tensor.3d.shared::cluster.global.mbarrier::complete_tx::bytes [%0], [%1, {%3, %4, %5}], [%2];"
    ::"r"(dst), "l"(m), "r"(bar), "r"(c0), "r"(c1), "r"(c2) : "memory");
}
__device__ __forceinline__ void tma3d_mc(uint32_t dst, const CUtensorMap* m, uint32_t bar, int c0, int c1, int c2) {
  asm volatile("cp.async.bulk.tensor.3d.shared::cluster.global.mbarrier::complete_tx::bytes.multicast::cluster [%0], [%1, {%3, %4, %5}], [%2], %6;"
    ::"r"(dst), "l"(m), "r"(bar), "r"(c0), "r"(c1), "r"(c2), "h"((uint16_t)3) : "memory");
}
__device__ __forceinline__ void tma2d_store(const CUtensorMap* m, uint32_t src, int c0, int c1) {
  asm volatile("cp.async.bulk.tensor.2d.global.shared::cta.bulk_group [%0, {%2, %3}], [%1];" ::"l"(m), "r"(src), "r"(c0), "r"(c1) : "memory");
}
__device__ __forceinline__ void bulk_ld(uint32_t dst, const void* src, uint32_t bytes, uint32_t bar) {
  asm volatile("cp.async.bulk.shared::cluster.global.mbarrier::complete_tx::bytes [%0], [%1], %2, [%3];" ::"r"(dst), "l"(src), "r"(bytes), "r"(bar) : "memory");
}
__device__ __forceinline__ void bulk_ld_mc(uint32_t dst, const void* src, uint32_t bytes, uint32_t bar) {
  asm volatile("cp.async.bulk.shared::cluster.global.mbarrier::complete_tx::bytes.multicast::cluster [%0], [%1], %2, [%3], %4;"
    ::"r"(dst), "l"(src), "r"(bytes), "r"(bar), "h"((uint16_t)3) : "memory");
}
__device__ __forceinline__ void bulk_st(void* dst, uint32_t src, uint32_t bytes) {
  asm volatile("cp.async.bulk.global.shared::cta.bulk_group [%0], [%1], %2;" ::"l"(dst), "r"(src), "r"(bytes) : "memory");
}
__device__ __forceinline__ void bulk_s2s(uint32_t cdst, uint32_t src, uint32_t bytes, uint32_t cbar) {
  asm volatile("cp.async.bulk.shared::cluster.shared::cta.mbarrier::complete_tx::bytes [%0], [%1], %2, [%3];" ::"r"(cdst), "r"(src), "r"(bytes), "r"(cbar) : "memory");
}
__device__ __forceinline__ void bulk_commit() { asm volatile("cp.async.bulk.commit_group;" ::: "memory"); }
__device__ __forceinline__ void bulk_wait0() { asm volatile("cp.async.bulk.wait_group 0;" ::: "memory"); }
__device__ __forceinline__ void fence_async_smem() { asm volatile("fence.proxy.async.shared::cta;" ::: "memory"); }
__device__ __forceinline__ void wg_fence() { asm volatile("wgmma.fence.sync.aligned;" ::: "memory"); }
__device__ __forceinline__ void wg_commit() { asm volatile("wgmma.commit_group.sync.aligned;" ::: "memory"); }
template <int N> __device__ __forceinline__ void wg_wait() { asm volatile("wgmma.wait_group.sync.aligned %0;" ::"n"(N) : "memory"); }
template <int R> __device__ __forceinline__ void reg_alloc() { asm volatile("setmaxnreg.inc.sync.aligned.u32 %0;" ::"n"(R)); }
template <int R> __device__ __forceinline__ void reg_dealloc() { asm volatile("setmaxnreg.dec.sync.aligned.u32 %0;" ::"n"(R)); }
__device__ __forceinline__ void cluster_bar() { asm volatile("barrier.cluster.arrive.relaxed;\nbarrier.cluster.wait;" ::: "memory"); }
template <int ID> __device__ __forceinline__ void nb_sync(int n) { asm volatile("barrier.sync %0, %1;" ::"n"(ID), "r"(n) : "memory"); }
template <int ID> __device__ __forceinline__ void nb_arrive(int n) { asm volatile("barrier.arrive %0, %1;" ::"n"(ID), "r"(n) : "memory"); }
__device__ __forceinline__ int fresh_tid() { int t; asm volatile("mov.u32 %0, %%tid.x;" : "=r"(t)); return t; }
__device__ __forceinline__ void sched_fence(uint32_t z) { asm volatile("{\n.reg .pred p;\nsetp.ne.u32 p, %0, 0;\nLAB_S:\n@p nanosleep.u32 0;\n@p bra LAB_S;\n}\n" ::"r"(z) : "memory"); }
__device__ __forceinline__ float rsq(float x) { float y; asm("rsqrt.approx.ftz.f32 %0, %1;" : "=f"(y) : "f"(x)); return y; }
struct True { static constexpr bool value = true; };
struct False { static constexpr bool value = false; };
template <int N> __device__ __forceinline__ void fence_regs(float (&d)[N]) {
#pragma unroll
  for (int i = 0; i < N; i++) asm volatile("" : "+f"(d[i])::"memory");
}
__device__ __forceinline__ uint64_t mkdesc(uint32_t addr, uint32_t lbo, uint32_t sbo) {
  return (uint64_t)((addr & 0x3FFFF) >> 4) | ((uint64_t)(lbo >> 4) << 16) | ((uint64_t)(sbo >> 4) << 32) | (1ull << 62);
}
__device__ __forceinline__ uint32_t pack2(float lo, float hi) { uint32_t r; asm("cvt.rn.bf16x2.f32 %0, %1, %2;" : "=r"(r) : "f"(hi), "f"(lo)); return r; }
__device__ __forceinline__ float bf_lo(uint32_t v) { return __uint_as_float(v << 16); }
__device__ __forceinline__ float bf_hi(uint32_t v) { return __uint_as_float(v & 0xffff0000u); }
__device__ __forceinline__ void stsm4(uint32_t a, uint32_t r0, uint32_t r1, uint32_t r2, uint32_t r3) {
  asm volatile("stmatrix.sync.aligned.m8n8.x4.shared.b16 [%0], {%1, %2, %3, %4};" ::"r"(a), "r"(r0), "r"(r1), "r"(r2), "r"(r3) : "memory");
}
__device__ __forceinline__ void stsm4t(uint32_t a, uint32_t r0, uint32_t r1, uint32_t r2, uint32_t r3) {
  asm volatile("stmatrix.sync.aligned.m8n8.x4.trans.shared.b16 [%0], {%1, %2, %3, %4};" ::"r"(a), "r"(r0), "r"(r1), "r"(r2), "r"(r3) : "memory");
}
__device__ __forceinline__ void ldsm4(uint32_t a, uint32_t& r0, uint32_t& r1, uint32_t& r2, uint32_t& r3) {
  asm volatile("ldmatrix.sync.aligned.m8n8.x4.shared.b16 {%0, %1, %2, %3}, [%4];" : "=r"(r0), "=r"(r1), "=r"(r2), "=r"(r3) : "r"(a) : "memory");
}
__device__ __forceinline__ void ldsm4t(uint32_t a, uint32_t& r0, uint32_t& r1, uint32_t& r2, uint32_t& r3) {
  asm volatile("ldmatrix.sync.aligned.m8n8.x4.trans.shared.b16 {%0, %1, %2, %3}, [%4];" : "=r"(r0), "=r"(r1), "=r"(r2), "=r"(r3) : "r"(a) : "memory");
}
__device__ __forceinline__ void mma16816(float (&c)[4], uint32_t a0, uint32_t a1, uint32_t a2, uint32_t a3, uint32_t b0, uint32_t b1) {
  asm volatile("mma.sync.aligned.m16n8k16.row.col.f32.bf16.bf16.f32 {%0, %1, %2, %3}, {%4, %5, %6, %7}, {%8, %9}, {%0, %1, %2, %3};"
    : "+f"(c[0]), "+f"(c[1]), "+f"(c[2]), "+f"(c[3]) : "r"(a0), "r"(a1), "r"(a2), "r"(a3), "r"(b0), "r"(b1));
}
__device__ __forceinline__ void sts128(uint32_t a, uint32_t r0, uint32_t r1, uint32_t r2, uint32_t r3) {
  asm volatile("st.shared.v4.b32 [%0], {%1, %2, %3, %4};" ::"r"(a), "r"(r0), "r"(r1), "r"(r2), "r"(r3) : "memory");
}
__device__ __forceinline__ void lds128(uint32_t a, uint32_t& r0, uint32_t& r1, uint32_t& r2, uint32_t& r3) {
  asm volatile("ld.shared.v4.b32 {%0, %1, %2, %3}, [%4];" : "=r"(r0), "=r"(r1), "=r"(r2), "=r"(r3) : "r"(a) : "memory");
}
__device__ __forceinline__ float2 lds64f(uint32_t a) { float2 v; asm volatile("ld.shared.v2.f32 {%0, %1}, [%2];" : "=f"(v.x), "=f"(v.y) : "r"(a) : "memory"); return v; }
__device__ __forceinline__ float4 lds128f(uint32_t a) { float4 v; asm volatile("ld.shared.v4.f32 {%0, %1, %2, %3}, [%4];" : "=f"(v.x), "=f"(v.y), "=f"(v.z), "=f"(v.w) : "r"(a) : "memory"); return v; }
__device__ __forceinline__ void sts64f(uint32_t a, float x, float y) { asm volatile("st.shared.v2.f32 [%0], {%1, %2};" ::"r"(a), "f"(x), "f"(y) : "memory"); }
__device__ __forceinline__ float lds32f(uint32_t a) { float v; asm volatile("ld.shared.f32 %0, [%1];" : "=f"(v) : "r"(a) : "memory"); return v; }
__device__ __forceinline__ void sts32f(uint32_t a, float x) { asm volatile("st.shared.f32 [%0], %1;" ::"r"(a), "f"(x) : "memory"); }
__device__ __forceinline__ void stat_st(uint2* p, float sum, float sq, uint32_t tag) {
  const float mean = sum * (1.f / 128), m2 = fmaxf(fmaf(-mean, sum, sq), 0.f);
  const uint32_t a = ((__float_as_uint(mean) + 8u) & ~15u) | (tag & 15u), b = ((__float_as_uint(m2) + 8u) & ~15u) | (tag & 15u);
  asm volatile("{\n.reg .b64 x;\nmov.b64 x, {%1, %2};\nst.relaxed.gpu.global.b64 [%0], x;\n}\n" ::"l"(p), "r"(a), "r"(b) : "memory");
}
__device__ __forceinline__ void stat_ld2(const uint2* p, uint32_t (&v)[4]) {
  asm volatile("{\n.reg .b64 x, y;\nld.relaxed.gpu.global.v2.b64 {x, y}, [%4];\nmov.b64 {%0, %1}, x;\nmov.b64 {%2, %3}, y;\n}\n"
    : "=r"(v[0]), "=r"(v[1]), "=r"(v[2]), "=r"(v[3]) : "l"(p) : "memory");
}
__device__ __forceinline__ float untag(uint32_t v) { return __uint_as_float(v & ~15u); }
__device__ __forceinline__ void ll_st3(uint4* p, uint32_t a, uint32_t b, uint32_t c, uint32_t tag) {
  asm volatile("{\n.reg .b64 x, y;\n.reg .b128 z;\nmov.b64 x, {%1, %2};\nmov.b64 y, {%3, %4};\nmov.b128 z, {x, y};\nst.relaxed.gpu.global.b128 [%0], z;\n}\n"
    ::"l"(p), "r"(a), "r"(b), "r"(c), "r"(tag) : "memory");
}
__device__ __forceinline__ uint32_t ll_ld3(const uint4* p, uint32_t& a, uint32_t& b, uint32_t& c, uint32_t tag) {
  uint32_t t;
  asm volatile("{\n.reg .b64 x, y;\n.reg .b128 z;\nld.relaxed.gpu.global.b128 z, [%4];\nmov.b128 {x, y}, z;\nmov.b64 {%0, %1}, x;\nmov.b64 {%2, %3}, y;\n}\n"
    : "=r"(a), "=r"(b), "=r"(c), "=r"(t) : "l"(p) : "memory");
  return t ^ tag;
}
__device__ __forceinline__ void warp_store(uint8_t* dst, uint32_t src, int bytes) {
#pragma unroll 1
  for (int o = 0; o < bytes; o += 2048) {
    uint4 v[4];
#pragma unroll
    for (int k = 0; k < 4; k++) lds128(src + o + k * 512, v[k].x, v[k].y, v[k].z, v[k].w);
#pragma unroll
    for (int k = 0; k < 4; k++) asm volatile("st.global.v4.b32 [%0], {%1, %2, %3, %4};" ::"l"(dst + o + k * 512), "r"(v[k].x), "r"(v[k].y), "r"(v[k].z), "r"(v[k].w) : "memory");
  }
  __syncwarp();
}
__device__ __forceinline__ uint32_t clock32() { uint32_t t; asm volatile("mov.u32 %0, %%clock;" : "=r"(t)); return t; }
__device__ __forceinline__ void flag_set(uint32_t* p, uint32_t bit) { asm volatile("red.release.gpu.global.xor.b32 [%0], %1;" ::"l"(p), "r"(bit) : "memory"); }
__device__ __forceinline__ void flag_wait(const uint32_t* p, uint32_t inv, uint32_t need, uint32_t& ready) {
  if ((ready & need) == need) return;
  uint32_t n = 0;
  do {
    asm volatile("ld.relaxed.gpu.global.b32 %0, [%1];" : "=r"(ready) : "l"(p) : "memory");
    ready = __shfl_sync(0xffffffffu, ready, 0) ^ inv;
  } while ((ready & need) != need && ++n < SPIN_MAX);
  asm volatile("fence.acquire.gpu;\nfence.proxy.async.global;" ::: "memory");
}
__device__ __forceinline__ bool elect_one() {
  uint32_t p;
  asm volatile("{\n.reg .pred P;\nelect.sync _|P, 0xffffffff;\nselp.u32 %0, 1, 0, P;\n}\n" : "=r"(p));
  return p;
}
__device__ __forceinline__ float gelu_half(float hx) {
  const float y = hx * fmaf(hx * hx, 8.f * 0.0356774081f, 2.f * 0.7978845608f);
  float th;
  asm("tanh.approx.f32 %0, %1;" : "=f"(th) : "f"(y));
  return fmaf(hx, th, hx);
}
__device__ __forceinline__ float ex2(float x) { float y; asm("ex2.approx.ftz.f32 %0, %1;" : "=f"(y) : "f"(x)); return y; }

__device__ __forceinline__ void stat_combine(uint32_t am, uint32_t aq, uint32_t bm, uint32_t bq, float pv, float& mean, float& var) {
  const float d0 = untag(am) - pv, d1 = untag(bm) - pv;
  float s = d0 + d1, q = fmaf(fmaf(d0, d0, d1 * d1), 128.f, untag(aq) + untag(bq));
  s += __shfl_xor_sync(0xffffffffu, s, 8); q += __shfl_xor_sync(0xffffffffu, q, 8);
  s += __shfl_xor_sync(0xffffffffu, s, 16); q += __shfl_xor_sync(0xffffffffu, q, 16);
  s *= 0.125f;
  mean = pv + s;
  var = fmaxf(fmaf(-s, s, q * (1.f / D_)), 0.f);
}

__device__ __forceinline__ void attn_probs(const uint32_t* q0, const uint32_t* q1,
                                           const uint32_t* k0, const uint32_t* k1, const uint32_t* k2, const uint32_t* k3,
                                           float sc0, float sc1, bool first, bool e, bool zneg, uint32_t (&pr)[6]) {
  float s[4][4];
#pragma unroll
  for (int n = 0; n < 4; n++) {
    const uint32_t* k = n == 0 ? k0 : n == 1 ? k1 : n == 2 ? k2 : k3;
    s[n][0] = s[n][1] = s[n][2] = s[n][3] = 0.f;
    mma16816(s[n], q0[0], q1[0], q0[1], q1[1], k[0], k[1]);
    mma16816(s[n], q0[2], q1[2], q0[3], q1[3], k[2], k[3]);
  }
  const float MASKED = -1.0e9f * 1.4426950409f;
  float a0 = (e ? s[1][1] : s[1][0]) * sc0;
  float b0 = (zneg ? (e ? s[0][1] : s[0][0]) : (e ? s[2][1] : s[2][0])) * sc0;
  float a1 = (e ? s[2][3] : s[2][2]) * sc1;
  float b1 = (zneg ? (e ? s[1][3] : s[1][2]) : (e ? s[3][3] : s[3][2])) * sc1;
  if (first) { a0 = MASKED; if (zneg) { b0 = MASKED; b1 = MASKED; } }
  float m0 = fmaxf(a0, b0), m1 = fmaxf(a1, b1);
  m0 = fmaxf(m0, __shfl_xor_sync(0xffffffffu, m0, 1)); m1 = fmaxf(m1, __shfl_xor_sync(0xffffffffu, m1, 1));
  m0 = fmaxf(m0, __shfl_xor_sync(0xffffffffu, m0, 2)); m1 = fmaxf(m1, __shfl_xor_sync(0xffffffffu, m1, 2));
  a0 = ex2(a0 - m0); b0 = ex2(b0 - m0); a1 = ex2(a1 - m1); b1 = ex2(b1 - m1);
  float l0 = a0 + b0, l1 = a1 + b1;
  l0 += __shfl_xor_sync(0xffffffffu, l0, 1); l1 += __shfl_xor_sync(0xffffffffu, l1, 1);
  l0 += __shfl_xor_sync(0xffffffffu, l0, 2); l1 += __shfl_xor_sync(0xffffffffu, l1, 2);
  asm("rcp.approx.ftz.f32 %0, %0;" : "+f"(l0)); asm("rcp.approx.ftz.f32 %0, %0;" : "+f"(l1));
  const int sh = e ? 16 : 0;
  uint32_t pa0 = pack2(a0 * l0, 0.f) << sh, pb0 = pack2(b0 * l0, 0.f) << sh;
  uint32_t pa1 = pack2(a1 * l1, 0.f) << sh, pb1 = pack2(b1 * l1, 0.f) << sh;
  pr[0] = zneg ? pb0 : 0u; pr[1] = pa0; pr[2] = zneg ? 0u : pb0;
  pr[3] = zneg ? pb1 : 0u; pr[4] = pa1; pr[5] = zneg ? 0u : pb1;
}
__device__ __forceinline__ void attn_pv(const uint32_t (&pr)[6], const uint32_t* vh, const uint32_t* v, float (&o)[4][4]) {
#pragma unroll
  for (int dt = 0; dt < 4; dt++) {
    o[dt][0] = o[dt][1] = o[dt][2] = o[dt][3] = 0.f;
    mma16816(o[dt], pr[0], 0u, pr[1], pr[3], vh[2 * dt], vh[2 * dt + 1]);
    mma16816(o[dt], pr[2], pr[4], 0u, pr[5], v[2 * dt], v[2 * dt + 1]);
  }
}

#define SF 12
#define SLICE 1
#define HALO_NS 0
#define STAT_CLK 150
__global__ void __cluster_dims__(2, 1, 1) __launch_bounds__(384, 1) fused_kernel(const __grid_constant__ Params P) {
  extern __shared__ __align__(1024) uint8_t smem_raw[];
  const uint32_t sb = smem_u32(smem_raw);
  const uint32_t bars = sb + OFF_BAR;
  const int tid = threadIdx.x;
  const int wu = __shfl_sync(0xffffffffu, tid >> 5, 0), wg = wu >> 2;
  const int r = blockIdx.x & 1, cl = blockIdx.x >> 1;
  int grp, slt;
  if (cl < 4) { grp = 0; slt = 4 + cl; }
  else if (cl < 36) { grp = (cl - 4) & 7; slt = (cl - 4) >> 3; }
  else { grp = 1 + (cl - 36) % 7; slt = 4 + (cl - 36) / 7; }
#define MAP 0
  const int m = grp, j = slt;
  const int i = 2 * m + r;
  auto BAR = [&](int k) { return bars + 8 * k; };

  auto kb1 = [&](int n) { const int h = n >= 9, t = n - 2 - 7 * h; return n < 2 ? 2 * j + n : 2 * (t + (t >= j)) + h; };
  if (wu == 8) {
    if (elect_one()) {
      asm volatile("prefetch.tensormap [%0];" ::"l"(&P.x0) : "memory");
      asm volatile("prefetch.tensormap [%0];" ::"l"(&P.wqkv) : "memory");
#pragma unroll
      for (int k = 0; k < 6; k++) mbar_init(BAR(k < 4 ? F1 + k : XF + k - 4), 1);
      asm volatile("fence.mbarrier_init.release.cluster;" ::: "memory");
      fence_async_smem();
    }
    __syncwarp();
  } else if (wu == 0) {
    if (elect_one()) {
#pragma unroll
      for (int k = E1; k < 64; k++) {
        int cnt = 1;
        if (k < F2 || (k >= E2 && k < F3) || (k >= E3 && k < F4) || (k >= E4 && k < JOB) || k == JOB + 2 || k == JOB + 3) cnt = 4;
        else if ((k >= JOB && k < RD) || k == CSJ) cnt = 8;
        else if ((k >= RD && k < XF && k != RD + 1) || k == STD || k == STAT || k >= HALO) cnt = 2;
        if (k != XF && k != XF + 1) mbar_init(BAR(k), cnt);
      }
      asm volatile("fence.mbarrier_init.release.cluster;" ::: "memory");
      fence_async_smem();
    }
    __syncwarp();
  }
  auto load_tag = [&]() { uint32_t t; asm volatile("ld.relaxed.gpu.global.u32 %0, [%1];" : "=r"(t) : "l"(&gEpoch) : "memory"); return t + 1; };
  TS(0);
  if (wu == 8) nb_arrive<3>(384); else nb_sync<3>(384);
  asm volatile("barrier.cluster.arrive.relaxed;" ::: "memory");

  if (wg == 2) {
    reg_dealloc<40>();
    if (wu == 8) {
    if (elect_one()) {
#pragma unroll 1
      for (int u = 0; u < 4; u++) {
        const int kb = kb1(u);
        if (u < 2) { mbar_expect(BAR(XF + u), 16384); tma2d(sb + OFF_X + u * 16384, &P.x0, BAR(XF + u), kb * 64, 128 * i); }
        mbar_expect(BAR(F1 + u), u < 2 ? 24576 : 40960);
        tma3d(sb + slot1(u) + 16384, &P.wqkv, BAR(F1 + u), 128 * j, kb * 64, 0);
        tma3d(sb + slot1(u) + 28672, &P.wqkv, BAR(F1 + u), 128 * j, kb * 64 + 32, 0);
        if (u >= 2) tma2d(sb + slot1(u), &P.x0, BAR(F1 + u), kb * 64, 128 * i);
      }
    }
    __syncwarp();
    }
    asm volatile("barrier.cluster.wait;" ::: "memory");
    auto kb3 = [&](int n) { const int h = n >= 17, t = n - 3 - 14 * h; return n < 2 ? 2 * i + n : (n == 2 || n == 31) ? 2 * (i ^ 1) + h : 2 * ((2 * m + 2 + t) & 15) + h; };
    if (wu == 8) {
#pragma unroll 1
      for (int L = 0; L < 2; L++) {
#pragma unroll 1
        for (int u = L ? 0 : 4; u < 32; u++) {
          const int v = (L && u >= 2 && u < 18) ? (u < 4 ? u + 14 : u - 2) : u;
          const int p = u & 3, ab = v >> 4, nn = v & 15;
          if (u >= 4) mbar_wait(BAR(E1 + p), ((u >> 2) - 1) & 1);
          else mbar_wait(BAR(E4 + (u == 3 ? 0 : u + 3)), u == 3);
          if (elect_one()) {
            mbar_expect(BAR(F1 + p), nn < 2 ? 24576 : 40960);
            tma3d_mc(sb + slot1(p) + 16384 + r * 12288, &P.wqkv, BAR(F1 + p), 128 * j + 64 * ab, kb1(nn) * 64 + 32 * r, 0);
          }
        }
        int p = 0; uint32_t par = L ? 0x1e : 0;
#pragma unroll 1
        for (int n = 0; n < 16; n++) {
          if (n >= 5) { mbar_wait(BAR(E2 + p), (par >> p) & 1); par ^= 1u << p; }
          else if (n < 4) mbar_wait(BAR(E1 + n), 1);
          if (elect_one()) {
            mbar_expect(BAR(F2 + p), 32768);
            tma2d_mc(sb + slot2(p) + 16384 + r * 8192, &P.wo, BAR(F2 + p), 128 * j + 64 * r, (2 * (n & 7) + (n >> 3)) * 64);
          }
          if (++p == 5) p = 0;
        }
#pragma unroll 1
        for (int u = 0; u < 32; u++) {
          const int n = u < 4 ? (0x2031 >> (4 * u)) & 3 : u, p = n & 3, kb = kb3(n);
          if (n >= 4) mbar_wait(BAR(E3 + p), ((n >> 2) - 1) & 1);
          else if (n == 1) mbar_wait(BAR(STD + 1), L);
          else if (n == 3) mbar_wait(BAR(E2 + 2), L);
          else if (n == 0) mbar_wait(BAR(E2 + 4), L);
          else mbar_wait(BAR(E2 + 0), 1);
          if (elect_one()) {
            mbar_expect(BAR(F3 + p), n < 2 ? 32768 : 49152);
            tma3d(sb + slot3(p) + 16384, &P.w1, BAR(F3 + p), 0, kb * 64, 7 * m + 4 * r);
            tma3d(sb + slot3(p) + 40960, &P.w1h, BAR(F3 + p), 0, kb * 64, 14 * m + 6 + r);
          }
        }
#pragma unroll 1
        for (int n = 0; n < 6; n++) {
          if (n < 3) mbar_wait(BAR(E3 + n), 1);
          else if (n == 4) mbar_wait(BAR(E3 + 3), 1);
          if (elect_one()) {
            mbar_expect(BAR(F4 + n), n < 3 ? 16384 : 32768);
            tma3d(sb + slot4(n), &P.w2, BAR(F4 + n), 0, (n < 3 ? 7 * m + 4 * r + n : 7 * ((m + n - 2) & 7) + 3) * 64, 2 * i);
          }
        }
        p = 0; par = L ? 0x3c : 0;
        auto g4w = [&](int kb) {
          mbar_wait(BAR(E4 + p), (par >> p) & 1); par ^= 1u << p;
          if (elect_one()) {
            mbar_expect(BAR(F4 + p), 32768);
            tma3d(sb + slot4(p), &P.w2, BAR(F4 + p), 0, kb * 64, 2 * i);
          }
          if (++p == 6) p = 0;
        };
#pragma unroll 1
        for (int t = 4; t < 9; t++) g4w(7 * ((m + t) & 7) + 3);
#pragma unroll 1
        for (int c = 0; c < 3; c++)
#pragma unroll 1
          for (int t = 0; t < 15; t++) { const int ii = t < 14 ? (2 * m + 2 + t) & 15 : i ^ 1; g4w(((7 * ii + 1) >> 1) + c); }
      }
    } else if (wu == 9) {
      uint32_t inv = 0;
#pragma unroll 1
      for (int L = 0; L < 2; L++) {
        uint32_t ready = 0;
#pragma unroll 1
        for (int u = 4; u < 32; u++) {
          const int p = u & 3, nn = (L && u < 18 ? u - 2 : u) & 15, kb = kb1(nn);
          if (nn < 2) continue;
          if (L && u < 12) mbar_wait(BAR(F1 + p), u >> 3);
          if (u >= 4 + 4 * L) mbar_wait(BAR(E1 + p), ((u >> 2) - 1) & 1);
          if (L) {
            flag_wait(gFlag[0][0][i], inv, 1u << kb, ready);
            if (elect_one()) bulk_ld(sb + slot1(p), gXB + (i * 16 + kb) * 16384, 16384, BAR(F1 + p));
          } else if (elect_one()) tma2d(sb + slot1(p), &P.x0, BAR(F1 + p), kb * 64, 128 * i);
        }
        ready = 0;
        if (L == 0) inv = (__shfl_sync(0xffffffffu, load_tag(), 0) & 1) - 1;
        int p = 0; uint32_t par = L ? 0x1e : 0;
#pragma unroll 1
        for (int n = 0; n < 16; n++) {
          const int hp = 2 * (n & 7) + (n >> 3);
          if (n >= 5) { mbar_wait(BAR(E2 + p), (par >> p) & 1); par ^= 1u << p; }
          else if (n < 4) mbar_wait(BAR(E1 + n), 1);
          flag_wait(gFlag[L][1][i], inv, 1u << hp, ready);
          if (n == 8) ST(4);
          if (elect_one()) bulk_ld(sb + slot2(p), gOB + (i * 16 + hp) * 16384, 16384, BAR(F2 + p));
          if (++p == 5) p = 0;
        }
        ready = 0;
        mbar_wait(BAR(E2 + 0), 1);
#pragma unroll 1
        for (int n = 3; n < 32; n++) {
          const int p = n & 3, kb = kb3(n);
          if (n > 3) mbar_wait(BAR(E3 + p), ((n >> 2) - 1) & 1);
          flag_wait(gFlag[L][2][j], inv, 1u << kb, ready);
          if (n == 3) ST(12);
          if (elect_one()) {
            const uint8_t* src = gHB + (j * 32 + kb) * 16384;
            if (n < 31) bulk_ld_mc(sb + slot3(p) + r * 8192, src + r * 8192, 8192, BAR(F3 + p));
            else bulk_ld(sb + slot3(p), src, 16384, BAR(F3 + p));
          }
        }
        ready = 0; p = 3; par = L ? 0x3c : 0;
        mbar_wait(BAR(E3 + 3), 1);
#pragma unroll 1
        for (int t = 0; t < 8; t++) {
          const int mm = (m + t + 1) & 7;
          if (t >= 3) { if (t < 5) mbar_wait(BAR(RD + t - 1), L); mbar_wait(BAR(E4 + p), (par >> p) & 1); par ^= 1u << p; }
          flag_wait(gFlag[L][6][j], inv, 3u << (2 * mm), ready);
          if (t == 0) ST(20);
          if (elect_one()) bulk_ld_mc(sb + slot4(p) + 16384 + r * 8192, gUB + (j * 56 + 48 + mm) * 16384 + r * 8192, 8192, BAR(F4 + p));
          if (++p == 6) p = 0;
        }
#pragma unroll 1
        for (int c = 0; c < 3; c++) {
          ready = 0;
#pragma unroll 1
          for (int t = 0; t < 15; t++) {
            const int ii = t < 14 ? (2 * m + 2 + t) & 15 : i ^ 1;
            mbar_wait(BAR(E4 + p), (par >> p) & 1); par ^= 1u << p;
            flag_wait(gFlag[L][3 + c][j], inv, 1u << ii, ready);
            if (elect_one()) {
              const uint8_t* src = gUB + (j * 56 + 16 * c + ii) * 16384;
              if (t < 14) bulk_ld_mc(sb + slot4(p) + 16384 + r * 8192, src + r * 8192, 8192, BAR(F4 + p));
              else bulk_ld(sb + slot4(p) + 16384, src, 16384, BAR(F4 + p));
            }
            if (++p == 6) p = 0;
          }
        }
      }
    } else {
      const int h = wu - 10;
      const uint32_t tag = load_tag();
      int lane = tid & 31, z = 0;
#define FRESH asm volatile("" : "+r"(lane), "+r"(z))
      const uint32_t rs = mapa(sb, r ^ 1), rb = rs + OFF_BAR;
      auto signal = [&](int k) { if (lane == 0) mbar_arrive(BAR(k)); };
      auto drained = [&](int k) { if (lane == 0) { mbar_arrive(BAR(RD + k)); mbar_arrive_cl(rb + 8 * (RD + k)); } };
      auto publish = [&](uint32_t* f, int bit) { if (lane == 0) flag_set(f + z, 1u << (bit + z)); __syncwarp(); };
      for (int c = 32 * h + lane; c < 224; c += 64)
        sts32f(sb + OFF_B1 + (((c >> 1) & 3) * 56 + (c >> 3) * 2 + (c & 1)) * 4, 0.5f * __bfloat162float(P.b1[c < 192 ? 64 * (7 * m + 4 * r) + c : 64 * (7 * m + 3) + 32 * r + c - 192]));
#pragma unroll 1
      for (int L = 0; L < 2; L++) {
        FRESH;
        if (L == 0) {
          mbar_wait(BAR(CSJ), 0);
          float c0 = 0.f, c1 = 0.f, c2 = 0.f;
          const uint32_t a = sb + OFF_STG + (32 * h + lane) * 4;
#pragma unroll 8
          for (int k = 0; k < 32; k++) { c0 += lds32f(a + k * 784); c1 += lds32f(a + k * 784 + 256); c2 += lds32f(a + k * 784 + 512); }
          ll_st3(&gCS[j][i][32 * h + lane], __float_as_uint(c0), __float_as_uint(c1), __float_as_uint(c2), tag);
          __nanosleep(500);
        }
        FRESH;
        if (L == 0) {
#pragma unroll 1
          for (int ab = 0; ab < 2; ab++) {
            float c0 = 0.f, c1 = 0.f, c2 = 0.f;
#pragma unroll 1
            for (int b4 = 0; b4 < 8; b4 += 4) {
              uint32_t a[4], b[4], c[4], n = 0, bad;
              do {
                bad = 0;
#pragma unroll
                for (int e = 0; e < 4; e++) bad |= ll_ld3(&gCS[j][2 * (b4 + e) + ab][32 * h + lane], a[e], b[e], c[e], tag);
              } while (bad && ++n < SPIN_MAX);
#pragma unroll
              for (int e = 0; e < 4; e++) { c0 += __uint_as_float(a[e]); c1 += __uint_as_float(b[e]); c2 += __uint_as_float(c[e]); }
            }
            const uint32_t a = sb + OFF_CS + (ab * 192 + ((lane >> 1) & 3) * 48 + (4 * h + (lane >> 3)) * 2 + (lane & 1)) * 4;
            sts32f(a, c0); sts32f(a + 64, c1); sts32f(a + 128, c2);
            __syncwarp();
            if (ab == 0) signal(STAT);
          }
        }
#pragma unroll 1
        for (int ab = 0; ab < 2; ab++) {
          FRESH;
          uint32_t v[18];
          const uint32_t xs = sb + OFF_STG + h * 16384 + lane * 4;
          mbar_wait(BAR(FOLD + ab), L);
          if (ab && h == 0) ST(6);
          if (i < 15) {
#pragma unroll
            for (int c = 0; c < 16; c++) v[c] = __float_as_uint(lds32f(xs + c * 128));
            uint4* hp = &gHalo[L][i][j][6 * h][lane];
#pragma unroll
            for (int c = 0; c < 6; c++) ll_st3(hp + c * 32, v[3 * c], v[c < 5 ? 3 * c + 1 : 15], v[c < 5 ? 3 * c + 2 : 15], 2 * tag + ab);
          }
          if (i > 0) {
            __nanosleep(ab ? HALO_NS : 700);
            const uint4* hp = &gHalo[L][i - 1][j][6 * h][lane];
            uint32_t n = 0, bad;
            do {
              bad = 0;
#pragma unroll
              for (int c = 0; c < 6; c++) bad |= ll_ld3(hp + c * 32, v[3 * c], v[3 * c + 1], v[3 * c + 2], 2 * tag + ab);
            } while (bad && ++n < SPIN_MAX);
          } else {
#pragma unroll
            for (int c = 0; c < 16; c++) v[c] = 0u;
          }
#pragma unroll
          for (int c = 0; c < 16; c++) sts32f(xs + c * 128, __uint_as_float(v[c]));
          __syncwarp();
          signal(HALO + ab);
          if (ab && h == 0) ST(7);
          FRESH;
          if (ab == 0 && lane == 0) asm volatile("st.relaxed.gpu.global.u32 [%0], %1;" ::"l"(&gAck[L][i][j][h][z]), "r"(tag) : "memory");
          mbar_wait(BAR(JOB + ab), L);
          if (h == 0) {
            if (ab) ST(1);
            if (lane == 0) { bulk_st(gOB + (i * 16 + 2 * j + ab + z) * 16384, sb + OFF_STG, 16384); bulk_commit(); bulk_wait0(); }
            signal(STD + ab);
            if (ab) ST(2);
            publish(gFlag[L][1][i], 2 * j + ab);
            if (ab) ST(3);
          } else if (ab == 0) {
            if (i < 15 && lane < 2) {
              uint32_t t, n = 0;
              do { asm volatile("ld.relaxed.gpu.global.u32 %0, [%1];" : "=r"(t) : "l"(&gAck[L][i + 1][j][lane][0]) : "memory"); } while (t != tag && ++n < SPIN_MAX);
            }
            __syncwarp();
            signal(STD);
          }
        }
        FRESH;
        if (h == 0) {
          mbar_wait(BAR(JOB + 2), L);
          ST(9);
          if (lane == 0) { bulk_st(gHB + (j * 32 + 2 * i + z) * 16384, sb + OFF_X, 16384); bulk_commit(); }
          mbar_wait(BAR(E2 + 0), 1);
          if (lane == 0) { bulk_s2s(rs + slot3(2), sb + OFF_X, 16384, rb + 8 * (F3 + 2)); bulk_wait0(); }
          signal(RD);
          ST(10);
          publish(gFlag[L][2][j], 2 * i);
          ST(11);
          nb_arrive<NB_HELP>(64);
        } else {
          mbar_wait(BAR(JOB + 3), L);
          nb_sync<NB_HELP>(64);
          warp_store(gHB + (j * 32 + 2 * i + 1) * 16384 + lane * 16, sb + lane * 16 + OFF_X + 16384, 16384);
          signal(RD);
          ST(15);
          publish(gFlag[L][2][j], 2 * i + 1);
        }
        FRESH;
        if (h == 0) {
          mbar_wait(BAR(JOB + 7), L);
          ST(17);
          if (lane == 0) {
            for (int a = 0; a < 2; a++) bulk_st(gUB + (j * 56 + 48 + m + z) * 16384 + a * 8192 + r * 4096, sb + slot4(1) + 16384 + a * 8192, 4096);
            bulk_commit(); bulk_wait0();
          }
          drained(3);
          ST(18);
          publish(gFlag[L][6][j], i);
          ST(19);
          nb_sync<NB_HELP>(64);
#pragma unroll 1
          for (int c = 1; c < 3; c++) {
            warp_store(gUB + (j * 56 + 16 * c + i) * 16384 + lane * 16, sb + lane * 16 + OFF_X + (c - 1) * 16384, 16384);
            ST(22 + c);
            if (c == 2) signal(RD + 1);
            publish(gFlag[L][3 + c][j], i);
          }
        } else {
          mbar_wait(BAR(JOB + 6), L);
          warp_store(gUB + (j * 56 + i) * 16384 + lane * 16, sb + lane * 16 + slot4(0) + 16384, 16384);
          nb_arrive<NB_HELP>(64);
          drained(2);
          ST(25);
          publish(gFlag[L][3][j], i);
        }
        FRESH;
        mbar_wait(BAR(JOB + 8 + h), L);
        if (L == 0) {
          if (h == 0 && lane == 0) { bulk_st(gXB + (i * 16 + 2 * j + z) * 16384, sb + OFF_X, 16384); bulk_commit(); bulk_wait0(); }
          __syncwarp();
          nb_sync<NB_HELP>(64);
          if (h == 1) warp_store(gXB + (i * 16 + 2 * j + 1) * 16384 + lane * 16, sb + lane * 16 + OFF_X + 16384, 16384);
          publish(gFlag[0][0][i], 2 * j + h);
        } else if (lane == 0) {
          tma2d_store(&P.out, sb + OFF_X + h * 16384, 128 * j + 64 * h, 128 * i);
          bulk_commit(); bulk_wait0();
        }
      }
      if (blockIdx.x == 0 && h == 0 && lane == 0) asm volatile("st.relaxed.gpu.global.u32 [%0], %1;" ::"l"(&gEpoch), "r"(tag) : "memory");
    }
    __syncwarp();
    cluster_bar();
  } else {
    reg_alloc<232>();
    asm volatile("barrier.cluster.wait;" ::: "memory");
    const uint32_t rbars = mapa(bars, tid & 1);
    const bool relp = (tid & 127) < 2;
    uint32_t tag;
    asm volatile("ld.relaxed.gpu.global.u32 %0, [%1];" : "=r"(tag) : "l"(&gEpoch + (fresh_tid() >> 10)) : "memory");
    auto release = [&](int k) { if (relp) mbar_arrive_cl(rbars + 8 * k); };
    auto signal = [&](int k) { __syncwarp(); if ((fresh_tid() & 31) == 0) mbar_arrive(BAR(k)); };
#define GEOM const int t7 = fresh_tid() & 127, lane = t7 & 31, w = t7 >> 5, g = lane >> 2, q = lane & 3, \
                       lr = lane & 15, lt = lane >> 4, l7 = lane & 7; (void)w; (void)g; (void)q; (void)lr; (void)lt; (void)l7

#pragma unroll 1
    for (int L = 0; L < 2; L++) {
      float acca[96], accb[96], xa[64], acc3[112];
      float nmean0, nmean1, rstd0, rstd1;
      uint16_t b2a, b2b;
      uint32_t Q[2][8], K[2][8], V[16];
      auto g1_issue = [&](float (&acc)[96], uint32_t a, uint32_t st, auto first) {
        const uint64_t da = mkdesc(a + wg * 8192, 16, 1024), db = mkdesc(st + 16384, 4096, 1024);
        wg_fence();
#pragma unroll
        for (int kk = 0; kk < 4; kk++) {
          const uint64_t b = db + (((kk >> 1) * 12288 + (kk & 1) * 2048) >> 4);
          if (first.value && kk == 0) wgmma_192z<0, 1>(acc, da, b); else wgmma_192<0, 1>(acc, da + kk * 2, b);
        }
        wg_commit();
      };
      auto g1_step = [&](float (&acc)[96], int u, bool rel) {
        const int p = u & 3;
        mbar_wait(BAR(F1 + p), (u >> 2) & 1);
        KB(u);
        g1_issue(acc, sb + slot1(p), sb + slot1(p), False{});
        wg_wait<1>();
        if (rel) release(E1 + ((u - 1) & 3));
      };
      auto g1_loop = [&](float (&acc)[96], int u0, int u1, int urel) {
#pragma unroll 1
        for (int u = u0; u < u1; u++) g1_step(acc, u, u > urel);
      };
      auto load_x = [&]() {
        GEOM;
#pragma unroll
        for (int t = 0; t < 16; t += 2) {
          uint32_t v0, v1, v2, v3;
          ldsm4(sb + OFF_X + (t >> 3) * 16384 + (16 * wu + lr) * 128 + ((((t & 7) + lt) ^ l7) << 4), v0, v1, v2, v3);
          xa[4 * t + 0] = bf_lo(v0); xa[4 * t + 1] = bf_hi(v0); xa[4 * t + 2] = bf_lo(v1); xa[4 * t + 3] = bf_hi(v1);
          xa[4 * t + 4] = bf_lo(v2); xa[4 * t + 5] = bf_hi(v2); xa[4 * t + 6] = bf_lo(v3); xa[4 * t + 7] = bf_hi(v3);
        }
      };
      auto stat_publish = [&](float s0, float q0, float s2, float q2, uint32_t tg) {
        GEOM;
        const bool h1 = q & 1;
        float sm = (h1 ? s2 : s0) + __shfl_xor_sync(0xffffffffu, h1 ? s0 : s2, 1);
        float sq = (h1 ? q2 : q0) + __shfl_xor_sync(0xffffffffu, h1 ? q0 : q2, 1);
        sm += __shfl_xor_sync(0xffffffffu, sm, 2); sq += __shfl_xor_sync(0xffffffffu, sq, 2);
        if (q < 2) stat_st(&gST[L][i][wu][j][2 * g + q], sm, sq, tg);
        return sm;
      };
      auto g1_stats = [&](int u0) {
        GEOM;
        const uint32_t xr = sb + OFF_X + (16 * wu + lr) * 128;
        float s0 = 0.f, q0 = 0.f, s2 = 0.f, q2 = 0.f;
        uint32_t v[8] = {0u, 0u, 0u, 0u, 0u, 0u, 0u, 0u};
#pragma unroll 1
        for (int k = 0; k < 5; k++) {
#pragma unroll
          for (int e = 0; e < 8; e += 2) {
            const float a = bf_lo(v[e]), b = bf_hi(v[e]), c = bf_lo(v[e + 1]), d = bf_hi(v[e + 1]);
            s0 += a + b; q0 = fmaf(a, a, fmaf(b, b, q0)); s2 += c + d; q2 = fmaf(c, c, fmaf(d, d, q2));
          }
          if (k == 4) break;
          const uint32_t o = ((2 * k + lt) ^ l7) << 4;
          ldsm4(xr + o, v[0], v[1], v[2], v[3]);
          ldsm4(xr + o + 16384, v[4], v[5], v[6], v[7]);
          g1_step(acca, u0 + k, true);
        }
        stat_publish(s0, q0, s2, q2, 2 * (tag + 1));
      };
      uint32_t sv0[4], sv1[4];
      auto stat_fetch = [&]() {
        const uint2* sp = &gST[L][i][wu][0][0] + 2 * (fresh_tid() & 31);
        stat_ld2(sp, sv0); stat_ld2(sp + 64, sv1);
      };
      auto stat_await = [&](uint32_t tg) {
#pragma unroll 1
        for (uint32_t n = 0; (((sv0[0] ^ tg) | (sv0[2] ^ tg) | (sv1[0] ^ tg) | (sv1[2] ^ tg)) & 15u) && n < SPIN_MAX; n++) stat_fetch();
        __syncwarp();
      };
      auto ln_stats = [&]() {
        GEOM;
        stat_await(2 * (tag + 1));
        float mean0, var0, mean1, var1;
        stat_combine(sv0[0], sv0[1], sv1[0], sv1[1], untag(__shfl_sync(0xffffffffu, sv0[0], l7)), mean0, var0);
        stat_combine(sv0[2], sv0[3], sv1[2], sv1[3], untag(__shfl_sync(0xffffffffu, sv0[2], l7)), mean1, var1);
        nmean0 = -__shfl_sync(0xffffffffu, mean0, g); rstd0 = rsq(__shfl_sync(0xffffffffu, var0, g) + 1e-5f);
        nmean1 = -__shfl_sync(0xffffffffu, mean1, g); rstd1 = rsq(__shfl_sync(0xffffffffu, var1, g) + 1e-5f);
      };
      float4 cs[12];
      auto cs_load = [&](int ab, int part) {
        const uint32_t ca = sb + OFF_CS + (ab * 192 + 48 * (fresh_tid() & 3) + 16 * part) * 4;
#pragma unroll
        for (int k = 0; k < 4; k++) cs[4 * part + k] = lds128f(ca + 16 * k);
      };
      auto frag = [&](float (&acc)[96], int t, uint32_t& p0, uint32_t& p1) {
        const float cx = (t & 1) ? cs[t >> 1].z : cs[t >> 1].x, cy = (t & 1) ? cs[t >> 1].w : cs[t >> 1].y;
        float v0 = fmaf(nmean0, cx, acc[4 * t]), v1 = fmaf(nmean0, cy, acc[4 * t + 1]);
        float v2 = fmaf(nmean1, cx, acc[4 * t + 2]), v3 = fmaf(nmean1, cy, acc[4 * t + 3]);
        if (t >= 8) { v0 *= rstd0; v1 *= rstd0; v2 *= rstd1; v3 *= rstd1; }
        p0 = pack2(v0, v1); p1 = pack2(v2, v3);
      };
      auto fold_v = [&](float (&acc)[96]) {
        GEOM;
        const uint32_t a = sb + OFF_STG + 16384 + ((wu + 1) & 7) * 2048 + lr * 128;
#pragma unroll
        for (int t = 0; t < 8; t += 2) {
          uint32_t p0, p1, p2, p3;
          frag(acc, 16 + t, p0, p1); frag(acc, 17 + t, p2, p3);
          stsm4(a + (((t + lt) ^ l7) << 4), p0, p1, p2, p3);
        }
        __syncwarp();
#pragma unroll
        for (int t = 0; t < 8; t += 2) ldsm4t(a + (((t + lt) ^ l7) << 4), V[2 * t], V[2 * t + 1], V[2 * t + 2], V[2 * t + 3]);
      };
      auto fold_k = [&](float (&acc)[96], int ab) {
        GEOM;
#pragma unroll
        for (int t = 8; t < 16; t++) frag(acc, t, K[0][t - 8], K[1][t - 8]);
        const uint32_t a = sb + OFF_STG + ((wu + 1) & 7) * 2048 + lane * 16;
#pragma unroll
        for (int c = 0; c < 4; c++)
          sts128(a + c * 512, K[c >> 1][4 * (c & 1)], K[c >> 1][4 * (c & 1) + 1], K[c >> 1][4 * (c & 1) + 2], K[c >> 1][4 * (c & 1) + 3]);
        if (wu == 7) signal(FOLD + ab);
      };
      auto fold_q = [&](float (&acc)[96]) {
#pragma unroll
        for (int t = 0; t < 8; t++) frag(acc, t, Q[0][t], Q[1][t]);
      };
      auto attend = [&](int ab, auto drain) {
        GEOM;
        nb_sync<NB_BOTH>(256);
        const uint32_t xa_ = sb + OFF_STG + wu * 2048 + lane * 16;
        if (wu == 0) mbar_wait(BAR(HALO + ab), L);
        uint32_t KH[2][8], VH[16];
#pragma unroll
        for (int c = 0; c < 4; c++) {
          lds128(xa_ + c * 512, KH[c >> 1][4 * (c & 1)], KH[c >> 1][4 * (c & 1) + 1], KH[c >> 1][4 * (c & 1) + 2], KH[c >> 1][4 * (c & 1) + 3]);
          ldsm4t(sb + OFF_STG + 16384 + wu * 2048 + lr * 128 + (((2 * c + lt) ^ l7) << 4), VH[4 * c], VH[4 * c + 1], VH[4 * c + 2], VH[4 * c + 3]);
        }
        TS2(11 + ab + 32 * L);
        drain();
        if (SF & 4) sched_fence(P.zero);
        const bool e = g & 1, zneg = (g >> 1) < q, first = (i == 0) && (wu == 0);
        const float qs = 0.17677669530f * 1.4426950409f;
        uint32_t pr[2][6];
#pragma unroll
        for (int hh = 0; hh < 2; hh++)
          attn_probs(&Q[0][4 * hh], &Q[1][4 * hh], &KH[0][4 * hh], &KH[1][4 * hh], &K[0][4 * hh], &K[1][4 * hh], rstd0 * qs, rstd1 * qs, first, e, zneg, pr[hh]);
        float o[2][4][4];
#pragma unroll
        for (int hh = 0; hh < 2; hh++) attn_pv(pr[hh], &VH[8 * hh], &V[8 * hh], o[hh]);
#pragma unroll
        for (int hh = 0; hh < 2; hh++)
#pragma unroll
          for (int dt = 0; dt < 4; dt += 2)
            stsm4(sb + OFF_STG + (16 * wu + lr) * 128 + (((4 * hh + dt + lt) ^ l7) << 4),
                  pack2(o[hh][dt][0], o[hh][dt][1]), pack2(o[hh][dt][2], o[hh][dt][3]), pack2(o[hh][dt + 1][0], o[hh][dt + 1][1]), pack2(o[hh][dt + 1][2], o[hh][dt + 1][3]));
        fence_async_smem();
        signal(JOB + ab);
        nb_sync<NB_BOTH>(256);
      };

      if (L == 0) mbar_wait(BAR(XF), 0);
      TS(1 + 32 * L);
      mbar_wait(BAR(F1), 0); KB(0);    g1_issue(acca, sb + OFF_X, sb + slot1(0), True{});
      if (L == 0) mbar_wait(BAR(XF + 1), 0);
      mbar_wait(BAR(F1 + 1), 0); KB(1); g1_issue(acca, sb + OFF_X + 16384, sb + slot1(1), False{});
      wg_wait<1>(); release(E1 + 0);
      auto g1_bhead = [&](int p) {
        mbar_wait(BAR(F1 + p), 0); KB(p ? 2 : 16); g1_issue(accb, sb + OFF_X, sb + slot1(p), True{});
        if (p) { wg_wait<1>(); release(E1 + 1); }
        mbar_wait(BAR(F1 + p + 1), 0); KB(p ? 3 : 17); g1_issue(accb, sb + OFF_X + 16384, sb + slot1(p + 1), False{});
        wg_wait<1>(); release(E1 + p);
      };
      if (L == 0) {
        GEOM;
        const bf16* wp = P.wqkv_p + (size_t)(128 * m + 16 * wg + (t7 >> 3)) * 3072 + 128 * j + 64 * r + l7 * 8;
        const uint32_t ca = sb + OFF_STG + (16 * wg + (t7 >> 3)) * 784 + l7 * 32;
#pragma unroll 1
        for (int p = 0; p < 3; p++) {
          uint4 wv[4];
#pragma unroll
          for (int k = 0; k < 4; k++)
            asm volatile("ld.global.nc.v4.u32 {%0, %1, %2, %3}, [%4];" : "=r"(wv[k].x), "=r"(wv[k].y), "=r"(wv[k].z), "=r"(wv[k].w)
                         : "l"(wp + (size_t)k * 32 * 3072 + p * 1024));
          g1_loop(acca, 2 + 2 * p, 4 + 2 * p, 0);
          float cs[8];
#pragma unroll
          for (int k = 0; k < 4; k++) {
            const uint4 v = wv[k];
            const float t[8] = {bf_lo(v.x), bf_hi(v.x), bf_lo(v.y), bf_hi(v.y), bf_lo(v.z), bf_hi(v.z), bf_lo(v.w), bf_hi(v.w)};
#pragma unroll
            for (int e = 0; e < 8; e++) cs[e] = k ? cs[e] + t[e] : t[e];
          }
          sts128(ca + p * 256, __float_as_uint(cs[0]), __float_as_uint(cs[1]), __float_as_uint(cs[2]), __float_as_uint(cs[3]));
          sts128(ca + p * 256 + 16, __float_as_uint(cs[4]), __float_as_uint(cs[5]), __float_as_uint(cs[6]), __float_as_uint(cs[7]));
        }
        signal(CSJ);
        TS2(17);
        g1_stats(8);
        g1_loop(acca, 12, 14, 0);
        stat_fetch();
        g1_loop(acca, 14, 16, 0);
        ln_stats();
        wg_wait<0>(); release(E1 + 3);
        fence_regs(acca);
        g1_bhead(0);
        mbar_wait(BAR(STAT), 0);
      } else {
        g1_bhead(2);
        g1_stats(4);
        g1_loop(acca, 8, 12, 0);
        stat_fetch();
        g1_loop(acca, 12, 14, 0);
        ln_stats();
        g1_loop(acca, 14, 18, 0);
      }
      cs_load(0, 2);
      g1_step(accb, 18, true);
      fence_regs(acca);
      TS(2 + 32 * L);
      fold_v(acca); cs_load(0, 1);
      g1_loop(accb, 19, 21, 0);
      fold_k(acca, 0); cs_load(0, 0);
      g1_loop(accb, 21, 23, 0);
      fold_q(acca);
      sched_fence(P.zero);
      g1_step(accb, 23, true);
      attend(0, [&]() { wg_wait<0>(); release(E1 + 3); });
      TS(3 + 32 * L);
      g1_loop(accb, 24, 27, 24);
      load_x();
      fence_regs(xa);
      g1_loop(accb, 27, 32, 0);
      mbar_wait(BAR(STD), L);
      cs_load(1, 2); cs_load(1, 1); cs_load(1, 0);
      wg_wait<0>(); release(E1 + 3);
      fence_regs(accb);
      TS(4 + 32 * L);
      if (wu == 7) ST(0);
      fold_v(accb); fold_k(accb, 1);
      if (SF & 2) sched_fence(P.zero);
      fold_q(accb);
      TS2(29 + 32 * L);
      {
        auto g2_issue = [&](int p) {
          const uint32_t st = sb + slot2(p);
          const uint64_t da = mkdesc(st + wg * 8192, 16, 1024), db = mkdesc(st + 16384, 8192, 1024);
          wg_fence();
#pragma unroll
          for (int kk = 0; kk < 4; kk++) wgmma_128<0, 1>(xa, da + kk * 2, db + kk * 128);
          wg_commit();
        };
        uint32_t par = L ? 0x1e : 0;
        mbar_wait(BAR(F2 + 0), par & 1); KB(32); g2_issue(0);
        mbar_wait(BAR(F2 + 1), (par >> 1) & 1); KB(33); g2_issue(1);
        par ^= 3;
        attend(1, [&]() { wg_wait<0>(); release(E2 + 0); release(E2 + 1); });
        TS(30 + 32 * L);
        int p = 2, pp = 0;
        auto g2_loop = [&](int n0, int n1) {
#pragma unroll 1
          for (int n = n0; n < n1; n++) {
            mbar_wait(BAR(F2 + p), (par >> p) & 1);
            KB(32 + n);
            if (n == 8 && wu == 0) ST(5);
            par ^= 1u << p;
            g2_issue(p);
            wg_wait<1>();
            if (n > 2) release(E2 + pp);
            pp = p; if (++p == 5) p = 0;
          }
        };
        g2_loop(2, 8);
        {
          GEOM;
#pragma unroll
          for (int t = 0; t < 28; t += 2) {
            const float4 b = lds128f(sb + OFF_B1 + (56 * q + 2 * t) * 4);
            acc3[4 * t] = b.x; acc3[4 * t + 1] = b.y; acc3[4 * t + 2] = b.x; acc3[4 * t + 3] = b.y;
            acc3[4 * t + 4] = b.z; acc3[4 * t + 5] = b.w; acc3[4 * t + 6] = b.z; acc3[4 * t + 7] = b.w;
          }
          fence_regs(acc3);
          const bf16* bp = P.b2 + 128 * i + 16 * wu + g;
          asm volatile("ld.global.nc.u16 %0, [%1];" : "=h"(b2a) : "l"(bp));
          asm volatile("ld.global.nc.u16 %0, [%1];" : "=h"(b2b) : "l"(bp + 8));
        }
        TS2(14 + 32 * L);
        g2_loop(8, 16);
        wg_wait<0>();
        release(E2 + 0);
        fence_regs(xa);
      }
      TS(5 + 32 * L);
      if (wu == 0) ST(8);
      {
        GEOM;
        const uint32_t tg = 2 * (tag + 1) + 1;
        float s0 = 0.f, s1 = 0.f, s2 = 0.f, s3 = 0.f, q0 = 0.f, q1 = 0.f, q2 = 0.f, q3 = 0.f;
#pragma unroll
        for (int t = 0; t < 16; t++) {
          s0 += xa[4 * t]; s1 += xa[4 * t + 1]; s2 += xa[4 * t + 2]; s3 += xa[4 * t + 3];
          q0 = fmaf(xa[4 * t], xa[4 * t], q0); q1 = fmaf(xa[4 * t + 1], xa[4 * t + 1], q1);
          q2 = fmaf(xa[4 * t + 2], xa[4 * t + 2], q2); q3 = fmaf(xa[4 * t + 3], xa[4 * t + 3], q3);
        }
        const float sm = stat_publish(s0 + s1, q0 + q1, s2 + s3, q2 + q3, tg);
        const uint32_t t0 = clock32();
        TS2(13 + 32 * L);
        const float pv0 = __shfl_sync(0xffffffffu, sm, 4 * l7) * (1.f / 128), pv1 = __shfl_sync(0xffffffffu, sm, 4 * l7 + 1) * (1.f / 128);
        while (clock32() - t0 < STAT_CLK) {}
        stat_fetch();
        stat_await(tg);
        float r0, m0, r1, m1;
        {
          float mean0, var0, mean1, var1;
          stat_combine(sv0[0], sv0[1], sv1[0], sv1[1], pv0, mean0, var0); stat_combine(sv0[2], sv0[3], sv1[2], sv1[3], pv1, mean1, var1);
          mean0 = __shfl_sync(0xffffffffu, mean0, g); var0 = __shfl_sync(0xffffffffu, var0, g);
          mean1 = __shfl_sync(0xffffffffu, mean1, g); var1 = __shfl_sync(0xffffffffu, var1, g);
          r0 = 0.5f * rsq(fmaf(var0 + 1e-5f, 1e-5f, var0)); r1 = 0.5f * rsq(fmaf(var1 + 1e-5f, 1e-5f, var1));
          m0 = -mean0 * r0; m1 = -mean1 * r1;
        }
        TS2(15 + 32 * L);
        const uint32_t ha = sb + OFF_X + wg * 16384 + (16 * w + lr) * 128;
#pragma unroll
        for (int t = 0; t < 16; t += 2)
          stsm4(ha + (t >> 3) * 8192 + ((((t & 7) + lt) ^ l7) << 4),
                pack2(fmaf(xa[4 * t], r0, m0), fmaf(xa[4 * t + 1], r0, m0)), pack2(fmaf(xa[4 * t + 2], r1, m1), fmaf(xa[4 * t + 3], r1, m1)),
                pack2(fmaf(xa[4 * t + 4], r0, m0), fmaf(xa[4 * t + 5], r0, m0)), pack2(fmaf(xa[4 * t + 6], r1, m1), fmaf(xa[4 * t + 7], r1, m1)));
        fence_async_smem();
        signal(JOB + 2 + wg);
        nb_sync<NB_BOTH>(256);
      }
      TS(6 + 32 * L);
      auto g3_issue = [&](uint32_t a, int p) {
        const uint32_t st = sb + slot3(p);
        const uint64_t da = mkdesc(a + wg * 8192, 8192, 1024), db = mkdesc(st + 16384, 8192, 1024);
        wg_fence();
#pragma unroll
        for (int kk = 0; kk < 4; kk++) wgmma_224<1, 1>(acc3, da + kk * 128, db + kk * 128);
        wg_commit();
      };
      mbar_wait(BAR(F3 + 0), 0); KB(48); g3_issue(sb + OFF_X, 0);
      mbar_wait(BAR(F3 + 1), 0); KB(49); g3_issue(sb + OFF_X + 16384, 1);
      sched_fence(P.zero);
      {
        const float c0 = __uint_as_float((uint32_t)b2a << 16), c1 = __uint_as_float((uint32_t)b2b << 16);
#pragma unroll
        for (int t = 0; t < 16; t++) { xa[4 * t] += c0; xa[4 * t + 1] += c0; xa[4 * t + 2] += c1; xa[4 * t + 3] += c1; }
        fence_regs(xa);
      }
      wg_wait<1>(); release(E3 + 0);
#pragma unroll 1
      for (int n = 2; n < 32; n++) {
        const int p = n & 3;
        mbar_wait(BAR(F3 + p), (n >> 2) & 1);
        KB(48 + n);
        if (n == 3 && wu == 0) ST(13);
        if (n == 2 && wu == 0) ST(14);
        g3_issue(sb + slot3(p), p);
        wg_wait<1>();
        release(E3 + ((n - 1) & 3));
      }
      mbar_wait(BAR(RD), L);
      wg_wait<0>();
      release(E3 + 3);
      fence_regs(acc3);
      TS(7 + 32 * L);
      if (wu == 0) ST(16);
      auto g4_issue = [&](int p, uint32_t b) {
        const uint64_t da = mkdesc(sb + slot4(p) + wg * 8192, 8192, 1024), db = mkdesc(b, 8192, 1024);
        wg_fence();
#pragma unroll
        for (int kk = 0; kk < 4; kk++) wgmma_128<1, 1>(xa, da + kk * 128, db + kk * 128);
        wg_commit();
      };
      uint32_t par = L ? 0x3c : 0;
      {
        GEOM;
        const uint32_t ua = sb + wg * 8192 + (8 * lt + l7) * 128 + (((2 * w + ((lane >> 3) & 1)) ^ l7) << 4);
#pragma unroll
        for (int cc = 0; cc < 4; cc++) {
          const int c = (cc + 3) & 3;
          uint32_t u[16];
#pragma unroll
          for (int k = 0; k < (c == 3 ? 8 : 16); k++) u[k] = pack2(gelu_half(acc3[32 * c + 2 * k]), gelu_half(acc3[32 * c + 2 * k + 1]));
          if (c == 3) mbar_wait(BAR(E3 + 1), 1);
#pragma unroll
          for (int k = 0; k < (c == 3 ? 2 : 4); k++)
            stsm4t(ua + (c == 3 ? slot4(1) + 16384 : c == 0 ? slot4(0) + 16384 : OFF_X + (c - 1) * 16384) + k * 2048, u[4 * k], u[4 * k + 1], u[4 * k + 2], u[4 * k + 3]);
          if (c >= 2) { fence_async_smem(); signal(JOB + 4 + c); }
          if ((c == 3 && (SF & 8)) || (c == 0 && (SF & 16))) sched_fence(P.zero);
          TS2(16 + 3 * c + 32 * L);
        }
        nb_sync<NB_BOTH>(256);
      }
      TS(8 + 32 * L);
      {
        int p = 0, pp = 0;
#pragma unroll 1
        for (int n = 0; n < 56; n++) {
          mbar_wait(BAR(F4 + p), (par >> p) & 1);
          KB(80 + n);
          if (n == 3 && wu == 0) ST(21);
          if (n == 0 && wu == 0) ST(22);
          par ^= 1u << p;
          g4_issue(p, (n == 1 || n == 2) ? sb + OFF_X + (n - 1) * 16384 : sb + slot4(p) + 16384);
          wg_wait<1>();
          if (n) release(E4 + pp);
          pp = p; if (++p == 6) p = 0;
        }
      }
      mbar_wait(BAR(RD + 1), L);
      wg_wait<0>();
      release(E4 + 1);
      fence_regs(xa);
      TS(9 + 32 * L);
      {
        GEOM;
#pragma unroll
        for (int t = 0; t < 16; t += 2) {
          stsm4(sb + OFF_X + (t >> 3) * 16384 + (16 * wu + lr) * 128 + ((((t & 7) + lt) ^ l7) << 4),
                pack2(xa[4 * t], xa[4 * t + 1]), pack2(xa[4 * t + 2], xa[4 * t + 3]),
                pack2(xa[4 * t + 4], xa[4 * t + 5]), pack2(xa[4 * t + 6], xa[4 * t + 7]));
          if ((t & 7) == 6) { fence_async_smem(); signal(JOB + 8 + (t >> 3)); }
        }
        nb_sync<NB_BOTH>(256);
      }
      TS(10 + 32 * L);
      KB(136);
    }
    cluster_bar();
    TS(32);
  }
}

typedef CUresult (*EncodeFn)(CUtensorMap*, CUtensorMapDataType, cuuint32_t, void*, const cuuint64_t*, const cuuint64_t*, const cuuint32_t*,
                             const cuuint32_t*, CUtensorMapInterleave, CUtensorMapSwizzle, CUtensorMapL2promotion, CUtensorMapFloatOOBfill);

void make_map(EncodeFn enc, CUtensorMap* mp, const void* base, int rank, cuuint64_t d0, cuuint64_t d1, cuuint64_t d2, cuuint64_t s1, cuuint64_t s2,
              cuuint32_t b0, cuuint32_t b1, cuuint32_t b2) {
  cuuint64_t dims[3] = {d0, d1, d2}, strides[2] = {s1, s2};
  cuuint32_t box[3] = {b0, b1, b2}, es[3] = {1, 1, 1};
  CUresult res = enc(mp, CU_TENSOR_MAP_DATA_TYPE_BFLOAT16, rank, const_cast<void*>(base), dims, strides, box, es, CU_TENSOR_MAP_INTERLEAVE_NONE,
                     CU_TENSOR_MAP_SWIZZLE_128B, CU_TENSOR_MAP_L2_PROMOTION_L2_128B, CU_TENSOR_MAP_FLOAT_OOB_FILL_NONE);
  (void)res;
}

}

extern "C" void kernel_launch(void* const* d_in, const int* in_sizes, int n_in, void* d_out, int out_size) {
  (void)in_sizes; (void)n_in; (void)out_size;
  static EncodeFn enc = nullptr;
  if (!enc) {
    void* fn = nullptr;
    cudaDriverEntryPointQueryResult qr;
    cudaGetDriverEntryPoint("cuTensorMapEncodeTiled", &fn, cudaEnableDefault, &qr);
    enc = (EncodeFn)fn;
    cudaFuncSetAttribute(fused_kernel, cudaFuncAttributeMaxDynamicSharedMemorySize, SMEM_BYTES);
  }
  Params P;
  make_map(enc, &P.x0, d_in[0], 2, D_, S_, 1, D_ * 2, 0, 64, 128, 1);
  make_map(enc, &P.wqkv, d_in[1], 3, D_, D_, 3, 3 * D_ * 2, D_ * 2, 64, 32, 3);
  make_map(enc, &P.wo, d_in[2], 2, D_, D_, 1, D_ * 2, 0, 64, 64, 1);
  make_map(enc, &P.w1, d_in[4], 3, 64, S_, F_ / 64, F_ * 2, 128, 64, 64, 3);
  make_map(enc, &P.w1h, d_in[4], 3, 32, S_, F_ / 32, F_ * 2, 64, 64, 64, 1);
  make_map(enc, &P.w2, d_in[6], 3, 64, F_, S_ / 64, S_ * 2, 128, 64, 64, 2);
  make_map(enc, &P.out, d_out, 2, D_, S_, 1, D_ * 2, 0, 64, 128, 1);
  P.wqkv_p = (const bf16*)d_in[1];
  P.b1 = (const bf16*)d_in[5];
  P.b2 = (const bf16*)d_in[7];
  P.zero = 0;
  fused_kernel<<<128, 384, SMEM_BYTES>>>(P);
}
```

```cpp
#include <cuda_runtime.h>
#include <cuda_bf16.h>
#include <cuda.h>
#include <stdint.h>

namespace {

typedef __nv_bfloat16 bf16;
constexpr int S_ = 2048, D_ = 1024, F_ = 3584;

constexpr uint32_t OFF_STG  = 163840;
constexpr uint32_t OFF_X    = 196608;
constexpr uint32_t OFF_BAR  = 229376;
constexpr uint32_t OFF_CS   = OFF_BAR + 512;
constexpr uint32_t OFF_B1   = OFF_CS + 1536;
constexpr uint32_t SMEM_BYTES = OFF_B1 + 896 + 128;
constexpr int F1 = 0, E1 = 4, F2 = 8, E2 = 13, F3 = 18, E3 = 22, F4 = 26, E4 = 32;
constexpr int JOB = 38;
constexpr int RD = 48;
constexpr int XF = 54, STD = 56, STAT = 58, FOLD = 59, CSJ = 61, HALO = 62;
constexpr int NB_BOTH = 1, NB_HELP = 2, NB_INIT = 3, NB_LEAD = 4;

__device__ __forceinline__ uint32_t slot1(int p) { return p * 40960; }
__device__ __forceinline__ uint32_t slot2(int p) { return p * 32768; }
__device__ __forceinline__ uint32_t slot3(int p) { return ((p + 2) & 3) * 49152; }
__device__ __forceinline__ uint32_t slot4(int p) { return (p < 2 ? p + 4 : p - 2) * 32768; }

__device__ __align__(1024) uint8_t gXB[16 * 16 * 16384];
__device__ __align__(1024) uint8_t gOB[16 * 16 * 16384];
__device__ __align__(1024) uint8_t gHB[8 * 32 * 16384];
__device__ __align__(1024) uint8_t gUB[8 * 56 * 16384];
__device__ __align__(1024) uint2   gST[2][16][8][8][16];
__device__ __align__(1024) uint4   gHalo[2][16][8][12][32];
__device__ __align__(1024) uint32_t gAck[2][16][8][2][8];
__device__ __align__(1024) uint4   gCS[8][16][64];
__device__ __align__(1024) uint32_t gFlag[2][7][16][32];
__device__ uint32_t gEpoch;
#define TS(k)
#define TS2(k)

#define KB(k)
#define ST(k)
struct Params {
  CUtensorMap x0, wqkv, wo, w1, w1h, w2, out;
  const bf16 *wqkv_p, *b1, *b2;
  uint32_t zero;
};

template <int TA, int TB> __device__ __forceinline__ void wgmma_128(float (&d)[64], uint64_t da, uint64_t db) {
  asm volatile("wgmma.mma_async.sync.aligned.m64n128k16.f32.bf16.bf16 {"
  "%0, %1, %2, %3, %4, %5, %6, %7, %8, %9, %10, %11, %12, %13, %14, %15, "
  "%16, %17, %18, %19, %20, %21, %22, %23, %24, %25, %26, %27, %28, %29, %30, %31, "
  "%32, %33, %34, %35, %36, %37, %38, %39, %40, %41, %42, %43, %44, %45, %46, %47, "
  "%48, %49, %50, %51, %52, %53, %54, %55, %56, %57, %58, %59, %60, %61, %62, %63"
  "}, %64, %65, 1, 1, 1, %66, %67;\n"
  : "+f"(d[0]), "+f"(d[1]), "+f"(d[2]), "+f"(d[3]), "+f"(d[4]), "+f"(d[5]), "+f"(d[6]), "+f"(d[7]),
    "+f"(d[8]), "+f"(d[9]), "+f"(d[10]), "+f"(d[11]), "+f"(d[12]), "+f"(d[13]), "+f"(d[14]), "+f"(d[15]),
    "+f"(d[16]), "+f"(d[17]), "+f"(d[18]), "+f"(d[19]), "+f"(d[20]), "+f"(d[21]), "+f"(d[22]), "+f"(d[23]),
    "+f"(d[24]), "+f"(d[25]), "+f"(d[26]), "+f"(d[27]), "+f"(d[28]), "+f"(d[29]), "+f"(d[30]), "+f"(d[31]),
    "+f"(d[32]), "+f"(d[33]), "+f"(d[34]), "+f"(d[35]), "+f"(d[36]), "+f"(d[37]), "+f"(d[38]), "+f"(d[39]),
    "+f"(d[40]), "+f"(d[41]), "+f"(d[42]), "+f"(d[43]), "+f"(d[44]), "+f"(d[45]), "+f"(d[46]), "+f"(d[47]),
    "+f"(d[48]), "+f"(d[49]), "+f"(d[50]), "+f"(d[51]), "+f"(d[52]), "+f"(d[53]), "+f"(d[54]), "+f"(d[55]),
    "+f"(d[56]), "+f"(d[57]), "+f"(d[58]), "+f"(d[59]), "+f"(d[60]), "+f"(d[61]), "+f"(d[62]), "+f"(d[63])
  : "l"(da), "l"(db), "n"(TA), "n"(TB));
}
template <int TA, int TB> __device__ __forceinline__ void wgmma_192(float (&d)[96], uint64_t da, uint64_t db) {
  asm volatile("wgmma.mma_async.sync.aligned.m64n192k16.f32.bf16.bf16 {"
  "%0, %1, %2, %3, %4, %5, %6, %7, %8, %9, %10, %11, %12, %13, %14, %15, "
  "%16, %17, %18, %19, %20, %21, %22, %23, %24, %25, %26, %27, %28, %29, %30, %31, "
  "%32, %33, %34, %35, %36, %37, %38, %39, %40, %41, %42, %43, %44, %45, %46, %47, "
  "%48, %49, %50, %51, %52, %53, %54, %55, %56, %57, %58, %59, %60, %61, %62, %63, "
  "%64, %65, %66, %67, %68, %69, %70, %71, %72, %73, %74, %75, %76, %77, %78, %79, "
  "%80, %81, %82, %83, %84, %85, %86, %87, %88, %89, %90, %91, %92, %93, %94, %95"
  "}, %96, %97, 1, 1, 1, %98, %99;\n"
  : "+f"(d[0]), "+f"(d[1]), "+f"(d[2]), "+f"(d[3]), "+f"(d[4]), "+f"(d[5]), "+f"(d[6]), "+f"(d[7]),
    "+f"(d[8]), "+f"(d[9]), "+f"(d[10]), "+f"(d[11]), "+f"(d[12]), "+f"(d[13]), "+f"(d[14]), "+f"(d[15]),
    "+f"(d[16]), "+f"(d[17]), "+f"(d[18]), "+f"(d[19]), "+f"(d[20]), "+f"(d[21]), "+f"(d[22]), "+f"(d[23]),
    "+f"(d[24]), "+f"(d[25]), "+f"(d[26]), "+f"(d[27]), "+f"(d[28]), "+f"(d[29]), "+f"(d[30]), "+f"(d[31]),
    "+f"(d[32]), "+f"(d[33]), "+f"(d[34]), "+f"(d[35]), "+f"(d[36]), "+f"(d[37]), "+f"(d[38]), "+f"(d[39]),
    "+f"(d[40]), "+f"(d[41]), "+f"(d[42]), "+f"(d[43]), "+f"(d[44]), "+f"(d[45]), "+f"(d[46]), "+f"(d[47]),
    "+f"(d[48]), "+f"(d[49]), "+f"(d[50]), "+f"(d[51]), "+f"(d[52]), "+f"(d[53]), "+f"(d[54]), "+f"(d[55]),
    "+f"(d[56]), "+f"(d[57]), "+f"(d[58]), "+f"(d[59]), "+f"(d[60]), "+f"(d[61]), "+f"(d[62]), "+f"(d[63]),
    "+f"(d[64]), "+f"(d[65]), "+f"(d[66]), "+f"(d[67]), "+f"(d[68]), "+f"(d[69]), "+f"(d[70]), "+f"(d[71]),
    "+f"(d[72]), "+f"(d[73]), "+f"(d[74]), "+f"(d[75]), "+f"(d[76]), "+f"(d[77]), "+f"(d[78]), "+f"(d[79]),
    "+f"(d[80]), "+f"(d[81]), "+f"(d[82]), "+f"(d[83]), "+f"(d[84]), "+f"(d[85]), "+f"(d[86]), "+f"(d[87]),
    "+f"(d[88]), "+f"(d[89]), "+f"(d[90]), "+f"(d[91]), "+f"(d[92]), "+f"(d[93]), "+f"(d[94]), "+f"(d[95])
  : "l"(da), "l"(db), "n"(TA), "n"(TB));
}
template <int TA, int TB> __device__ __forceinline__ void wgmma_192z(float (&d)[96], uint64_t da, uint64_t db) {
  asm volatile("wgmma.mma_async.sync.aligned.m64n192k16.f32.bf16.bf16 {"
  "%0, %1, %2, %3, %4, %5, %6, %7, %8, %9, %10, %11, %12, %13, %14, %15, "
  "%16, %17, %18, %19, %20, %21, %22, %23, %24, %25, %26, %27, %28, %29, %30, %31, "
  "%32, %33, %34, %35, %36, %37, %38, %39, %40, %41, %42, %43, %44, %45, %46, %47, "
  "%48, %49, %50, %51, %52, %53, %54, %55, %56, %57, %58, %59, %60, %61, %62, %63, "
  "%64, %65, %66, %67, %68, %69, %70, %71, %72, %73, %74, %75, %76, %77, %78, %79, "
  "%80, %81, %82, %83, %84, %85, %86, %87, %88, %89, %90, %91, %92, %93, %94, %95"
  "}, %96, %97, 0, 1, 1, %98, %99;\n"
  : "=f"(d[0]), "=f"(d[1]), "=f"(d[2]), "=f"(d[3]), "=f"(d[4]), "=f"(d[5]), "=f"(d[6]), "=f"(d[7]),
    "=f"(d[8]), "=f"(d[9]), "=f"(d[10]), "=f"(d[11]), "=f"(d[12]), "=f"(d[13]), "=f"(d[14]), "=f"(d[15]),
    "=f"(d[16]), "=f"(d[17]), "=f"(d[18]), "=f"(d[19]), "=f"(d[20]), "=f"(d[21]), "=f"(d[22]), "=f"(d[23]),
    "=f"(d[24]), "=f"(d[25]), "=f"(d[26]), "=f"(d[27]), "=f"(d[28]), "=f"(d[29]), "=f"(d[30]), "=f"(d[31]),
    "=f"(d[32]), "=f"(d[33]), "=f"(d[34]), "=f"(d[35]), "=f"(d[36]), "=f"(d[37]), "=f"(d[38]), "=f"(d[39]),
    "=f"(d[40]), "=f"(d[41]), "=f"(d[42]), "=f"(d[43]), "=f"(d[44]), "=f"(d[45]), "=f"(d[46]), "=f"(d[47]),
    "=f"(d[48]), "=f"(d[49]), "=f"(d[50]), "=f"(d[51]), "=f"(d[52]), "=f"(d[53]), "=f"(d[54]), "=f"(d[55]),
    "=f"(d[56]), "=f"(d[57]), "=f"(d[58]), "=f"(d[59]), "=f"(d[60]), "=f"(d[61]), "=f"(d[62]), "=f"(d[63]),
    "=f"(d[64]), "=f"(d[65]), "=f"(d[66]), "=f"(d[67]), "=f"(d[68]), "=f"(d[69]), "=f"(d[70]), "=f"(d[71]),
    "=f"(d[72]), "=f"(d[73]), "=f"(d[74]), "=f"(d[75]), "=f"(d[76]), "=f"(d[77]), "=f"(d[78]), "=f"(d[79]),
    "=f"(d[80]), "=f"(d[81]), "=f"(d[82]), "=f"(d[83]), "=f"(d[84]), "=f"(d[85]), "=f"(d[86]), "=f"(d[87]),
    "=f"(d[88]), "=f"(d[89]), "=f"(d[90]), "=f"(d[91]), "=f"(d[92]), "=f"(d[93]), "=f"(d[94]), "=f"(d[95])
  : "l"(da), "l"(db), "n"(TA), "n"(TB));
}
template <int TA, int TB> __device__ __forceinline__ void wgmma_224(float (&d)[112], uint64_t da, uint64_t db) {
  asm volatile("wgmma.mma_async.sync.aligned.m64n224k16.f32.bf16.bf16 {"
  "%0, %1, %2, %3, %4, %5, %6, %7, %8, %9, %10, %11, %12, %13, %14, %15, "
  "%16, %17, %18, %19, %20, %21, %22, %23, %24, %25, %26, %27, %28, %29, %30, %31, "
  "%32, %33, %34, %35, %36, %37, %38, %39, %40, %41, %42, %43, %44, %45, %46, %47, "
  "%48, %49, %50, %51, %52, %53, %54, %55, %56, %57, %58, %59, %60, %61, %62, %63, "
  "%64, %65, %66, %67, %68, %69, %70, %71, %72, %73, %74, %75, %76, %77, %78, %79, "
  "%80, %81, %82, %83, %84, %85, %86, %87, %88, %89, %90, %91, %92, %93, %94, %95, "
  "%96, %97, %98, %99, %100, %101, %102, %103, %104, %105, %106, %107, %108, %109, %110, %111"
  "}, %112, %113, 1, 1, 1, %114, %115;\n"
  : "+f"(d[0]), "+f"(d[1]), "+f"(d[2]), "+f"(d[3]), "+f"(d[4]), "+f"(d[5]), "+f"(d[6]), "+f"(d[7]),
    "+f"(d[8]), "+f"(d[9]), "+f"(d[10]), "+f"(d[11]), "+f"(d[12]), "+f"(d[13]), "+f"(d[14]), "+f"(d[15]),
    "+f"(d[16]), "+f"(d[17]), "+f"(d[18]), "+f"(d[19]), "+f"(d[20]), "+f"(d[21]), "+f"(d[22]), "+f"(d[23]),
    "+f"(d[24]), "+f"(d[25]), "+f"(d[26]), "+f"(d[27]), "+f"(d[28]), "+f"(d[29]), "+f"(d[30]), "+f"(d[31]),
    "+f"(d[32]), "+f"(d[33]), "+f"(d[34]), "+f"(d[35]), "+f"(d[36]), "+f"(d[37]), "+f"(d[38]), "+f"(d[39]),
    "+f"(d[40]), "+f"(d[41]), "+f"(d[42]), "+f"(d[43]), "+f"(d[44]), "+f"(d[45]), "+f"(d[46]), "+f"(d[47]),
    "+f"(d[48]), "+f"(d[49]), "+f"(d[50]), "+f"(d[51]), "+f"(d[52]), "+f"(d[53]), "+f"(d[54]), "+f"(d[55]),
    "+f"(d[56]), "+f"(d[57]), "+f"(d[58]), "+f"(d[59]), "+f"(d[60]), "+f"(d[61]), "+f"(d[62]), "+f"(d[63]),
    "+f"(d[64]), "+f"(d[65]), "+f"(d[66]), "+f"(d[67]), "+f"(d[68]), "+f"(d[69]), "+f"(d[70]), "+f"(d[71]),
    "+f"(d[72]), "+f"(d[73]), "+f"(d[74]), "+f"(d[75]), "+f"(d[76]), "+f"(d[77]), "+f"(d[78]), "+f"(d[79]),
    "+f"(d[80]), "+f"(d[81]), "+f"(d[82]), "+f"(d[83]), "+f"(d[84]), "+f"(d[85]), "+f"(d[86]), "+f"(d[87]),
    "+f"(d[88]), "+f"(d[89]), "+f"(d[90]), "+f"(d[91]), "+f"(d[92]), "+f"(d[93]), "+f"(d[94]), "+f"(d[95]),
    "+f"(d[96]), "+f"(d[97]), "+f"(d[98]), "+f"(d[99]), "+f"(d[100]), "+f"(d[101]), "+f"(d[102]), "+f"(d[103]),
    "+f"(d[104]), "+f"(d[105]), "+f"(d[106]), "+f"(d[107]), "+f"(d[108]), "+f"(d[109]), "+f"(d[110]), "+f"(d[111])
  : "l"(da), "l"(db), "n"(TA), "n"(TB));
}
__device__ __forceinline__ void wgmma_rs_192(float (&d)[96], uint32_t a0, uint32_t a1, uint32_t a2, uint32_t a3, uint64_t db) {
  asm volatile("wgmma.mma_async.sync.aligned.m64n192k16.f32.bf16.bf16 {"
  "%0, %1, %2, %3, %4, %5, %6, %7, %8, %9, %10, %11, %12, %13, %14, %15, "
  "%16, %17, %18, %19, %20, %21, %22, %23, %24, %25, %26, %27, %28, %29, %30, %31, "
  "%32, %33, %34, %35, %36, %37, %38, %39, %40, %41, %42, %43, %44, %45, %46, %47, "
  "%48, %49, %50, %51, %52, %53, %54, %55, %56, %57, %58, %59, %60, %61, %62, %63, "
  "%64, %65, %66, %67, %68, %69, %70, %71, %72, %73, %74, %75, %76, %77, %78, %79, "
  "%80, %81, %82, %83, %84, %85, %86, %87, %88, %89, %90, %91, %92, %93, %94, %95"
  "}, {%96, %97, %98, %99}, %100, 1, 1, 1, 1;\n"
  : "+f"(d[0]), "+f"(d[1]), "+f"(d[2]), "+f"(d[3]), "+f"(d[4]), "+f"(d[5]), "+f"(d[6]), "+f"(d[7]),
    "+f"(d[8]), "+f"(d[9]), "+f"(d[10]), "+f"(d[11]), "+f"(d[12]), "+f"(d[13]), "+f"(d[14]), "+f"(d[15]),
    "+f"(d[16]), "+f"(d[17]), "+f"(d[18]), "+f"(d[19]), "+f"(d[20]), "+f"(d[21]), "+f"(d[22]), "+f"(d[23]),
    "+f"(d[24]), "+f"(d[25]), "+f"(d[26]), "+f"(d[27]), "+f"(d[28]), "+f"(d[29]), "+f"(d[30]), "+f"(d[31]),
    "+f"(d[32]), "+f"(d[33]), "+f"(d[34]), "+f"(d[35]), "+f"(d[36]), "+f"(d[37]), "+f"(d[38]), "+f"(d[39]),
    "+f"(d[40]), "+f"(d[41]), "+f"(d[42]), "+f"(d[43]), "+f"(d[44]), "+f"(d[45]), "+f"(d[46]), "+f"(d[47]),
    "+f"(d[48]), "+f"(d[49]), "+f"(d[50]), "+f"(d[51]), "+f"(d[52]), "+f"(d[53]), "+f"(d[54]), "+f"(d[55]),
    "+f"(d[56]), "+f"(d[57]), "+f"(d[58]), "+f"(d[59]), "+f"(d[60]), "+f"(d[61]), "+f"(d[62]), "+f"(d[63]),
    "+f"(d[64]), "+f"(d[65]), "+f"(d[66]), "+f"(d[67]), "+f"(d[68]), "+f"(d[69]), "+f"(d[70]), "+f"(d[71]),
    "+f"(d[72]), "+f"(d[73]), "+f"(d[74]), "+f"(d[75]), "+f"(d[76]), "+f"(d[77]), "+f"(d[78]), "+f"(d[79]),
    "+f"(d[80]), "+f"(d[81]), "+f"(d[82]), "+f"(d[83]), "+f"(d[84]), "+f"(d[85]), "+f"(d[86]), "+f"(d[87]),
    "+f"(d[88]), "+f"(d[89]), "+f"(d[90]), "+f"(d[91]), "+f"(d[92]), "+f"(d[93]), "+f"(d[94]), "+f"(d[95])
  : "r"(a0), "r"(a1), "r"(a2), "r"(a3), "l"(db));
}
__device__ __forceinline__ void wgmma_rs_224z(float (&d)[112], uint32_t a0, uint32_t a1, uint32_t a2, uint32_t a3, uint64_t db) {
  asm volatile("wgmma.mma_async.sync.aligned.m64n224k16.f32.bf16.bf16 {"
  "%0, %1, %2, %3, %4, %5, %6, %7, %8, %9, %10, %11, %12, %13, %14, %15, "
  "%16, %17, %18, %19, %20, %21, %22, %23, %24, %25, %26, %27, %28, %29, %30, %31, "
  "%32, %33, %34, %35, %36, %37, %38, %39, %40, %41, %42, %43, %44, %45, %46, %47, "
  "%48, %49, %50, %51, %52, %53, %54, %55, %56, %57, %58, %59, %60, %61, %62, %63, "
  "%64, %65, %66, %67, %68, %69, %70, %71, %72, %73, %74, %75, %76, %77, %78, %79, "
  "%80, %81, %82, %83, %84, %85, %86, %87, %88, %89, %90, %91, %92, %93, %94, %95, "
  "%96, %97, %98, %99, %100, %101, %102, %103, %104, %105, %106, %107, %108, %109, %110, %111"
  "}, {%112, %113, %114, %115}, %116, 0, 1, 1, 1;\n"
  : "=f"(d[0]), "=f"(d[1]), "=f"(d[2]), "=f"(d[3]), "=f"(d[4]), "=f"(d[5]), "=f"(d[6]), "=f"(d[7]),
    "=f"(d[8]), "=f"(d[9]), "=f"(d[10]), "=f"(d[11]), "=f"(d[12]), "=f"(d[13]), "=f"(d[14]), "=f"(d[15]),
    "=f"(d[16]), "=f"(d[17]), "=f"(d[18]), "=f"(d[19]), "=f"(d[20]), "=f"(d[21]), "=f"(d[22]), "=f"(d[23]),
    "=f"(d[24]), "=f"(d[25]), "=f"(d[26]), "=f"(d[27]), "=f"(d[28]), "=f"(d[29]), "=f"(d[30]), "=f"(d[31]),
    "=f"(d[32]), "=f"(d[33]), "=f"(d[34]), "=f"(d[35]), "=f"(d[36]), "=f"(d[37]), "=f"(d[38]), "=f"(d[39]),
    "=f"(d[40]), "=f"(d[41]), "=f"(d[42]), "=f"(d[43]), "=f"(d[44]), "=f"(d[45]), "=f"(d[46]), "=f"(d[47]),
    "=f"(d[48]), "=f"(d[49]), "=f"(d[50]), "=f"(d[51]), "=f"(d[52]), "=f"(d[53]), "=f"(d[54]), "=f"(d[55]),
    "=f"(d[56]), "=f"(d[57]), "=f"(d[58]), "=f"(d[59]), "=f"(d[60]), "=f"(d[61]), "=f"(d[62]), "=f"(d[63]),
    "=f"(d[64]), "=f"(d[65]), "=f"(d[66]), "=f"(d[67]), "=f"(d[68]), "=f"(d[69]), "=f"(d[70]), "=f"(d[71]),
    "=f"(d[72]), "=f"(d[73]), "=f"(d[74]), "=f"(d[75]), "=f"(d[76]), "=f"(d[77]), "=f"(d[78]), "=f"(d[79]),
    "=f"(d[80]), "=f"(d[81]), "=f"(d[82]), "=f"(d[83]), "=f"(d[84]), "=f"(d[85]), "=f"(d[86]), "=f"(d[87]),
    "=f"(d[88]), "=f"(d[89]), "=f"(d[90]), "=f"(d[91]), "=f"(d[92]), "=f"(d[93]), "=f"(d[94]), "=f"(d[95]),
    "=f"(d[96]), "=f"(d[97]), "=f"(d[98]), "=f"(d[99]), "=f"(d[100]), "=f"(d[101]), "=f"(d[102]), "=f"(d[103]),
    "=f"(d[104]), "=f"(d[105]), "=f"(d[106]), "=f"(d[107]), "=f"(d[108]), "=f"(d[109]), "=f"(d[110]), "=f"(d[111])
  : "r"(a0), "r"(a1), "r"(a2), "r"(a3), "l"(db));
}

__device__ __forceinline__ uint32_t smem_u32(const void* p) { return (uint32_t)__cvta_generic_to_shared(p); }
__device__ __forceinline__ void mbar_init(uint32_t bar, uint32_t cnt) { asm volatile("mbarrier.init.shared::cta.b64 [%0], %1;" ::"r"(bar), "r"(cnt) : "memory"); }
__device__ __forceinline__ void mbar_expect(uint32_t bar, uint32_t bytes) { asm volatile("mbarrier.arrive.expect_tx.shared::cta.b64 _, [%0], %1;" ::"r"(bar), "r"(bytes) : "memory"); }
__device__ __forceinline__ void mbar_arrive(uint32_t bar) { asm volatile("mbarrier.arrive.shared::cta.b64 _, [%0];" ::"r"(bar) : "memory"); }
__device__ __forceinline__ void mbar_arrive_cl(uint32_t cbar) { asm volatile("mbarrier.arrive.shared::cluster.b64 _, [%0];" ::"r"(cbar) : "memory"); }
__device__ __forceinline__ uint32_t mapa(uint32_t a, uint32_t cta) { uint32_t r; asm("mapa.shared::cluster.u32 %0, %1, %2;" : "=r"(r) : "r"(a), "r"(cta)); return r; }
__device__ __forceinline__ void mbar_wait(uint32_t bar, uint32_t parity) {
  asm volatile("{\n.reg .pred p;\n.reg .u32 n;\nmov.u32 n, 0;\n"
    "LAB_WAIT:\n"
    "mbarrier.try_wait.parity.shared::cta.b64 p, [%0], %1;\n"
    "@p bra LAB_DONE;\n"
    "add.u32 n, n, 1;\n"
    "setp.lt.u32 p, n, 2000000;\n"
    "@p bra LAB_WAIT;\n"
    "trap;\n"
    "LAB_DONE:\n}\n" ::"r"(bar), "r"(parity) : "memory");
}
constexpr uint32_t SPIN_MAX = 2000000;
__device__ __forceinline__ void tma2d(uint32_t dst, const CUtensorMap* m, uint32_t bar, int c0, int c1) {
  asm volatile("cp.async.bulk.tensor.2d.shared::cluster.global.mbarrier::complete_tx::bytes [%0], [%1, {%3, %4}], [%2];"
    ::"r"(dst), "l"(m), "r"(bar), "r"(c0), "r"(c1) : "memory");
}
__device__ __forceinline__ void tma2d_mc(uint32_t dst, const CUtensorMap* m, uint32_t bar, int c0, int c1) {
  asm volatile("cp.async.bulk.tensor.2d.shared::cluster.global.mbarrier::complete_tx::bytes.multicast::cluster [%0], [%1, {%3, %4}], [%2], %5;"
    ::"r"(dst), "l"(m), "r"(bar), "r"(c0), "r"(c1), "h"((uint16_t)3) : "memory");
}
__device__ __forceinline__ void tma3d(uint32_t dst, const CUtensorMap* m, uint32_t bar, int c0, int c1, int c2) {
  asm volatile("cp.async.bulk.tensor.3d.shared::cluster.global.mbarrier::complete_tx::bytes [%0], [%1, {%3, %4, %5}], [%2];"
    ::"r"(dst), "l"(m), "r"(bar), "r"(c0), "r"(c1), "r"(c2) : "memory");
}
__device__ __forceinline__ void tma3d_mc(uint32_t dst, const CUtensorMap* m, uint32_t bar, int c0, int c1, int c2) {
  asm volatile("cp.async.bulk.tensor.3d.shared::cluster.global.mbarrier::complete_tx::bytes.multicast::cluster [%0], [%1, {%3, %4, %5}], [%2], %6;"
    ::"r"(dst), "l"(m), "r"(bar), "r"(c0), "r"(c1), "r"(c2), "h"((uint16_t)3) : "memory");
}
__device__ __forceinline__ void tma2d_store(const CUtensorMap* m, uint32_t src, int c0, int c1) {
  asm volatile("cp.async.bulk.tensor.2d.global.shared::cta.bulk_group [%0, {%2, %3}], [%1];" ::"l"(m), "r"(src), "r"(c0), "r"(c1) : "memory");
}
__device__ __forceinline__ void bulk_ld(uint32_t dst, const void* src, uint32_t bytes, uint32_t bar) {
  asm volatile("cp.async.bulk.shared::cluster.global.mbarrier::complete_tx::bytes [%0], [%1], %2, [%3];" ::"r"(dst), "l"(src), "r"(bytes), "r"(bar) : "memory");
}
__device__ __forceinline__ void bulk_ld_mc(uint32_t dst, const void* src, uint32_t bytes, uint32_t bar) {
  asm volatile("cp.async.bulk.shared::cluster.global.mbarrier::complete_tx::bytes.multicast::cluster [%0], [%1], %2, [%3], %4;"
    ::"r"(dst), "l"(src), "r"(bytes), "r"(bar), "h"((uint16_t)3) : "memory");
}
__device__ __forceinline__ void bulk_st(void* dst, uint32_t src, uint32_t bytes) {
  asm volatile("cp.async.bulk.global.shared::cta.bulk_group [%0], [%1], %2;" ::"l"(dst), "r"(src), "r"(bytes) : "memory");
}
__device__ __forceinline__ void bulk_s2s(uint32_t cdst, uint32_t src, uint32_t bytes, uint32_t cbar) {
  asm volatile("cp.async.bulk.shared::cluster.shared::cta.mbarrier::complete_tx::bytes [%0], [%1], %2, [%3];" ::"r"(cdst), "r"(src), "r"(bytes), "r"(cbar) : "memory");
}
__device__ __forceinline__ void bulk_commit() { asm volatile("cp.async.bulk.commit_group;" ::: "memory"); }
__device__ __forceinline__ void bulk_wait0() { asm volatile("cp.async.bulk.wait_group 0;" ::: "memory"); }
__device__ __forceinline__ void fence_async_smem() { asm volatile("fence.proxy.async.shared::cta;" ::: "memory"); }
__device__ __forceinline__ void wg_fence() { asm volatile("wgmma.fence.sync.aligned;" ::: "memory"); }
__device__ __forceinline__ void wg_commit() { asm volatile("wgmma.commit_group.sync.aligned;" ::: "memory"); }
template <int N> __device__ __forceinline__ void wg_wait() { asm volatile("wgmma.wait_group.sync.aligned %0;" ::"n"(N) : "memory"); }
template <int R> __device__ __forceinline__ void reg_alloc() { asm volatile("setmaxnreg.inc.sync.aligned.u32 %0;" ::"n"(R)); }
template <int R> __device__ __forceinline__ void reg_dealloc() { asm volatile("setmaxnreg.dec.sync.aligned.u32 %0;" ::"n"(R)); }
__device__ __forceinline__ void cluster_bar() { asm volatile("barrier.cluster.arrive.relaxed;\nbarrier.cluster.wait;" ::: "memory"); }
template <int ID> __device__ __forceinline__ void nb_sync(int n) { asm volatile("barrier.sync %0, %1;" ::"n"(ID), "r"(n) : "memory"); }
template <int ID> __device__ __forceinline__ void nb_arrive(int n) { asm volatile("barrier.arrive %0, %1;" ::"n"(ID), "r"(n) : "memory"); }
__device__ __forceinline__ int fresh_tid() { int t; asm volatile("mov.u32 %0, %%tid.x;" : "=r"(t)); return t; }
__device__ __forceinline__ void sched_fence(uint32_t z) { asm volatile("{\n.reg .pred p;\nsetp.ne.u32 p, %0, 0;\nLAB_S:\n@p nanosleep.u32 0;\n@p bra LAB_S;\n}\n" ::"r"(z) : "memory"); }
__device__ __forceinline__ float rsq(float x) { float y; asm("rsqrt.approx.ftz.f32 %0, %1;" : "=f"(y) : "f"(x)); return y; }
struct True { static constexpr bool value = true; };
struct False { static constexpr bool value = false; };
template <int N> __device__ __forceinline__ void fence_regs(float (&d)[N]) {
#pragma unroll
  for (int i = 0; i < N; i++) asm volatile("" : "+f"(d[i])::"memory");
}
__device__ __forceinline__ uint64_t mkdesc(uint32_t addr, uint32_t lbo, uint32_t sbo) {
  return (uint64_t)((addr & 0x3FFFF) >> 4) | ((uint64_t)(lbo >> 4) << 16) | ((uint64_t)(sbo >> 4) << 32) | (1ull << 62);
}
__device__ __forceinline__ uint64_t mkdesc_vec(uint32_t addr, uint32_t sbo) { return (uint64_t)((addr & 0x3FFFF) >> 4) | ((uint64_t)(sbo >> 4) << 32); }
__device__ __forceinline__ void sts16(uint32_t a, uint32_t v) { asm volatile("st.shared.u16 [%0], %1;" ::"r"(a), "h"((uint16_t)v) : "memory"); }
__device__ __forceinline__ uint32_t pack2(float lo, float hi) { uint32_t r; asm("cvt.rn.bf16x2.f32 %0, %1, %2;" : "=r"(r) : "f"(hi), "f"(lo)); return r; }
__device__ __forceinline__ float bf_lo(uint32_t v) { return __uint_as_float(v << 16); }
__device__ __forceinline__ float bf_hi(uint32_t v) { return __uint_as_float(v & 0xffff0000u); }
__device__ __forceinline__ void stsm4(uint32_t a, uint32_t r0, uint32_t r1, uint32_t r2, uint32_t r3) {
  asm volatile("stmatrix.sync.aligned.m8n8.x4.shared.b16 [%0], {%1, %2, %3, %4};" ::"r"(a), "r"(r0), "r"(r1), "r"(r2), "r"(r3) : "memory");
}
__device__ __forceinline__ void stsm4t(uint32_t a, uint32_t r0, uint32_t r1, uint32_t r2, uint32_t r3) {
  asm volatile("stmatrix.sync.aligned.m8n8.x4.trans.shared.b16 [%0], {%1, %2, %3, %4};" ::"r"(a), "r"(r0), "r"(r1), "r"(r2), "r"(r3) : "memory");
}
__device__ __forceinline__ void ldsm4(uint32_t a, uint32_t& r0, uint32_t& r1, uint32_t& r2, uint32_t& r3) {
  asm volatile("ldmatrix.sync.aligned.m8n8.x4.shared.b16 {%0, %1, %2, %3}, [%4];" : "=r"(r0), "=r"(r1), "=r"(r2), "=r"(r3) : "r"(a) : "memory");
}
__device__ __forceinline__ void ldsm4t(uint32_t a, uint32_t& r0, uint32_t& r1, uint32_t& r2, uint32_t& r3) {
  asm volatile("ldmatrix.sync.aligned.m8n8.x4.trans.shared.b16 {%0, %1, %2, %3}, [%4];" : "=r"(r0), "=r"(r1), "=r"(r2), "=r"(r3) : "r"(a) : "memory");
}
__device__ __forceinline__ void mma16816(float (&c)[4], uint32_t a0, uint32_t a1, uint32_t a2, uint32_t a3, uint32_t b0, uint32_t b1) {
  asm volatile("mma.sync.aligned.m16n8k16.row.col.f32.bf16.bf16.f32 {%0, %1, %2, %3}, {%4, %5, %6, %7}, {%8, %9}, {%0, %1, %2, %3};"
    : "+f"(c[0]), "+f"(c[1]), "+f"(c[2]), "+f"(c[3]) : "r"(a0), "r"(a1), "r"(a2), "r"(a3), "r"(b0), "r"(b1));
}
__device__ __forceinline__ void sts128(uint32_t a, uint32_t r0, uint32_t r1, uint32_t r2, uint32_t r3) {
  asm volatile("st.shared.v4.b32 [%0], {%1, %2, %3, %4};" ::"r"(a), "r"(r0), "r"(r1), "r"(r2), "r"(r3) : "memory");
}
__device__ __forceinline__ void lds128(uint32_t a, uint32_t& r0, uint32_t& r1, uint32_t& r2, uint32_t& r3) {
  asm volatile("ld.shared.v4.b32 {%0, %1, %2, %3}, [%4];" : "=r"(r0), "=r"(r1), "=r"(r2), "=r"(r3) : "r"(a) : "memory");
}
__device__ __forceinline__ float2 lds64f(uint32_t a) { float2 v; asm volatile("ld.shared.v2.f32 {%0, %1}, [%2];" : "=f"(v.x), "=f"(v.y) : "r"(a) : "memory"); return v; }
__device__ __forceinline__ float4 lds128f(uint32_t a) { float4 v; asm volatile("ld.shared.v4.f32 {%0, %1, %2, %3}, [%4];" : "=f"(v.x), "=f"(v.y), "=f"(v.z), "=f"(v.w) : "r"(a) : "memory"); return v; }
__device__ __forceinline__ void sts64f(uint32_t a, float x, float y) { asm volatile("st.shared.v2.f32 [%0], {%1, %2};" ::"r"(a), "f"(x), "f"(y) : "memory"); }
__device__ __forceinline__ float lds32f(uint32_t a) { float v; asm volatile("ld.shared.f32 %0, [%1];" : "=f"(v) : "r"(a) : "memory"); return v; }
__device__ __forceinline__ void sts32f(uint32_t a, float x) { asm volatile("st.shared.f32 [%0], %1;" ::"r"(a), "f"(x) : "memory"); }
__device__ __forceinline__ void stat_st(uint2* p, float sum, float sq, uint32_t tag) {
  const float mean = sum * (1.f / 128), m2 = fmaxf(fmaf(-mean, sum, sq), 0.f);
  const uint32_t a = ((__float_as_uint(mean) + 8u) & ~15u) | (tag & 15u), b = ((__float_as_uint(m2) + 8u) & ~15u) | (tag & 15u);
  asm volatile("{\n.reg .b64 x;\nmov.b64 x, {%1, %2};\nst.relaxed.gpu.global.b64 [%0], x;\n}\n" ::"l"(p), "r"(a), "r"(b) : "memory");
}
__device__ __forceinline__ void stat_ld2(const uint2* p, uint32_t (&v)[4]) {
  asm volatile("{\n.reg .b64 x, y;\nld.relaxed.gpu.global.v2.b64 {x, y}, [%4];\nmov.b64 {%0, %1}, x;\nmov.b64 {%2, %3}, y;\n}\n"
    : "=r"(v[0]), "=r"(v[1]), "=r"(v[2]), "=r"(v[3]) : "l"(p) : "memory");
}
__device__ __forceinline__ float untag(uint32_t v) { return __uint_as_float(v & ~15u); }
__device__ __forceinline__ void ll_st3(uint4* p, uint32_t a, uint32_t b, uint32_t c, uint32_t tag) {
  asm volatile("{\n.reg .b64 x, y;\n.reg .b128 z;\nmov.b64 x, {%1, %2};\nmov.b64 y, {%3, %4};\nmov.b128 z, {x, y};\nst.relaxed.gpu.global.b128 [%0], z;\n}\n"
    ::"l"(p), "r"(a), "r"(b), "r"(c), "r"(tag) : "memory");
}
__device__ __forceinline__ uint32_t ll_ld3(const uint4* p, uint32_t& a, uint32_t& b, uint32_t& c, uint32_t tag) {
  uint32_t t;
  asm volatile("{\n.reg .b64 x, y;\n.reg .b128 z;\nld.relaxed.gpu.global.b128 z, [%4];\nmov.b128 {x, y}, z;\nmov.b64 {%0, %1}, x;\nmov.b64 {%2, %3}, y;\n}\n"
    : "=r"(a), "=r"(b), "=r"(c), "=r"(t) : "l"(p) : "memory");
  return t ^ tag;
}
__device__ __forceinline__ void halo_send(uint4* p, uint32_t a, const uint32_t (&tg)[6]) {
  asm volatile("{\n.reg .b64 x<6>, y<6>, w<2>;\n.reg .b32 c<4>;\n.reg .b128 z<6>;\n"
    "ld.shared.b64 w0, [%1+1536];\nld.shared.b64 w1, [%1+1792];\n"
    "ld.shared.b64 x0, [%1];\nld.shared.b64 x1, [%1+256];\nld.shared.b64 x2, [%1+512];\n"
    "ld.shared.b64 x3, [%1+768];\nld.shared.b64 x4, [%1+1024];\nld.shared.b64 x5, [%1+1280];\n"
    "mov.b64 {c0, c1}, w0;\nmov.b64 {c2, c3}, w1;\n"
    "mov.b64 y0, {c0, %2};\nmov.b64 y1, {c1, %3};\nmov.b64 y2, {c2, %4};\nmov.b64 y3, {c3, %5};\nmov.b64 y4, {%6, %6};\nmov.b64 y5, {%7, %7};\n"
    "mov.b128 z0, {x0, y0};\nmov.b128 z1, {x1, y1};\nmov.b128 z2, {x2, y2};\nmov.b128 z3, {x3, y3};\nmov.b128 z4, {x4, y4};\nmov.b128 z5, {x5, y5};\n"
    "st.relaxed.gpu.global.b128 [%0], z0;\nst.relaxed.gpu.global.b128 [%0+512], z1;\nst.relaxed.gpu.global.b128 [%0+1024], z2;\n"
    "st.relaxed.gpu.global.b128 [%0+1536], z3;\nst.relaxed.gpu.global.b128 [%0+2048], z4;\nst.relaxed.gpu.global.b128 [%0+2560], z5;\n}\n"
    ::"l"(p), "r"(a), "r"(tg[0]), "r"(tg[1]), "r"(tg[2]), "r"(tg[3]), "r"(tg[4]), "r"(tg[5]) : "memory");
}
__device__ __forceinline__ void warp_store(uint8_t* dst, uint32_t src, int bytes, uint32_t delay, uint32_t pace) {
  __nanosleep(delay);
#pragma unroll 1
  for (int o = 0; o < bytes; o += 2048) {
    if (pace) __nanosleep(pace);
    uint4 v[4];
#pragma unroll
    for (int k = 0; k < 4; k++) lds128(src + o + k * 512, v[k].x, v[k].y, v[k].z, v[k].w);
#pragma unroll
    for (int k = 0; k < 4; k++) asm volatile("st.global.v4.b32 [%0], {%1, %2, %3, %4};" ::"l"(dst + o + k * 512), "r"(v[k].x), "r"(v[k].y), "r"(v[k].z), "r"(v[k].w) : "memory");
  }
  __syncwarp();
}
__device__ __forceinline__ uint32_t clock32() { uint32_t t; asm volatile("mov.u32 %0, %%clock;" : "=r"(t)); return t; }
__device__ __forceinline__ void flag_set(uint32_t* p, uint32_t bit) { asm volatile("red.release.gpu.global.xor.b32 [%0], %1;" ::"l"(p), "r"(bit) : "memory"); }
__device__ __forceinline__ void flag_wait(const uint32_t* p, uint32_t inv, uint32_t need, uint32_t& ready) {
  if ((ready & need) == need) return;
  uint32_t n = 0;
  do {
    asm volatile("ld.relaxed.gpu.global.b32 %0, [%1];" : "=r"(ready) : "l"(p) : "memory");
    ready = __shfl_sync(0xffffffffu, ready, 0) ^ inv;
  } while ((ready & need) != need && ++n < SPIN_MAX);
  asm volatile("fence.acquire.gpu;\nfence.proxy.async.global;" ::: "memory");
}
__device__ __forceinline__ bool elect_one() {
  uint32_t p;
  asm volatile("{\n.reg .pred P;\nelect.sync _|P, 0xffffffff;\nselp.u32 %0, 1, 0, P;\n}\n" : "=r"(p));
  return p;
}
__device__ __forceinline__ float gelu_half(float hx) {
  const float y = hx * fmaf(hx * hx, 8.f * 0.0356774081f, 2.f * 0.7978845608f);
  float th;
  asm("tanh.approx.f32 %0, %1;" : "=f"(th) : "f"(y));
  return fmaf(hx, th, hx);
}
__device__ __forceinline__ float ex2(float x) { float y; asm("ex2.approx.ftz.f32 %0, %1;" : "=f"(y) : "f"(x)); return y; }

__device__ __forceinline__ void stat_combine(uint32_t am, uint32_t aq, uint32_t bm, uint32_t bq, float pv, float& mean, float& var) {
  const float d0 = untag(am) - pv, d1 = untag(bm) - pv;
  float s = d0 + d1, q = fmaf(fmaf(d0, d0, d1 * d1), 128.f, untag(aq) + untag(bq));
  s += __shfl_xor_sync(0xffffffffu, s, 8); q += __shfl_xor_sync(0xffffffffu, q, 8);
  s += __shfl_xor_sync(0xffffffffu, s, 16); q += __shfl_xor_sync(0xffffffffu, q, 16);
  s *= 0.125f;
  mean = pv + s;
  var = fmaxf(fmaf(-s, s, q * (1.f / D_)), 0.f);
}

__device__ __forceinline__ void attn_probs(const uint32_t* q0, const uint32_t* q1,
                                           const uint32_t* k0, const uint32_t* k1, const uint32_t* k2, const uint32_t* k3,
                                           float sc0, float sc1, bool first, bool e, bool zneg, uint32_t (&pr)[6]) {
  float s[4][4];
#pragma unroll
  for (int n = 0; n < 4; n++) {
    const uint32_t* k = n == 0 ? k0 : n == 1 ? k1 : n == 2 ? k2 : k3;
    s[n][0] = s[n][1] = s[n][2] = s[n][3] = 0.f;
    mma16816(s[n], q0[0], q1[0], q0[1], q1[1], k[0], k[1]);
    mma16816(s[n], q0[2], q1[2], q0[3], q1[3], k[2], k[3]);
  }
  const float MASKED = -1.0e9f * 1.4426950409f;
  float a0 = (e ? s[1][1] : s[1][0]) * sc0;
  float b0 = (zneg ? (e ? s[0][1] : s[0][0]) : (e ? s[2][1] : s[2][0])) * sc0;
  float a1 = (e ? s[2][3] : s[2][2]) * sc1;
  float b1 = (zneg ? (e ? s[1][3] : s[1][2]) : (e ? s[3][3] : s[3][2])) * sc1;
  if (first) { a0 = MASKED; if (zneg) { b0 = MASKED; b1 = MASKED; } }
  float m0 = fmaxf(a0, b0), m1 = fmaxf(a1, b1);
  m0 = fmaxf(m0, __shfl_xor_sync(0xffffffffu, m0, 1)); m1 = fmaxf(m1, __shfl_xor_sync(0xffffffffu, m1, 1));
  m0 = fmaxf(m0, __shfl_xor_sync(0xffffffffu, m0, 2)); m1 = fmaxf(m1, __shfl_xor_sync(0xffffffffu, m1, 2));
  a0 = ex2(a0 - m0); b0 = ex2(b0 - m0); a1 = ex2(a1 - m1); b1 = ex2(b1 - m1);
  float l0 = a0 + b0, l1 = a1 + b1;
  l0 += __shfl_xor_sync(0xffffffffu, l0, 1); l1 += __shfl_xor_sync(0xffffffffu, l1, 1);
  l0 += __shfl_xor_sync(0xffffffffu, l0, 2); l1 += __shfl_xor_sync(0xffffffffu, l1, 2);
  asm("rcp.approx.ftz.f32 %0, %0;" : "+f"(l0)); asm("rcp.approx.ftz.f32 %0, %0;" : "+f"(l1));
  const int sh = e ? 16 : 0;
  uint32_t pa0 = pack2(a0 * l0, 0.f) << sh, pb0 = pack2(b0 * l0, 0.f) << sh;
  uint32_t pa1 = pack2(a1 * l1, 0.f) << sh, pb1 = pack2(b1 * l1, 0.f) << sh;
  pr[0] = zneg ? pb0 : 0u; pr[1] = pa0; pr[2] = zneg ? 0u : pb0;
  pr[3] = zneg ? pb1 : 0u; pr[4] = pa1; pr[5] = zneg ? 0u : pb1;
}
__device__ __forceinline__ void attn_pv(const uint32_t (&pr)[6], const uint32_t* vh, const uint32_t* v, float (&o)[4][4]) {
#pragma unroll
  for (int dt = 0; dt < 4; dt++) {
    o[dt][0] = o[dt][1] = o[dt][2] = o[dt][3] = 0.f;
    mma16816(o[dt], pr[0], 0u, pr[1], pr[3], vh[2 * dt], vh[2 * dt + 1]);
    mma16816(o[dt], pr[2], pr[4], 0u, pr[5], v[2 * dt], v[2 * dt + 1]);
  }
}

#define SF 12
#define SLICE 1
#define COVER 2
#define S2S 0
#define WGATE 1
#define HALO_A_NS 300
#define H1D 900
#define U0D 300
#define U2D 3000
#define X1D 1200
#define PACE 150
#define LEAD1 2
#define LEAD2 3
#define HALO_NS 0
#define STAT_CLK 150
__global__ void __cluster_dims__(2, 1, 1) __launch_bounds__(384, 1) fused_kernel(const __grid_constant__ Params P) {
  extern __shared__ __align__(1024) uint8_t smem_raw[];
  const uint32_t sb = smem_u32(smem_raw);
  const uint32_t bars = sb + OFF_BAR;
  const int tid = threadIdx.x;
  const int wu = __shfl_sync(0xffffffffu, tid >> 5, 0), wg = wu >> 2;
  const int r = blockIdx.x & 1, cl = blockIdx.x >> 1;
  int grp, slt;
  if (cl < 4) { grp = 0; slt = 4 + cl; }
  else if (cl < 36) { grp = (cl - 4) & 7; slt = (cl - 4) >> 3; }
  else { grp = 1 + (cl - 36) % 7; slt = 4 + (cl - 36) / 7; }
#define MAP 0
  const int m = grp, j = slt;
  const int i = 2 * m + r;
  auto BAR = [&](int k) { return bars + 8 * k; };

  auto kb1 = [&](int n) { const int h = n >= 9, t = n - 2 - 7 * h; return n < 2 ? 2 * j + n : 2 * (t + (t >= j)) + h; };
  if (wu == 8) {
    if (elect_one()) {
      asm volatile("prefetch.tensormap [%0];" ::"l"(&P.x0) : "memory");
      asm volatile("prefetch.tensormap [%0];" ::"l"(&P.wqkv) : "memory");
#pragma unroll
      for (int k = 0; k < 6; k++) mbar_init(BAR(k < 4 ? F1 + k : XF + k - 4), 1);
      asm volatile("fence.mbarrier_init.release.cluster;" ::: "memory");
      fence_async_smem();
    }
    __syncwarp();
  } else if (wu == 0) {
    if (elect_one()) {
#pragma unroll
      for (int k = E1; k < 64; k++) {
        int cnt = 1;
        if (k < F2 || (k >= E2 && k < F3) || (k >= E3 && k < F4) || (k >= E4 && k < JOB) || k == JOB + 2 || k == JOB + 3) cnt = 4;
        else if ((k >= JOB && k < RD) || k == CSJ) cnt = 8;
        else if ((k >= RD && k < RD + 4) || k == STD || k == STAT || k >= HALO) cnt = 2;
        if (k != XF && k != XF + 1) mbar_init(BAR(k), cnt);
      }
      asm volatile("fence.mbarrier_init.release.cluster;" ::: "memory");
      fence_async_smem();
    }
    __syncwarp();
  }
  auto load_tag = [&]() { uint32_t t; asm volatile("ld.relaxed.gpu.global.u32 %0, [%1];" : "=r"(t) : "l"(&gEpoch) : "memory"); return t + 1; };
  TS(0);
  if (wu == 8) nb_arrive<NB_INIT>(384); else nb_sync<NB_INIT>(384);
  asm volatile("barrier.cluster.arrive.relaxed;" ::: "memory");

  if (wg == 2) {
    reg_dealloc<40>();
    if (wu == 8) {
    if (elect_one()) {
#pragma unroll 1
      for (int u = 0; u < 4; u++) {
        const int kb = kb1(u);
        if (u < 2) { mbar_expect(BAR(XF + u), 16384); tma2d(sb + OFF_X + u * 16384, &P.x0, BAR(XF + u), kb * 64, 128 * i); }
        mbar_expect(BAR(F1 + u), u < 2 ? 24576 : 40960);
        tma3d(sb + slot1(u) + 16384, &P.wqkv, BAR(F1 + u), 128 * j, kb * 64, 0);
        tma3d(sb + slot1(u) + 28672, &P.wqkv, BAR(F1 + u), 128 * j, kb * 64 + 32, 0);
        if (u >= 2) tma2d(sb + slot1(u), &P.x0, BAR(F1 + u), kb * 64, 128 * i);
      }
    }
    __syncwarp();
    }
    asm volatile("barrier.cluster.wait;" ::: "memory");
    auto kb3 = [&](int n) { const int h = n >= 17, t = S2S ? n - 3 - 14 * h : n - 2 - 15 * h; return n < 2 ? 2 * i + n : (n == (S2S ? 2 : 16) || n == 31) ? 2 * (i ^ 1) + h : 2 * ((2 * m + 2 + t) & 15) + h; };
    auto kb2 = [&](int n) { return n < 8 ? 2 * n : n == 8 ? 2 * j + 1 : 2 * (n - 9 + (n - 9 >= j)) + 1; };
    if (wu == 8) {
#pragma unroll 1
      for (int L = 0; L < 2; L++) {
#pragma unroll 1
        for (int u = L ? 0 : 4; u < 32; u++) {
          const int v = (L && u >= 2 && u < 18) ? (u < 4 ? u + 14 : u - 2) : u;
          const int p = u & 3, ab = v >> 4, nn = v & 15;
          if (u >= 4) mbar_wait(BAR(E1 + p), ((u >> 2) - 1) & 1);
          else mbar_wait(BAR(E4 + (u == 3 ? 0 : u + 3)), u == 3);
          if (elect_one()) {
            mbar_expect(BAR(F1 + p), nn < 2 ? 24576 : 40960);
            tma3d_mc(sb + slot1(p) + 16384 + r * 12288, &P.wqkv, BAR(F1 + p), 128 * j + 64 * ab, kb1(nn) * 64 + 32 * r, 0);
          }
        }
        int p = 0; uint32_t par = L ? 0x1e : 0;
#pragma unroll 1
        for (int n = 0; n < 16; n++) {
          if (n >= 5) { mbar_wait(BAR(E2 + p), (par >> p) & 1); par ^= 1u << p; }
          else if (n < 4) mbar_wait(BAR(E1 + n), 1);
          if (elect_one()) {
            mbar_expect(BAR(F2 + p), n == 8 ? 16384 : 32768);
            tma2d_mc(sb + slot2(p) + 16384 + r * 8192, &P.wo, BAR(F2 + p), 128 * j + 64 * r, kb2(n) * 64);
          }
          if (++p == 5) p = 0;
        }
#pragma unroll 1
        for (int u = 0; u < 32; u++) {
          const int n = u < 4 ? (0x2031 >> (4 * u)) & 3 : u, p = n & 3, kb = kb3(n);
          if (WGATE && n == 4) mbar_wait(BAR(RD + 4), L);
          if (n >= 4) mbar_wait(BAR(E3 + p), ((n >> 2) - 1) & 1);
          else if (n == 1) mbar_wait(BAR(STD + 1), L);
          else if (n == 3) mbar_wait(BAR(E2 + 2), L);
          else if (n == 0) mbar_wait(BAR(E2 + 4), L);
          else mbar_wait(BAR(E2 + 0), 1);
          if (elect_one()) {
            mbar_expect(BAR(F3 + p), n < 2 ? 32768 : 49152);
            tma3d(sb + slot3(p) + 16384, &P.w1, BAR(F3 + p), 0, kb * 64, 7 * m + 4 * r);
            tma3d(sb + slot3(p) + 40960, &P.w1h, BAR(F3 + p), 0, kb * 64, 14 * m + 6 + r);
          }
        }
#pragma unroll 1
        for (int n = 0; n < 6; n++) {
          if (n < 3) mbar_wait(BAR(E3 + n), 1);
          else if (n == 4) mbar_wait(BAR(E3 + 3), 1);
          if (elect_one()) {
            mbar_expect(BAR(F4 + n), n < 3 ? 16384 : 32768);
            tma3d(sb + slot4(n), &P.w2, BAR(F4 + n), 0, (n < 3 ? 7 * m + 4 * r + (n == 2 ? 0 : n + 1) : 7 * ((m + n - 2) & 7) + 3) * 64, 2 * i);
          }
        }
        p = 0; par = L ? 0x3c : 0;
        auto g4w = [&](int kb) {
          mbar_wait(BAR(E4 + p), (par >> p) & 1); par ^= 1u << p;
          if (elect_one()) {
            mbar_expect(BAR(F4 + p), 32768);
            tma3d(sb + slot4(p), &P.w2, BAR(F4 + p), 0, kb * 64, 2 * i);
          }
          if (++p == 6) p = 0;
        };
#pragma unroll 1
        for (int t = 4; t < 9; t++) g4w(7 * ((m + t) & 7) + 3);
#pragma unroll 1
        for (int c = 0; c < 3; c++)
#pragma unroll 1
          for (int t = 0; t < 15; t++) { const int ii = t < 14 ? (2 * m + 2 + t) & 15 : i ^ 1; g4w(((7 * ii + 1) >> 1) + c); }
      }
    } else if (wu == 9) {
      uint32_t inv = 0;
#pragma unroll 1
      for (int L = 0; L < 2; L++) {
        uint32_t ready = 0;
#pragma unroll 1
        for (int u = 4; u < 32; u++) {
          const int p = u & 3, nn = (L && u < 18 ? u - 2 : u) & 15, kb = kb1(nn);
          if (nn < 2) continue;
          if (L && u < 12) mbar_wait(BAR(F1 + p), u >> 3);
          if (u >= 4 + 4 * L) mbar_wait(BAR(E1 + p), ((u >> 2) - 1) & 1);
          if (L) {
            flag_wait(gFlag[0][0][i], inv, 1u << kb, ready);
            if (elect_one()) bulk_ld(sb + slot1(p), gXB + (i * 16 + kb) * 16384, 16384, BAR(F1 + p));
          } else if (elect_one()) tma2d(sb + slot1(p), &P.x0, BAR(F1 + p), kb * 64, 128 * i);
        }
        ready = 0;
        if (L == 0) inv = (__shfl_sync(0xffffffffu, load_tag(), 0) & 1) - 1;
        int p = 0; uint32_t par = L ? 0x1e : 0;
#pragma unroll 1
        for (int n = 0; n < 16; n++) {
          const int hp = kb2(n);
          if (n == 8) { par ^= 8; p = 4; continue; }
          if (n >= 5) { mbar_wait(BAR(E2 + p), (par >> p) & 1); par ^= 1u << p; }
          else if (n < 4) mbar_wait(BAR(E1 + n), 1);
          flag_wait(gFlag[L][1][i], inv, 1u << hp, ready);
          if (n == 9) ST(4);
          if (elect_one()) bulk_ld(sb + slot2(p), gOB + (i * 16 + hp) * 16384, 16384, BAR(F2 + p));
          if (++p == 5) p = 0;
        }
        ready = 0;
        mbar_wait(BAR(E2 + 0), 1);
#pragma unroll 1
        for (int n = 2 + S2S; n < 32; n++) {
          const int p = n & 3, kb = kb3(n);
          if (n > 3) mbar_wait(BAR(E3 + p), ((n >> 2) - 1) & 1);
          flag_wait(gFlag[L][2][j], inv, 1u << kb, ready);
          if (n == 2 + S2S) ST(12);
          if (elect_one()) {
            const uint8_t* src = gHB + (j * 32 + kb) * 16384;
            if (n < 31 && (S2S || n != 16)) bulk_ld_mc(sb + slot3(p) + r * 8192, src + r * 8192, 8192, BAR(F3 + p));
            else bulk_ld(sb + slot3(p), src, 16384, BAR(F3 + p));
          }
        }
        ready = 0; p = 3; par = L ? 0x3c : 0;
        mbar_wait(BAR(E3 + 3), 1);
#pragma unroll 1
        for (int t = 0; t < 8; t++) {
          const int mm = (m + t + 1) & 7;
          if (t >= 3) { if (t == 4 || t == 5) mbar_wait(BAR(RD + 7 - t), L); mbar_wait(BAR(E4 + p), (par >> p) & 1); par ^= 1u << p; }
          flag_wait(gFlag[L][6][j], inv, 3u << (2 * mm), ready);
          if (t == 0) ST(20);
          if (elect_one()) bulk_ld_mc(sb + slot4(p) + 16384 + r * 8192, gUB + (j * 56 + 48 + mm) * 16384 + r * 8192, 8192, BAR(F4 + p));
          if (++p == 6) p = 0;
        }
#pragma unroll 1
        for (int c = 0; c < 3; c++) {
          ready = 0;
#pragma unroll 1
          for (int t = 0; t < 15; t++) {
            const int ii = t < 14 ? (2 * m + 2 + t) & 15 : i ^ 1;
            mbar_wait(BAR(E4 + p), (par >> p) & 1); par ^= 1u << p;
            flag_wait(gFlag[L][3 + c][j], inv, 1u << ii, ready);
            if (elect_one()) {
              const uint8_t* src = gUB + (j * 56 + 16 * c + ii) * 16384;
              if (t < 14) bulk_ld_mc(sb + slot4(p) + 16384 + r * 8192, src + r * 8192, 8192, BAR(F4 + p));
              else bulk_ld(sb + slot4(p) + 16384, src, 16384, BAR(F4 + p));
            }
            if (++p == 6) p = 0;
          }
        }
      }
    } else {
      const int h = wu - 10;
      const uint32_t tag = load_tag();
      int lane = tid & 31, z = 0;
#define FRESH asm volatile("" : "+r"(lane), "+r"(z))
      const uint32_t rs = mapa(sb, r ^ 1), rb = rs + OFF_BAR;
      auto signal = [&](int k) { if (lane == 0) mbar_arrive(BAR(k)); };
      auto drained = [&](int k) { if (lane == 0) { mbar_arrive(BAR(RD + k)); mbar_arrive_cl(rb + 8 * (RD + k)); } };
      auto publish = [&](uint32_t* f, int bit) { if (lane == 0) flag_set(f + z, 1u << (bit + z)); __syncwarp(); };
      for (int c = 32 * h + lane; c < 288; c += 64)
        sts16(sb + OFF_B1 + 2 * c, c >= 224 ? 0u : pack2(0.5f * __bfloat162float(P.b1[c < 192 ? 64 * (7 * m + 4 * r) + c : 64 * (7 * m + 3) + 32 * r + c - 192]), 0.f));
      if (h == 0) sts32f(sb + OFF_CS + 768 + 4 * lane, 0.f);
#pragma unroll 1
      for (int L = 0; L < 2; L++) {
        FRESH;
        if (L == 0) {
          mbar_wait(BAR(CSJ), 0);
          float c0 = 0.f, c1 = 0.f, c2 = 0.f;
          const uint32_t a = sb + OFF_STG + (32 * h + lane) * 4;
#pragma unroll 8
          for (int k = 0; k < 32; k++) { c0 += lds32f(a + k * 784); c1 += lds32f(a + k * 784 + 256); c2 += lds32f(a + k * 784 + 512); }
          ll_st3(&gCS[j][i][32 * h + lane], __float_as_uint(c0), __float_as_uint(c1), __float_as_uint(c2), tag);
          __nanosleep(500);
        }
        FRESH;
        if (L == 0) {
#pragma unroll 1
          for (int ab = 0; ab < 2; ab++) {
            float c0 = 0.f, c1 = 0.f, c2 = 0.f;
#pragma unroll 1
            for (int b4 = 0; b4 < 8; b4 += 4) {
              uint32_t a[4], b[4], c[4], n = 0, bad;
              do {
                bad = 0;
#pragma unroll
                for (int e = 0; e < 4; e++) bad |= ll_ld3(&gCS[j][2 * (b4 + e) + ab][32 * h + lane], a[e], b[e], c[e], tag);
              } while (bad && ++n < SPIN_MAX);
#pragma unroll
              for (int e = 0; e < 4; e++) { c0 += __uint_as_float(a[e]); c1 += __uint_as_float(b[e]); c2 += __uint_as_float(c[e]); }
            }
            const uint32_t a = sb + OFF_CS + ab * 768 + (4 * h + (lane >> 3)) * 32 + (lane & 7) * 2;
            const uint32_t h0 = pack2(c0, 0.f), h1 = pack2(c1, 0.f), h2 = pack2(c2, 0.f);
            sts16(a, h0); sts16(a + 256, h1); sts16(a + 512, h2);
            sts16(a + 16, pack2(c0 - bf_lo(h0), 0.f)); sts16(a + 272, pack2(c1 - bf_lo(h1), 0.f)); sts16(a + 528, pack2(c2 - bf_lo(h2), 0.f));
            fence_async_smem();
            __syncwarp();
            if (ab == 0) signal(STAT);
          }
        }
#pragma unroll 1
        for (int ab = 0; ab < 2; ab++) {
          FRESH;
          uint32_t v[18], tg[6];
          const uint32_t xs = sb + OFF_STG + h * 16384 + lane * 8;
          uint4* hp = &gHalo[L][i][j][6 * h][lane];
#pragma unroll
          for (int c = 0; c < 6; c++) { tg[c] = (2 * tag + ab) * 8 + c; asm volatile("" : "+r"(tg[c])); }
          asm volatile("" : "+l"(hp));
          mbar_wait(BAR(FOLD + ab), L);
          if (ab && h == 0) ST(6);
          if (i < 15) {
            halo_send(hp, xs, tg);
          }
          if (ab && h == 0) ST(26);
          if (i > 0) {
            if (!ab) __nanosleep(HALO_A_NS);
            uint32_t n = 0, bad;
            do {
              bad = 0;
#pragma unroll
              for (int c = 0; c < 6; c++) bad |= ll_ld3(hp + c * 32 - 8 * 12 * 32, v[3 * c], v[3 * c + 1], v[3 * c + 2], (2 * tag + ab) * 8);
              if (ab && h == 0 && n == 0) ST(28);
            } while (bad > 7 && ++n < SPIN_MAX);
            if (ab && h == 0) ST(27);
          } else {
#pragma unroll
            for (int c = 0; c < 18; c++) v[c] = 0u;
          }
#pragma unroll
          for (int c = 0; c < 6; c++) sts64f(xs + c * 256, __uint_as_float(v[3 * c]), __uint_as_float(v[3 * c + 1]));
          sts64f(xs + 1536, __uint_as_float(v[2]), __uint_as_float(v[5]));
          sts64f(xs + 1792, __uint_as_float(v[8]), __uint_as_float(v[11]));
          __syncwarp();
          signal(HALO + ab);
          if (ab && h == 0) ST(7);
          FRESH;
          if (ab == 0 && lane == 0) asm volatile("st.relaxed.gpu.global.u32 [%0], %1;" ::"l"(&gAck[L][i][j][h][z]), "r"(tag) : "memory");
          mbar_wait(BAR(JOB + ab), L);
          if (h == 0) {
            if (ab) ST(1);
            if (lane == 0) { bulk_st(gOB + (i * 16 + 2 * j + ab + z) * 16384, sb + OFF_STG, 16384); bulk_commit(); bulk_wait0(); }
            signal(STD + ab);
            if (ab) ST(2);
            publish(gFlag[L][1][i], 2 * j + ab);
            if (ab) ST(3);
          } else if (ab == 0) {
            if (i < 15 && lane < 2) {
              uint32_t t, n = 0;
              do { asm volatile("ld.relaxed.gpu.global.u32 %0, [%1];" : "=r"(t) : "l"(&gAck[L][i + 1][j][lane][0]) : "memory"); } while (t != tag && ++n < SPIN_MAX);
            }
            __syncwarp();
            signal(STD);
          }
        }
        FRESH;
        if (h == 0) {
          mbar_wait(BAR(JOB + 2), L);
          ST(9);
          if (lane == 0) { bulk_st(gHB + (j * 32 + 2 * i + z) * 16384, sb + OFF_X, 16384); bulk_commit(); }
          if (S2S) mbar_wait(BAR(E2 + 0), 1);
          if (lane == 0) { if (S2S) bulk_s2s(rs + slot3(2), sb + OFF_X, 16384, rb + 8 * (F3 + 2)); bulk_wait0(); }
          signal(RD);
          ST(10);
          publish(gFlag[L][2][j], 2 * i);
          ST(11);
          signal(RD + 4);
          nb_arrive<NB_HELP>(64);
        } else {
          mbar_wait(BAR(JOB + 3), L);
          nb_sync<NB_HELP>(64);
          warp_store(gHB + (j * 32 + 2 * i + 1) * 16384 + lane * 16, sb + lane * 16 + OFF_X + 16384, 16384, H1D, PACE);
          signal(RD);
          ST(15);
          publish(gFlag[L][2][j], 2 * i + 1);
        }
        FRESH;
        if (h == 0) {
          mbar_wait(BAR(JOB + 7), L);
          ST(17);
          if (lane == 0) {
            for (int a = 0; a < 2; a++) bulk_st(gUB + (j * 56 + 48 + m + z) * 16384 + a * 8192 + r * 4096, sb + slot4(1) + 16384 + a * 8192, 4096);
            bulk_commit(); bulk_wait0();
          }
          drained(3);
          ST(18);
          publish(gFlag[L][6][j], i);
          ST(19);
        }
        mbar_wait(BAR(JOB + 6), L);
        if (h == 1) {
          warp_store(gUB + (j * 56 + i) * 16384 + lane * 16, sb + lane * 16 + slot4(2) + 16384, 16384, U0D, 0);
          drained(2); ST(25);
          publish(gFlag[L][3][j], i);
        }
        nb_sync<NB_HELP>(64);
        warp_store(gUB + (j * 56 + 16 + 16 * h + i) * 16384 + lane * 16, sb + lane * 16 + OFF_X + h * 16384, 16384, h ? U2D : 0, PACE);
        ST(23 + h);
        signal(RD + 1);
        publish(gFlag[L][4 + h][j], i);
        FRESH;
        mbar_wait(BAR(JOB + 8 + h), L);
        if (L == 0) {
          if (h == 0 && lane == 0) { bulk_st(gXB + (i * 16 + 2 * j + z) * 16384, sb + OFF_X, 16384); bulk_commit(); bulk_wait0(); }
          __syncwarp();
          nb_sync<NB_HELP>(64);
          if (h == 1) warp_store(gXB + (i * 16 + 2 * j + 1) * 16384 + lane * 16, sb + lane * 16 + OFF_X + 16384, 16384, X1D, 0);
          publish(gFlag[0][0][i], 2 * j + h);
        } else if (lane == 0) {
          tma2d_store(&P.out, sb + OFF_X + h * 16384, 128 * j + 64 * h, 128 * i);
          bulk_commit(); bulk_wait0();
        }
      }
      if (blockIdx.x == 0 && h == 0 && lane == 0) asm volatile("st.relaxed.gpu.global.u32 [%0], %1;" ::"l"(&gEpoch), "r"(tag) : "memory");
    }
    __syncwarp();
    cluster_bar();
  } else {
    reg_alloc<232>();
    asm volatile("barrier.cluster.wait;" ::: "memory");
    const uint32_t rbars = mapa(bars, tid & 1);
    const bool relp = (tid & 127) < 2;
    uint32_t tag;
    asm volatile("ld.relaxed.gpu.global.u32 %0, [%1];" : "=r"(tag) : "l"(&gEpoch + (fresh_tid() >> 10)) : "memory");
    auto release = [&](int k) { if (relp) mbar_arrive_cl(rbars + 8 * k); };
    auto signal = [&](int k) { __syncwarp(); if ((fresh_tid() & 31) == 0) mbar_arrive(BAR(k)); };
#define GEOM const int t7 = fresh_tid() & 127, lane = t7 & 31, w = t7 >> 5, g = lane >> 2, q = lane & 3, \
                       lr = lane & 15, lt = lane >> 4, l7 = lane & 7; (void)w; (void)g; (void)q; (void)lr; (void)lt; (void)l7

#pragma unroll 1
    for (int L = 0; L < 2; L++) {
      float acca[96], accb[96], xa[64], acc3[112];
      float nmean0, nmean1, rstd0, rstd1;
      uint16_t b2a, b2b;
      uint32_t Q[2][8], K[2][8], V[16];
      auto g1_issue = [&](float (&acc)[96], uint32_t a, uint32_t st, auto first) {
        const uint64_t da = mkdesc(a + wg * 8192, 16, 1024), db = mkdesc(st + 16384, 4096, 1024);
        wg_fence();
#pragma unroll
        for (int kk = 0; kk < 4; kk++) {
          const uint64_t b = db + (((kk >> 1) * 12288 + (kk & 1) * 2048) >> 4);
          if (first.value && kk == 0) wgmma_192z<0, 1>(acc, da, b); else wgmma_192<0, 1>(acc, da + kk * 2, b);
        }
        wg_commit();
      };
      auto g1_step = [&](float (&acc)[96], int u, bool rel) {
        const int p = u & 3;
        mbar_wait(BAR(F1 + p), (u >> 2) & 1);
        KB(u);
        g1_issue(acc, sb + slot1(p), sb + slot1(p), False{});
        if (LEAD1 && u == 31 && wg == 1) nb_arrive<NB_LEAD>(256);
        wg_wait<1>();
        if (rel) release(E1 + ((u - 1) & 3));
      };
      auto g1_loop = [&](float (&acc)[96], int u0, int u1, int urel) {
#pragma unroll 1
        for (int u = u0; u < u1; u++) g1_step(acc, u, u > urel);
      };
      auto load_x = [&]() {
        GEOM;
#pragma unroll
        for (int t = 0; t < 16; t += 2) {
          uint32_t v0, v1, v2, v3;
          ldsm4(sb + OFF_X + (t >> 3) * 16384 + (16 * wu + lr) * 128 + ((((t & 7) + lt) ^ l7) << 4), v0, v1, v2, v3);
          xa[4 * t + 0] = bf_lo(v0); xa[4 * t + 1] = bf_hi(v0); xa[4 * t + 2] = bf_lo(v1); xa[4 * t + 3] = bf_hi(v1);
          xa[4 * t + 4] = bf_lo(v2); xa[4 * t + 5] = bf_hi(v2); xa[4 * t + 6] = bf_lo(v3); xa[4 * t + 7] = bf_hi(v3);
        }
      };
      auto stat_publish = [&](float s0, float q0, float s2, float q2, uint32_t tg) {
        GEOM;
        const bool h1 = q & 1;
        float sm = (h1 ? s2 : s0) + __shfl_xor_sync(0xffffffffu, h1 ? s0 : s2, 1);
        float sq = (h1 ? q2 : q0) + __shfl_xor_sync(0xffffffffu, h1 ? q0 : q2, 1);
        sm += __shfl_xor_sync(0xffffffffu, sm, 2); sq += __shfl_xor_sync(0xffffffffu, sq, 2);
        if (q < 2) stat_st(&gST[L][i][wu][j][2 * g + q], sm, sq, tg);
        return sm;
      };
      auto g1_stats = [&](int u0) {
        GEOM;
        const uint32_t xr = sb + OFF_X + (16 * wu + lr) * 128;
        float s0 = 0.f, q0 = 0.f, s2 = 0.f, q2 = 0.f;
        uint32_t v[8] = {0u, 0u, 0u, 0u, 0u, 0u, 0u, 0u};
#pragma unroll 1
        for (int k = 0; k < 5; k++) {
#pragma unroll
          for (int e = 0; e < 8; e += 2) {
            const float a = bf_lo(v[e]), b = bf_hi(v[e]), c = bf_lo(v[e + 1]), d = bf_hi(v[e + 1]);
            s0 += a + b; q0 = fmaf(a, a, fmaf(b, b, q0)); s2 += c + d; q2 = fmaf(c, c, fmaf(d, d, q2));
          }
          if (k == 4) break;
          const uint32_t o = ((2 * k + lt) ^ l7) << 4;
          ldsm4(xr + o, v[0], v[1], v[2], v[3]);
          ldsm4(xr + o + 16384, v[4], v[5], v[6], v[7]);
          g1_step(acca, u0 + k, true);
        }
        stat_publish(s0, q0, s2, q2, 2 * (tag + 1));
      };
      uint32_t sv0[4], sv1[4];
      auto stat_fetch = [&]() {
        const uint2* sp = &gST[L][i][wu][0][0] + 2 * (fresh_tid() & 31);
        stat_ld2(sp, sv0); stat_ld2(sp + 64, sv1);
      };
      auto stat_await = [&](uint32_t tg) {
#pragma unroll 1
        for (uint32_t n = 0; (((sv0[0] ^ tg) | (sv0[2] ^ tg) | (sv1[0] ^ tg) | (sv1[2] ^ tg)) & 15u) && n < SPIN_MAX; n++) stat_fetch();
        __syncwarp();
      };
      auto ln_stats = [&]() {
        GEOM;
        stat_await(2 * (tag + 1));
        float mean0, var0, mean1, var1;
        stat_combine(sv0[0], sv0[1], sv1[0], sv1[1], untag(__shfl_sync(0xffffffffu, sv0[0], l7)), mean0, var0);
        stat_combine(sv0[2], sv0[3], sv1[2], sv1[3], untag(__shfl_sync(0xffffffffu, sv0[2], l7)), mean1, var1);
        nmean0 = -__shfl_sync(0xffffffffu, mean0, g); rstd0 = rsq(__shfl_sync(0xffffffffu, var0, g) + 1e-5f);
        nmean1 = -__shfl_sync(0xffffffffu, mean1, g); rstd1 = rsq(__shfl_sync(0xffffffffu, var1, g) + 1e-5f);
      };
      auto center = [&](float (&acc)[96], int ab) {
        const bool q0 = (fresh_tid() & 3) == 0;
        const uint32_t h0 = pack2(nmean0, nmean0), h1 = pack2(nmean1, nmean1);
        const float l0 = nmean0 - bf_lo(h0), l1 = nmean1 - bf_lo(h1);
        const uint32_t a0 = q0 ? h0 : 0u, a1 = q0 ? h1 : 0u, a2 = q0 ? pack2(l0, l0) : 0u, a3 = q0 ? pack2(l1, l1) : 0u;
        wg_fence();
        wgmma_rs_192(acc, a0, a1, a2, a3, mkdesc_vec(sb + OFF_CS + ab * 768, 32));
      };
      auto frag = [&](float (&acc)[96], int t, uint32_t& p0, uint32_t& p1) {
        if (t >= 8) { p0 = pack2(acc[4 * t] * rstd0, acc[4 * t + 1] * rstd0); p1 = pack2(acc[4 * t + 2] * rstd1, acc[4 * t + 3] * rstd1); }
        else { p0 = pack2(acc[4 * t], acc[4 * t + 1]); p1 = pack2(acc[4 * t + 2], acc[4 * t + 3]); }
      };
      auto fold_v = [&](float (&acc)[96]) {
        GEOM;
        const uint32_t a = sb + OFF_STG + 16384 + ((wu + 1) & 7) * 2048 + lr * 128;
#pragma unroll
        for (int t = 0; t < 8; t += 2) {
          uint32_t p0, p1, p2, p3;
          frag(acc, 16 + t, p0, p1); frag(acc, 17 + t, p2, p3);
          stsm4(a + (((t + lt) ^ l7) << 4), p0, p1, p2, p3);
        }
        __syncwarp();
#pragma unroll
        for (int t = 0; t < 8; t += 2) ldsm4t(a + (((t + lt) ^ l7) << 4), V[2 * t], V[2 * t + 1], V[2 * t + 2], V[2 * t + 3]);
      };
      auto fold_k = [&](float (&acc)[96], int ab) {
        GEOM;
#pragma unroll
        for (int t = 8; t < 16; t++) frag(acc, t, K[0][t - 8], K[1][t - 8]);
        const uint32_t a = sb + OFF_STG + ((wu + 1) & 7) * 2048 + lane * 16;
#pragma unroll
        for (int c = 0; c < 4; c++)
          sts128(a + c * 512, K[c >> 1][4 * (c & 1)], K[c >> 1][4 * (c & 1) + 1], K[c >> 1][4 * (c & 1) + 2], K[c >> 1][4 * (c & 1) + 3]);
        if (wu == 7) signal(FOLD + ab);
      };
      auto fold_q = [&](float (&acc)[96]) {
#pragma unroll
        for (int t = 0; t < 8; t++) frag(acc, t, Q[0][t], Q[1][t]);
      };
      auto attend = [&](int ab, auto drain) {
        GEOM;
        nb_sync<NB_BOTH>(256);
        const uint32_t xa_ = sb + OFF_STG + wu * 2048 + lane * 16;
        if (wu == 0) mbar_wait(BAR(HALO + ab), L);
        uint32_t KH[2][8], VH[16];
#pragma unroll
        for (int c = 0; c < 4; c++) {
          lds128(xa_ + c * 512, KH[c >> 1][4 * (c & 1)], KH[c >> 1][4 * (c & 1) + 1], KH[c >> 1][4 * (c & 1) + 2], KH[c >> 1][4 * (c & 1) + 3]);
          ldsm4t(sb + OFF_STG + 16384 + wu * 2048 + lr * 128 + (((2 * c + lt) ^ l7) << 4), VH[4 * c], VH[4 * c + 1], VH[4 * c + 2], VH[4 * c + 3]);
        }
        TS2(11 + ab + 32 * L);
        drain();
        if (SF & 4) sched_fence(P.zero);
        const bool e = g & 1, zneg = (g >> 1) < q, first = (i == 0) && (wu == 0);
        const float qs = 0.17677669530f * 1.4426950409f;
        uint32_t pr[2][6];
#pragma unroll
        for (int hh = 0; hh < 2; hh++)
          attn_probs(&Q[0][4 * hh], &Q[1][4 * hh], &KH[0][4 * hh], &KH[1][4 * hh], &K[0][4 * hh], &K[1][4 * hh], rstd0 * qs, rstd1 * qs, first, e, zneg, pr[hh]);
        float o[2][4][4];
#pragma unroll
        for (int hh = 0; hh < 2; hh++) attn_pv(pr[hh], &VH[8 * hh], &V[8 * hh], o[hh]);
#pragma unroll
        for (int hh = 0; hh < 2; hh++)
#pragma unroll
          for (int dt = 0; dt < 4; dt += 2)
            stsm4(sb + OFF_STG + (16 * wu + lr) * 128 + (((4 * hh + dt + lt) ^ l7) << 4),
                  pack2(o[hh][dt][0], o[hh][dt][1]), pack2(o[hh][dt][2], o[hh][dt][3]), pack2(o[hh][dt + 1][0], o[hh][dt + 1][1]), pack2(o[hh][dt + 1][2], o[hh][dt + 1][3]));
        fence_async_smem();
        signal(JOB + ab);
        nb_sync<NB_BOTH>(256);
      };

      if (L == 0) mbar_wait(BAR(XF), 0);
      TS(1 + 32 * L);
      mbar_wait(BAR(F1), 0); KB(0);    g1_issue(acca, sb + OFF_X, sb + slot1(0), True{});
      if (L == 0) mbar_wait(BAR(XF + 1), 0);
      mbar_wait(BAR(F1 + 1), 0); KB(1); g1_issue(acca, sb + OFF_X + 16384, sb + slot1(1), False{});
      wg_wait<1>(); release(E1 + 0);
      auto g1_bhead = [&](int p) {
        mbar_wait(BAR(F1 + p), 0); KB(p ? 2 : 16); g1_issue(accb, sb + OFF_X, sb + slot1(p), True{});
        if (p) { wg_wait<1>(); release(E1 + 1); }
        mbar_wait(BAR(F1 + p + 1), 0); KB(p ? 3 : 17); g1_issue(accb, sb + OFF_X + 16384, sb + slot1(p + 1), False{});
        wg_wait<1>(); release(E1 + p);
      };
      if (L == 0) {
        GEOM;
        const bf16* wp = P.wqkv_p + (size_t)(128 * m + 16 * wg + (t7 >> 3)) * 3072 + 128 * j + 64 * r + l7 * 8;
        const uint32_t ca = sb + OFF_STG + (16 * wg + (t7 >> 3)) * 784 + l7 * 32;
#pragma unroll 1
        for (int p = 0; p < 3; p++) {
          uint4 wv[4];
#pragma unroll
          for (int k = 0; k < 4; k++)
            asm volatile("ld.global.nc.v4.u32 {%0, %1, %2, %3}, [%4];" : "=r"(wv[k].x), "=r"(wv[k].y), "=r"(wv[k].z), "=r"(wv[k].w)
                         : "l"(wp + (size_t)k * 32 * 3072 + p * 1024));
          g1_loop(acca, 2 + 2 * p, 4 + 2 * p, 0);
          float cs[8];
#pragma unroll
          for (int k = 0; k < 4; k++) {
            const uint4 v = wv[k];
            const float t[8] = {bf_lo(v.x), bf_hi(v.x), bf_lo(v.y), bf_hi(v.y), bf_lo(v.z), bf_hi(v.z), bf_lo(v.w), bf_hi(v.w)};
#pragma unroll
            for (int e = 0; e < 8; e++) cs[e] = k ? cs[e] + t[e] : t[e];
          }
          sts128(ca + p * 256, __float_as_uint(cs[0]), __float_as_uint(cs[1]), __float_as_uint(cs[2]), __float_as_uint(cs[3]));
          sts128(ca + p * 256 + 16, __float_as_uint(cs[4]), __float_as_uint(cs[5]), __float_as_uint(cs[6]), __float_as_uint(cs[7]));
        }
        signal(CSJ);
        TS2(17);
        g1_stats(8);
        g1_loop(acca, 12, 14, 0);
        stat_fetch();
        g1_loop(acca, 14, 16, 0);
        ln_stats();
        wg_wait<0>(); release(E1 + 3);
        fence_regs(acca);
        g1_bhead(0);
        mbar_wait(BAR(STAT), 0);
      } else {
        g1_bhead(2);
        g1_stats(4);
        g1_loop(acca, 8, 12, 0);
        stat_fetch();
        g1_loop(acca, 12, 14, 0);
        ln_stats();
        g1_loop(acca, 14, 18, 0);
      }
      center(acca, 0); wg_commit();
      g1_step(accb, 18, true);
      fence_regs(acca);
      TS(2 + 32 * L);
      fold_v(acca);
      g1_loop(accb, 19, 21, 0);
      fold_k(acca, 0); fold_q(acca);
      sched_fence(P.zero);
      g1_loop(accb, 21, 24, 0);
      attend(0, [&]() { wg_wait<0>(); release(E1 + 3); });
      TS(3 + 32 * L);
      g1_loop(accb, 24, 26, 24);
      load_x();
      fence_regs(xa);
      center(accb, 1);
      g1_loop(accb, 26, 32 - LEAD1, 0);
      if (LEAD1 && wg == 0) { wg_wait<0>(); release(E1 + ((31 - LEAD1) & 3)); nb_sync<NB_LEAD>(256); }
      g1_loop(accb, 32 - LEAD1, 32, wg == 0 ? 32 - LEAD1 : 0);
      mbar_wait(BAR(STD), L);
      wg_wait<0>(); release(E1 + 3);
      fence_regs(accb);
      TS(4 + 32 * L);
      if (wu == 7) ST(0);
      fold_v(accb); fold_k(accb, 1);
      if (SF & 2) sched_fence(P.zero);
      fold_q(accb);
      TS2(29 + 32 * L);
      {
        auto g2_issue = [&](int p, bool own) {
          const uint32_t st = sb + slot2(p);
          const uint64_t da = mkdesc((own ? sb + OFF_STG : st) + wg * 8192, 16, 1024), db = mkdesc(st + 16384, 8192, 1024);
          wg_fence();
#pragma unroll
          for (int kk = 0; kk < 4; kk++) wgmma_128<0, 1>(xa, da + kk * 2, db + kk * 128);
          wg_commit();
        };
        uint32_t par = L ? 0x1e : 0;
        int p = 0, pp = 0;
        auto g2_loop = [&](int n0, int n1, int nrel) {
#pragma unroll 1
          for (int n = n0; n < n1; n++) {
            mbar_wait(BAR(F2 + p), (par >> p) & 1);
            KB(32 + n);
            if (n == 9 && wu == 0) ST(5);
            par ^= 1u << p;
            g2_issue(p, n == 8);
            if (LEAD2 && n == 15 && wg == 0) nb_arrive<NB_LEAD>(256);
            wg_wait<1>();
            if (n > nrel) release(E2 + pp);
            pp = p; if (++p == 5) p = 0;
          }
        };
        g2_loop(0, COVER, 0);
        attend(1, [&]() { wg_wait<0>(); release(E2 + COVER - 1); });
        TS(30 + 32 * L);
        {
          const bf16* bp = P.b2 + 128 * i + 16 * wu + ((fresh_tid() & 31) >> 2);
          asm volatile("ld.global.nc.u16 %0, [%1];" : "=h"(b2a) : "l"(bp));
          asm volatile("ld.global.nc.u16 %0, [%1];" : "=h"(b2b) : "l"(bp + 8));
        }
        TS2(14 + 32 * L);
        g2_loop(COVER, 16 - LEAD2, COVER);
        if (LEAD2 && wg == 1) { wg_wait<0>(); release(E2 + pp); nb_sync<NB_LEAD>(256); }
        g2_loop(16 - LEAD2, 16, wg == 1 ? 16 - LEAD2 : 0);
        wg_wait<0>();
        release(E2 + 0);
        fence_regs(xa);
      }
      TS(5 + 32 * L);
      if (wu == 0) ST(8);
      {
        GEOM;
        const uint32_t tg = 2 * (tag + 1) + 1;
        float s0 = 0.f, s1 = 0.f, s2 = 0.f, s3 = 0.f, q0 = 0.f, q1 = 0.f, q2 = 0.f, q3 = 0.f;
#pragma unroll
        for (int t = 0; t < 16; t++) {
          s0 += xa[4 * t]; s1 += xa[4 * t + 1]; s2 += xa[4 * t + 2]; s3 += xa[4 * t + 3];
          q0 = fmaf(xa[4 * t], xa[4 * t], q0); q1 = fmaf(xa[4 * t + 1], xa[4 * t + 1], q1);
          q2 = fmaf(xa[4 * t + 2], xa[4 * t + 2], q2); q3 = fmaf(xa[4 * t + 3], xa[4 * t + 3], q3);
        }
        const float sm = stat_publish(s0 + s1, q0 + q1, s2 + s3, q2 + q3, tg);
        const uint32_t t0 = clock32();
        wg_fence();
        wgmma_rs_224z(acc3, q == 0 ? 0x3f80u : 0u, q == 0 ? 0x3f80u : 0u, 0u, 0u, mkdesc_vec(sb + OFF_B1, 16));
        wg_commit();
        TS2(13 + 32 * L);
        const float pv0 = __shfl_sync(0xffffffffu, sm, 4 * l7) * (1.f / 128), pv1 = __shfl_sync(0xffffffffu, sm, 4 * l7 + 1) * (1.f / 128);
        while (clock32() - t0 < STAT_CLK) {}
        stat_fetch();
        stat_await(tg);
        float r0, m0, r1, m1;
        {
          float mean0, var0, mean1, var1;
          stat_combine(sv0[0], sv0[1], sv1[0], sv1[1], pv0, mean0, var0); stat_combine(sv0[2], sv0[3], sv1[2], sv1[3], pv1, mean1, var1);
          mean0 = __shfl_sync(0xffffffffu, mean0, g); var0 = __shfl_sync(0xffffffffu, var0, g);
          mean1 = __shfl_sync(0xffffffffu, mean1, g); var1 = __shfl_sync(0xffffffffu, var1, g);
          r0 = 0.5f * rsq(fmaf(var0 + 1e-5f, 1e-5f, var0)); r1 = 0.5f * rsq(fmaf(var1 + 1e-5f, 1e-5f, var1));
          m0 = -mean0 * r0; m1 = -mean1 * r1;
        }
        TS2(15 + 32 * L);
        const uint32_t ha = sb + OFF_X + wg * 16384 + (16 * w + lr) * 128;
#pragma unroll
        for (int t = 0; t < 16; t += 2)
          stsm4(ha + (t >> 3) * 8192 + ((((t & 7) + lt) ^ l7) << 4),
                pack2(fmaf(xa[4 * t], r0, m0), fmaf(xa[4 * t + 1], r0, m0)), pack2(fmaf(xa[4 * t + 2], r1, m1), fmaf(xa[4 * t + 3], r1, m1)),
                pack2(fmaf(xa[4 * t + 4], r0, m0), fmaf(xa[4 * t + 5], r0, m0)), pack2(fmaf(xa[4 * t + 6], r1, m1), fmaf(xa[4 * t + 7], r1, m1)));
        fence_async_smem();
        signal(JOB + 2 + wg);
        nb_sync<NB_BOTH>(256);
      }
      TS(6 + 32 * L);
      auto g3_issue = [&](uint32_t a, int p) {
        const uint32_t st = sb + slot3(p);
        const uint64_t da = mkdesc(a + wg * 8192, 8192, 1024), db = mkdesc(st + 16384, 8192, 1024);
        wg_fence();
#pragma unroll
        for (int kk = 0; kk < 4; kk++) wgmma_224<1, 1>(acc3, da + kk * 128, db + kk * 128);
        wg_commit();
      };
      mbar_wait(BAR(F3 + 0), 0); KB(48); g3_issue(sb + OFF_X, 0);
      mbar_wait(BAR(F3 + 1), 0); KB(49); g3_issue(sb + OFF_X + 16384, 1);
      sched_fence(P.zero);
      {
        const float c0 = __uint_as_float((uint32_t)b2a << 16), c1 = __uint_as_float((uint32_t)b2b << 16);
#pragma unroll
        for (int t = 0; t < 16; t++) { xa[4 * t] += c0; xa[4 * t + 1] += c0; xa[4 * t + 2] += c1; xa[4 * t + 3] += c1; }
        fence_regs(xa);
      }
      wg_wait<1>(); release(E3 + 0);
#pragma unroll 1
      for (int n = 2; n < 32; n++) {
        const int p = n & 3;
        mbar_wait(BAR(F3 + p), (n >> 2) & 1);
        KB(48 + n);
        if (n == 3 && wu == 0) ST(13);
        if (n == 2 && wu == 0) ST(14);
        g3_issue(sb + slot3(p), p);
        wg_wait<1>();
        release(E3 + ((n - 1) & 3));
      }
      mbar_wait(BAR(RD), L);
      wg_wait<0>();
      release(E3 + 3);
      fence_regs(acc3);
      TS(7 + 32 * L);
      if (wu == 0) ST(16);
      auto g4_issue = [&](int p, uint32_t b) {
        const uint64_t da = mkdesc(sb + slot4(p) + wg * 8192, 8192, 1024), db = mkdesc(b, 8192, 1024);
        wg_fence();
#pragma unroll
        for (int kk = 0; kk < 4; kk++) wgmma_128<1, 1>(xa, da + kk * 128, db + kk * 128);
        wg_commit();
      };
      uint32_t par = L ? 0x3c : 0;
      {
        GEOM;
        const uint32_t ua = sb + wg * 8192 + (8 * lt + l7) * 128 + (((2 * w + ((lane >> 3) & 1)) ^ l7) << 4);
#pragma unroll
        for (int cc = 0; cc < 4; cc++) {
          const int c = (cc + 3) & 3;
          uint32_t u[16];
#pragma unroll
          for (int k = 0; k < (c == 3 ? 8 : 16); k++) u[k] = pack2(gelu_half(acc3[32 * c + 2 * k]), gelu_half(acc3[32 * c + 2 * k + 1]));
          if (c == 3) mbar_wait(BAR(E3 + 2), 1);
#pragma unroll
          for (int k = 0; k < (c == 3 ? 2 : 4); k++)
            stsm4t(ua + (c == 3 ? slot4(1) + 16384 : c == 0 ? slot4(2) + 16384 : OFF_X + (c - 1) * 16384) + k * 2048, u[4 * k], u[4 * k + 1], u[4 * k + 2], u[4 * k + 3]);
          if (c >= 2) { fence_async_smem(); signal(JOB + 4 + c); }
          if ((c == 3 && (SF & 8)) || (c == 0 && (SF & 16))) sched_fence(P.zero);
          TS2(16 + 3 * c + 32 * L);
        }
        nb_sync<NB_BOTH>(256);
      }
      TS(8 + 32 * L);
      {
        int p = 0, pp = 0;
#pragma unroll 1
        for (int n = 0; n < 56; n++) {
          mbar_wait(BAR(F4 + p), (par >> p) & 1);
          KB(80 + n);
          if (n == 3 && wu == 0) ST(21);
          if (n == 0 && wu == 0) ST(22);
          par ^= 1u << p;
          g4_issue(p, n < 2 ? sb + OFF_X + n * 16384 : sb + slot4(p) + 16384);
          wg_wait<1>();
          if (n) release(E4 + pp);
          pp = p; if (++p == 6) p = 0;
        }
      }
      mbar_wait(BAR(RD + 1), L);
      wg_wait<0>();
      release(E4 + 1);
      fence_regs(xa);
      TS(9 + 32 * L);
      {
        GEOM;
#pragma unroll
        for (int t = 0; t < 16; t += 2) {
          stsm4(sb + OFF_X + (t >> 3) * 16384 + (16 * wu + lr) * 128 + ((((t & 7) + lt) ^ l7) << 4),
                pack2(xa[4 * t], xa[4 * t + 1]), pack2(xa[4 * t + 2], xa[4 * t + 3]),
                pack2(xa[4 * t + 4], xa[4 * t + 5]), pack2(xa[4 * t + 6], xa[4 * t + 7]));
          if ((t & 7) == 6) { fence_async_smem(); signal(JOB + 8 + (t >> 3)); }
        }
        nb_sync<NB_BOTH>(256);
      }
      TS(10 + 32 * L);
      KB(136);
    }
    cluster_bar();
    TS(32);
  }
}

typedef CUresult (*EncodeFn)(CUtensorMap*, CUtensorMapDataType, cuuint32_t, void*, const cuuint64_t*, const cuuint64_t*, const cuuint32_t*,
                             const cuuint32_t*, CUtensorMapInterleave, CUtensorMapSwizzle, CUtensorMapL2promotion, CUtensorMapFloatOOBfill);

void make_map(EncodeFn enc, CUtensorMap* mp, const void* base, int rank, cuuint64_t d0, cuuint64_t d1, cuuint64_t d2, cuuint64_t s1, cuuint64_t s2,
              cuuint32_t b0, cuuint32_t b1, cuuint32_t b2) {
  cuuint64_t dims[3] = {d0, d1, d2}, strides[2] = {s1, s2};
  cuuint32_t box[3] = {b0, b1, b2}, es[3] = {1, 1, 1};
  CUresult res = enc(mp, CU_TENSOR_MAP_DATA_TYPE_BFLOAT16, rank, const_cast<void*>(base), dims, strides, box, es, CU_TENSOR_MAP_INTERLEAVE_NONE,
                     CU_TENSOR_MAP_SWIZZLE_128B, CU_TENSOR_MAP_L2_PROMOTION_L2_128B, CU_TENSOR_MAP_FLOAT_OOB_FILL_NONE);
  (void)res;
}

}

extern "C" void kernel_launch(void* const* d_in, const int* in_sizes, int n_in, void* d_out, int out_size) {
  (void)in_sizes; (void)n_in; (void)out_size;
  static EncodeFn enc = nullptr;
  if (!enc) {
    void* fn = nullptr;
    cudaDriverEntryPointQueryResult qr;
    cudaGetDriverEntryPoint("cuTensorMapEncodeTiled", &fn, cudaEnableDefault, &qr);
    enc = (EncodeFn)fn;
    cudaFuncSetAttribute(fused_kernel, cudaFuncAttributeMaxDynamicSharedMemorySize, SMEM_BYTES);
  }
  Params P;
  make_map(enc, &P.x0, d_in[0], 2, D_, S_, 1, D_ * 2, 0, 64, 128, 1);
  make_map(enc, &P.wqkv, d_in[1], 3, D_, D_, 3, 3 * D_ * 2, D_ * 2, 64, 32, 3);
  make_map(enc, &P.wo, d_in[2], 2, D_, D_, 1, D_ * 2, 0, 64, 64, 1);
  make_map(enc, &P.w1, d_in[4], 3, 64, S_, F_ / 64, F_ * 2, 128, 64, 64, 3);
  make_map(enc, &P.w1h, d_in[4], 3, 32, S_, F_ / 32, F_ * 2, 64, 64, 64, 1);
  make_map(enc, &P.w2, d_in[6], 3, 64, F_, S_ / 64, S_ * 2, 128, 64, 64, 2);
  make_map(enc, &P.out, d_out, 2, D_, S_, 1, D_ * 2, 0, 64, 128, 1);
  P.wqkv_p = (const bf16*)d_in[1];
  P.b1 = (const bf16*)d_in[5];
  P.b2 = (const bf16*)d_in[7];
  P.zero = 0;
  fused_kernel<<<128, 384, SMEM_BYTES>>>(P);
}
```

```cpp
#include <cuda_runtime.h>
#include <cuda_bf16.h>
#include <cuda.h>
#include <stdint.h>

namespace {

typedef __nv_bfloat16 bf16;
constexpr int S_ = 2048, D_ = 1024, F_ = 3584;

constexpr uint32_t OFF_STG  = 163840;
constexpr uint32_t OFF_X    = 196608;
constexpr uint32_t OFF_BAR  = 229376;
constexpr uint32_t OFF_CS   = OFF_BAR + 512;
constexpr uint32_t OFF_B1   = OFF_CS + 1536;
constexpr uint32_t SMEM_BYTES = OFF_B1 + 896 + 128;
constexpr int F1 = 0, E1 = 4, F2 = 8, E2 = 13, F3 = 18, E3 = 22, F4 = 26, E4 = 32;
constexpr int JOB = 38;
constexpr int RD = 48;
constexpr int XF = 54, STD = 56, STAT = 58, FOLD = 59, CSJ = 61, HALO = 62;
constexpr int NB_BOTH = 1, NB_HELP = 2, NB_INIT = 3, NB_LEAD = 4;

__device__ __forceinline__ uint32_t slot1(int p) { return p * 40960; }
__device__ __forceinline__ uint32_t slot2(int p) { return p * 32768; }
__device__ __forceinline__ uint32_t slot3(int p) { return ((p + 2) & 3) * 49152; }
__device__ __forceinline__ uint32_t slot4(int p) { return (p < 2 ? p + 4 : p - 2) * 32768; }

__device__ __align__(1024) uint8_t gXB[16 * 16 * 16384];
__device__ __align__(1024) uint8_t gOB[16 * 16 * 16384];
__device__ __align__(1024) uint8_t gHB[8 * 32 * 16384];
__device__ __align__(1024) uint8_t gUB[8 * 56 * 16384];
__device__ __align__(1024) uint2   gST[2][16][8][8][16];
__device__ __align__(1024) uint4   gHalo[2][16][8][12][32];
__device__ __align__(1024) uint32_t gAck[2][16][8][2][8];
__device__ __align__(1024) uint4   gCS[8][16][64];
__device__ __align__(1024) uint32_t gFlag[2][7][16][32];
__device__ uint32_t gEpoch;
#define TS(k)
#define TS2(k)

#define KB(k)
#define ST(k)
struct Params {
  CUtensorMap x0, wqkv, wo, w1, w1h, w2, out;
  const bf16 *wqkv_p, *b1, *b2;
  uint32_t zero;
};

template <int TA, int TB> __device__ __forceinline__ void wgmma_128(float (&d)[64], uint64_t da, uint64_t db) {
  asm volatile("wgmma.mma_async.sync.aligned.m64n128k16.f32.bf16.bf16 {"
  "%0, %1, %2, %3, %4, %5, %6, %7, %8, %9, %10, %11, %12, %13, %14, %15, "
  "%16, %17, %18, %19, %20, %21, %22, %23, %24, %25, %26, %27, %28, %29, %30, %31, "
  "%32, %33, %34, %35, %36, %37, %38, %39, %40, %41, %42, %43, %44, %45, %46, %47, "
  "%48, %49, %50, %51, %52, %53, %54, %55, %56, %57, %58, %59, %60, %61, %62, %63"
  "}, %64, %65, 1, 1, 1, %66, %67;\n"
  : "+f"(d[0]), "+f"(d[1]), "+f"(d[2]), "+f"(d[3]), "+f"(d[4]), "+f"(d[5]), "+f"(d[6]), "+f"(d[7]),
    "+f"(d[8]), "+f"(d[9]), "+f"(d[10]), "+f"(d[11]), "+f"(d[12]), "+f"(d[13]), "+f"(d[14]), "+f"(d[15]),
    "+f"(d[16]), "+f"(d[17]), "+f"(d[18]), "+f"(d[19]), "+f"(d[20]), "+f"(d[21]), "+f"(d[22]), "+f"(d[23]),
    "+f"(d[24]), "+f"(d[25]), "+f"(d[26]), "+f"(d[27]), "+f"(d[28]), "+f"(d[29]), "+f"(d[30]), "+f"(d[31]),
    "+f"(d[32]), "+f"(d[33]), "+f"(d[34]), "+f"(d[35]), "+f"(d[36]), "+f"(d[37]), "+f"(d[38]), "+f"(d[39]),
    "+f"(d[40]), "+f"(d[41]), "+f"(d[42]), "+f"(d[43]), "+f"(d[44]), "+f"(d[45]), "+f"(d[46]), "+f"(d[47]),
    "+f"(d[48]), "+f"(d[49]), "+f"(d[50]), "+f"(d[51]), "+f"(d[52]), "+f"(d[53]), "+f"(d[54]), "+f"(d[55]),
    "+f"(d[56]), "+f"(d[57]), "+f"(d[58]), "+f"(d[59]), "+f"(d[60]), "+f"(d[61]), "+f"(d[62]), "+f"(d[63])
  : "l"(da), "l"(db), "n"(TA), "n"(TB));
}
template <int TA, int TB> __device__ __forceinline__ void wgmma_192(float (&d)[96], uint64_t da, uint64_t db) {
  asm volatile("wgmma.mma_async.sync.aligned.m64n192k16.f32.bf16.bf16 {"
  "%0, %1, %2, %3, %4, %5, %6, %7, %8, %9, %10, %11, %12, %13, %14, %15, "
  "%16, %17, %18, %19, %20, %21, %22, %23, %24, %25, %26, %27, %28, %29, %30, %31, "
  "%32, %33, %34, %35, %36, %37, %38, %39, %40, %41, %42, %43, %44, %45, %46, %47, "
  "%48, %49, %50, %51, %52, %53, %54, %55, %56, %57, %58, %59, %60, %61, %62, %63, "
  "%64, %65, %66, %67, %68, %69, %70, %71, %72, %73, %74, %75, %76, %77, %78, %79, "
  "%80, %81, %82, %83, %84, %85, %86, %87, %88, %89, %90, %91, %92, %93, %94, %95"
  "}, %96, %97, 1, 1, 1, %98, %99;\n"
  : "+f"(d[0]), "+f"(d[1]), "+f"(d[2]), "+f"(d[3]), "+f"(d[4]), "+f"(d[5]), "+f"(d[6]), "+f"(d[7]),
    "+f"(d[8]), "+f"(d[9]), "+f"(d[10]), "+f"(d[11]), "+f"(d[12]), "+f"(d[13]), "+f"(d[14]), "+f"(d[15]),
    "+f"(d[16]), "+f"(d[17]), "+f"(d[18]), "+f"(d[19]), "+f"(d[20]), "+f"(d[21]), "+f"(d[22]), "+f"(d[23]),
    "+f"(d[24]), "+f"(d[25]), "+f"(d[26]), "+f"(d[27]), "+f"(d[28]), "+f"(d[29]), "+f"(d[30]), "+f"(d[31]),
    "+f"(d[32]), "+f"(d[33]), "+f"(d[34]), "+f"(d[35]), "+f"(d[36]), "+f"(d[37]), "+f"(d[38]), "+f"(d[39]),
    "+f"(d[40]), "+f"(d[41]), "+f"(d[42]), "+f"(d[43]), "+f"(d[44]), "+f"(d[45]), "+f"(d[46]), "+f"(d[47]),
    "+f"(d[48]), "+f"(d[49]), "+f"(d[50]), "+f"(d[51]), "+f"(d[52]), "+f"(d[53]), "+f"(d[54]), "+f"(d[55]),
    "+f"(d[56]), "+f"(d[57]), "+f"(d[58]), "+f"(d[59]), "+f"(d[60]), "+f"(d[61]), "+f"(d[62]), "+f"(d[63]),
    "+f"(d[64]), "+f"(d[65]), "+f"(d[66]), "+f"(d[67]), "+f"(d[68]), "+f"(d[69]), "+f"(d[70]), "+f"(d[71]),
    "+f"(d[72]), "+f"(d[73]), "+f"(d[74]), "+f"(d[75]), "+f"(d[76]), "+f"(d[77]), "+f"(d[78]), "+f"(d[79]),
    "+f"(d[80]), "+f"(d[81]), "+f"(d[82]), "+f"(d[83]), "+f"(d[84]), "+f"(d[85]), "+f"(d[86]), "+f"(d[87]),
    "+f"(d[88]), "+f"(d[89]), "+f"(d[90]), "+f"(d[91]), "+f"(d[92]), "+f"(d[93]), "+f"(d[94]), "+f"(d[95])
  : "l"(da), "l"(db), "n"(TA), "n"(TB));
}
template <int TA, int TB> __device__ __forceinline__ void wgmma_192z(float (&d)[96], uint64_t da, uint64_t db) {
  asm volatile("wgmma.mma_async.sync.aligned.m64n192k16.f32.bf16.bf16 {"
  "%0, %1, %2, %3, %4, %5, %6, %7, %8, %9, %10, %11, %12, %13, %14, %15, "
  "%16, %17, %18, %19, %20, %21, %22, %23, %24, %25, %26, %27, %28, %29, %30, %31, "
  "%32, %33, %34, %35, %36, %37, %38, %39, %40, %41, %42, %43, %44, %45, %46, %47, "
  "%48, %49, %50, %51, %52, %53, %54, %55, %56, %57, %58, %59, %60, %61, %62, %63, "
  "%64, %65, %66, %67, %68, %69, %70, %71, %72, %73, %74, %75, %76, %77, %78, %79, "
  "%80, %81, %82, %83, %84, %85, %86, %87, %88, %89, %90, %91, %92, %93, %94, %95"
  "}, %96, %97, 0, 1, 1, %98, %99;\n"
  : "=f"(d[0]), "=f"(d[1]), "=f"(d[2]), "=f"(d[3]), "=f"(d[4]), "=f"(d[5]), "=f"(d[6]), "=f"(d[7]),
    "=f"(d[8]), "=f"(d[9]), "=f"(d[10]), "=f"(d[11]), "=f"(d[12]), "=f"(d[13]), "=f"(d[14]), "=f"(d[15]),
    "=f"(d[16]), "=f"(d[17]), "=f"(d[18]), "=f"(d[19]), "=f"(d[20]), "=f"(d[21]), "=f"(d[22]), "=f"(d[23]),
    "=f"(d[24]), "=f"(d[25]), "=f"(d[26]), "=f"(d[27]), "=f"(d[28]), "=f"(d[29]), "=f"(d[30]), "=f"(d[31]),
    "=f"(d[32]), "=f"(d[33]), "=f"(d[34]), "=f"(d[35]), "=f"(d[36]), "=f"(d[37]), "=f"(d[38]), "=f"(d[39]),
    "=f"(d[40]), "=f"(d[41]), "=f"(d[42]), "=f"(d[43]), "=f"(d[44]), "=f"(d[45]), "=f"(d[46]), "=f"(d[47]),
    "=f"(d[48]), "=f"(d[49]), "=f"(d[50]), "=f"(d[51]), "=f"(d[52]), "=f"(d[53]), "=f"(d[54]), "=f"(d[55]),
    "=f"(d[56]), "=f"(d[57]), "=f"(d[58]), "=f"(d[59]), "=f"(d[60]), "=f"(d[61]), "=f"(d[62]), "=f"(d[63]),
    "=f"(d[64]), "=f"(d[65]), "=f"(d[66]), "=f"(d[67]), "=f"(d[68]), "=f"(d[69]), "=f"(d[70]), "=f"(d[71]),
    "=f"(d[72]), "=f"(d[73]), "=f"(d[74]), "=f"(d[75]), "=f"(d[76]), "=f"(d[77]), "=f"(d[78]), "=f"(d[79]),
    "=f"(d[80]), "=f"(d[81]), "=f"(d[82]), "=f"(d[83]), "=f"(d[84]), "=f"(d[85]), "=f"(d[86]), "=f"(d[87]),
    "=f"(d[88]), "=f"(d[89]), "=f"(d[90]), "=f"(d[91]), "=f"(d[92]), "=f"(d[93]), "=f"(d[94]), "=f"(d[95])
  : "l"(da), "l"(db), "n"(TA), "n"(TB));
}
template <int TA, int TB> __device__ __forceinline__ void wgmma_224(float (&d)[112], uint64_t da, uint64_t db) {
  asm volatile("wgmma.mma_async.sync.aligned.m64n224k16.f32.bf16.bf16 {"
  "%0, %1, %2, %3, %4, %5, %6, %7, %8, %9, %10, %11, %12, %13, %14, %15, "
  "%16, %17, %18, %19, %20, %21, %22, %23, %24, %25, %26, %27, %28, %29, %30, %31, "
  "%32, %33, %34, %35, %36, %37, %38, %39, %40, %41, %42, %43, %44, %45, %46, %47, "
  "%48, %49, %50, %51, %52, %53, %54, %55, %56, %57, %58, %59, %60, %61, %62, %63, "
  "%64, %65, %66, %67, %68, %69, %70, %71, %72, %73, %74, %75, %76, %77, %78, %79, "
  "%80, %81, %82, %83, %84, %85, %86, %87, %88, %89, %90, %91, %92, %93, %94, %95, "
  "%96, %97, %98, %99, %100, %101, %102, %103, %104, %105, %106, %107, %108, %109, %110, %111"
  "}, %112, %113, 1, 1, 1, %114, %115;\n"
  : "+f"(d[0]), "+f"(d[1]), "+f"(d[2]), "+f"(d[3]), "+f"(d[4]), "+f"(d[5]), "+f"(d[6]), "+f"(d[7]),
    "+f"(d[8]), "+f"(d[9]), "+f"(d[10]), "+f"(d[11]), "+f"(d[12]), "+f"(d[13]), "+f"(d[14]), "+f"(d[15]),
    "+f"(d[16]), "+f"(d[17]), "+f"(d[18]), "+f"(d[19]), "+f"(d[20]), "+f"(d[21]), "+f"(d[22]), "+f"(d[23]),
    "+f"(d[24]), "+f"(d[25]), "+f"(d[26]), "+f"(d[27]), "+f"(d[28]), "+f"(d[29]), "+f"(d[30]), "+f"(d[31]),
    "+f"(d[32]), "+f"(d[33]), "+f"(d[34]), "+f"(d[35]), "+f"(d[36]), "+f"(d[37]), "+f"(d[38]), "+f"(d[39]),
    "+f"(d[40]), "+f"(d[41]), "+f"(d[42]), "+f"(d[43]), "+f"(d[44]), "+f"(d[45]), "+f"(d[46]), "+f"(d[47]),
    "+f"(d[48]), "+f"(d[49]), "+f"(d[50]), "+f"(d[51]), "+f"(d[52]), "+f"(d[53]), "+f"(d[54]), "+f"(d[55]),
    "+f"(d[56]), "+f"(d[57]), "+f"(d[58]), "+f"(d[59]), "+f"(d[60]), "+f"(d[61]), "+f"(d[62]), "+f"(d[63]),
    "+f"(d[64]), "+f"(d[65]), "+f"(d[66]), "+f"(d[67]), "+f"(d[68]), "+f"(d[69]), "+f"(d[70]), "+f"(d[71]),
    "+f"(d[72]), "+f"(d[73]), "+f"(d[74]), "+f"(d[75]), "+f"(d[76]), "+f"(d[77]), "+f"(d[78]), "+f"(d[79]),
    "+f"(d[80]), "+f"(d[81]), "+f"(d[82]), "+f"(d[83]), "+f"(d[84]), "+f"(d[85]), "+f"(d[86]), "+f"(d[87]),
    "+f"(d[88]), "+f"(d[89]), "+f"(d[90]), "+f"(d[91]), "+f"(d[92]), "+f"(d[93]), "+f"(d[94]), "+f"(d[95]),
    "+f"(d[96]), "+f"(d[97]), "+f"(d[98]), "+f"(d[99]), "+f"(d[100]), "+f"(d[101]), "+f"(d[102]), "+f"(d[103]),
    "+f"(d[104]), "+f"(d[105]), "+f"(d[106]), "+f"(d[107]), "+f"(d[108]), "+f"(d[109]), "+f"(d[110]), "+f"(d[111])
  : "l"(da), "l"(db), "n"(TA), "n"(TB));
}
__device__ __forceinline__ void wgmma_rs_192(float (&d)[96], uint32_t a0, uint32_t a1, uint32_t a2, uint32_t a3, uint64_t db) {
  asm volatile("wgmma.mma_async.sync.aligned.m64n192k16.f32.bf16.bf16 {"
  "%0, %1, %2, %3, %4, %5, %6, %7, %8, %9, %10, %11, %12, %13, %14, %15, "
  "%16, %17, %18, %19, %20, %21, %22, %23, %24, %25, %26, %27, %28, %29, %30, %31, "
  "%32, %33, %34, %35, %36, %37, %38, %39, %40, %41, %42, %43, %44, %45, %46, %47, "
  "%48, %49, %50, %51, %52, %53, %54, %55, %56, %57, %58, %59, %60, %61, %62, %63, "
  "%64, %65, %66, %67, %68, %69, %70, %71, %72, %73, %74, %75, %76, %77, %78, %79, "
  "%80, %81, %82, %83, %84, %85, %86, %87, %88, %89, %90, %91, %92, %93, %94, %95"
  "}, {%96, %97, %98, %99}, %100, 1, 1, 1, 1;\n"
  : "+f"(d[0]), "+f"(d[1]), "+f"(d[2]), "+f"(d[3]), "+f"(d[4]), "+f"(d[5]), "+f"(d[6]), "+f"(d[7]),
    "+f"(d[8]), "+f"(d[9]), "+f"(d[10]), "+f"(d[11]), "+f"(d[12]), "+f"(d[13]), "+f"(d[14]), "+f"(d[15]),
    "+f"(d[16]), "+f"(d[17]), "+f"(d[18]), "+f"(d[19]), "+f"(d[20]), "+f"(d[21]), "+f"(d[22]), "+f"(d[23]),
    "+f"(d[24]), "+f"(d[25]), "+f"(d[26]), "+f"(d[27]), "+f"(d[28]), "+f"(d[29]), "+f"(d[30]), "+f"(d[31]),
    "+f"(d[32]), "+f"(d[33]), "+f"(d[34]), "+f"(d[35]), "+f"(d[36]), "+f"(d[37]), "+f"(d[38]), "+f"(d[39]),
    "+f"(d[40]), "+f"(d[41]), "+f"(d[42]), "+f"(d[43]), "+f"(d[44]), "+f"(d[45]), "+f"(d[46]), "+f"(d[47]),
    "+f"(d[48]), "+f"(d[49]), "+f"(d[50]), "+f"(d[51]), "+f"(d[52]), "+f"(d[53]), "+f"(d[54]), "+f"(d[55]),
    "+f"(d[56]), "+f"(d[57]), "+f"(d[58]), "+f"(d[59]), "+f"(d[60]), "+f"(d[61]), "+f"(d[62]), "+f"(d[63]),
    "+f"(d[64]), "+f"(d[65]), "+f"(d[66]), "+f"(d[67]), "+f"(d[68]), "+f"(d[69]), "+f"(d[70]), "+f"(d[71]),
    "+f"(d[72]), "+f"(d[73]), "+f"(d[74]), "+f"(d[75]), "+f"(d[76]), "+f"(d[77]), "+f"(d[78]), "+f"(d[79]),
    "+f"(d[80]), "+f"(d[81]), "+f"(d[82]), "+f"(d[83]), "+f"(d[84]), "+f"(d[85]), "+f"(d[86]), "+f"(d[87]),
    "+f"(d[88]), "+f"(d[89]), "+f"(d[90]), "+f"(d[91]), "+f"(d[92]), "+f"(d[93]), "+f"(d[94]), "+f"(d[95])
  : "r"(a0), "r"(a1), "r"(a2), "r"(a3), "l"(db));
}
__device__ __forceinline__ void wgmma_rs_224z(float (&d)[112], uint32_t a0, uint32_t a1, uint32_t a2, uint32_t a3, uint64_t db) {
  asm volatile("wgmma.mma_async.sync.aligned.m64n224k16.f32.bf16.bf16 {"
  "%0, %1, %2, %3, %4, %5, %6, %7, %8, %9, %10, %11, %12, %13, %14, %15, "
  "%16, %17, %18, %19, %20, %21, %22, %23, %24, %25, %26, %27, %28, %29, %30, %31, "
  "%32, %33, %34, %35, %36, %37, %38, %39, %40, %41, %42, %43, %44, %45, %46, %47, "
  "%48, %49, %50, %51, %52, %53, %54, %55, %56, %57, %58, %59, %60, %61, %62, %63, "
  "%64, %65, %66, %67, %68, %69, %70, %71, %72, %73, %74, %75, %76, %77, %78, %79, "
  "%80, %81, %82, %83, %84, %85, %86, %87, %88, %89, %90, %91, %92, %93, %94, %95, "
  "%96, %97, %98, %99, %100, %101, %102, %103, %104, %105, %106, %107, %108, %109, %110, %111"
  "}, {%112, %113, %114, %115}, %116, 0, 1, 1, 1;\n"
  : "=f"(d[0]), "=f"(d[1]), "=f"(d[2]), "=f"(d[3]), "=f"(d[4]), "=f"(d[5]), "=f"(d[6]), "=f"(d[7]),
    "=f"(d[8]), "=f"(d[9]), "=f"(d[10]), "=f"(d[11]), "=f"(d[12]), "=f"(d[13]), "=f"(d[14]), "=f"(d[15]),
    "=f"(d[16]), "=f"(d[17]), "=f"(d[18]), "=f"(d[19]), "=f"(d[20]), "=f"(d[21]), "=f"(d[22]), "=f"(d[23]),
    "=f"(d[24]), "=f"(d[25]), "=f"(d[26]), "=f"(d[27]), "=f"(d[28]), "=f"(d[29]), "=f"(d[30]), "=f"(d[31]),
    "=f"(d[32]), "=f"(d[33]), "=f"(d[34]), "=f"(d[35]), "=f"(d[36]), "=f"(d[37]), "=f"(d[38]), "=f"(d[39]),
    "=f"(d[40]), "=f"(d[41]), "=f"(d[42]), "=f"(d[43]), "=f"(d[44]), "=f"(d[45]), "=f"(d[46]), "=f"(d[47]),
    "=f"(d[48]), "=f"(d[49]), "=f"(d[50]), "=f"(d[51]), "=f"(d[52]), "=f"(d[53]), "=f"(d[54]), "=f"(d[55]),
    "=f"(d[56]), "=f"(d[57]), "=f"(d[58]), "=f"(d[59]), "=f"(d[60]), "=f"(d[61]), "=f"(d[62]), "=f"(d[63]),
    "=f"(d[64]), "=f"(d[65]), "=f"(d[66]), "=f"(d[67]), "=f"(d[68]), "=f"(d[69]), "=f"(d[70]), "=f"(d[71]),
    "=f"(d[72]), "=f"(d[73]), "=f"(d[74]), "=f"(d[75]), "=f"(d[76]), "=f"(d[77]), "=f"(d[78]), "=f"(d[79]),
    "=f"(d[80]), "=f"(d[81]), "=f"(d[82]), "=f"(d[83]), "=f"(d[84]), "=f"(d[85]), "=f"(d[86]), "=f"(d[87]),
    "=f"(d[88]), "=f"(d[89]), "=f"(d[90]), "=f"(d[91]), "=f"(d[92]), "=f"(d[93]), "=f"(d[94]), "=f"(d[95]),
    "=f"(d[96]), "=f"(d[97]), "=f"(d[98]), "=f"(d[99]), "=f"(d[100]), "=f"(d[101]), "=f"(d[102]), "=f"(d[103]),
    "=f"(d[104]), "=f"(d[105]), "=f"(d[106]), "=f"(d[107]), "=f"(d[108]), "=f"(d[109]), "=f"(d[110]), "=f"(d[111])
  : "r"(a0), "r"(a1), "r"(a2), "r"(a3), "l"(db));
}

__device__ __forceinline__ uint32_t smem_u32(const void* p) { return (uint32_t)__cvta_generic_to_shared(p); }
__device__ __forceinline__ void mbar_init(uint32_t bar, uint32_t cnt) { asm volatile("mbarrier.init.shared::cta.b64 [%0], %1;" ::"r"(bar), "r"(cnt) : "memory"); }
__device__ __forceinline__ void mbar_expect(uint32_t bar, uint32_t bytes) { asm volatile("mbarrier.arrive.expect_tx.shared::cta.b64 _, [%0], %1;" ::"r"(bar), "r"(bytes) : "memory"); }
__device__ __forceinline__ void mbar_arrive(uint32_t bar) { asm volatile("mbarrier.arrive.shared::cta.b64 _, [%0];" ::"r"(bar) : "memory"); }
__device__ __forceinline__ void mbar_arrive_cl(uint32_t cbar) { asm volatile("mbarrier.arrive.shared::cluster.b64 _, [%0];" ::"r"(cbar) : "memory"); }
__device__ __forceinline__ uint32_t mapa(uint32_t a, uint32_t cta) { uint32_t r; asm("mapa.shared::cluster.u32 %0, %1, %2;" : "=r"(r) : "r"(a), "r"(cta)); return r; }
__device__ __forceinline__ void mbar_wait(uint32_t bar, uint32_t parity) {
  asm volatile("{\n.reg .pred p;\n.reg .u32 n;\nmov.u32 n, 0;\n"
    "LAB_WAIT:\n"
    "mbarrier.try_wait.parity.shared::cta.b64 p, [%0], %1;\n"
    "@p bra LAB_DONE;\n"
    "add.u32 n, n, 1;\n"
    "setp.lt.u32 p, n, 2000000;\n"
    "@p bra LAB_WAIT;\n"
    "trap;\n"
    "LAB_DONE:\n}\n" ::"r"(bar), "r"(parity) : "memory");
}
constexpr uint32_t SPIN_MAX = 2000000;
__device__ __forceinline__ void tma2d(uint32_t dst, const CUtensorMap* m, uint32_t bar, int c0, int c1) {
  asm volatile("cp.async.bulk.tensor.2d.shared::cluster.global.mbarrier::complete_tx::bytes [%0], [%1, {%3, %4}], [%2];"
    ::"r"(dst), "l"(m), "r"(bar), "r"(c0), "r"(c1) : "memory");
}
__device__ __forceinline__ void tma2d_mc(uint32_t dst, const CUtensorMap* m, uint32_t bar, int c0, int c1) {
  asm volatile("cp.async.bulk.tensor.2d.shared::cluster.global.mbarrier::complete_tx::bytes.multicast::cluster [%0], [%1, {%3, %4}], [%2], %5;"
    ::"r"(dst), "l"(m), "r"(bar), "r"(c0), "r"(c1), "h"((uint16_t)3) : "memory");
}
__device__ __forceinline__ void tma3d(uint32_t dst, const CUtensorMap* m, uint32_t bar, int c0, int c1, int c2) {
  asm volatile("cp.async.bulk.tensor.3d.shared::cluster.global.mbarrier::complete_tx::bytes [%0], [%1, {%3, %4, %5}], [%2];"
    ::"r"(dst), "l"(m), "r"(bar), "r"(c0), "r"(c1), "r"(c2) : "memory");
}
__device__ __forceinline__ void tma3d_mc(uint32_t dst, const CUtensorMap* m, uint32_t bar, int c0, int c1, int c2) {
  asm volatile("cp.async.bulk.tensor.3d.shared::cluster.global.mbarrier::complete_tx::bytes.multicast::cluster [%0], [%1, {%3, %4, %5}], [%2], %6;"
    ::"r"(dst), "l"(m), "r"(bar), "r"(c0), "r"(c1), "r"(c2), "h"((uint16_t)3) : "memory");
}
__device__ __forceinline__ void tma2d_store(const CUtensorMap* m, uint32_t src, int c0, int c1) {
  asm volatile("cp.async.bulk.tensor.2d.global.shared::cta.bulk_group [%0, {%2, %3}], [%1];" ::"l"(m), "r"(src), "r"(c0), "r"(c1) : "memory");
}
__device__ __forceinline__ void bulk_ld(uint32_t dst, const void* src, uint32_t bytes, uint32_t bar) {
  asm volatile("cp.async.bulk.shared::cluster.global.mbarrier::complete_tx::bytes [%0], [%1], %2, [%3];" ::"r"(dst), "l"(src), "r"(bytes), "r"(bar) : "memory");
}
__device__ __forceinline__ void bulk_ld_mc(uint32_t dst, const void* src, uint32_t bytes, uint32_t bar) {
  asm volatile("cp.async.bulk.shared::cluster.global.mbarrier::complete_tx::bytes.multicast::cluster [%0], [%1], %2, [%3], %4;"
    ::"r"(dst), "l"(src), "r"(bytes), "r"(bar), "h"((uint16_t)3) : "memory");
}
__device__ __forceinline__ void bulk_st(void* dst, uint32_t src, uint32_t bytes) {
  asm volatile("cp.async.bulk.global.shared::cta.bulk_group [%0], [%1], %2;" ::"l"(dst), "r"(src), "r"(bytes) : "memory");
}
__device__ __forceinline__ void bulk_s2s(uint32_t cdst, uint32_t src, uint32_t bytes, uint32_t cbar) {
  asm volatile("cp.async.bulk.shared::cluster.shared::cta.mbarrier::complete_tx::bytes [%0], [%1], %2, [%3];" ::"r"(cdst), "r"(src), "r"(bytes), "r"(cbar) : "memory");
}
__device__ __forceinline__ void bulk_commit() { asm volatile("cp.async.bulk.commit_group;" ::: "memory"); }
__device__ __forceinline__ void bulk_wait0() { asm volatile("cp.async.bulk.wait_group 0;" ::: "memory"); }
__device__ __forceinline__ void fence_async_smem() { asm volatile("fence.proxy.async.shared::cta;" ::: "memory"); }
__device__ __forceinline__ void wg_fence() { asm volatile("wgmma.fence.sync.aligned;" ::: "memory"); }
__device__ __forceinline__ void wg_commit() { asm volatile("wgmma.commit_group.sync.aligned;" ::: "memory"); }
template <int N> __device__ __forceinline__ void wg_wait() { asm volatile("wgmma.wait_group.sync.aligned %0;" ::"n"(N) : "memory"); }
template <int R> __device__ __forceinline__ void reg_alloc() { asm volatile("setmaxnreg.inc.sync.aligned.u32 %0;" ::"n"(R)); }
template <int R> __device__ __forceinline__ void reg_dealloc() { asm volatile("setmaxnreg.dec.sync.aligned.u32 %0;" ::"n"(R)); }
__device__ __forceinline__ void cluster_bar() { asm volatile("barrier.cluster.arrive.relaxed;\nbarrier.cluster.wait;" ::: "memory"); }
template <int ID> __device__ __forceinline__ void nb_sync(int n) { asm volatile("barrier.sync %0, %1;" ::"n"(ID), "r"(n) : "memory"); }
template <int ID> __device__ __forceinline__ void nb_arrive(int n) { asm volatile("barrier.arrive %0, %1;" ::"n"(ID), "r"(n) : "memory"); }
__device__ __forceinline__ int fresh_tid() { int t; asm volatile("mov.u32 %0, %%tid.x;" : "=r"(t)); return t; }
__device__ __forceinline__ void sched_fence(uint32_t z) { asm volatile("{\n.reg .pred p;\nsetp.ne.u32 p, %0, 0;\nLAB_S:\n@p nanosleep.u32 0;\n@p bra LAB_S;\n}\n" ::"r"(z) : "memory"); }
__device__ __forceinline__ float rsq(float x) { float y; asm("rsqrt.approx.ftz.f32 %0, %1;" : "=f"(y) : "f"(x)); return y; }
__device__ __forceinline__ int opq(int v) { asm volatile("" : "+r"(v)); return v; }
struct True { static constexpr bool value = true; };
struct False { static constexpr bool value = false; };
template <int N> __device__ __forceinline__ void fence_regs(float (&d)[N]) {
#pragma unroll
  for (int i = 0; i < N; i++) asm volatile("" : "+f"(d[i])::"memory");
}
__device__ __forceinline__ uint64_t mkdesc(uint32_t addr, uint32_t lbo, uint32_t sbo) {
  return (uint64_t)((addr & 0x3FFFF) >> 4) | ((uint64_t)(lbo >> 4) << 16) | ((uint64_t)(sbo >> 4) << 32) | (1ull << 62);
}
__device__ __forceinline__ uint64_t mkdesc_vec(uint32_t addr, uint32_t sbo) { return (uint64_t)((addr & 0x3FFFF) >> 4) | ((uint64_t)(sbo >> 4) << 32); }
__device__ __forceinline__ void sts16(uint32_t a, uint32_t v) { asm volatile("st.shared.u16 [%0], %1;" ::"r"(a), "h"((uint16_t)v) : "memory"); }
__device__ __forceinline__ uint32_t pack2(float lo, float hi) { uint32_t r; asm("cvt.rn.bf16x2.f32 %0, %1, %2;" : "=r"(r) : "f"(hi), "f"(lo)); return r; }
__device__ __forceinline__ float bf_lo(uint32_t v) { return __uint_as_float(v << 16); }
__device__ __forceinline__ float bf_hi(uint32_t v) { return __uint_as_float(v & 0xffff0000u); }
__device__ __forceinline__ void stsm4(uint32_t a, uint32_t r0, uint32_t r1, uint32_t r2, uint32_t r3) {
  asm volatile("stmatrix.sync.aligned.m8n8.x4.shared.b16 [%0], {%1, %2, %3, %4};" ::"r"(a), "r"(r0), "r"(r1), "r"(r2), "r"(r3) : "memory");
}
__device__ __forceinline__ void stsm4t(uint32_t a, uint32_t r0, uint32_t r1, uint32_t r2, uint32_t r3) {
  asm volatile("stmatrix.sync.aligned.m8n8.x4.trans.shared.b16 [%0], {%1, %2, %3, %4};" ::"r"(a), "r"(r0), "r"(r1), "r"(r2), "r"(r3) : "memory");
}
__device__ __forceinline__ void ldsm4(uint32_t a, uint32_t& r0, uint32_t& r1, uint32_t& r2, uint32_t& r3) {
  asm volatile("ldmatrix.sync.aligned.m8n8.x4.shared.b16 {%0, %1, %2, %3}, [%4];" : "=r"(r0), "=r"(r1), "=r"(r2), "=r"(r3) : "r"(a) : "memory");
}
__device__ __forceinline__ void ldsm4t(uint32_t a, uint32_t& r0, uint32_t& r1, uint32_t& r2, uint32_t& r3) {
  asm volatile("ldmatrix.sync.aligned.m8n8.x4.trans.shared.b16 {%0, %1, %2, %3}, [%4];" : "=r"(r0), "=r"(r1), "=r"(r2), "=r"(r3) : "r"(a) : "memory");
}
__device__ __forceinline__ void mma16816(float (&c)[4], uint32_t a0, uint32_t a1, uint32_t a2, uint32_t a3, uint32_t b0, uint32_t b1) {
  asm volatile("mma.sync.aligned.m16n8k16.row.col.f32.bf16.bf16.f32 {%0, %1, %2, %3}, {%4, %5, %6, %7}, {%8, %9}, {%0, %1, %2, %3};"
    : "+f"(c[0]), "+f"(c[1]), "+f"(c[2]), "+f"(c[3]) : "r"(a0), "r"(a1), "r"(a2), "r"(a3), "r"(b0), "r"(b1));
}
__device__ __forceinline__ void sts128(uint32_t a, uint32_t r0, uint32_t r1, uint32_t r2, uint32_t r3) {
  asm volatile("st.shared.v4.b32 [%0], {%1, %2, %3, %4};" ::"r"(a), "r"(r0), "r"(r1), "r"(r2), "r"(r3) : "memory");
}
__device__ __forceinline__ void lds128(uint32_t a, uint32_t& r0, uint32_t& r1, uint32_t& r2, uint32_t& r3) {
  asm volatile("ld.shared.v4.b32 {%0, %1, %2, %3}, [%4];" : "=r"(r0), "=r"(r1), "=r"(r2), "=r"(r3) : "r"(a) : "memory");
}
__device__ __forceinline__ float2 lds64f(uint32_t a) { float2 v; asm volatile("ld.shared.v2.f32 {%0, %1}, [%2];" : "=f"(v.x), "=f"(v.y) : "r"(a) : "memory"); return v; }
__device__ __forceinline__ float4 lds128f(uint32_t a) { float4 v; asm volatile("ld.shared.v4.f32 {%0, %1, %2, %3}, [%4];" : "=f"(v.x), "=f"(v.y), "=f"(v.z), "=f"(v.w) : "r"(a) : "memory"); return v; }
__device__ __forceinline__ void sts64f(uint32_t a, float x, float y) { asm volatile("st.shared.v2.f32 [%0], {%1, %2};" ::"r"(a), "f"(x), "f"(y) : "memory"); }
__device__ __forceinline__ float lds32f(uint32_t a) { float v; asm volatile("ld.shared.f32 %0, [%1];" : "=f"(v) : "r"(a) : "memory"); return v; }
__device__ __forceinline__ void sts32f(uint32_t a, float x) { asm volatile("st.shared.f32 [%0], %1;" ::"r"(a), "f"(x) : "memory"); }
__device__ __forceinline__ void stat_st(uint2* p, float sum, float sq, uint32_t tag) {
  const float mean = sum * (1.f / 128), m2 = fmaxf(fmaf(-mean, sum, sq), 0.f);
  const uint32_t a = ((__float_as_uint(mean) + 8u) & ~15u) | (tag & 15u), b = ((__float_as_uint(m2) + 8u) & ~15u) | (tag & 15u);
  asm volatile("{\n.reg .b64 x;\nmov.b64 x, {%1, %2};\nst.relaxed.gpu.global.b64 [%0], x;\n}\n" ::"l"(p), "r"(a), "r"(b) : "memory");
}
__device__ __forceinline__ void stat_ld2(const uint2* p, uint32_t (&v)[4]) {
  asm volatile("{\n.reg .b64 x, y;\nld.relaxed.gpu.global.v2.b64 {x, y}, [%4];\nmov.b64 {%0, %1}, x;\nmov.b64 {%2, %3}, y;\n}\n"
    : "=r"(v[0]), "=r"(v[1]), "=r"(v[2]), "=r"(v[3]) : "l"(p) : "memory");
}
__device__ __forceinline__ float untag(uint32_t v) { return __uint_as_float(v & ~15u); }
__device__ __forceinline__ void ll_st3(uint4* p, uint32_t a, uint32_t b, uint32_t c, uint32_t tag) {
  asm volatile("{\n.reg .b64 x, y;\n.reg .b128 z;\nmov.b64 x, {%1, %2};\nmov.b64 y, {%3, %4};\nmov.b128 z, {x, y};\nst.relaxed.gpu.global.b128 [%0], z;\n}\n"
    ::"l"(p), "r"(a), "r"(b), "r"(c), "r"(tag) : "memory");
}
__device__ __forceinline__ uint32_t ll_ld3(const uint4* p, uint32_t& a, uint32_t& b, uint32_t& c, uint32_t tag) {
  uint32_t t;
  asm volatile("{\n.reg .b64 x, y;\n.reg .b128 z;\nld.relaxed.gpu.global.b128 z, [%4];\nmov.b128 {x, y}, z;\nmov.b64 {%0, %1}, x;\nmov.b64 {%2, %3}, y;\n}\n"
    : "=r"(a), "=r"(b), "=r"(c), "=r"(t) : "l"(p) : "memory");
  return t ^ tag;
}
__device__ __forceinline__ void halo_send(uint4* p, uint32_t a, const uint32_t (&tg)[6]) {
  asm volatile("{\n.reg .b64 x<6>, y<6>, w<2>;\n.reg .b32 c<4>;\n.reg .b128 z<6>;\n"
    "ld.shared.b64 w0, [%1+1536];\nld.shared.b64 w1, [%1+1792];\n"
    "ld.shared.b64 x0, [%1];\nld.shared.b64 x1, [%1+256];\nld.shared.b64 x2, [%1+512];\n"
    "ld.shared.b64 x3, [%1+768];\nld.shared.b64 x4, [%1+1024];\nld.shared.b64 x5, [%1+1280];\n"
    "mov.b64 {c0, c1}, w0;\nmov.b64 {c2, c3}, w1;\n"
    "mov.b64 y0, {c0, %2};\nmov.b64 y1, {c1, %3};\nmov.b64 y2, {c2, %4};\nmov.b64 y3, {c3, %5};\nmov.b64 y4, {%6, %6};\nmov.b64 y5, {%7, %7};\n"
    "mov.b128 z0, {x0, y0};\nmov.b128 z1, {x1, y1};\nmov.b128 z2, {x2, y2};\nmov.b128 z3, {x3, y3};\nmov.b128 z4, {x4, y4};\nmov.b128 z5, {x5, y5};\n"
    "st.relaxed.gpu.global.b128 [%0], z0;\nst.relaxed.gpu.global.b128 [%0+512], z1;\nst.relaxed.gpu.global.b128 [%0+1024], z2;\n"
    "st.relaxed.gpu.global.b128 [%0+1536], z3;\nst.relaxed.gpu.global.b128 [%0+2048], z4;\nst.relaxed.gpu.global.b128 [%0+2560], z5;\n}\n"
    ::"l"(p), "r"(a), "r"(tg[0]), "r"(tg[1]), "r"(tg[2]), "r"(tg[3]), "r"(tg[4]), "r"(tg[5]) : "memory");
}
template <int N> __device__ __forceinline__ void copy_out(uint8_t* dst, uint32_t src, int stride) {
  uint4 v[N];
#pragma unroll
  for (int k = 0; k < N; k++) lds128(src + k * stride, v[k].x, v[k].y, v[k].z, v[k].w);
#pragma unroll
  for (int k = 0; k < N; k++) asm volatile("st.global.v4.b32 [%0], {%1, %2, %3, %4};" ::"l"(dst + k * stride), "r"(v[k].x), "r"(v[k].y), "r"(v[k].z), "r"(v[k].w) : "memory");
}
__device__ __forceinline__ void warp_store(uint8_t* dst, uint32_t src, int bytes, uint32_t delay, uint32_t pace) {
  __nanosleep(delay);
#pragma unroll 1
  for (int o = 0; o < bytes; o += 2048) {
    if (pace) __nanosleep(pace);
    uint4 v[4];
#pragma unroll
    for (int k = 0; k < 4; k++) lds128(src + o + k * 512, v[k].x, v[k].y, v[k].z, v[k].w);
#pragma unroll
    for (int k = 0; k < 4; k++) asm volatile("st.global.v4.b32 [%0], {%1, %2, %3, %4};" ::"l"(dst + o + k * 512), "r"(v[k].x), "r"(v[k].y), "r"(v[k].z), "r"(v[k].w) : "memory");
  }
  __syncwarp();
}
__device__ __forceinline__ uint32_t clock32() { uint32_t t; asm volatile("mov.u32 %0, %%clock;" : "=r"(t)); return t; }
__device__ __forceinline__ void flag_set(uint32_t* p, uint32_t bit) { asm volatile("red.release.gpu.global.xor.b32 [%0], %1;" ::"l"(p), "r"(bit) : "memory"); }
__device__ __forceinline__ void flag_wait(const uint32_t* p, uint32_t inv, uint32_t need, uint32_t& ready) {
  if ((ready & need) == need) return;
  uint32_t n = 0;
  do {
    asm volatile("ld.relaxed.gpu.global.b32 %0, [%1];" : "=r"(ready) : "l"(p) : "memory");
    ready = __shfl_sync(0xffffffffu, ready, 0) ^ inv;
  } while ((ready & need) != need && ++n < SPIN_MAX);
  asm volatile("fence.acquire.gpu;\nfence.proxy.async.global;" ::: "memory");
}
__device__ __forceinline__ bool elect_one() {
  uint32_t p;
  asm volatile("{\n.reg .pred P;\nelect.sync _|P, 0xffffffff;\nselp.u32 %0, 1, 0, P;\n}\n" : "=r"(p));
  return p;
}
__device__ __forceinline__ float gelu_half(float hx) {
  const float y = hx * fmaf(hx * hx, 8.f * 0.0356774081f, 2.f * 0.7978845608f);
  float th;
  asm("tanh.approx.f32 %0, %1;" : "=f"(th) : "f"(y));
  return fmaf(hx, th, hx);
}
__device__ __forceinline__ float ex2(float x) { float y; asm("ex2.approx.ftz.f32 %0, %1;" : "=f"(y) : "f"(x)); return y; }

__device__ __forceinline__ void stat_combine(uint32_t am, uint32_t aq, uint32_t bm, uint32_t bq, float pv, float& mean, float& var) {
  const float d0 = untag(am) - pv, d1 = untag(bm) - pv;
  float s = d0 + d1, q = fmaf(fmaf(d0, d0, d1 * d1), 128.f, untag(aq) + untag(bq));
  s += __shfl_xor_sync(0xffffffffu, s, 8); q += __shfl_xor_sync(0xffffffffu, q, 8);
  s += __shfl_xor_sync(0xffffffffu, s, 16); q += __shfl_xor_sync(0xffffffffu, q, 16);
  s *= 0.125f;
  mean = pv + s;
  var = fmaxf(fmaf(-s, s, q * (1.f / D_)), 0.f);
}

__device__ __forceinline__ void attn_probs(const uint32_t* q0, const uint32_t* q1,
                                           const uint32_t* k0, const uint32_t* k1, const uint32_t* k2, const uint32_t* k3,
                                           float sc0, float sc1, bool first, bool e, bool zneg, uint32_t (&pr)[6], float (&l)[2]) {
  float s[4][4];
#pragma unroll
  for (int n = 0; n < 4; n++) {
    const uint32_t* k = n == 0 ? k0 : n == 1 ? k1 : n == 2 ? k2 : k3;
    s[n][0] = s[n][1] = s[n][2] = s[n][3] = 0.f;
    mma16816(s[n], q0[0], q1[0], q0[1], q1[1], k[0], k[1]);
    mma16816(s[n], q0[2], q1[2], q0[3], q1[3], k[2], k[3]);
  }
  const float MASKED = -1.0e9f * 1.4426950409f;
  float a0 = (e ? s[1][1] : s[1][0]) * sc0;
  float b0 = (zneg ? (e ? s[0][1] : s[0][0]) : (e ? s[2][1] : s[2][0])) * sc0;
  float a1 = (e ? s[2][3] : s[2][2]) * sc1;
  float b1 = (zneg ? (e ? s[1][3] : s[1][2]) : (e ? s[3][3] : s[3][2])) * sc1;
  if (first) { a0 = MASKED; if (zneg) { b0 = MASKED; b1 = MASKED; } }
  float m0 = fmaxf(a0, b0), m1 = fmaxf(a1, b1);
  m0 = fmaxf(m0, __shfl_xor_sync(0xffffffffu, m0, 1)); m1 = fmaxf(m1, __shfl_xor_sync(0xffffffffu, m1, 1));
  m0 = fmaxf(m0, __shfl_xor_sync(0xffffffffu, m0, 2)); m1 = fmaxf(m1, __shfl_xor_sync(0xffffffffu, m1, 2));
  a0 = ex2(a0 - m0); b0 = ex2(b0 - m0); a1 = ex2(a1 - m1); b1 = ex2(b1 - m1);
  l[0] = a0 + b0; l[1] = a1 + b1;
  const int sh = e ? 16 : 0;
  const uint32_t pa0 = pack2(a0, 0.f) << sh, pb0 = pack2(b0, 0.f) << sh, pa1 = pack2(a1, 0.f) << sh, pb1 = pack2(b1, 0.f) << sh;
  pr[0] = zneg ? pb0 : 0u; pr[1] = pa0; pr[2] = zneg ? 0u : pb0;
  pr[3] = zneg ? pb1 : 0u; pr[4] = pa1; pr[5] = zneg ? 0u : pb1;
}
__device__ __forceinline__ void attn_pv(const uint32_t (&pr)[6], const uint32_t* vh, const uint32_t* v, float (&o)[4][4]) {
#pragma unroll
  for (int dt = 0; dt < 4; dt++) {
    o[dt][0] = o[dt][1] = o[dt][2] = o[dt][3] = 0.f;
    mma16816(o[dt], pr[0], 0u, pr[1], pr[3], vh[2 * dt], vh[2 * dt + 1]);
    mma16816(o[dt], pr[2], pr[4], 0u, pr[5], v[2 * dt], v[2 * dt + 1]);
  }
}

#define SF 12
#define SLICE 0
#define ATT 22
#define COVER 2
#define S2S 0
#define WGATE 1
#define HALO_A_NS 300
#define H1D 900
#define U0D 300
#define U2D 3000
#define X1D 1200
#define PACE 150
#define LEAD1 3
#define LEAD2 3
#define EARLY 0
#define LEAD3 0
#define DIRECT 7
#define HALO_NS 0
#define STAT_CLK 150
__global__ void __cluster_dims__(2, 1, 1) __launch_bounds__(384, 1) fused_kernel(const __grid_constant__ Params P) {
  extern __shared__ __align__(1024) uint8_t smem_raw[];
  const uint32_t sb = smem_u32(smem_raw);
  const uint32_t bars = sb + OFF_BAR;
  const int tid = threadIdx.x;
  const int wu = __shfl_sync(0xffffffffu, tid >> 5, 0), wg = wu >> 2;
  const int r = blockIdx.x & 1, cl = blockIdx.x >> 1;
  int grp, slt;
  if (cl < 4) { grp = 0; slt = 4 + cl; }
  else if (cl < 36) { grp = (cl - 4) & 7; slt = (cl - 4) >> 3; }
  else { grp = 1 + (cl - 36) % 7; slt = 4 + (cl - 36) / 7; }
#define MAP 0
  const int m = grp, j = slt;
  const int i = 2 * m + r;
  auto BAR = [&](int k) { return bars + 8 * k; };

  auto kb1 = [&](int n) { const int h = n >= 9, t = n - 2 - 7 * h; return n < 2 ? 2 * j + n : 2 * (t + (t >= j)) + h; };
  if (wu == 8) {
    if (elect_one()) {
      asm volatile("prefetch.tensormap [%0];" ::"l"(&P.x0) : "memory");
      asm volatile("prefetch.tensormap [%0];" ::"l"(&P.wqkv) : "memory");
#pragma unroll
      for (int k = 0; k < 6; k++) mbar_init(BAR(k < 4 ? F1 + k : XF + k - 4), 1);
      asm volatile("fence.mbarrier_init.release.cluster;" ::: "memory");
      fence_async_smem();
    }
    __syncwarp();
  } else if (wu == 0) {
    if (elect_one()) {
#pragma unroll
      for (int k = E1; k < 64; k++) {
        int cnt = 1;
        if (k < F2 || (k >= E2 && k < F3) || (k >= E3 && k < F4) || (k >= E4 && k < JOB) || k == JOB + 2 || k == JOB + 3) cnt = 4;
        else if ((k >= JOB && k < RD) || k == CSJ) cnt = 8;
        else if ((k >= RD && k < RD + 4) || k == STD || k == STAT || k >= HALO) cnt = 2;
        if (k != XF && k != XF + 1) mbar_init(BAR(k), cnt);
      }
      asm volatile("fence.mbarrier_init.release.cluster;" ::: "memory");
      fence_async_smem();
    }
    __syncwarp();
  }
  auto load_tag = [&]() { uint32_t t; asm volatile("ld.relaxed.gpu.global.u32 %0, [%1];" : "=r"(t) : "l"(&gEpoch) : "memory"); return t + 1; };
  TS(0);
  if (wu == 8) nb_arrive<NB_INIT>(384); else nb_sync<NB_INIT>(384);
  asm volatile("barrier.cluster.arrive.relaxed;" ::: "memory");

  if (wg == 2) {
    reg_dealloc<40>();
    if (wu == 8) {
    if (elect_one()) {
#pragma unroll 1
      for (int u = 0; u < 4; u++) {
        const int kb = kb1(u);
        if (u < 2) { mbar_expect(BAR(XF + u), 16384); tma2d(sb + OFF_X + u * 16384, &P.x0, BAR(XF + u), kb * 64, 128 * i); }
        mbar_expect(BAR(F1 + u), u < 2 ? 24576 : 40960);
        tma3d(sb + slot1(u) + 16384, &P.wqkv, BAR(F1 + u), 128 * j, kb * 64, 0);
        tma3d(sb + slot1(u) + 28672, &P.wqkv, BAR(F1 + u), 128 * j, kb * 64 + 32, 0);
        if (u >= 2) tma2d(sb + slot1(u), &P.x0, BAR(F1 + u), kb * 64, 128 * i);
      }
    }
    __syncwarp();
    }
    asm volatile("barrier.cluster.wait;" ::: "memory");
    auto kb3 = [&](int n) { const int h = n >= 17, t = S2S ? n - 3 - 14 * h : n - 2 - 15 * h; return n < 2 ? 2 * i + n : (n == (S2S ? 2 : 16) || n == 31) ? 2 * (i ^ 1) + h : 2 * ((2 * m + 2 + t) & 15) + h; };
    auto kb2 = [&](int n) { return n < 8 ? 2 * n : n == 8 ? 2 * j + 1 : 2 * (n - 9 + (n - 9 >= j)) + 1; };
    if (wu == 8) {
#pragma unroll 1
      for (int L = 0; L < 2; L++) {
#pragma unroll 1
        for (int u = L ? 0 : 4; u < 32; u++) {
          const int v = (L && u >= 2 && u < 18) ? (u < 4 ? u + 14 : u - 2) : u;
          const int p = u & 3, ab = v >> 4, nn = v & 15;
          if (u >= 4) mbar_wait(BAR(E1 + p), ((u >> 2) - 1) & 1);
          else mbar_wait(BAR(E4 + (u == 3 ? 0 : u + 3)), u == 3);
          if (elect_one()) {
            mbar_expect(BAR(F1 + p), nn < 2 ? 24576 : 40960);
            tma3d_mc(sb + slot1(p) + 16384 + r * 12288, &P.wqkv, BAR(F1 + p), 128 * j + 64 * ab, kb1(nn) * 64 + 32 * r, 0);
          }
        }
        int p = 0; uint32_t par = L ? 0x1e : 0;
#pragma unroll 1
        for (int n = 0; n < 16; n++) {
          if (n >= 5) { mbar_wait(BAR(E2 + p), (par >> p) & 1); par ^= 1u << p; }
          else if (n < 4) mbar_wait(BAR(E1 + n), 1);
          if (elect_one()) {
            mbar_expect(BAR(F2 + p), n == 8 ? 16384 : 32768);
            tma2d_mc(sb + slot2(p) + 16384 + r * 8192, &P.wo, BAR(F2 + p), 128 * j + 64 * r, kb2(n) * 64);
          }
          if (++p == 5) p = 0;
        }
#pragma unroll 1
        for (int u = 0; u < 32; u++) {
          const int n = u < 4 ? (0x2031 >> (4 * u)) & 3 : u, p = n & 3, kb = kb3(n);
          if (WGATE && n == 4) mbar_wait(BAR(RD + 4), L);
          if (n >= 4) mbar_wait(BAR(E3 + p), ((n >> 2) - 1) & 1);
          else if (n == 1) mbar_wait(BAR(STD + 1), L);
          else if (n == 3) mbar_wait(BAR(E2 + 2), L);
          else if (n == 0) mbar_wait(BAR(E2 + 4), L);
          else mbar_wait(BAR(E2 + 0), 1);
          if (elect_one()) {
            mbar_expect(BAR(F3 + p), n < 2 ? 32768 : 49152);
            tma3d(sb + slot3(p) + 16384, &P.w1, BAR(F3 + p), 0, kb * 64, 7 * m + 4 * r);
            tma3d(sb + slot3(p) + 40960, &P.w1h, BAR(F3 + p), 0, kb * 64, 14 * m + 6 + r);
          }
        }
#pragma unroll 1
        for (int n = 0; n < 6; n++) {
          if (n < 3) mbar_wait(BAR(E3 + n), 1);
          else if (n == 4) mbar_wait(BAR(E3 + 3), 1);
          if (elect_one()) {
            mbar_expect(BAR(F4 + n), n < 3 ? 16384 : 32768);
            tma3d(sb + slot4(n), &P.w2, BAR(F4 + n), 0, (n < 3 ? 7 * m + 4 * r + (n == 2 ? 0 : n + 1) : 7 * ((m + n - 2) & 7) + 3) * 64, 2 * i);
          }
        }
        p = 0; par = L ? 0x3c : 0;
        auto g4w = [&](int kb) {
          mbar_wait(BAR(E4 + p), (par >> p) & 1); par ^= 1u << p;
          if (elect_one()) {
            mbar_expect(BAR(F4 + p), 32768);
            tma3d(sb + slot4(p), &P.w2, BAR(F4 + p), 0, kb * 64, 2 * i);
          }
          if (++p == 6) p = 0;
        };
#pragma unroll 1
        for (int t = 4; t < 9; t++) g4w(7 * ((m + t) & 7) + 3);
#pragma unroll 1
        for (int c = 0; c < 3; c++)
#pragma unroll 1
          for (int t = 0; t < 15; t++) { const int ii = t < 14 ? (2 * m + 2 + t) & 15 : i ^ 1; g4w(((7 * ii + 1) >> 1) + c); }
      }
    } else if (wu == 9) {
      uint32_t inv = 0;
#pragma unroll 1
      for (int L = 0; L < 2; L++) {
        uint32_t ready = 0;
#pragma unroll 1
        for (int u = 4; u < 32; u++) {
          const int p = u & 3, nn = (L && u < 18 ? u - 2 : u) & 15, kb = kb1(nn);
          if (nn < 2) continue;
          if (L && u < 12) mbar_wait(BAR(F1 + p), u >> 3);
          if (u >= 4 + 4 * L) mbar_wait(BAR(E1 + p), ((u >> 2) - 1) & 1);
          if (L) {
            flag_wait(gFlag[0][0][i], inv, 1u << kb, ready);
            if (elect_one()) bulk_ld(sb + slot1(p), gXB + (i * 16 + kb) * 16384, 16384, BAR(F1 + p));
          } else if (elect_one()) tma2d(sb + slot1(p), &P.x0, BAR(F1 + p), kb * 64, 128 * i);
        }
        ready = 0;
        if (L == 0) inv = (__shfl_sync(0xffffffffu, load_tag(), 0) & 1) - 1;
        int p = 0; uint32_t par = L ? 0x1e : 0;
#pragma unroll 1
        for (int n = 0; n < 16; n++) {
          const int hp = kb2(n);
          if (n == 8) { par ^= 8; p = 4; continue; }
          if (n >= 5) { mbar_wait(BAR(E2 + p), (par >> p) & 1); par ^= 1u << p; }
          else if (n < 4) mbar_wait(BAR(E1 + n), 1);
          flag_wait(gFlag[L][1][i], inv, 1u << hp, ready);
          if (n == 9) ST(4);
          if (elect_one()) bulk_ld(sb + slot2(p), gOB + (i * 16 + hp) * 16384, 16384, BAR(F2 + p));
          if (++p == 5) p = 0;
        }
        ready = 0;
        mbar_wait(BAR(E2 + 0), 1);
#pragma unroll 1
        for (int n = 2 + S2S; n < 32; n++) {
          const int p = n & 3, kb = kb3(n);
          if (n > 3) mbar_wait(BAR(E3 + p), ((n >> 2) - 1) & 1);
          flag_wait(gFlag[L][2][j], inv, 1u << kb, ready);
          if (n == 2 + S2S) ST(12);
          if (elect_one()) {
            const uint8_t* src = gHB + (j * 32 + kb) * 16384;
            if (n < 31 && (S2S || n != 16)) bulk_ld_mc(sb + slot3(p) + r * 8192, src + r * 8192, 8192, BAR(F3 + p));
            else bulk_ld(sb + slot3(p), src, 16384, BAR(F3 + p));
          }
        }
        ready = 0; p = 3; par = L ? 0x3c : 0;
        mbar_wait(BAR(E3 + 3), 1);
#pragma unroll 1
        for (int t = 0; t < 8; t++) {
          const int mm = (m + t + 1) & 7;
          if (t == 2 || t == 5) mbar_wait(BAR(RD + (t == 2 ? 3 : 2)), L);
          if (t >= 3) { mbar_wait(BAR(E4 + p), (par >> p) & 1); par ^= 1u << p; }
          flag_wait(gFlag[L][6][j], inv, 3u << (2 * mm), ready);
          if (t == 0) ST(20);
          if (elect_one()) bulk_ld_mc(sb + slot4(p) + 16384 + r * 8192, gUB + (j * 56 + 48 + mm) * 16384 + r * 8192, 8192, BAR(F4 + p));
          if (++p == 6) p = 0;
        }
#pragma unroll 1
        for (int c = 0; c < 3; c++) {
          ready = 0;
#pragma unroll 1
          for (int t = 0; t < 15; t++) {
            const int ii = t < 14 ? (2 * m + 2 + t) & 15 : i ^ 1;
            mbar_wait(BAR(E4 + p), (par >> p) & 1); par ^= 1u << p;
            flag_wait(gFlag[L][3 + c][j], inv, 1u << ii, ready);
            if (elect_one()) {
              const uint8_t* src = gUB + (j * 56 + 16 * c + ii) * 16384;
              if (t < 14) bulk_ld_mc(sb + slot4(p) + 16384 + r * 8192, src + r * 8192, 8192, BAR(F4 + p));
              else bulk_ld(sb + slot4(p) + 16384, src, 16384, BAR(F4 + p));
            }
            if (++p == 6) p = 0;
          }
        }
      }
    } else {
      const int h = wu - 10, i0 = i, j0 = j;
      {
      const uint32_t tag = load_tag();
      int lane = tid & 31, i = i0, j = j0;
#define FRESH asm volatile("" : "+r"(lane), "+r"(i), "+r"(j))
      const uint32_t rs = mapa(sb, r ^ 1), rb = rs + OFF_BAR;
      auto signal = [&](int k) { if (lane == 0) mbar_arrive(BAR(k)); };
      auto drained = [&](int k) { if (lane == 0) { mbar_arrive(BAR(RD + k)); mbar_arrive_cl(rb + 8 * (RD + k)); } };
      auto publish = [&](uint32_t* f, int bit) { if (lane == 0) flag_set(f, 1u << bit); __syncwarp(); };
      for (int c = 32 * h + lane; c < 288; c += 64)
        sts16(sb + OFF_B1 + 2 * c, c >= 224 ? 0u : pack2(0.5f * __bfloat162float(P.b1[c < 192 ? 64 * (7 * m + 4 * r) + c : 64 * (7 * m + 3) + 32 * r + c - 192]), 0.f));
      if (h == 0) sts32f(sb + OFF_CS + 768 + 4 * lane, 0.f);
#pragma unroll 1
      for (int L = 0; L < 2; L++) {
        FRESH;
        if (L == 0) {
          mbar_wait(BAR(CSJ), 0);
          float c0 = 0.f, c1 = 0.f, c2 = 0.f;
          const uint32_t a = sb + OFF_STG + (32 * h + lane) * 4;
#pragma unroll 8
          for (int k = 0; k < 32; k++) { c0 += lds32f(a + k * 784); c1 += lds32f(a + k * 784 + 256); c2 += lds32f(a + k * 784 + 512); }
          ll_st3(&gCS[j][i][32 * h + lane], __float_as_uint(c0), __float_as_uint(c1), __float_as_uint(c2), tag);
          __nanosleep(500);
        }
        FRESH;
        if (L == 0) {
#pragma unroll 1
          for (int ab = 0; ab < 2; ab++) {
            float c0 = 0.f, c1 = 0.f, c2 = 0.f;
#pragma unroll 1
            for (int b4 = 0; b4 < 8; b4 += 4) {
              uint32_t a[4], b[4], c[4], n = 0, bad;
              do {
                bad = 0;
#pragma unroll
                for (int e = 0; e < 4; e++) bad |= ll_ld3(&gCS[j][2 * (b4 + e) + ab][32 * h + lane], a[e], b[e], c[e], tag);
              } while (bad && ++n < SPIN_MAX);
#pragma unroll
              for (int e = 0; e < 4; e++) { c0 += __uint_as_float(a[e]); c1 += __uint_as_float(b[e]); c2 += __uint_as_float(c[e]); }
            }
            const uint32_t a = sb + OFF_CS + ab * 768 + (4 * h + (lane >> 3)) * 32 + (lane & 7) * 2;
            const uint32_t h0 = pack2(c0, 0.f), h1 = pack2(c1, 0.f), h2 = pack2(c2, 0.f);
            sts16(a, h0); sts16(a + 256, h1); sts16(a + 512, h2);
            sts16(a + 16, pack2(c0 - bf_lo(h0), 0.f)); sts16(a + 272, pack2(c1 - bf_lo(h1), 0.f)); sts16(a + 528, pack2(c2 - bf_lo(h2), 0.f));
            fence_async_smem();
            __syncwarp();
            if (ab == 0) signal(STAT);
          }
        }
#pragma unroll 1
        for (int ab = 0; ab < 2; ab++) {
          FRESH;
          uint32_t v[18], tg[6];
          const uint32_t xs = sb + OFF_STG + h * 16384 + lane * 8;
          uint4* hp = &gHalo[L][i][j][6 * h][lane];
#pragma unroll
          for (int c = 0; c < 6; c++) { tg[c] = (2 * tag + ab) * 8 + c; asm volatile("" : "+r"(tg[c])); }
          asm volatile("" : "+l"(hp));
          mbar_wait(BAR(FOLD + ab), L);
          if (ab && h == 0) ST(6);
          if (i < 15) {
            halo_send(hp, xs, tg);
          }
          if (ab && h == 0) ST(26);
          if (i > 0) {
            if (!ab) __nanosleep(HALO_A_NS);
            uint32_t n = 0, bad;
            do {
              bad = 0;
#pragma unroll
              for (int c = 0; c < 6; c++) bad |= ll_ld3(hp + c * 32 - 8 * 12 * 32, v[3 * c], v[3 * c + 1], v[3 * c + 2], (2 * tag + ab) * 8);
              if (ab && h == 0 && n == 0) ST(28);
            } while (bad > 7 && ++n < SPIN_MAX);
            if (ab && h == 0) ST(27);
          } else {
#pragma unroll
            for (int c = 0; c < 18; c++) v[c] = 0u;
          }
#pragma unroll
          for (int c = 0; c < 6; c++) sts64f(xs + c * 256, __uint_as_float(v[3 * c]), __uint_as_float(v[3 * c + 1]));
          sts64f(xs + 1536, __uint_as_float(v[2]), __uint_as_float(v[5]));
          sts64f(xs + 1792, __uint_as_float(v[8]), __uint_as_float(v[11]));
          __syncwarp();
          signal(HALO + ab);
          if (ab && h == 0) ST(7);
          FRESH;
          if (ab == 0 && lane == 0) asm volatile("st.relaxed.gpu.global.u32 [%0], %1;" ::"l"(&gAck[L][i][j][h][0]), "r"(tag) : "memory");
          mbar_wait(BAR(JOB + ab), L);
          if (h == 0) {
            if (ab) ST(1);
            if (lane == 0) { bulk_st(gOB + (i * 16 + 2 * j + ab) * 16384, sb + OFF_STG, 16384); bulk_commit(); bulk_wait0(); }
            signal(STD + ab);
            if (ab) ST(2);
            publish(gFlag[L][1][i], 2 * j + ab);
            if (ab) ST(3);
          } else if (ab == 0) {
            if (i < 15 && lane < 2) {
              uint32_t t, n = 0;
              do { asm volatile("ld.relaxed.gpu.global.u32 %0, [%1];" : "=r"(t) : "l"(&gAck[L][i + 1][j][lane][0]) : "memory"); } while (t != tag && ++n < SPIN_MAX);
            }
            __syncwarp();
            signal(STD);
          }
        }
        FRESH;
        if (h == 0) {
          mbar_wait(BAR(JOB + 2), L);
          ST(9);
          if (!(DIRECT & 1) && lane == 0) { bulk_st(gHB + (j * 32 + 2 * i) * 16384, sb + OFF_X, 16384); bulk_commit(); bulk_wait0(); }
          signal(RD);
          ST(10);
          publish(gFlag[L][2][j], 2 * i);
          ST(11);
          signal(RD + 4);
          nb_arrive<NB_HELP>(64);
        } else {
          mbar_wait(BAR(JOB + 3), L);
          nb_sync<NB_HELP>(64);
          warp_store(gHB + (j * 32 + 2 * i + 1) * 16384 + lane * 16, sb + lane * 16 + OFF_X + 16384, 16384, H1D, PACE);
          signal(RD);
          ST(15);
          publish(gFlag[L][2][j], 2 * i + 1);
        }
        FRESH;
        if (h == 0) {
          mbar_wait(BAR(JOB + 7), L);
          ST(17);
          if (!(DIRECT & 2) && lane == 0) {
            for (int a = 0; a < 2; a++) bulk_st(gUB + (j * 56 + 48 + (i >> 1)) * 16384 + a * 8192 + r * 4096, sb + slot4(5) + 16384 + a * 8192, 4096);
            bulk_commit(); bulk_wait0();
          }
          drained(3);
          ST(18);
          publish(gFlag[L][6][j], i);
          ST(19);
        }
        mbar_wait(BAR(JOB + 6), L);
        if (h == 1) {
          warp_store(gUB + (j * 56 + i) * 16384 + lane * 16, sb + lane * 16 + slot4(2) + 16384, 16384, U0D, 0);
          drained(2); ST(25);
          publish(gFlag[L][3][j], i);
        }
        nb_sync<NB_HELP>(64);
        warp_store(gUB + (j * 56 + 16 + 16 * h + i) * 16384 + lane * 16, sb + lane * 16 + OFF_X + h * 16384, 16384, h ? U2D : 0, PACE);
        ST(23 + h);
        signal(RD + 1);
        publish(gFlag[L][4 + h][j], i);
        FRESH;
        mbar_wait(BAR(JOB + 8 + h), L);
        if (L == 0) {
          if (!(DIRECT & 4) && h == 0 && lane == 0) { bulk_st(gXB + (i * 16 + 2 * j) * 16384, sb + OFF_X, 16384); bulk_commit(); bulk_wait0(); }
          __syncwarp();
          nb_sync<NB_HELP>(64);
          if (h == 1) warp_store(gXB + (i * 16 + 2 * j + 1) * 16384 + lane * 16, sb + lane * 16 + OFF_X + 16384, 16384, X1D, 0);
          publish(gFlag[0][0][i], 2 * j + h);
        } else if (lane == 0) {
          tma2d_store(&P.out, sb + OFF_X + h * 16384, 128 * j + 64 * h, 128 * i);
          bulk_commit(); bulk_wait0();
        }
      }
      if (blockIdx.x == 0 && h == 0 && lane == 0) asm volatile("st.relaxed.gpu.global.u32 [%0], %1;" ::"l"(&gEpoch), "r"(tag) : "memory");
      }
    }
    __syncwarp();
    cluster_bar();
  } else {
    reg_alloc<232>();
    asm volatile("barrier.cluster.wait;" ::: "memory");
    const uint32_t rbars = mapa(bars, tid & 1);
    const bool relp = (tid & 127) < 2;
    uint32_t tag;
    asm volatile("ld.relaxed.gpu.global.u32 %0, [%1];" : "=r"(tag) : "l"(&gEpoch + (fresh_tid() >> 10)) : "memory");
    auto release = [&](int k) { if (relp) mbar_arrive_cl(rbars + 8 * k); };
    auto signal = [&](int k) { __syncwarp(); if ((fresh_tid() & 31) == 0) mbar_arrive(BAR(k)); };
#define GEOM const int t7 = fresh_tid() & 127, lane = t7 & 31, w = t7 >> 5, g = lane >> 2, q = lane & 3, \
                       lr = lane & 15, lt = lane >> 4, l7 = lane & 7; (void)w; (void)g; (void)q; (void)lr; (void)lt; (void)l7

#pragma unroll 1
    for (int L = 0; L < 2; L++) {
      float acca[96], accb[96], xa[64], acc3[112];
      float nmean0, nmean1, rstd0, rstd1;
      uint16_t b2a, b2b;
      uint32_t Q[2][8], K[2][8], V[16];
      auto g1_issue = [&](float (&acc)[96], uint32_t a, uint32_t st, auto first) {
        const uint64_t da = mkdesc(a + wg * 8192, 16, 1024), db = mkdesc(st + 16384, 4096, 1024);
        wg_fence();
#pragma unroll
        for (int kk = 0; kk < 4; kk++) {
          const uint64_t b = db + (((kk >> 1) * 12288 + (kk & 1) * 2048) >> 4);
          if (first.value && kk == 0) wgmma_192z<0, 1>(acc, da, b); else wgmma_192<0, 1>(acc, da + kk * 2, b);
        }
        wg_commit();
      };
      auto g1_step = [&](float (&acc)[96], int u, bool rel) {
        const int p = u & 3;
        mbar_wait(BAR(F1 + p), (u >> 2) & 1);
        KB(u);
        g1_issue(acc, sb + slot1(p), sb + slot1(p), False{});
        if (LEAD1 && u == 31 && wg == 1) nb_arrive<NB_LEAD>(256);
        wg_wait<1>();
        if (rel) release(E1 + ((u - 1) & 3));
      };
      auto g1_loop = [&](float (&acc)[96], int u0, int u1, int urel) {
#pragma unroll 1
        for (int u = u0; u < u1; u++) g1_step(acc, u, u > urel);
      };
      auto load_x = [&]() {
        GEOM;
#pragma unroll
        for (int t = 0; t < 16; t += 2) {
          uint32_t v0, v1, v2, v3;
          ldsm4(sb + OFF_X + (t >> 3) * 16384 + (16 * wu + lr) * 128 + ((((t & 7) + lt) ^ l7) << 4), v0, v1, v2, v3);
          xa[4 * t + 0] = bf_lo(v0); xa[4 * t + 1] = bf_hi(v0); xa[4 * t + 2] = bf_lo(v1); xa[4 * t + 3] = bf_hi(v1);
          xa[4 * t + 4] = bf_lo(v2); xa[4 * t + 5] = bf_hi(v2); xa[4 * t + 6] = bf_lo(v3); xa[4 * t + 7] = bf_hi(v3);
        }
      };
      auto stat_publish = [&](float s0, float q0, float s2, float q2, uint32_t tg) {
        GEOM;
        const bool h1 = q & 1;
        float sm = (h1 ? s2 : s0) + __shfl_xor_sync(0xffffffffu, h1 ? s0 : s2, 1);
        float sq = (h1 ? q2 : q0) + __shfl_xor_sync(0xffffffffu, h1 ? q0 : q2, 1);
        sm += __shfl_xor_sync(0xffffffffu, sm, 2); sq += __shfl_xor_sync(0xffffffffu, sq, 2);
        if (q < 2) stat_st(&gST[0][0][0][0][0] + (((L * 16 + opq(i)) * 8 + wu) * 8 + j) * 16 + 2 * g + q, sm, sq, tg);
        return sm;
      };
      auto g1_stats = [&](int u0) {
        GEOM;
        const uint32_t xr = sb + OFF_X + (16 * wu + lr) * 128;
        float s0 = 0.f, q0 = 0.f, s2 = 0.f, q2 = 0.f;
        uint32_t v[8] = {0u, 0u, 0u, 0u, 0u, 0u, 0u, 0u};
#pragma unroll 1
        for (int k = 0; k < 5; k++) {
#pragma unroll
          for (int e = 0; e < 8; e += 2) {
            const float a = bf_lo(v[e]), b = bf_hi(v[e]), c = bf_lo(v[e + 1]), d = bf_hi(v[e + 1]);
            s0 += a + b; q0 = fmaf(a, a, fmaf(b, b, q0)); s2 += c + d; q2 = fmaf(c, c, fmaf(d, d, q2));
          }
          if (k == 4) break;
          const uint32_t o = ((2 * k + lt) ^ l7) << 4;
          ldsm4(xr + o, v[0], v[1], v[2], v[3]);
          ldsm4(xr + o + 16384, v[4], v[5], v[6], v[7]);
          g1_step(acca, u0 + k, true);
        }
        stat_publish(s0, q0, s2, q2, 2 * (tag + 1));
      };
      uint32_t sv0[4], sv1[4];
      auto stat_fetch = [&]() {
        const uint2* sp = &gST[0][0][0][0][0] + ((L * 16 + opq(i)) * 8 + wu) * 128 + 2 * (fresh_tid() & 31);
        stat_ld2(sp, sv0); stat_ld2(sp + 64, sv1);
      };
      auto stat_await = [&](uint32_t tg) {
#pragma unroll 1
        for (uint32_t n = 0; (((sv0[0] ^ tg) | (sv0[2] ^ tg) | (sv1[0] ^ tg) | (sv1[2] ^ tg)) & 15u) && n < SPIN_MAX; n++) stat_fetch();
        __syncwarp();
      };
      auto ln_stats = [&]() {
        GEOM;
        stat_await(2 * (tag + 1));
        float mean0, var0, mean1, var1;
        stat_combine(sv0[0], sv0[1], sv1[0], sv1[1], untag(__shfl_sync(0xffffffffu, sv0[0], l7)), mean0, var0);
        stat_combine(sv0[2], sv0[3], sv1[2], sv1[3], untag(__shfl_sync(0xffffffffu, sv0[2], l7)), mean1, var1);
        nmean0 = -__shfl_sync(0xffffffffu, mean0, g); rstd0 = rsq(__shfl_sync(0xffffffffu, var0, g) + 1e-5f);
        nmean1 = -__shfl_sync(0xffffffffu, mean1, g); rstd1 = rsq(__shfl_sync(0xffffffffu, var1, g) + 1e-5f);
      };
      auto center = [&](float (&acc)[96], int ab) {
        const bool q0 = (fresh_tid() & 3) == 0;
        const uint32_t h0 = pack2(nmean0, nmean0), h1 = pack2(nmean1, nmean1);
        const float l0 = nmean0 - bf_lo(h0), l1 = nmean1 - bf_lo(h1);
        const uint32_t a0 = q0 ? h0 : 0u, a1 = q0 ? h1 : 0u, a2 = q0 ? pack2(l0, l0) : 0u, a3 = q0 ? pack2(l1, l1) : 0u;
        wg_fence();
        wgmma_rs_192(acc, a0, a1, a2, a3, mkdesc_vec(sb + OFF_CS + ab * 768, 32));
      };
      auto frag = [&](float (&acc)[96], int t, uint32_t& p0, uint32_t& p1) {
        if (t >= 8) { p0 = pack2(acc[4 * t] * rstd0, acc[4 * t + 1] * rstd0); p1 = pack2(acc[4 * t + 2] * rstd1, acc[4 * t + 3] * rstd1); }
        else { p0 = pack2(acc[4 * t], acc[4 * t + 1]); p1 = pack2(acc[4 * t + 2], acc[4 * t + 3]); }
      };
      auto fold_v = [&](float (&acc)[96]) {
        GEOM;
        const uint32_t a = sb + OFF_STG + 16384 + ((wu + 1) & 7) * 2048 + lr * 128;
#pragma unroll
        for (int t = 0; t < 8; t += 2) {
          uint32_t p0, p1, p2, p3;
          frag(acc, 16 + t, p0, p1); frag(acc, 17 + t, p2, p3);
          stsm4(a + (((t + lt) ^ l7) << 4), p0, p1, p2, p3);
        }
        __syncwarp();
#pragma unroll
        for (int t = 0; t < 8; t += 2) ldsm4t(a + (((t + lt) ^ l7) << 4), V[2 * t], V[2 * t + 1], V[2 * t + 2], V[2 * t + 3]);
      };
      auto fold_k = [&](float (&acc)[96], int ab) {
        GEOM;
#pragma unroll
        for (int t = 8; t < 16; t++) frag(acc, t, K[0][t - 8], K[1][t - 8]);
        const uint32_t a = sb + OFF_STG + ((wu + 1) & 7) * 2048 + lane * 16;
#pragma unroll
        for (int c = 0; c < 4; c++)
          sts128(a + c * 512, K[c >> 1][4 * (c & 1)], K[c >> 1][4 * (c & 1) + 1], K[c >> 1][4 * (c & 1) + 2], K[c >> 1][4 * (c & 1) + 3]);
        if (wu == 7) signal(FOLD + ab);
      };
      auto fold_q = [&](float (&acc)[96]) {
#pragma unroll
        for (int t = 0; t < 8; t++) frag(acc, t, Q[0][t], Q[1][t]);
      };
      auto attend = [&](int ab, auto drain, auto resume) {
        GEOM;
        nb_sync<NB_BOTH>(256);
        const uint32_t xa_ = sb + OFF_STG + wu * 2048 + lane * 16;
        if (wu == 0) mbar_wait(BAR(HALO + ab), L);
        uint32_t KH[2][8], VH[16];
#pragma unroll
        for (int c = 0; c < 4; c++) {
          lds128(xa_ + c * 512, KH[c >> 1][4 * (c & 1)], KH[c >> 1][4 * (c & 1) + 1], KH[c >> 1][4 * (c & 1) + 2], KH[c >> 1][4 * (c & 1) + 3]);
          ldsm4t(sb + OFF_STG + 16384 + wu * 2048 + lr * 128 + (((2 * c + lt) ^ l7) << 4), VH[4 * c], VH[4 * c + 1], VH[4 * c + 2], VH[4 * c + 3]);
        }
        TS2(11 + ab + 32 * L);
        drain();
        if (SF & 4) sched_fence(P.zero);
        const bool e = g & 1, zneg = (g >> 1) < q, first = (i == 0) && (wu == 0);
        const float qs = 0.17677669530f * 1.4426950409f;
        uint32_t pr[2][6];
        float l[2][2];
#pragma unroll
        for (int hh = 0; hh < 2; hh++)
          attn_probs(&Q[0][4 * hh], &Q[1][4 * hh], &KH[0][4 * hh], &KH[1][4 * hh], &K[0][4 * hh], &K[1][4 * hh], rstd0 * qs, rstd1 * qs, first, e, zneg, pr[hh], l[hh]);
        float o[2][4][4];
#pragma unroll
        for (int hh = 0; hh < 2; hh++) attn_pv(pr[hh], &VH[8 * hh], &V[8 * hh], o[hh]);
        const bool early = (EARLY >> ab) & 1;
        if (early) { sched_fence(P.zero); nb_sync<NB_BOTH>(256); resume(); sched_fence(P.zero); }
#pragma unroll
        for (int hh = 0; hh < 2; hh++) {
          float l0 = l[hh][0], l1 = l[hh][1];
          l0 += __shfl_xor_sync(0xffffffffu, l0, 1); l1 += __shfl_xor_sync(0xffffffffu, l1, 1);
          l0 += __shfl_xor_sync(0xffffffffu, l0, 2); l1 += __shfl_xor_sync(0xffffffffu, l1, 2);
          asm("rcp.approx.ftz.f32 %0, %0;" : "+f"(l0)); asm("rcp.approx.ftz.f32 %0, %0;" : "+f"(l1));
#pragma unroll
          for (int dt = 0; dt < 4; dt += 2)
            stsm4(sb + OFF_STG + (16 * wu + lr) * 128 + (((4 * hh + dt + lt) ^ l7) << 4),
                  pack2(o[hh][dt][0] * l0, o[hh][dt][1] * l0), pack2(o[hh][dt][2] * l1, o[hh][dt][3] * l1),
                  pack2(o[hh][dt + 1][0] * l0, o[hh][dt + 1][1] * l0), pack2(o[hh][dt + 1][2] * l1, o[hh][dt + 1][3] * l1));
        }
        fence_async_smem();
        signal(JOB + ab);
        if (!early) { nb_sync<NB_BOTH>(256); resume(); }
      };

      if (L == 0) mbar_wait(BAR(XF), 0);
      TS(1 + 32 * L);
      mbar_wait(BAR(F1), 0); KB(0);    g1_issue(acca, sb + OFF_X, sb + slot1(0), True{});
      if (L == 0) mbar_wait(BAR(XF + 1), 0);
      mbar_wait(BAR(F1 + 1), 0); KB(1); g1_issue(acca, sb + OFF_X + 16384, sb + slot1(1), False{});
      wg_wait<1>(); release(E1 + 0);
      auto g1_bhead = [&](int p) {
        mbar_wait(BAR(F1 + p), 0); KB(p ? 2 : 16); g1_issue(accb, sb + OFF_X, sb + slot1(p), True{});
        if (p) { wg_wait<1>(); release(E1 + 1); }
        mbar_wait(BAR(F1 + p + 1), 0); KB(p ? 3 : 17); g1_issue(accb, sb + OFF_X + 16384, sb + slot1(p + 1), False{});
        wg_wait<1>(); release(E1 + p);
      };
      if (L == 0) {
        GEOM;
        const bf16* wp = P.wqkv_p + ((128 * opq(m) + 16 * wg + (t7 >> 3)) * 3072 + 128 * opq(j) + 64 * r + l7 * 8);
        const uint32_t ca = sb + OFF_STG + (16 * wg + (t7 >> 3)) * 784 + l7 * 32;
#pragma unroll 1
        for (int p = 0; p < 3; p++) {
          uint4 wv[4];
#pragma unroll
          for (int k = 0; k < 4; k++)
            asm volatile("ld.global.nc.v4.u32 {%0, %1, %2, %3}, [%4];" : "=r"(wv[k].x), "=r"(wv[k].y), "=r"(wv[k].z), "=r"(wv[k].w)
                         : "l"(wp + (size_t)k * 32 * 3072 + p * 1024));
          g1_loop(acca, 2 + 2 * p, 4 + 2 * p, 0);
          float cs[8];
#pragma unroll
          for (int k = 0; k < 4; k++) {
            const uint4 v = wv[k];
            const float t[8] = {bf_lo(v.x), bf_hi(v.x), bf_lo(v.y), bf_hi(v.y), bf_lo(v.z), bf_hi(v.z), bf_lo(v.w), bf_hi(v.w)};
#pragma unroll
            for (int e = 0; e < 8; e++) cs[e] = k ? cs[e] + t[e] : t[e];
          }
          sts128(ca + p * 256, __float_as_uint(cs[0]), __float_as_uint(cs[1]), __float_as_uint(cs[2]), __float_as_uint(cs[3]));
          sts128(ca + p * 256 + 16, __float_as_uint(cs[4]), __float_as_uint(cs[5]), __float_as_uint(cs[6]), __float_as_uint(cs[7]));
        }
        signal(CSJ);
        TS2(17);
        g1_stats(8);
        g1_loop(acca, 12, 14, 0);
        stat_fetch();
        g1_loop(acca, 14, 16, 0);
        ln_stats();
        wg_wait<0>(); release(E1 + 3);
        fence_regs(acca);
        g1_bhead(0);
        mbar_wait(BAR(STAT), 0);
      } else {
        g1_bhead(2);
        g1_stats(4);
        g1_loop(acca, 8, 12, 0);
        stat_fetch();
        g1_loop(acca, 12, 14, 0);
        ln_stats();
        g1_loop(acca, 14, 18, 0);
      }
      center(acca, 0); wg_commit();
      wg_wait<0>(); release(E1 + 1);
      fence_regs(acca);
      fold_v(acca); fold_k(acca, 0); fold_q(acca);
      sched_fence(P.zero);
      g1_loop(accb, 18, ATT, 18);
      attend(0, [&]() { wg_wait<0>(); release(E1 + ((ATT - 1) & 3)); mbar_wait(BAR(F1 + (ATT & 3)), (ATT >> 2) & 1); },
             [&]() { KB(ATT); g1_issue(accb, sb + slot1(ATT & 3), sb + slot1(ATT & 3), False{});
                     mbar_wait(BAR(F1 + ((ATT + 1) & 3)), ((ATT + 1) >> 2) & 1);
                     KB(ATT + 1); g1_issue(accb, sb + slot1((ATT + 1) & 3), sb + slot1((ATT + 1) & 3), False{}); });
      wg_wait<1>(); release(E1 + (ATT & 3));
      TS(3 + 32 * L);
      g1_loop(accb, ATT + 2, ATT + 4, 0);
      load_x();
      fence_regs(xa);
      center(accb, 1);
      g1_loop(accb, ATT + 4, 32 - LEAD1, 0);
      if (LEAD1 && wg == 0) { wg_wait<0>(); release(E1 + ((31 - LEAD1) & 3)); nb_sync<NB_LEAD>(256); }
      g1_loop(accb, 32 - LEAD1, 32, wg == 0 ? 32 - LEAD1 : 0);
      mbar_wait(BAR(STD), L);
      wg_wait<0>(); release(E1 + 3);
      fence_regs(accb);
      TS(4 + 32 * L);
      if (wu == 7) ST(0);
      fold_v(accb); fold_k(accb, 1);
      if (SF & 2) sched_fence(P.zero);
      fold_q(accb);
      TS2(29 + 32 * L);
      {
        auto g2_issue = [&](int p, bool own) {
          const uint32_t st = sb + slot2(p);
          const uint64_t da = mkdesc((own ? sb + OFF_STG : st) + wg * 8192, 16, 1024), db = mkdesc(st + 16384, 8192, 1024);
          wg_fence();
#pragma unroll
          for (int kk = 0; kk < 4; kk++) wgmma_128<0, 1>(xa, da + kk * 2, db + kk * 128);
          wg_commit();
        };
        uint32_t par = L ? 0x1e : 0;
        int p = 0, pp = 0;
        auto g2_loop = [&](int n0, int n1, int nrel) {
#pragma unroll 1
          for (int n = n0; n < n1; n++) {
            mbar_wait(BAR(F2 + p), (par >> p) & 1);
            KB(32 + n);
            if (n == 9 && wu == 0) ST(5);
            par ^= 1u << p;
            g2_issue(p, n == 8);
            if (LEAD2 && n == 15 && wg == 0) nb_arrive<NB_LEAD>(256);
            wg_wait<1>();
            if (n > nrel) release(E2 + pp);
            pp = p; if (++p == 5) p = 0;
          }
        };
        g2_loop(0, COVER, 0);
        attend(1, [&]() { wg_wait<0>(); release(E2 + COVER - 1); mbar_wait(BAR(F2 + COVER), (par >> COVER) & 1); },
               [&]() { KB(32 + COVER); g2_issue(COVER, false);
                       mbar_wait(BAR(F2 + COVER + 1), (par >> (COVER + 1)) & 1);
                       KB(33 + COVER); g2_issue(COVER + 1, false); });
        wg_wait<1>(); release(E2 + COVER);
        par ^= 3u << COVER; pp = COVER + 1; p = (COVER + 2) % 5;
        TS(30 + 32 * L);
        {
          const bf16* bp = P.b2 + (128 * opq(i) + 16 * wu + ((fresh_tid() & 31) >> 2));
          asm volatile("ld.global.nc.u16 %0, [%1];" : "=h"(b2a) : "l"(bp));
          asm volatile("ld.global.nc.u16 %0, [%1];" : "=h"(b2b) : "l"(bp + 8));
        }
        TS2(14 + 32 * L);
        g2_loop(COVER + 2, 8, 0);
        mbar_wait(BAR(JOB + 1), L);
        g2_loop(8, 16 - LEAD2, 0);
        if (LEAD2 && wg == 1) { wg_wait<0>(); release(E2 + pp); nb_sync<NB_LEAD>(256); }
        g2_loop(16 - LEAD2, 16, wg == 1 ? 16 - LEAD2 : 0);
        wg_wait<0>();
        release(E2 + 0);
        fence_regs(xa);
      }
      TS(5 + 32 * L);
      if (wu == 0) ST(8);
      {
        GEOM;
        const uint32_t tg = 2 * (tag + 1) + 1;
        float s0 = 0.f, s1 = 0.f, s2 = 0.f, s3 = 0.f, q0 = 0.f, q1 = 0.f, q2 = 0.f, q3 = 0.f;
#pragma unroll
        for (int t = 0; t < 16; t++) {
          s0 += xa[4 * t]; s1 += xa[4 * t + 1]; s2 += xa[4 * t + 2]; s3 += xa[4 * t + 3];
          q0 = fmaf(xa[4 * t], xa[4 * t], q0); q1 = fmaf(xa[4 * t + 1], xa[4 * t + 1], q1);
          q2 = fmaf(xa[4 * t + 2], xa[4 * t + 2], q2); q3 = fmaf(xa[4 * t + 3], xa[4 * t + 3], q3);
        }
        const float sm = stat_publish(s0 + s1, q0 + q1, s2 + s3, q2 + q3, tg);
        const uint32_t t0 = clock32();
        wg_fence();
        wgmma_rs_224z(acc3, q == 0 ? 0x3f80u : 0u, q == 0 ? 0x3f80u : 0u, 0u, 0u, mkdesc_vec(sb + OFF_B1, 16));
        wg_commit();
        TS2(13 + 32 * L);
        const float pv0 = __shfl_sync(0xffffffffu, sm, 4 * l7) * (1.f / 128), pv1 = __shfl_sync(0xffffffffu, sm, 4 * l7 + 1) * (1.f / 128);
        while (clock32() - t0 < STAT_CLK) {}
        stat_fetch();
        stat_await(tg);
        float r0, m0, r1, m1;
        {
          float mean0, var0, mean1, var1;
          stat_combine(sv0[0], sv0[1], sv1[0], sv1[1], pv0, mean0, var0); stat_combine(sv0[2], sv0[3], sv1[2], sv1[3], pv1, mean1, var1);
          mean0 = __shfl_sync(0xffffffffu, mean0, g); var0 = __shfl_sync(0xffffffffu, var0, g);
          mean1 = __shfl_sync(0xffffffffu, mean1, g); var1 = __shfl_sync(0xffffffffu, var1, g);
          r0 = 0.5f * rsq(fmaf(var0 + 1e-5f, 1e-5f, var0)); r1 = 0.5f * rsq(fmaf(var1 + 1e-5f, 1e-5f, var1));
          m0 = -mean0 * r0; m1 = -mean1 * r1;
        }
        TS2(15 + 32 * L);
        const uint32_t ha = sb + OFF_X + wg * 16384 + (16 * w + lr) * 128;
#pragma unroll
        for (int t = 0; t < 16; t += 2) {
          stsm4(ha + (t >> 3) * 8192 + ((((t & 7) + lt) ^ l7) << 4),
                pack2(fmaf(xa[4 * t], r0, m0), fmaf(xa[4 * t + 1], r0, m0)), pack2(fmaf(xa[4 * t + 2], r1, m1), fmaf(xa[4 * t + 3], r1, m1)),
                pack2(fmaf(xa[4 * t + 4], r0, m0), fmaf(xa[4 * t + 5], r0, m0)), pack2(fmaf(xa[4 * t + 6], r1, m1), fmaf(xa[4 * t + 7], r1, m1)));
          if ((DIRECT & 1) && (t & 7) == 6 && wg == 0) {
            __syncwarp();
            const int o = (t >> 3) * 8192 + w * 2048 + lane * 16;
            copy_out<4>(gHB + (opq(j) * 32 + 2 * i) * 16384 + o, sb + OFF_X + o, 512);
          }
        }
        if (DIRECT & 1) { signal(JOB + 2 + wg); fence_async_smem(); } else { fence_async_smem(); signal(JOB + 2 + wg); }
        nb_sync<NB_BOTH>(256);
      }
      TS(6 + 32 * L);
      auto g3_issue = [&](uint32_t a, int p) {
        const uint32_t st = sb + slot3(p);
        const uint64_t da = mkdesc(a + wg * 8192, 8192, 1024), db = mkdesc(st + 16384, 8192, 1024);
        wg_fence();
#pragma unroll
        for (int kk = 0; kk < 4; kk++) wgmma_224<1, 1>(acc3, da + kk * 128, db + kk * 128);
        wg_commit();
      };
      mbar_wait(BAR(F3 + 0), 0); KB(48); g3_issue(sb + OFF_X, 0);
      mbar_wait(BAR(F3 + 1), 0); KB(49); g3_issue(sb + OFF_X + 16384, 1);
      sched_fence(P.zero);
      {
        const float c0 = __uint_as_float((uint32_t)b2a << 16), c1 = __uint_as_float((uint32_t)b2b << 16);
#pragma unroll
        for (int t = 0; t < 16; t++) { xa[4 * t] += c0; xa[4 * t + 1] += c0; xa[4 * t + 2] += c1; xa[4 * t + 3] += c1; }
        fence_regs(xa);
      }
      wg_wait<1>(); release(E3 + 0);
      auto g3_loop = [&](int n0, int n1, int nrel) {
#pragma unroll 1
        for (int n = n0; n < n1; n++) {
          const int p = n & 3;
          mbar_wait(BAR(F3 + p), (n >> 2) & 1);
          KB(48 + n);
          if (n == 3 && wu == 0) ST(13);
          if (n == 2 && wu == 0) ST(14);
          g3_issue(sb + slot3(p), p);
          if (LEAD3 && n == 31 && wg == 0) nb_arrive<NB_LEAD>(256);
          wg_wait<1>();
          if (n > nrel) release(E3 + ((n - 1) & 3));
        }
      };
      g3_loop(2, 32 - LEAD3, 0);
      if (LEAD3 && wg == 1) { wg_wait<0>(); release(E3 + ((31 - LEAD3) & 3)); nb_sync<NB_LEAD>(256); }
      g3_loop(32 - LEAD3, 32, wg == 1 ? 32 - LEAD3 : 0);
      mbar_wait(BAR(RD), L);
      wg_wait<0>();
      release(E3 + 3);
      fence_regs(acc3);
      TS(7 + 32 * L);
      if (wu == 0) ST(16);
      auto g4_issue = [&](int p, uint32_t b) {
        const uint64_t da = mkdesc(sb + slot4(p) + wg * 8192, 8192, 1024), db = mkdesc(b, 8192, 1024);
        wg_fence();
#pragma unroll
        for (int kk = 0; kk < 4; kk++) wgmma_128<1, 1>(xa, da + kk * 128, db + kk * 128);
        wg_commit();
      };
      uint32_t par = L ? 0x3c : 0;
      {
        GEOM;
        const uint32_t ua = sb + wg * 8192 + (8 * lt + l7) * 128 + (((2 * w + ((lane >> 3) & 1)) ^ l7) << 4);
#pragma unroll
        for (int cc = 0; cc < 4; cc++) {
          const int c = cc == 0 ? 3 : cc == 3 ? 0 : cc;
          uint32_t u[16];
#pragma unroll
          for (int k = 0; k < (c == 3 ? 8 : 16); k++) u[k] = pack2(gelu_half(acc3[32 * c + 2 * k]), gelu_half(acc3[32 * c + 2 * k + 1]));
          if (c == 3 || c == 0) mbar_wait(BAR(E3 + (c ? 0 : 2)), 1);
#pragma unroll
          for (int k = 0; k < (c == 3 ? 2 : 4); k++)
            stsm4t(ua + (c == 3 ? slot4(5) + 16384 : c == 0 ? slot4(2) + 16384 : OFF_X + (c - 1) * 16384) + k * 2048, u[4 * k], u[4 * k + 1], u[4 * k + 2], u[4 * k + 3]);
          if ((DIRECT & 2) && c == 3) {
            __syncwarp();
            const int o = wg * 8192 + (lane >> 1) * 128 + (((2 * w + (lane & 1)) ^ ((lane >> 1) & 7)) << 4);
            copy_out<2>(gUB + (opq(j) * 56 + 48 + m) * 16384 + r * 4096 + o, sb + slot4(5) + 16384 + o, 2048);
            signal(JOB + 7);
          } else if (c == 3 || c == 0) { fence_async_smem(); signal(JOB + (c ? 7 : 6)); }
          if (c == 3) sched_fence(P.zero);
          TS2(16 + 3 * c + 32 * L);
        }
        nb_sync<NB_BOTH>(256);
      }
      TS(8 + 32 * L);
      {
        int p = 0, pp = 0;
#pragma unroll 1
        for (int n = 0; n < 56; n++) {
          mbar_wait(BAR(F4 + p), (par >> p) & 1);
          KB(80 + n);
          if (n == 3 && wu == 0) ST(21);
          if (n == 0 && wu == 0) ST(22);
          par ^= 1u << p;
          g4_issue(p, n < 2 ? sb + OFF_X + n * 16384 : sb + slot4(p) + 16384);
          wg_wait<1>();
          if (n) release(E4 + pp);
          pp = p; if (++p == 6) p = 0;
        }
      }
      mbar_wait(BAR(RD + 1), L);
      wg_wait<0>();
      release(E4 + 1);
      fence_regs(xa);
      TS(9 + 32 * L);
      {
        GEOM;
#pragma unroll
        for (int t = 0; t < 16; t += 2) {
          stsm4(sb + OFF_X + (t >> 3) * 16384 + (16 * wu + lr) * 128 + ((((t & 7) + lt) ^ l7) << 4),
                pack2(xa[4 * t], xa[4 * t + 1]), pack2(xa[4 * t + 2], xa[4 * t + 3]),
                pack2(xa[4 * t + 4], xa[4 * t + 5]), pack2(xa[4 * t + 6], xa[4 * t + 7]));
          if ((DIRECT & 4) && t == 6 && L == 0) {
            __syncwarp();
            const int o = wu * 2048 + lane * 16;
            copy_out<4>(gXB + (opq(i) * 16 + 2 * j) * 16384 + o, sb + OFF_X + o, 512);
            signal(JOB + 8);
          } else if ((t & 7) == 6) { fence_async_smem(); signal(JOB + 8 + (t >> 3)); }
        }
        nb_sync<NB_BOTH>(256);
      }
      TS(10 + 32 * L);
      KB(136);
    }
    cluster_bar();
    TS(32);
  }
}

typedef CUresult (*EncodeFn)(CUtensorMap*, CUtensorMapDataType, cuuint32_t, void*, const cuuint64_t*, const cuuint64_t*, const cuuint32_t*,
                             const cuuint32_t*, CUtensorMapInterleave, CUtensorMapSwizzle, CUtensorMapL2promotion, CUtensorMapFloatOOBfill);

void make_map(EncodeFn enc, CUtensorMap* mp, const void* base, int rank, cuuint64_t d0, cuuint64_t d1, cuuint64_t d2, cuuint64_t s1, cuuint64_t s2,
              cuuint32_t b0, cuuint32_t b1, cuuint32_t b2) {
  cuuint64_t dims[3] = {d0, d1, d2}, strides[2] = {s1, s2};
  cuuint32_t box[3] = {b0, b1, b2}, es[3] = {1, 1, 1};
  CUresult res = enc(mp, CU_TENSOR_MAP_DATA_TYPE_BFLOAT16, rank, const_cast<void*>(base), dims, strides, box, es, CU_TENSOR_MAP_INTERLEAVE_NONE,
                     CU_TENSOR_MAP_SWIZZLE_128B, CU_TENSOR_MAP_L2_PROMOTION_L2_128B, CU_TENSOR_MAP_FLOAT_OOB_FILL_NONE);
  (void)res;
}

}

extern "C" void kernel_launch(void* const* d_in, const int* in_sizes, int n_in, void* d_out, int out_size) {
  (void)in_sizes; (void)n_in; (void)out_size;
  static EncodeFn enc = nullptr;
  if (!enc) {
    void* fn = nullptr;
    cudaDriverEntryPointQueryResult qr;
    cudaGetDriverEntryPoint("cuTensorMapEncodeTiled", &fn, cudaEnableDefault, &qr);
    enc = (EncodeFn)fn;
    cudaFuncSetAttribute(fused_kernel, cudaFuncAttributeMaxDynamicSharedMemorySize, SMEM_BYTES);
  }
  Params P;
  make_map(enc, &P.x0, d_in[0], 2, D_, S_, 1, D_ * 2, 0, 64, 128, 1);
  make_map(enc, &P.wqkv, d_in[1], 3, D_, D_, 3, 3 * D_ * 2, D_ * 2, 64, 32, 3);
  make_map(enc, &P.wo, d_in[2], 2, D_, D_, 1, D_ * 2, 0, 64, 64, 1);
  make_map(enc, &P.w1, d_in[4], 3, 64, S_, F_ / 64, F_ * 2, 128, 64, 64, 3);
  make_map(enc, &P.w1h, d_in[4], 3, 32, S_, F_ / 32, F_ * 2, 64, 64, 64, 1);
  make_map(enc, &P.w2, d_in[6], 3, 64, F_, S_ / 64, S_ * 2, 128, 64, 64, 2);
  make_map(enc, &P.out, d_out, 2, D_, S_, 1, D_ * 2, 0, 64, 128, 1);
  P.wqkv_p = (const bf16*)d_in[1];
  P.b1 = (const bf16*)d_in[5];
  P.b2 = (const bf16*)d_in[7];
  P.zero = 0;
  fused_kernel<<<128, 384, SMEM_BYTES>>>(P);
}
```

```cpp
#include <cuda_runtime.h>
#include <cuda_bf16.h>
#include <cuda.h>
#include <stdint.h>

namespace {

typedef __nv_bfloat16 bf16;
constexpr int S_ = 2048, D_ = 1024, F_ = 3584;

constexpr uint32_t OFF_STG  = 163840;
constexpr uint32_t OFF_X    = 196608;
constexpr uint32_t OFF_BAR  = 229376;
constexpr uint32_t OFF_CS   = OFF_BAR + 512;
constexpr uint32_t OFF_B1   = OFF_CS + 1536;
constexpr uint32_t SMEM_BYTES = OFF_B1 + 896 + 128;
constexpr int F1 = 0, E1 = 4, F2 = 8, E2 = 13, F3 = 18, E3 = 22, F4 = 26, E4 = 32;
constexpr int JOB = 38;
constexpr int RD = 48;
constexpr int XF = 54, STD = 56, STAT = 58, FOLD = 59, CSJ = 61, HALO = 62;
constexpr int NB_BOTH = 1, NB_HELP = 2, NB_INIT = 3, NB_LEAD = 4;

__device__ __forceinline__ uint32_t slot1(int p) { return p * 40960; }
__device__ __forceinline__ uint32_t slot2(int p) { return p * 32768; }
__device__ __forceinline__ uint32_t slot3(int p) { return ((p + 2) & 3) * 49152; }
__device__ __forceinline__ uint32_t slot4(int p) { return (p < 2 ? p + 4 : p - 2) * 32768; }

__device__ __align__(1024) uint8_t gXB[16 * 16 * 16384];
__device__ __align__(1024) uint8_t gOB[16 * 16 * 16384];
__device__ __align__(1024) uint8_t gHB[8 * 32 * 16384];
__device__ __align__(1024) uint8_t gUB[8 * 56 * 16384];
__device__ __align__(1024) uint2   gST[2][16][8][8][16];
__device__ __align__(1024) uint4   gHalo[2][16][8][12][32];
__device__ __align__(1024) uint32_t gAck[2][16][8][2][8];
__device__ __align__(1024) uint4   gCS[8][16][64];
__device__ __align__(1024) uint32_t gFlag[2][7][16][32];
__device__ uint32_t gEpoch;
#define TS(k)
#define TS2(k)

#define KB(k)
#define ST(k)
struct Params {
  CUtensorMap x0, wqkv, wo, w1, w1h, w2, out;
  const bf16 *wqkv_p, *b1, *b2;
  uint32_t zero;
};

template <int TA, int TB> __device__ __forceinline__ void wgmma_128(float (&d)[64], uint64_t da, uint64_t db) {
  asm volatile("wgmma.mma_async.sync.aligned.m64n128k16.f32.bf16.bf16 {"
  "%0, %1, %2, %3, %4, %5, %6, %7, %8, %9, %10, %11, %12, %13, %14, %15, "
  "%16, %17, %18, %19, %20, %21, %22, %23, %24, %25, %26, %27, %28, %29, %30, %31, "
  "%32, %33, %34, %35, %36, %37, %38, %39, %40, %41, %42, %43, %44, %45, %46, %47, "
  "%48, %49, %50, %51, %52, %53, %54, %55, %56, %57, %58, %59, %60, %61, %62, %63"
  "}, %64, %65, 1, 1, 1, %66, %67;\n"
  : "+f"(d[0]), "+f"(d[1]), "+f"(d[2]), "+f"(d[3]), "+f"(d[4]), "+f"(d[5]), "+f"(d[6]), "+f"(d[7]),
    "+f"(d[8]), "+f"(d[9]), "+f"(d[10]), "+f"(d[11]), "+f"(d[12]), "+f"(d[13]), "+f"(d[14]), "+f"(d[15]),
    "+f"(d[16]), "+f"(d[17]), "+f"(d[18]), "+f"(d[19]), "+f"(d[20]), "+f"(d[21]), "+f"(d[22]), "+f"(d[23]),
    "+f"(d[24]), "+f"(d[25]), "+f"(d[26]), "+f"(d[27]), "+f"(d[28]), "+f"(d[29]), "+f"(d[30]), "+f"(d[31]),
    "+f"(d[32]), "+f"(d[33]), "+f"(d[34]), "+f"(d[35]), "+f"(d[36]), "+f"(d[37]), "+f"(d[38]), "+f"(d[39]),
    "+f"(d[40]), "+f"(d[41]), "+f"(d[42]), "+f"(d[43]), "+f"(d[44]), "+f"(d[45]), "+f"(d[46]), "+f"(d[47]),
    "+f"(d[48]), "+f"(d[49]), "+f"(d[50]), "+f"(d[51]), "+f"(d[52]), "+f"(d[53]), "+f"(d[54]), "+f"(d[55]),
    "+f"(d[56]), "+f"(d[57]), "+f"(d[58]), "+f"(d[59]), "+f"(d[60]), "+f"(d[61]), "+f"(d[62]), "+f"(d[63])
  : "l"(da), "l"(db), "n"(TA), "n"(TB));
}
template <int TA, int TB> __device__ __forceinline__ void wgmma_192(float (&d)[96], uint64_t da, uint64_t db) {
  asm volatile("wgmma.mma_async.sync.aligned.m64n192k16.f32.bf16.bf16 {"
  "%0, %1, %2, %3, %4, %5, %6, %7, %8, %9, %10, %11, %12, %13, %14, %15, "
  "%16, %17, %18, %19, %20, %21, %22, %23, %24, %25, %26, %27, %28, %29, %30, %31, "
  "%32, %33, %34, %35, %36, %37, %38, %39, %40, %41, %42, %43, %44, %45, %46, %47, "
  "%48, %49, %50, %51, %52, %53, %54, %55, %56, %57, %58, %59, %60, %61, %62, %63, "
  "%64, %65, %66, %67, %68, %69, %70, %71, %72, %73, %74, %75, %76, %77, %78, %79, "
  "%80, %81, %82, %83, %84, %85, %86, %87, %88, %89, %90, %91, %92, %93, %94, %95"
  "}, %96, %97, 1, 1, 1, %98, %99;\n"
  : "+f"(d[0]), "+f"(d[1]), "+f"(d[2]), "+f"(d[3]), "+f"(d[4]), "+f"(d[5]), "+f"(d[6]), "+f"(d[7]),
    "+f"(d[8]), "+f"(d[9]), "+f"(d[10]), "+f"(d[11]), "+f"(d[12]), "+f"(d[13]), "+f"(d[14]), "+f"(d[15]),
    "+f"(d[16]), "+f"(d[17]), "+f"(d[18]), "+f"(d[19]), "+f"(d[20]), "+f"(d[21]), "+f"(d[22]), "+f"(d[23]),
    "+f"(d[24]), "+f"(d[25]), "+f"(d[26]), "+f"(d[27]), "+f"(d[28]), "+f"(d[29]), "+f"(d[30]), "+f"(d[31]),
    "+f"(d[32]), "+f"(d[33]), "+f"(d[34]), "+f"(d[35]), "+f"(d[36]), "+f"(d[37]), "+f"(d[38]), "+f"(d[39]),
    "+f"(d[40]), "+f"(d[41]), "+f"(d[42]), "+f"(d[43]), "+f"(d[44]), "+f"(d[45]), "+f"(d[46]), "+f"(d[47]),
    "+f"(d[48]), "+f"(d[49]), "+f"(d[50]), "+f"(d[51]), "+f"(d[52]), "+f"(d[53]), "+f"(d[54]), "+f"(d[55]),
    "+f"(d[56]), "+f"(d[57]), "+f"(d[58]), "+f"(d[59]), "+f"(d[60]), "+f"(d[61]), "+f"(d[62]), "+f"(d[63]),
    "+f"(d[64]), "+f"(d[65]), "+f"(d[66]), "+f"(d[67]), "+f"(d[68]), "+f"(d[69]), "+f"(d[70]), "+f"(d[71]),
    "+f"(d[72]), "+f"(d[73]), "+f"(d[74]), "+f"(d[75]), "+f"(d[76]), "+f"(d[77]), "+f"(d[78]), "+f"(d[79]),
    "+f"(d[80]), "+f"(d[81]), "+f"(d[82]), "+f"(d[83]), "+f"(d[84]), "+f"(d[85]), "+f"(d[86]), "+f"(d[87]),
    "+f"(d[88]), "+f"(d[89]), "+f"(d[90]), "+f"(d[91]), "+f"(d[92]), "+f"(d[93]), "+f"(d[94]), "+f"(d[95])
  : "l"(da), "l"(db), "n"(TA), "n"(TB));
}
template <int TA, int TB> __device__ __forceinline__ void wgmma_192z(float (&d)[96], uint64_t da, uint64_t db) {
  asm volatile("wgmma.mma_async.sync.aligned.m64n192k16.f32.bf16.bf16 {"
  "%0, %1, %2, %3, %4, %5, %6, %7, %8, %9, %10, %11, %12, %13, %14, %15, "
  "%16, %17, %18, %19, %20, %21, %22, %23, %24, %25, %26, %27, %28, %29, %30, %31, "
  "%32, %33, %34, %35, %36, %37, %38, %39, %40, %41, %42, %43, %44, %45, %46, %47, "
  "%48, %49, %50, %51, %52, %53, %54, %55, %56, %57, %58, %59, %60, %61, %62, %63, "
  "%64, %65, %66, %67, %68, %69, %70, %71, %72, %73, %74, %75, %76, %77, %78, %79, "
  "%80, %81, %82, %83, %84, %85, %86, %87, %88, %89, %90, %91, %92, %93, %94, %95"
  "}, %96, %97, 0, 1, 1, %98, %99;\n"
  : "=f"(d[0]), "=f"(d[1]), "=f"(d[2]), "=f"(d[3]), "=f"(d[4]), "=f"(d[5]), "=f"(d[6]), "=f"(d[7]),
    "=f"(d[8]), "=f"(d[9]), "=f"(d[10]), "=f"(d[11]), "=f"(d[12]), "=f"(d[13]), "=f"(d[14]), "=f"(d[15]),
    "=f"(d[16]), "=f"(d[17]), "=f"(d[18]), "=f"(d[19]), "=f"(d[20]), "=f"(d[21]), "=f"(d[22]), "=f"(d[23]),
    "=f"(d[24]), "=f"(d[25]), "=f"(d[26]), "=f"(d[27]), "=f"(d[28]), "=f"(d[29]), "=f"(d[30]), "=f"(d[31]),
    "=f"(d[32]), "=f"(d[33]), "=f"(d[34]), "=f"(d[35]), "=f"(d[36]), "=f"(d[37]), "=f"(d[38]), "=f"(d[39]),
    "=f"(d[40]), "=f"(d[41]), "=f"(d[42]), "=f"(d[43]), "=f"(d[44]), "=f"(d[45]), "=f"(d[46]), "=f"(d[47]),
    "=f"(d[48]), "=f"(d[49]), "=f"(d[50]), "=f"(d[51]), "=f"(d[52]), "=f"(d[53]), "=f"(d[54]), "=f"(d[55]),
    "=f"(d[56]), "=f"(d[57]), "=f"(d[58]), "=f"(d[59]), "=f"(d[60]), "=f"(d[61]), "=f"(d[62]), "=f"(d[63]),
    "=f"(d[64]), "=f"(d[65]), "=f"(d[66]), "=f"(d[67]), "=f"(d[68]), "=f"(d[69]), "=f"(d[70]), "=f"(d[71]),
    "=f"(d[72]), "=f"(d[73]), "=f"(d[74]), "=f"(d[75]), "=f"(d[76]), "=f"(d[77]), "=f"(d[78]), "=f"(d[79]),
    "=f"(d[80]), "=f"(d[81]), "=f"(d[82]), "=f"(d[83]), "=f"(d[84]), "=f"(d[85]), "=f"(d[86]), "=f"(d[87]),
    "=f"(d[88]), "=f"(d[89]), "=f"(d[90]), "=f"(d[91]), "=f"(d[92]), "=f"(d[93]), "=f"(d[94]), "=f"(d[95])
  : "l"(da), "l"(db), "n"(TA), "n"(TB));
}
template <int TA, int TB> __device__ __forceinline__ void wgmma_224(float (&d)[112], uint64_t da, uint64_t db) {
  asm volatile("wgmma.mma_async.sync.aligned.m64n224k16.f32.bf16.bf16 {"
  "%0, %1, %2, %3, %4, %5, %6, %7, %8, %9, %10, %11, %12, %13, %14, %15, "
  "%16, %17, %18, %19, %20, %21, %22, %23, %24, %25, %26, %27, %28, %29, %30, %31, "
  "%32, %33, %34, %35, %36, %37, %38, %39, %40, %41, %42, %43, %44, %45, %46, %47, "
  "%48, %49, %50, %51, %52, %53, %54, %55, %56, %57, %58, %59, %60, %61, %62, %63, "
  "%64, %65, %66, %67, %68, %69, %70, %71, %72, %73, %74, %75, %76, %77, %78, %79, "
  "%80, %81, %82, %83, %84, %85, %86, %87, %88, %89, %90, %91, %92, %93, %94, %95, "
  "%96, %97, %98, %99, %100, %101, %102, %103, %104, %105, %106, %107, %108, %109, %110, %111"
  "}, %112, %113, 1, 1, 1, %114, %115;\n"
  : "+f"(d[0]), "+f"(d[1]), "+f"(d[2]), "+f"(d[3]), "+f"(d[4]), "+f"(d[5]), "+f"(d[6]), "+f"(d[7]),
    "+f"(d[8]), "+f"(d[9]), "+f"(d[10]), "+f"(d[11]), "+f"(d[12]), "+f"(d[13]), "+f"(d[14]), "+f"(d[15]),
    "+f"(d[16]), "+f"(d[17]), "+f"(d[18]), "+f"(d[19]), "+f"(d[20]), "+f"(d[21]), "+f"(d[22]), "+f"(d[23]),
    "+f"(d[24]), "+f"(d[25]), "+f"(d[26]), "+f"(d[27]), "+f"(d[28]), "+f"(d[29]), "+f"(d[30]), "+f"(d[31]),
    "+f"(d[32]), "+f"(d[33]), "+f"(d[34]), "+f"(d[35]), "+f"(d[36]), "+f"(d[37]), "+f"(d[38]), "+f"(d[39]),
    "+f"(d[40]), "+f"(d[41]), "+f"(d[42]), "+f"(d[43]), "+f"(d[44]), "+f"(d[45]), "+f"(d[46]), "+f"(d[47]),
    "+f"(d[48]), "+f"(d[49]), "+f"(d[50]), "+f"(d[51]), "+f"(d[52]), "+f"(d[53]), "+f"(d[54]), "+f"(d[55]),
    "+f"(d[56]), "+f"(d[57]), "+f"(d[58]), "+f"(d[59]), "+f"(d[60]), "+f"(d[61]), "+f"(d[62]), "+f"(d[63]),
    "+f"(d[64]), "+f"(d[65]), "+f"(d[66]), "+f"(d[67]), "+f"(d[68]), "+f"(d[69]), "+f"(d[70]), "+f"(d[71]),
    "+f"(d[72]), "+f"(d[73]), "+f"(d[74]), "+f"(d[75]), "+f"(d[76]), "+f"(d[77]), "+f"(d[78]), "+f"(d[79]),
    "+f"(d[80]), "+f"(d[81]), "+f"(d[82]), "+f"(d[83]), "+f"(d[84]), "+f"(d[85]), "+f"(d[86]), "+f"(d[87]),
    "+f"(d[88]), "+f"(d[89]), "+f"(d[90]), "+f"(d[91]), "+f"(d[92]), "+f"(d[93]), "+f"(d[94]), "+f"(d[95]),
    "+f"(d[96]), "+f"(d[97]), "+f"(d[98]), "+f"(d[99]), "+f"(d[100]), "+f"(d[101]), "+f"(d[102]), "+f"(d[103]),
    "+f"(d[104]), "+f"(d[105]), "+f"(d[106]), "+f"(d[107]), "+f"(d[108]), "+f"(d[109]), "+f"(d[110]), "+f"(d[111])
  : "l"(da), "l"(db), "n"(TA), "n"(TB));
}
__device__ __forceinline__ void wgmma_rs_192(float (&d)[96], uint32_t a0, uint32_t a1, uint32_t a2, uint32_t a3, uint64_t db) {
  asm volatile("wgmma.mma_async.sync.aligned.m64n192k16.f32.bf16.bf16 {"
  "%0, %1, %2, %3, %4, %5, %6, %7, %8, %9, %10, %11, %12, %13, %14, %15, "
  "%16, %17, %18, %19, %20, %21, %22, %23, %24, %25, %26, %27, %28, %29, %30, %31, "
  "%32, %33, %34, %35, %36, %37, %38, %39, %40, %41, %42, %43, %44, %45, %46, %47, "
  "%48, %49, %50, %51, %52, %53, %54, %55, %56, %57, %58, %59, %60, %61, %62, %63, "
  "%64, %65, %66, %67, %68, %69, %70, %71, %72, %73, %74, %75, %76, %77, %78, %79, "
  "%80, %81, %82, %83, %84, %85, %86, %87, %88, %89, %90, %91, %92, %93, %94, %95"
  "}, {%96, %97, %98, %99}, %100, 1, 1, 1, 1;\n"
  : "+f"(d[0]), "+f"(d[1]), "+f"(d[2]), "+f"(d[3]), "+f"(d[4]), "+f"(d[5]), "+f"(d[6]), "+f"(d[7]),
    "+f"(d[8]), "+f"(d[9]), "+f"(d[10]), "+f"(d[11]), "+f"(d[12]), "+f"(d[13]), "+f"(d[14]), "+f"(d[15]),
    "+f"(d[16]), "+f"(d[17]), "+f"(d[18]), "+f"(d[19]), "+f"(d[20]), "+f"(d[21]), "+f"(d[22]), "+f"(d[23]),
    "+f"(d[24]), "+f"(d[25]), "+f"(d[26]), "+f"(d[27]), "+f"(d[28]), "+f"(d[29]), "+f"(d[30]), "+f"(d[31]),
    "+f"(d[32]), "+f"(d[33]), "+f"(d[34]), "+f"(d[35]), "+f"(d[36]), "+f"(d[37]), "+f"(d[38]), "+f"(d[39]),
    "+f"(d[40]), "+f"(d[41]), "+f"(d[42]), "+f"(d[43]), "+f"(d[44]), "+f"(d[45]), "+f"(d[46]), "+f"(d[47]),
    "+f"(d[48]), "+f"(d[49]), "+f"(d[50]), "+f"(d[51]), "+f"(d[52]), "+f"(d[53]), "+f"(d[54]), "+f"(d[55]),
    "+f"(d[56]), "+f"(d[57]), "+f"(d[58]), "+f"(d[59]), "+f"(d[60]), "+f"(d[61]), "+f"(d[62]), "+f"(d[63]),
    "+f"(d[64]), "+f"(d[65]), "+f"(d[66]), "+f"(d[67]), "+f"(d[68]), "+f"(d[69]), "+f"(d[70]), "+f"(d[71]),
    "+f"(d[72]), "+f"(d[73]), "+f"(d[74]), "+f"(d[75]), "+f"(d[76]), "+f"(d[77]), "+f"(d[78]), "+f"(d[79]),
    "+f"(d[80]), "+f"(d[81]), "+f"(d[82]), "+f"(d[83]), "+f"(d[84]), "+f"(d[85]), "+f"(d[86]), "+f"(d[87]),
    "+f"(d[88]), "+f"(d[89]), "+f"(d[90]), "+f"(d[91]), "+f"(d[92]), "+f"(d[93]), "+f"(d[94]), "+f"(d[95])
  : "r"(a0), "r"(a1), "r"(a2), "r"(a3), "l"(db));
}
__device__ __forceinline__ void wgmma_rs_224z(float (&d)[112], uint32_t a0, uint32_t a1, uint32_t a2, uint32_t a3, uint64_t db) {
  asm volatile("wgmma.mma_async.sync.aligned.m64n224k16.f32.bf16.bf16 {"
  "%0, %1, %2, %3, %4, %5, %6, %7, %8, %9, %10, %11, %12, %13, %14, %15, "
  "%16, %17, %18, %19, %20, %21, %22, %23, %24, %25, %26, %27, %28, %29, %30, %31, "
  "%32, %33, %34, %35, %36, %37, %38, %39, %40, %41, %42, %43, %44, %45, %46, %47, "
  "%48, %49, %50, %51, %52, %53, %54, %55, %56, %57, %58, %59, %60, %61, %62, %63, "
  "%64, %65, %66, %67, %68, %69, %70, %71, %72, %73, %74, %75, %76, %77, %78, %79, "
  "%80, %81, %82, %83, %84, %85, %86, %87, %88, %89, %90, %91, %92, %93, %94, %95, "
  "%96, %97, %98, %99, %100, %101, %102, %103, %104, %105, %106, %107, %108, %109, %110, %111"
  "}, {%112, %113, %114, %115}, %116, 0, 1, 1, 1;\n"
  : "=f"(d[0]), "=f"(d[1]), "=f"(d[2]), "=f"(d[3]), "=f"(d[4]), "=f"(d[5]), "=f"(d[6]), "=f"(d[7]),
    "=f"(d[8]), "=f"(d[9]), "=f"(d[10]), "=f"(d[11]), "=f"(d[12]), "=f"(d[13]), "=f"(d[14]), "=f"(d[15]),
    "=f"(d[16]), "=f"(d[17]), "=f"(d[18]), "=f"(d[19]), "=f"(d[20]), "=f"(d[21]), "=f"(d[22]), "=f"(d[23]),
    "=f"(d[24]), "=f"(d[25]), "=f"(d[26]), "=f"(d[27]), "=f"(d[28]), "=f"(d[29]), "=f"(d[30]), "=f"(d[31]),
    "=f"(d[32]), "=f"(d[33]), "=f"(d[34]), "=f"(d[35]), "=f"(d[36]), "=f"(d[37]), "=f"(d[38]), "=f"(d[39]),
    "=f"(d[40]), "=f"(d[41]), "=f"(d[42]), "=f"(d[43]), "=f"(d[44]), "=f"(d[45]), "=f"(d[46]), "=f"(d[47]),
    "=f"(d[48]), "=f"(d[49]), "=f"(d[50]), "=f"(d[51]), "=f"(d[52]), "=f"(d[53]), "=f"(d[54]), "=f"(d[55]),
    "=f"(d[56]), "=f"(d[57]), "=f"(d[58]), "=f"(d[59]), "=f"(d[60]), "=f"(d[61]), "=f"(d[62]), "=f"(d[63]),
    "=f"(d[64]), "=f"(d[65]), "=f"(d[66]), "=f"(d[67]), "=f"(d[68]), "=f"(d[69]), "=f"(d[70]), "=f"(d[71]),
    "=f"(d[72]), "=f"(d[73]), "=f"(d[74]), "=f"(d[75]), "=f"(d[76]), "=f"(d[77]), "=f"(d[78]), "=f"(d[79]),
    "=f"(d[80]), "=f"(d[81]), "=f"(d[82]), "=f"(d[83]), "=f"(d[84]), "=f"(d[85]), "=f"(d[86]), "=f"(d[87]),
    "=f"(d[88]), "=f"(d[89]), "=f"(d[90]), "=f"(d[91]), "=f"(d[92]), "=f"(d[93]), "=f"(d[94]), "=f"(d[95]),
    "=f"(d[96]), "=f"(d[97]), "=f"(d[98]), "=f"(d[99]), "=f"(d[100]), "=f"(d[101]), "=f"(d[102]), "=f"(d[103]),
    "=f"(d[104]), "=f"(d[105]), "=f"(d[106]), "=f"(d[107]), "=f"(d[108]), "=f"(d[109]), "=f"(d[110]), "=f"(d[111])
  : "r"(a0), "r"(a1), "r"(a2), "r"(a3), "l"(db));
}

__device__ __forceinline__ uint32_t smem_u32(const void* p) { return (uint32_t)__cvta_generic_to_shared(p); }
__device__ __forceinline__ void mbar_init(uint32_t bar, uint32_t cnt) { asm volatile("mbarrier.init.shared::cta.b64 [%0], %1;" ::"r"(bar), "r"(cnt) : "memory"); }
__device__ __forceinline__ void mbar_expect(uint32_t bar, uint32_t bytes) { asm volatile("mbarrier.arrive.expect_tx.shared::cta.b64 _, [%0], %1;" ::"r"(bar), "r"(bytes) : "memory"); }
__device__ __forceinline__ void mbar_arrive(uint32_t bar) { asm volatile("mbarrier.arrive.shared::cta.b64 _, [%0];" ::"r"(bar) : "memory"); }
__device__ __forceinline__ void mbar_arrive_cl(uint32_t cbar) { asm volatile("mbarrier.arrive.shared::cluster.b64 _, [%0];" ::"r"(cbar) : "memory"); }
__device__ __forceinline__ uint32_t mapa(uint32_t a, uint32_t cta) { uint32_t r; asm("mapa.shared::cluster.u32 %0, %1, %2;" : "=r"(r) : "r"(a), "r"(cta)); return r; }
__device__ __forceinline__ void mbar_wait(uint32_t bar, uint32_t parity) {
  asm volatile("{\n.reg .pred p;\n.reg .u32 n;\nmov.u32 n, 0;\n"
    "LAB_WAIT:\n"
    "mbarrier.try_wait.parity.shared::cta.b64 p, [%0], %1;\n"
    "@p bra LAB_DONE;\n"
    "add.u32 n, n, 1;\n"
    "setp.lt.u32 p, n, 2000000;\n"
    "@p bra LAB_WAIT;\n"
    "trap;\n"
    "LAB_DONE:\n}\n" ::"r"(bar), "r"(parity) : "memory");
}
constexpr uint32_t SPIN_MAX = 2000000;
__device__ __forceinline__ void tma2d(uint32_t dst, const CUtensorMap* m, uint32_t bar, int c0, int c1) {
  asm volatile("cp.async.bulk.tensor.2d.shared::cluster.global.mbarrier::complete_tx::bytes [%0], [%1, {%3, %4}], [%2];"
    ::"r"(dst), "l"(m), "r"(bar), "r"(c0), "r"(c1) : "memory");
}
__device__ __forceinline__ void tma2d_mc(uint32_t dst, const CUtensorMap* m, uint32_t bar, int c0, int c1) {
  asm volatile("cp.async.bulk.tensor.2d.shared::cluster.global.mbarrier::complete_tx::bytes.multicast::cluster [%0], [%1, {%3, %4}], [%2], %5;"
    ::"r"(dst), "l"(m), "r"(bar), "r"(c0), "r"(c1), "h"((uint16_t)3) : "memory");
}
__device__ __forceinline__ void tma3d(uint32_t dst, const CUtensorMap* m, uint32_t bar, int c0, int c1, int c2) {
  asm volatile("cp.async.bulk.tensor.3d.shared::cluster.global.mbarrier::complete_tx::bytes [%0], [%1, {%3, %4, %5}], [%2];"
    ::"r"(dst), "l"(m), "r"(bar), "r"(c0), "r"(c1), "r"(c2) : "memory");
}
__device__ __forceinline__ void tma3d_mc(uint32_t dst, const CUtensorMap* m, uint32_t bar, int c0, int c1, int c2) {
  asm volatile("cp.async.bulk.tensor.3d.shared::cluster.global.mbarrier::complete_tx::bytes.multicast::cluster [%0], [%1, {%3, %4, %5}], [%2], %6;"
    ::"r"(dst), "l"(m), "r"(bar), "r"(c0), "r"(c1), "r"(c2), "h"((uint16_t)3) : "memory");
}
__device__ __forceinline__ void tma2d_store(const CUtensorMap* m, uint32_t src, int c0, int c1) {
  asm volatile("cp.async.bulk.tensor.2d.global.shared::cta.bulk_group [%0, {%2, %3}], [%1];" ::"l"(m), "r"(src), "r"(c0), "r"(c1) : "memory");
}
__device__ __forceinline__ void bulk_ld(uint32_t dst, const void* src, uint32_t bytes, uint32_t bar) {
  asm volatile("cp.async.bulk.shared::cluster.global.mbarrier::complete_tx::bytes [%0], [%1], %2, [%3];" ::"r"(dst), "l"(src), "r"(bytes), "r"(bar) : "memory");
}
__device__ __forceinline__ void bulk_ld_mc(uint32_t dst, const void* src, uint32_t bytes, uint32_t bar) {
  asm volatile("cp.async.bulk.shared::cluster.global.mbarrier::complete_tx::bytes.multicast::cluster [%0], [%1], %2, [%3], %4;"
    ::"r"(dst), "l"(src), "r"(bytes), "r"(bar), "h"((uint16_t)3) : "memory");
}
__device__ __forceinline__ void bulk_st(void* dst, uint32_t src, uint32_t bytes) {
  asm volatile("cp.async.bulk.global.shared::cta.bulk_group [%0], [%1], %2;" ::"l"(dst), "r"(src), "r"(bytes) : "memory");
}
__device__ __forceinline__ void bulk_s2s(uint32_t cdst, uint32_t src, uint32_t bytes, uint32_t cbar) {
  asm volatile("cp.async.bulk.shared::cluster.shared::cta.mbarrier::complete_tx::bytes [%0], [%1], %2, [%3];" ::"r"(cdst), "r"(src), "r"(bytes), "r"(cbar) : "memory");
}
__device__ __forceinline__ void bulk_commit() { asm volatile("cp.async.bulk.commit_group;" ::: "memory"); }
__device__ __forceinline__ void bulk_wait0() { asm volatile("cp.async.bulk.wait_group 0;" ::: "memory"); }
__device__ __forceinline__ void fence_async_smem() { asm volatile("fence.proxy.async.shared::cta;" ::: "memory"); }
__device__ __forceinline__ void wg_fence() { asm volatile("wgmma.fence.sync.aligned;" ::: "memory"); }
__device__ __forceinline__ void wg_commit() { asm volatile("wgmma.commit_group.sync.aligned;" ::: "memory"); }
template <int N> __device__ __forceinline__ void wg_wait() { asm volatile("wgmma.wait_group.sync.aligned %0;" ::"n"(N) : "memory"); }
template <int R> __device__ __forceinline__ void reg_alloc() { asm volatile("setmaxnreg.inc.sync.aligned.u32 %0;" ::"n"(R)); }
template <int R> __device__ __forceinline__ void reg_dealloc() { asm volatile("setmaxnreg.dec.sync.aligned.u32 %0;" ::"n"(R)); }
__device__ __forceinline__ void cluster_bar() { asm volatile("barrier.cluster.arrive.relaxed;\nbarrier.cluster.wait;" ::: "memory"); }
template <int ID> __device__ __forceinline__ void nb_sync(int n) { asm volatile("barrier.sync %0, %1;" ::"n"(ID), "r"(n) : "memory"); }
template <int ID> __device__ __forceinline__ void nb_arrive(int n) { asm volatile("barrier.arrive %0, %1;" ::"n"(ID), "r"(n) : "memory"); }
__device__ __forceinline__ int fresh_tid() { int t; asm volatile("mov.u32 %0, %%tid.x;" : "=r"(t)); return t; }
__device__ __forceinline__ void sched_fence(uint32_t z) { asm volatile("{\n.reg .pred p;\nsetp.ne.u32 p, %0, 0;\nLAB_S:\n@p nanosleep.u32 0;\n@p bra LAB_S;\n}\n" ::"r"(z) : "memory"); }
__device__ __forceinline__ float rsq(float x) { float y; asm("rsqrt.approx.ftz.f32 %0, %1;" : "=f"(y) : "f"(x)); return y; }
__device__ __forceinline__ int opq(int v) { asm volatile("" : "+r"(v)); return v; }
struct True { static constexpr bool value = true; };
struct False { static constexpr bool value = false; };
template <int N> __device__ __forceinline__ void fence_regs(float (&d)[N]) {
#pragma unroll
  for (int i = 0; i < N; i++) asm volatile("" : "+f"(d[i])::"memory");
}
__device__ __forceinline__ uint64_t mkdesc(uint32_t addr, uint32_t lbo, uint32_t sbo) {
  return (uint64_t)((addr & 0x3FFFF) >> 4) | ((uint64_t)(lbo >> 4) << 16) | ((uint64_t)(sbo >> 4) << 32) | (1ull << 62);
}
__device__ __forceinline__ uint64_t mkdesc_vec(uint32_t addr, uint32_t sbo) { return (uint64_t)((addr & 0x3FFFF) >> 4) | ((uint64_t)(sbo >> 4) << 32); }
__device__ __forceinline__ void sts16(uint32_t a, uint32_t v) { asm volatile("st.shared.u16 [%0], %1;" ::"r"(a), "h"((uint16_t)v) : "memory"); }
__device__ __forceinline__ uint32_t pack2(float lo, float hi) { uint32_t r; asm("cvt.rn.bf16x2.f32 %0, %1, %2;" : "=r"(r) : "f"(hi), "f"(lo)); return r; }
__device__ __forceinline__ float bf_lo(uint32_t v) { return __uint_as_float(v << 16); }
__device__ __forceinline__ float bf_hi(uint32_t v) { return __uint_as_float(v & 0xffff0000u); }
__device__ __forceinline__ void stsm4(uint32_t a, uint32_t r0, uint32_t r1, uint32_t r2, uint32_t r3) {
  asm volatile("stmatrix.sync.aligned.m8n8.x4.shared.b16 [%0], {%1, %2, %3, %4};" ::"r"(a), "r"(r0), "r"(r1), "r"(r2), "r"(r3) : "memory");
}
__device__ __forceinline__ void stsm4t(uint32_t a, uint32_t r0, uint32_t r1, uint32_t r2, uint32_t r3) {
  asm volatile("stmatrix.sync.aligned.m8n8.x4.trans.shared.b16 [%0], {%1, %2, %3, %4};" ::"r"(a), "r"(r0), "r"(r1), "r"(r2), "r"(r3) : "memory");
}
__device__ __forceinline__ void ldsm4(uint32_t a, uint32_t& r0, uint32_t& r1, uint32_t& r2, uint32_t& r3) {
  asm volatile("ldmatrix.sync.aligned.m8n8.x4.shared.b16 {%0, %1, %2, %3}, [%4];" : "=r"(r0), "=r"(r1), "=r"(r2), "=r"(r3) : "r"(a) : "memory");
}
__device__ __forceinline__ void ldsm4t(uint32_t a, uint32_t& r0, uint32_t& r1, uint32_t& r2, uint32_t& r3) {
  asm volatile("ldmatrix.sync.aligned.m8n8.x4.trans.shared.b16 {%0, %1, %2, %3}, [%4];" : "=r"(r0), "=r"(r1), "=r"(r2), "=r"(r3) : "r"(a) : "memory");
}
__device__ __forceinline__ void mma16816(float (&c)[4], uint32_t a0, uint32_t a1, uint32_t a2, uint32_t a3, uint32_t b0, uint32_t b1) {
  asm volatile("mma.sync.aligned.m16n8k16.row.col.f32.bf16.bf16.f32 {%0, %1, %2, %3}, {%4, %5, %6, %7}, {%8, %9}, {%0, %1, %2, %3};"
    : "+f"(c[0]), "+f"(c[1]), "+f"(c[2]), "+f"(c[3]) : "r"(a0), "r"(a1), "r"(a2), "r"(a3), "r"(b0), "r"(b1));
}
__device__ __forceinline__ void sts128(uint32_t a, uint32_t r0, uint32_t r1, uint32_t r2, uint32_t r3) {
  asm volatile("st.shared.v4.b32 [%0], {%1, %2, %3, %4};" ::"r"(a), "r"(r0), "r"(r1), "r"(r2), "r"(r3) : "memory");
}
__device__ __forceinline__ void lds128(uint32_t a, uint32_t& r0, uint32_t& r1, uint32_t& r2, uint32_t& r3) {
  asm volatile("ld.shared.v4.b32 {%0, %1, %2, %3}, [%4];" : "=r"(r0), "=r"(r1), "=r"(r2), "=r"(r3) : "r"(a) : "memory");
}
__device__ __forceinline__ float2 lds64f(uint32_t a) { float2 v; asm volatile("ld.shared.v2.f32 {%0, %1}, [%2];" : "=f"(v.x), "=f"(v.y) : "r"(a) : "memory"); return v; }
__device__ __forceinline__ float4 lds128f(uint32_t a) { float4 v; asm volatile("ld.shared.v4.f32 {%0, %1, %2, %3}, [%4];" : "=f"(v.x), "=f"(v.y), "=f"(v.z), "=f"(v.w) : "r"(a) : "memory"); return v; }
__device__ __forceinline__ void sts64f(uint32_t a, float x, float y) { asm volatile("st.shared.v2.f32 [%0], {%1, %2};" ::"r"(a), "f"(x), "f"(y) : "memory"); }
__device__ __forceinline__ float lds32f(uint32_t a) { float v; asm volatile("ld.shared.f32 %0, [%1];" : "=f"(v) : "r"(a) : "memory"); return v; }
__device__ __forceinline__ void sts32f(uint32_t a, float x) { asm volatile("st.shared.f32 [%0], %1;" ::"r"(a), "f"(x) : "memory"); }
__device__ __forceinline__ void stat_st(uint2* p, float sum, float sq, uint32_t tag) {
  const float mean = sum * (1.f / 128), m2 = fmaxf(fmaf(-mean, sum, sq), 0.f);
  const uint32_t a = ((__float_as_uint(mean) + 8u) & ~15u) | (tag & 15u), b = ((__float_as_uint(m2) + 8u) & ~15u) | (tag & 15u);
  asm volatile("{\n.reg .b64 x;\nmov.b64 x, {%1, %2};\nst.relaxed.gpu.global.b64 [%0], x;\n}\n" ::"l"(p), "r"(a), "r"(b) : "memory");
}
__device__ __forceinline__ void stat_ld2(const uint2* p, uint32_t (&v)[4]) {
  asm volatile("{\n.reg .b64 x, y;\nld.relaxed.gpu.global.v2.b64 {x, y}, [%4];\nmov.b64 {%0, %1}, x;\nmov.b64 {%2, %3}, y;\n}\n"
    : "=r"(v[0]), "=r"(v[1]), "=r"(v[2]), "=r"(v[3]) : "l"(p) : "memory");
}
__device__ __forceinline__ float untag(uint32_t v) { return __uint_as_float(v & ~15u); }
__device__ __forceinline__ void ll_st3(uint4* p, uint32_t a, uint32_t b, uint32_t c, uint32_t tag) {
  asm volatile("{\n.reg .b64 x, y;\n.reg .b128 z;\nmov.b64 x, {%1, %2};\nmov.b64 y, {%3, %4};\nmov.b128 z, {x, y};\nst.relaxed.gpu.global.b128 [%0], z;\n}\n"
    ::"l"(p), "r"(a), "r"(b), "r"(c), "r"(tag) : "memory");
}
__device__ __forceinline__ uint32_t ll_ld3(const uint4* p, uint32_t& a, uint32_t& b, uint32_t& c, uint32_t tag) {
  uint32_t t;
  asm volatile("{\n.reg .b64 x, y;\n.reg .b128 z;\nld.relaxed.gpu.global.b128 z, [%4];\nmov.b128 {x, y}, z;\nmov.b64 {%0, %1}, x;\nmov.b64 {%2, %3}, y;\n}\n"
    : "=r"(a), "=r"(b), "=r"(c), "=r"(t) : "l"(p) : "memory");
  return t ^ tag;
}
__device__ __forceinline__ void halo_send(uint4* p, uint32_t a, const uint32_t (&tg)[6]) {
  asm volatile("{\n.reg .b64 x<6>, y<6>, w<2>;\n.reg .b32 c<4>;\n.reg .b128 z<6>;\n"
    "ld.shared.b64 w0, [%1+1536];\nld.shared.b64 w1, [%1+1792];\n"
    "ld.shared.b64 x0, [%1];\nld.shared.b64 x1, [%1+256];\nld.shared.b64 x2, [%1+512];\n"
    "ld.shared.b64 x3, [%1+768];\nld.shared.b64 x4, [%1+1024];\nld.shared.b64 x5, [%1+1280];\n"
    "mov.b64 {c0, c1}, w0;\nmov.b64 {c2, c3}, w1;\n"
    "mov.b64 y0, {c0, %2};\nmov.b64 y1, {c1, %3};\nmov.b64 y2, {c2, %4};\nmov.b64 y3, {c3, %5};\nmov.b64 y4, {%6, %6};\nmov.b64 y5, {%7, %7};\n"
    "mov.b128 z0, {x0, y0};\nmov.b128 z1, {x1, y1};\nmov.b128 z2, {x2, y2};\nmov.b128 z3, {x3, y3};\nmov.b128 z4, {x4, y4};\nmov.b128 z5, {x5, y5};\n"
    "st.relaxed.gpu.global.b128 [%0], z0;\nst.relaxed.gpu.global.b128 [%0+512], z1;\nst.relaxed.gpu.global.b128 [%0+1024], z2;\n"
    "st.relaxed.gpu.global.b128 [%0+1536], z3;\nst.relaxed.gpu.global.b128 [%0+2048], z4;\nst.relaxed.gpu.global.b128 [%0+2560], z5;\n}\n"
    ::"l"(p), "r"(a), "r"(tg[0]), "r"(tg[1]), "r"(tg[2]), "r"(tg[3]), "r"(tg[4]), "r"(tg[5]) : "memory");
}
template <int N> __device__ __forceinline__ void copy_out(uint8_t* dst, uint32_t src, int stride) {
  uint4 v[N];
#pragma unroll
  for (int k = 0; k < N; k++) lds128(src + k * stride, v[k].x, v[k].y, v[k].z, v[k].w);
#pragma unroll
  for (int k = 0; k < N; k++) asm volatile("st.global.v4.b32 [%0], {%1, %2, %3, %4};" ::"l"(dst + k * stride), "r"(v[k].x), "r"(v[k].y), "r"(v[k].z), "r"(v[k].w) : "memory");
}
__device__ __forceinline__ void warp_store(uint8_t* dst, uint32_t src, int bytes, uint32_t delay, uint32_t pace) {
  __nanosleep(delay);
#pragma unroll 1
  for (int o = 0; o < bytes; o += 2048) {
    if (pace) __nanosleep(pace);
    uint4 v[4];
#pragma unroll
    for (int k = 0; k < 4; k++) lds128(src + o + k * 512, v[k].x, v[k].y, v[k].z, v[k].w);
#pragma unroll
    for (int k = 0; k < 4; k++) asm volatile("st.global.v4.b32 [%0], {%1, %2, %3, %4};" ::"l"(dst + o + k * 512), "r"(v[k].x), "r"(v[k].y), "r"(v[k].z), "r"(v[k].w) : "memory");
  }
  __syncwarp();
}
__device__ __forceinline__ uint32_t clock32() { uint32_t t; asm volatile("mov.u32 %0, %%clock;" : "=r"(t)); return t; }
__device__ __forceinline__ void flag_set(uint32_t* p, uint32_t bit) { asm volatile("red.release.gpu.global.xor.b32 [%0], %1;" ::"l"(p), "r"(bit) : "memory"); }
__device__ __forceinline__ void flag_wait(const uint32_t* p, uint32_t inv, uint32_t need, uint32_t& ready) {
  if ((ready & need) == need) return;
  uint32_t n = 0;
  do {
    asm volatile("ld.relaxed.gpu.global.b32 %0, [%1];" : "=r"(ready) : "l"(p) : "memory");
    ready = __shfl_sync(0xffffffffu, ready, 0) ^ inv;
  } while ((ready & need) != need && ++n < SPIN_MAX);
  asm volatile("fence.acquire.gpu;\nfence.proxy.async.global;" ::: "memory");
}
__device__ __forceinline__ bool elect_one() {
  uint32_t p;
  asm volatile("{\n.reg .pred P;\nelect.sync _|P, 0xffffffff;\nselp.u32 %0, 1, 0, P;\n}\n" : "=r"(p));
  return p;
}
__device__ __forceinline__ float gelu_half(float hx) {
  const float y = hx * fmaf(hx * hx, 8.f * 0.0356774081f, 2.f * 0.7978845608f);
  float th;
  asm("tanh.approx.f32 %0, %1;" : "=f"(th) : "f"(y));
  return fmaf(hx, th, hx);
}
__device__ __forceinline__ float ex2(float x) { float y; asm("ex2.approx.ftz.f32 %0, %1;" : "=f"(y) : "f"(x)); return y; }

__device__ __forceinline__ void stat_combine(uint32_t am, uint32_t aq, uint32_t bm, uint32_t bq, float pv, float& mean, float& var) {
  const float d0 = untag(am) - pv, d1 = untag(bm) - pv;
  float s = d0 + d1, q = fmaf(fmaf(d0, d0, d1 * d1), 128.f, untag(aq) + untag(bq));
  s += __shfl_xor_sync(0xffffffffu, s, 8); q += __shfl_xor_sync(0xffffffffu, q, 8);
  s += __shfl_xor_sync(0xffffffffu, s, 16); q += __shfl_xor_sync(0xffffffffu, q, 16);
  s *= 0.125f;
  mean = pv + s;
  var = fmaxf(fmaf(-s, s, q * (1.f / D_)), 0.f);
}

__device__ __forceinline__ void attn_probs(const uint32_t* q0, const uint32_t* q1,
                                           const uint32_t* k0, const uint32_t* k1, const uint32_t* k2, const uint32_t* k3,
                                           float sc0, float sc1, bool first, bool e, bool zneg, uint32_t (&pr)[6], float (&l)[2]) {
  float s[4][4];
#pragma unroll
  for (int n = 0; n < 4; n++) {
    const uint32_t* k = n == 0 ? k0 : n == 1 ? k1 : n == 2 ? k2 : k3;
    s[n][0] = s[n][1] = s[n][2] = s[n][3] = 0.f;
    mma16816(s[n], q0[0], q1[0], q0[1], q1[1], k[0], k[1]);
    mma16816(s[n], q0[2], q1[2], q0[3], q1[3], k[2], k[3]);
  }
  const float MASKED = -1.0e9f * 1.4426950409f;
  float a0 = (e ? s[1][1] : s[1][0]) * sc0;
  float b0 = (zneg ? (e ? s[0][1] : s[0][0]) : (e ? s[2][1] : s[2][0])) * sc0;
  float a1 = (e ? s[2][3] : s[2][2]) * sc1;
  float b1 = (zneg ? (e ? s[1][3] : s[1][2]) : (e ? s[3][3] : s[3][2])) * sc1;
  if (first) { a0 = MASKED; if (zneg) { b0 = MASKED; b1 = MASKED; } }
  float m0 = fmaxf(a0, b0), m1 = fmaxf(a1, b1);
  m0 = fmaxf(m0, __shfl_xor_sync(0xffffffffu, m0, 1)); m1 = fmaxf(m1, __shfl_xor_sync(0xffffffffu, m1, 1));
  m0 = fmaxf(m0, __shfl_xor_sync(0xffffffffu, m0, 2)); m1 = fmaxf(m1, __shfl_xor_sync(0xffffffffu, m1, 2));
  a0 = ex2(a0 - m0); b0 = ex2(b0 - m0); a1 = ex2(a1 - m1); b1 = ex2(b1 - m1);
  l[0] = a0 + b0; l[1] = a1 + b1;
  const int sh = e ? 16 : 0;
  const uint32_t pa0 = pack2(a0, 0.f) << sh, pb0 = pack2(b0, 0.f) << sh, pa1 = pack2(a1, 0.f) << sh, pb1 = pack2(b1, 0.f) << sh;
  pr[0] = zneg ? pb0 : 0u; pr[1] = pa0; pr[2] = zneg ? 0u : pb0;
  pr[3] = zneg ? pb1 : 0u; pr[4] = pa1; pr[5] = zneg ? 0u : pb1;
}
__device__ __forceinline__ void attn_pv(const uint32_t (&pr)[6], const uint32_t* vh, const uint32_t* v, float (&o)[4][4]) {
#pragma unroll
  for (int dt = 0; dt < 4; dt++) {
    o[dt][0] = o[dt][1] = o[dt][2] = o[dt][3] = 0.f;
    mma16816(o[dt], pr[0], 0u, pr[1], pr[3], vh[2 * dt], vh[2 * dt + 1]);
    mma16816(o[dt], pr[2], pr[4], 0u, pr[5], v[2 * dt], v[2 * dt + 1]);
  }
}

#define SF 12
#define SLICE 0
#define ATT 24
#define COVER 2
#define S2S 0
#define WGATE 1
#define HALO_A_NS 300
#define H1D 900
#define U0D 300
#define U2D 3000
#define X1D 1200
#define PACE 150
#define LEAD1 3
#define LEAD2 3
#define EARLY 0
#define LEAD3 0
#define DIRECT 7
#define XLD 7
#define XST 3
#define FA 20
#define XPROMO CU_TENSOR_MAP_L2_PROMOTION_L2_128B
#define WPROMO CU_TENSOR_MAP_L2_PROMOTION_L2_128B
#define W2PROMO CU_TENSOR_MAP_L2_PROMOTION_L2_128B
#define HALO_NS 0
#define STAT_CLK 150
__global__ void __cluster_dims__(2, 1, 1) __launch_bounds__(384, 1) fused_kernel(const __grid_constant__ Params P) {
  extern __shared__ __align__(1024) uint8_t smem_raw[];
  const uint32_t sb = smem_u32(smem_raw);
  const uint32_t bars = sb + OFF_BAR;
  const int tid = threadIdx.x;
  const int wu = __shfl_sync(0xffffffffu, tid >> 5, 0), wg = wu >> 2;
  const int r = blockIdx.x & 1, cl = blockIdx.x >> 1;
  int grp, slt;
  if (cl < 4) { grp = 0; slt = 4 + cl; }
  else if (cl < 36) { grp = (cl - 4) & 7; slt = (cl - 4) >> 3; }
  else { grp = 1 + (cl - 36) % 7; slt = 4 + (cl - 36) / 7; }
#define MAP 0
  const int m = grp, j = slt;
  const int i = 2 * m + r;
  auto BAR = [&](int k) { return bars + 8 * k; };

  auto kb1 = [&](int n) { const int h = n >= 9, t = n - 2 - 7 * h; return n < 2 ? 2 * j + n : 2 * (t + (t >= j)) + h; };
  if (wu == 8) {
    if (elect_one()) {
      asm volatile("prefetch.tensormap [%0];" ::"l"(&P.x0) : "memory");
      asm volatile("prefetch.tensormap [%0];" ::"l"(&P.wqkv) : "memory");
#pragma unroll
      for (int k = 0; k < 6; k++) mbar_init(BAR(k < 4 ? F1 + k : XF + k - 4), 1);
      asm volatile("fence.mbarrier_init.release.cluster;" ::: "memory");
      fence_async_smem();
    }
    __syncwarp();
  } else if (wu == 0) {
    if (elect_one()) {
#pragma unroll
      for (int k = E1; k < 64; k++) {
        int cnt = 1;
        if (k < F2 || (k >= E2 && k < F3) || (k >= E3 && k < F4) || (k >= E4 && k < JOB) || k == JOB + 2 || k == JOB + 3) cnt = 4;
        else if ((k >= JOB && k < RD) || k == CSJ) cnt = 8;
        else if ((k >= RD && k < RD + 4) || k == STD || k == STAT || k >= HALO) cnt = 2;
        if (k != XF && k != XF + 1) mbar_init(BAR(k), cnt);
      }
      asm volatile("fence.mbarrier_init.release.cluster;" ::: "memory");
      fence_async_smem();
    }
    __syncwarp();
  }
  auto load_tag = [&]() { uint32_t t; asm volatile("ld.relaxed.gpu.global.u32 %0, [%1];" : "=r"(t) : "l"(&gEpoch) : "memory"); return t + 1; };
  TS(0);
  if (wu == 8) nb_arrive<NB_INIT>(384); else nb_sync<NB_INIT>(384);
  asm volatile("barrier.cluster.arrive.relaxed;" ::: "memory");

  if (wg == 2) {
    reg_dealloc<40>();
    if (wu == 8) {
    if (elect_one()) {
#pragma unroll 1
      for (int u = 0; u < 4; u++) {
        const int kb = u;
        mbar_expect(BAR(F1 + u), 40960);
        tma2d(sb + slot1(u), &P.x0, BAR(F1 + u), kb * 64, 128 * i);
        tma3d(sb + slot1(u) + 16384, &P.wqkv, BAR(F1 + u), 128 * j, kb * 64, 0);
        tma3d(sb + slot1(u) + 28672, &P.wqkv, BAR(F1 + u), 128 * j, kb * 64 + 32, 0);
      }
    }
    __syncwarp();
    }
    asm volatile("barrier.cluster.wait;" ::: "memory");
    auto kb3 = [&](int n) { const int h = n >= 17, t = S2S ? n - 3 - 14 * h : n - 2 - 15 * h; return n < 2 ? 2 * i + n : (n == (S2S ? 2 : 16) || n == 31) ? 2 * (i ^ 1) + h : 2 * ((2 * m + 2 + t) & 15) + h; };
    auto kb2 = [&](int n) { return n < 8 ? 2 * n : n == 8 ? 2 * j + 1 : 2 * (n - 9 + (n - 9 >= j)) + 1; };
    if (wu == 8) {
#pragma unroll 1
      for (int L = 0; L < 2; L++) {
#pragma unroll 1
        for (int u = L ? 0 : 4; u < 32; u++) {
          const int v = (L && u >= 2 && u < 18) ? (u < 4 ? u + 14 : u - 2) : u;
          const int p = u & 3, ab = v >> 4, nn = v & 15;
          if (u >= 4) mbar_wait(BAR(E1 + p), ((u >> 2) - 1) & 1);
          else mbar_wait(BAR(E4 + (u == 3 ? 0 : u + 3)), u == 3);
          if (elect_one()) {
            mbar_expect(BAR(F1 + p), nn < 2 ? 24576 : 40960);
            tma3d_mc(sb + slot1(p) + 16384 + r * 12288, &P.wqkv, BAR(F1 + p), 128 * j + 64 * ab, (L | ab ? kb1(nn) : nn) * 64 + 32 * r, 0);
          }
        }
        int p = 0; uint32_t par = L ? 0x1e : 0;
#pragma unroll 1
        for (int n = 0; n < 16; n++) {
          if (n >= 5) { mbar_wait(BAR(E2 + p), (par >> p) & 1); par ^= 1u << p; }
          else if (n < 4) mbar_wait(BAR(E1 + n), 1);
          if (elect_one()) {
            mbar_expect(BAR(F2 + p), n == 8 ? 16384 : 32768);
            tma2d_mc(sb + slot2(p) + 16384 + r * 8192, &P.wo, BAR(F2 + p), 128 * j + 64 * r, kb2(n) * 64);
          }
          if (++p == 5) p = 0;
        }
#pragma unroll 1
        for (int u = 0; u < 32; u++) {
          const int n = u < 4 ? (0x2031 >> (4 * u)) & 3 : u, p = n & 3, kb = kb3(n);
          if (WGATE && n == 4) mbar_wait(BAR(RD + 4), L);
          if (n >= 4) mbar_wait(BAR(E3 + p), ((n >> 2) - 1) & 1);
          else if (n == 1) mbar_wait(BAR(STD + 1), L);
          else if (n == 3) mbar_wait(BAR(E2 + 2), L);
          else if (n == 0) mbar_wait(BAR(E2 + 4), L);
          else mbar_wait(BAR(E2 + 0), 1);
          if (elect_one()) {
            mbar_expect(BAR(F3 + p), n < 2 ? 32768 : 49152);
            tma3d(sb + slot3(p) + 16384, &P.w1, BAR(F3 + p), 0, kb * 64, 7 * m + 4 * r);
            tma3d(sb + slot3(p) + 40960, &P.w1h, BAR(F3 + p), 0, kb * 64, 14 * m + 6 + r);
          }
        }
#pragma unroll 1
        for (int n = 0; n < 6; n++) {
          if (n < 3) mbar_wait(BAR(E3 + n), 1);
          else if (n == 4) mbar_wait(BAR(E3 + 3), 1);
          if (elect_one()) {
            mbar_expect(BAR(F4 + n), n < 3 ? 16384 : 32768);
            tma3d(sb + slot4(n), &P.w2, BAR(F4 + n), 0, (n < 3 ? 7 * m + 4 * r + (n == 2 ? 0 : n + 1) : 7 * ((m + n - 2) & 7) + 3) * 64, 2 * i);
          }
        }
        p = 0; par = L ? 0x3c : 0;
        auto g4w = [&](int kb) {
          mbar_wait(BAR(E4 + p), (par >> p) & 1); par ^= 1u << p;
          if (elect_one()) {
            mbar_expect(BAR(F4 + p), 32768);
            tma3d(sb + slot4(p), &P.w2, BAR(F4 + p), 0, kb * 64, 2 * i);
          }
          if (++p == 6) p = 0;
        };
#pragma unroll 1
        for (int t = 4; t < 9; t++) g4w(7 * ((m + t) & 7) + 3);
#pragma unroll 1
        for (int c = 0; c < 3; c++)
#pragma unroll 1
          for (int t = 0; t < 15; t++) { const int ii = t < 14 ? (2 * m + 2 + t) & 15 : i ^ 1; g4w(((7 * ii + 1) >> 1) + c); }
      }
    } else if (wu == 9) {
      uint32_t inv = 0;
#pragma unroll 1
      for (int L = 0; L < 2; L++) {
        uint32_t ready = 0;
#pragma unroll 1
        for (int u = 4; u < 32; u++) {
          const int p = u & 3, nn = (L && u < 18 ? u - 2 : u) & 15, kb = (L || u >= 16) ? kb1(nn) : nn;
          if (L == 0 && (u == XLD || u == XLD + XST) && elect_one()) {
            const int h = u != XLD;
            mbar_expect(BAR(XF + h), 16384);
            tma2d(sb + OFF_X + h * 16384, &P.x0, BAR(XF + h), 128 * j + 64 * h, 128 * i);
          }
          if (nn < 2) continue;
          if (L && u < 12) mbar_wait(BAR(F1 + p), u >> 3);
          if (u >= 4 + 4 * L) mbar_wait(BAR(E1 + p), ((u >> 2) - 1) & 1);
          if (L) {
            flag_wait(gFlag[0][0][i], inv, 1u << kb, ready);
            if (elect_one()) bulk_ld(sb + slot1(p), gXB + (i * 16 + kb) * 16384, 16384, BAR(F1 + p));
          } else if (elect_one()) tma2d(sb + slot1(p), &P.x0, BAR(F1 + p), kb * 64, 128 * i);
        }
        ready = 0;
        if (L == 0) inv = (__shfl_sync(0xffffffffu, load_tag(), 0) & 1) - 1;
        int p = 0; uint32_t par = L ? 0x1e : 0;
#pragma unroll 1
        for (int n = 0; n < 16; n++) {
          const int hp = kb2(n);
          if (n == 8) { par ^= 8; p = 4; continue; }
          if (n >= 5) { mbar_wait(BAR(E2 + p), (par >> p) & 1); par ^= 1u << p; }
          else if (n < 4) mbar_wait(BAR(E1 + n), 1);
          flag_wait(gFlag[L][1][i], inv, 1u << hp, ready);
          if (n == 9) ST(4);
          if (elect_one()) bulk_ld(sb + slot2(p), gOB + (i * 16 + hp) * 16384, 16384, BAR(F2 + p));
          if (++p == 5) p = 0;
        }
        ready = 0;
        mbar_wait(BAR(E2 + 0), 1);
#pragma unroll 1
        for (int n = 2 + S2S; n < 32; n++) {
          const int p = n & 3, kb = kb3(n);
          if (n > 3) mbar_wait(BAR(E3 + p), ((n >> 2) - 1) & 1);
          flag_wait(gFlag[L][2][j], inv, 1u << kb, ready);
          if (n == 2 + S2S) ST(12);
          if (elect_one()) {
            const uint8_t* src = gHB + (j * 32 + kb) * 16384;
            if (n < 31 && (S2S || n != 16)) bulk_ld_mc(sb + slot3(p) + r * 8192, src + r * 8192, 8192, BAR(F3 + p));
            else bulk_ld(sb + slot3(p), src, 16384, BAR(F3 + p));
          }
        }
        ready = 0; p = 3; par = L ? 0x3c : 0;
        mbar_wait(BAR(E3 + 3), 1);
#pragma unroll 1
        for (int t = 0; t < 8; t++) {
          const int mm = (m + t + 1) & 7;
          if (t == 2 || t == 5) mbar_wait(BAR(RD + (t == 2 ? 3 : 2)), L);
          if (t >= 3) { mbar_wait(BAR(E4 + p), (par >> p) & 1); par ^= 1u << p; }
          flag_wait(gFlag[L][6][j], inv, 3u << (2 * mm), ready);
          if (t == 0) ST(20);
          if (elect_one()) bulk_ld_mc(sb + slot4(p) + 16384 + r * 8192, gUB + (j * 56 + 48 + mm) * 16384 + r * 8192, 8192, BAR(F4 + p));
          if (++p == 6) p = 0;
        }
#pragma unroll 1
        for (int c = 0; c < 3; c++) {
          ready = 0;
#pragma unroll 1
          for (int t = 0; t < 15; t++) {
            const int ii = t < 14 ? (2 * m + 2 + t) & 15 : i ^ 1;
            mbar_wait(BAR(E4 + p), (par >> p) & 1); par ^= 1u << p;
            flag_wait(gFlag[L][3 + c][j], inv, 1u << ii, ready);
            if (elect_one()) {
              const uint8_t* src = gUB + (j * 56 + 16 * c + ii) * 16384;
              if (t < 14) bulk_ld_mc(sb + slot4(p) + 16384 + r * 8192, src + r * 8192, 8192, BAR(F4 + p));
              else bulk_ld(sb + slot4(p) + 16384, src, 16384, BAR(F4 + p));
            }
            if (++p == 6) p = 0;
          }
        }
      }
    } else {
      const int h = wu - 10, i0 = i, j0 = j;
      {
      const uint32_t tag = load_tag();
      int lane = tid & 31, i = i0, j = j0;
#define FRESH asm volatile("" : "+r"(lane), "+r"(i), "+r"(j))
      const uint32_t rs = mapa(sb, r ^ 1), rb = rs + OFF_BAR;
      auto signal = [&](int k) { if (lane == 0) mbar_arrive(BAR(k)); };
      auto drained = [&](int k) { if (lane == 0) { mbar_arrive(BAR(RD + k)); mbar_arrive_cl(rb + 8 * (RD + k)); } };
      auto publish = [&](uint32_t* f, int bit) { if (lane == 0) flag_set(f, 1u << bit); __syncwarp(); };
      for (int c = 32 * h + lane; c < 288; c += 64)
        sts16(sb + OFF_B1 + 2 * c, c >= 224 ? 0u : pack2(0.5f * __bfloat162float(P.b1[c < 192 ? 64 * (7 * m + 4 * r) + c : 64 * (7 * m + 3) + 32 * r + c - 192]), 0.f));
      if (h == 0) sts32f(sb + OFF_CS + 768 + 4 * lane, 0.f);
#pragma unroll 1
      for (int L = 0; L < 2; L++) {
        FRESH;
        if (L == 0) {
          mbar_wait(BAR(CSJ), 0);
          float c0 = 0.f, c1 = 0.f, c2 = 0.f;
          const uint32_t a = sb + OFF_STG + (32 * h + lane) * 4;
#pragma unroll 8
          for (int k = 0; k < 32; k++) { c0 += lds32f(a + k * 784); c1 += lds32f(a + k * 784 + 256); c2 += lds32f(a + k * 784 + 512); }
          ll_st3(&gCS[j][i][32 * h + lane], __float_as_uint(c0), __float_as_uint(c1), __float_as_uint(c2), tag);
          __nanosleep(500);
        }
        FRESH;
        if (L == 0) {
#pragma unroll 1
          for (int ab = 0; ab < 2; ab++) {
            float c0 = 0.f, c1 = 0.f, c2 = 0.f;
#pragma unroll 1
            for (int b4 = 0; b4 < 8; b4 += 4) {
              uint32_t a[4], b[4], c[4], n = 0, bad;
              do {
                bad = 0;
#pragma unroll
                for (int e = 0; e < 4; e++) bad |= ll_ld3(&gCS[j][2 * (b4 + e) + ab][32 * h + lane], a[e], b[e], c[e], tag);
              } while (bad && ++n < SPIN_MAX);
#pragma unroll
              for (int e = 0; e < 4; e++) { c0 += __uint_as_float(a[e]); c1 += __uint_as_float(b[e]); c2 += __uint_as_float(c[e]); }
            }
            const uint32_t a = sb + OFF_CS + ab * 768 + (4 * h + (lane >> 3)) * 32 + (lane & 7) * 2;
            const uint32_t h0 = pack2(c0, 0.f), h1 = pack2(c1, 0.f), h2 = pack2(c2, 0.f);
            sts16(a, h0); sts16(a + 256, h1); sts16(a + 512, h2);
            sts16(a + 16, pack2(c0 - bf_lo(h0), 0.f)); sts16(a + 272, pack2(c1 - bf_lo(h1), 0.f)); sts16(a + 528, pack2(c2 - bf_lo(h2), 0.f));
            fence_async_smem();
            __syncwarp();
            if (ab == 0) signal(STAT);
          }
        }
#pragma unroll 1
        for (int ab = 0; ab < 2; ab++) {
          FRESH;
          uint32_t v[18], tg[6];
          const uint32_t xs = sb + OFF_STG + h * 16384 + lane * 8;
          uint4* hp = &gHalo[L][i][j][6 * h][lane];
#pragma unroll
          for (int c = 0; c < 6; c++) { tg[c] = (2 * tag + ab) * 8 + c; asm volatile("" : "+r"(tg[c])); }
          asm volatile("" : "+l"(hp));
          mbar_wait(BAR(FOLD + ab), L);
          if (ab && h == 0) ST(6);
          if (i < 15) {
            halo_send(hp, xs, tg);
          }
          if (ab && h == 0) ST(26);
          if (i > 0) {
            if (!ab) __nanosleep(HALO_A_NS);
            uint32_t n = 0, bad;
            do {
              bad = 0;
#pragma unroll
              for (int c = 0; c < 6; c++) bad |= ll_ld3(hp + c * 32 - 8 * 12 * 32, v[3 * c], v[3 * c + 1], v[3 * c + 2], (2 * tag + ab) * 8);
              if (ab && h == 0 && n == 0) ST(28);
            } while (bad > 7 && ++n < SPIN_MAX);
            if (ab && h == 0) ST(27);
          } else {
#pragma unroll
            for (int c = 0; c < 18; c++) v[c] = 0u;
          }
#pragma unroll
          for (int c = 0; c < 6; c++) sts64f(xs + c * 256, __uint_as_float(v[3 * c]), __uint_as_float(v[3 * c + 1]));
          sts64f(xs + 1536, __uint_as_float(v[2]), __uint_as_float(v[5]));
          sts64f(xs + 1792, __uint_as_float(v[8]), __uint_as_float(v[11]));
          __syncwarp();
          signal(HALO + ab);
          if (ab && h == 0) ST(7);
          FRESH;
          if (ab == 0 && lane == 0) asm volatile("st.relaxed.gpu.global.u32 [%0], %1;" ::"l"(&gAck[L][i][j][h][0]), "r"(tag) : "memory");
          mbar_wait(BAR(JOB + ab), L);
          if (h == 0) {
            if (ab) ST(1);
            if (lane == 0) { bulk_st(gOB + (i * 16 + 2 * j + ab) * 16384, sb + OFF_STG, 16384); bulk_commit(); bulk_wait0(); }
            signal(STD + ab);
            if (ab) ST(2);
            publish(gFlag[L][1][i], 2 * j + ab);
            if (ab) ST(3);
          } else if (ab == 0) {
            if (i < 15 && lane < 2) {
              uint32_t t, n = 0;
              do { asm volatile("ld.relaxed.gpu.global.u32 %0, [%1];" : "=r"(t) : "l"(&gAck[L][i + 1][j][lane][0]) : "memory"); } while (t != tag && ++n < SPIN_MAX);
            }
            __syncwarp();
            signal(STD);
          }
        }
        FRESH;
        if (h == 0) {
          mbar_wait(BAR(JOB + 2), L);
          ST(9);
          if (!(DIRECT & 1) && lane == 0) { bulk_st(gHB + (j * 32 + 2 * i) * 16384, sb + OFF_X, 16384); bulk_commit(); bulk_wait0(); }
          signal(RD);
          ST(10);
          publish(gFlag[L][2][j], 2 * i);
          ST(11);
          signal(RD + 4);
          nb_arrive<NB_HELP>(64);
        } else {
          mbar_wait(BAR(JOB + 3), L);
          nb_sync<NB_HELP>(64);
          warp_store(gHB + (j * 32 + 2 * i + 1) * 16384 + lane * 16, sb + lane * 16 + OFF_X + 16384, 16384, H1D, PACE);
          signal(RD);
          ST(15);
          publish(gFlag[L][2][j], 2 * i + 1);
        }
        FRESH;
        if (h == 0) {
          mbar_wait(BAR(JOB + 7), L);
          ST(17);
          if (!(DIRECT & 2) && lane == 0) {
            for (int a = 0; a < 2; a++) bulk_st(gUB + (j * 56 + 48 + (i >> 1)) * 16384 + a * 8192 + r * 4096, sb + slot4(5) + 16384 + a * 8192, 4096);
            bulk_commit(); bulk_wait0();
          }
          drained(3);
          ST(18);
          publish(gFlag[L][6][j], i);
          ST(19);
        }
        mbar_wait(BAR(JOB + 6), L);
        if (h == 1) {
          warp_store(gUB + (j * 56 + i) * 16384 + lane * 16, sb + lane * 16 + slot4(2) + 16384, 16384, U0D, 0);
          drained(2); ST(25);
          publish(gFlag[L][3][j], i);
        }
        nb_sync<NB_HELP>(64);
        warp_store(gUB + (j * 56 + 16 + 16 * h + i) * 16384 + lane * 16, sb + lane * 16 + OFF_X + h * 16384, 16384, h ? U2D : 0, PACE);
        ST(23 + h);
        signal(RD + 1);
        publish(gFlag[L][4 + h][j], i);
        FRESH;
        mbar_wait(BAR(JOB + 8 + h), L);
        if (L == 0) {
          if (!(DIRECT & 4) && h == 0 && lane == 0) { bulk_st(gXB + (i * 16 + 2 * j) * 16384, sb + OFF_X, 16384); bulk_commit(); bulk_wait0(); }
          __syncwarp();
          nb_sync<NB_HELP>(64);
          if (h == 1) warp_store(gXB + (i * 16 + 2 * j + 1) * 16384 + lane * 16, sb + lane * 16 + OFF_X + 16384, 16384, X1D, 0);
          publish(gFlag[0][0][i], 2 * j + h);
        } else if (lane == 0) {
          tma2d_store(&P.out, sb + OFF_X + h * 16384, 128 * j + 64 * h, 128 * i);
          bulk_commit(); bulk_wait0();
        }
      }
      if (blockIdx.x == 0 && h == 0 && lane == 0) asm volatile("st.relaxed.gpu.global.u32 [%0], %1;" ::"l"(&gEpoch), "r"(tag) : "memory");
      }
    }
    __syncwarp();
    cluster_bar();
  } else {
    reg_alloc<232>();
    asm volatile("barrier.cluster.wait;" ::: "memory");
    const uint32_t rbars = mapa(bars, tid & 1);
    const bool relp = (tid & 127) < 2;
    uint32_t tag;
    asm volatile("ld.relaxed.gpu.global.u32 %0, [%1];" : "=r"(tag) : "l"(&gEpoch + (fresh_tid() >> 10)) : "memory");
    auto release = [&](int k) { if (relp) mbar_arrive_cl(rbars + 8 * k); };
    auto signal = [&](int k) { __syncwarp(); if ((fresh_tid() & 31) == 0) mbar_arrive(BAR(k)); };
#define GEOM const int t7 = fresh_tid() & 127, lane = t7 & 31, w = t7 >> 5, g = lane >> 2, q = lane & 3, \
                       lr = lane & 15, lt = lane >> 4, l7 = lane & 7; (void)w; (void)g; (void)q; (void)lr; (void)lt; (void)l7

#pragma unroll 1
    for (int L = 0; L < 2; L++) {
      float acca[96], accb[96], xa[64], acc3[112];
      float nmean0, nmean1, rstd0, rstd1;
      uint16_t b2a, b2b;
      uint32_t Q[2][8], K[2][8], V[16];
      auto g1_issue = [&](float (&acc)[96], uint32_t a, uint32_t st, auto first) {
        const uint64_t da = mkdesc(a + wg * 8192, 16, 1024), db = mkdesc(st + 16384, 4096, 1024);
        wg_fence();
#pragma unroll
        for (int kk = 0; kk < 4; kk++) {
          const uint64_t b = db + (((kk >> 1) * 12288 + (kk & 1) * 2048) >> 4);
          if (first.value && kk == 0) wgmma_192z<0, 1>(acc, da, b); else wgmma_192<0, 1>(acc, da + kk * 2, b);
        }
        wg_commit();
      };
      auto g1_step = [&](float (&acc)[96], int u, bool rel) {
        const int p = u & 3;
        mbar_wait(BAR(F1 + p), (u >> 2) & 1);
        KB(u);
        g1_issue(acc, sb + slot1(p), sb + slot1(p), False{});
        if (LEAD1 && u == 31 && wg == 1) nb_arrive<NB_LEAD>(256);
        wg_wait<1>();
        if (rel) release(E1 + ((u - 1) & 3));
      };
      auto g1_loop = [&](float (&acc)[96], int u0, int u1, int urel) {
#pragma unroll 1
        for (int u = u0; u < u1; u++) g1_step(acc, u, u > urel);
      };
      auto load_x = [&]() {
        GEOM;
#pragma unroll
        for (int t = 0; t < 16; t += 2) {
          uint32_t v0, v1, v2, v3;
          ldsm4(sb + OFF_X + (t >> 3) * 16384 + (16 * wu + lr) * 128 + ((((t & 7) + lt) ^ l7) << 4), v0, v1, v2, v3);
          xa[4 * t + 0] = bf_lo(v0); xa[4 * t + 1] = bf_hi(v0); xa[4 * t + 2] = bf_lo(v1); xa[4 * t + 3] = bf_hi(v1);
          xa[4 * t + 4] = bf_lo(v2); xa[4 * t + 5] = bf_hi(v2); xa[4 * t + 6] = bf_lo(v3); xa[4 * t + 7] = bf_hi(v3);
        }
      };
      auto stat_publish = [&](float s0, float q0, float s2, float q2, uint32_t tg) {
        GEOM;
        const bool h1 = q & 1;
        float sm = (h1 ? s2 : s0) + __shfl_xor_sync(0xffffffffu, h1 ? s0 : s2, 1);
        float sq = (h1 ? q2 : q0) + __shfl_xor_sync(0xffffffffu, h1 ? q0 : q2, 1);
        sm += __shfl_xor_sync(0xffffffffu, sm, 2); sq += __shfl_xor_sync(0xffffffffu, sq, 2);
        if (q < 2) stat_st(&gST[0][0][0][0][0] + (((L * 16 + opq(i)) * 8 + wu) * 8 + j) * 16 + 2 * g + q, sm, sq, tg);
        return sm;
      };
      auto g1_stats = [&](int u0) {
        GEOM;
        const uint32_t xr = sb + OFF_X + (16 * wu + lr) * 128;
        float s0 = 0.f, q0 = 0.f, s2 = 0.f, q2 = 0.f;
        uint32_t v[8] = {0u, 0u, 0u, 0u, 0u, 0u, 0u, 0u};
#pragma unroll 1
        for (int k = 0; k < 5; k++) {
#pragma unroll
          for (int e = 0; e < 8; e += 2) {
            const float a = bf_lo(v[e]), b = bf_hi(v[e]), c = bf_lo(v[e + 1]), d = bf_hi(v[e + 1]);
            s0 += a + b; q0 = fmaf(a, a, fmaf(b, b, q0)); s2 += c + d; q2 = fmaf(c, c, fmaf(d, d, q2));
          }
          if (k == 4) break;
          const uint32_t o = ((2 * k + lt) ^ l7) << 4;
          ldsm4(xr + o, v[0], v[1], v[2], v[3]);
          ldsm4(xr + o + 16384, v[4], v[5], v[6], v[7]);
          g1_step(acca, u0 + k, true);
        }
        stat_publish(s0, q0, s2, q2, 2 * (tag + 1));
      };
      uint32_t sv0[4], sv1[4];
      auto stat_fetch = [&]() {
        const uint2* sp = &gST[0][0][0][0][0] + ((L * 16 + opq(i)) * 8 + wu) * 128 + 2 * (fresh_tid() & 31);
        stat_ld2(sp, sv0); stat_ld2(sp + 64, sv1);
      };
      auto stat_await = [&](uint32_t tg) {
#pragma unroll 1
        for (uint32_t n = 0; (((sv0[0] ^ tg) | (sv0[2] ^ tg) | (sv1[0] ^ tg) | (sv1[2] ^ tg)) & 15u) && n < SPIN_MAX; n++) stat_fetch();
        __syncwarp();
      };
      auto ln_stats = [&]() {
        GEOM;
        stat_await(2 * (tag + 1));
        float mean0, var0, mean1, var1;
        stat_combine(sv0[0], sv0[1], sv1[0], sv1[1], untag(__shfl_sync(0xffffffffu, sv0[0], l7)), mean0, var0);
        stat_combine(sv0[2], sv0[3], sv1[2], sv1[3], untag(__shfl_sync(0xffffffffu, sv0[2], l7)), mean1, var1);
        nmean0 = -__shfl_sync(0xffffffffu, mean0, g); rstd0 = rsq(__shfl_sync(0xffffffffu, var0, g) + 1e-5f);
        nmean1 = -__shfl_sync(0xffffffffu, mean1, g); rstd1 = rsq(__shfl_sync(0xffffffffu, var1, g) + 1e-5f);
      };
      auto center = [&](float (&acc)[96], int ab) {
        const bool q0 = (fresh_tid() & 3) == 0;
        const uint32_t h0 = pack2(nmean0, nmean0), h1 = pack2(nmean1, nmean1);
        const float l0 = nmean0 - bf_lo(h0), l1 = nmean1 - bf_lo(h1);
        const uint32_t a0 = q0 ? h0 : 0u, a1 = q0 ? h1 : 0u, a2 = q0 ? pack2(l0, l0) : 0u, a3 = q0 ? pack2(l1, l1) : 0u;
        wg_fence();
        wgmma_rs_192(acc, a0, a1, a2, a3, mkdesc_vec(sb + OFF_CS + ab * 768, 32));
      };
      auto frag = [&](float (&acc)[96], int t, uint32_t& p0, uint32_t& p1) {
        if (t >= 8) { p0 = pack2(acc[4 * t] * rstd0, acc[4 * t + 1] * rstd0); p1 = pack2(acc[4 * t + 2] * rstd1, acc[4 * t + 3] * rstd1); }
        else { p0 = pack2(acc[4 * t], acc[4 * t + 1]); p1 = pack2(acc[4 * t + 2], acc[4 * t + 3]); }
      };
      auto fold_v = [&](float (&acc)[96]) {
        GEOM;
        const uint32_t a = sb + OFF_STG + 16384 + ((wu + 1) & 7) * 2048 + lr * 128;
#pragma unroll
        for (int t = 0; t < 8; t += 2) {
          uint32_t p0, p1, p2, p3;
          frag(acc, 16 + t, p0, p1); frag(acc, 17 + t, p2, p3);
          stsm4(a + (((t + lt) ^ l7) << 4), p0, p1, p2, p3);
        }
        __syncwarp();
#pragma unroll
        for (int t = 0; t < 8; t += 2) ldsm4t(a + (((t + lt) ^ l7) << 4), V[2 * t], V[2 * t + 1], V[2 * t + 2], V[2 * t + 3]);
      };
      auto fold_k = [&](float (&acc)[96], int ab) {
        GEOM;
#pragma unroll
        for (int t = 8; t < 16; t++) frag(acc, t, K[0][t - 8], K[1][t - 8]);
        const uint32_t a = sb + OFF_STG + ((wu + 1) & 7) * 2048 + lane * 16;
#pragma unroll
        for (int c = 0; c < 4; c++)
          sts128(a + c * 512, K[c >> 1][4 * (c & 1)], K[c >> 1][4 * (c & 1) + 1], K[c >> 1][4 * (c & 1) + 2], K[c >> 1][4 * (c & 1) + 3]);
        if (wu == 7) signal(FOLD + ab);
      };
      auto fold_q = [&](float (&acc)[96]) {
#pragma unroll
        for (int t = 0; t < 8; t++) frag(acc, t, Q[0][t], Q[1][t]);
      };
      auto attend = [&](int ab, auto drain, auto resume) {
        GEOM;
        nb_sync<NB_BOTH>(256);
        const uint32_t xa_ = sb + OFF_STG + wu * 2048 + lane * 16;
        if (wu == 0) mbar_wait(BAR(HALO + ab), L);
        uint32_t KH[2][8], VH[16];
#pragma unroll
        for (int c = 0; c < 4; c++) {
          lds128(xa_ + c * 512, KH[c >> 1][4 * (c & 1)], KH[c >> 1][4 * (c & 1) + 1], KH[c >> 1][4 * (c & 1) + 2], KH[c >> 1][4 * (c & 1) + 3]);
          ldsm4t(sb + OFF_STG + 16384 + wu * 2048 + lr * 128 + (((2 * c + lt) ^ l7) << 4), VH[4 * c], VH[4 * c + 1], VH[4 * c + 2], VH[4 * c + 3]);
        }
        TS2(11 + ab + 32 * L);
        drain();
        if (SF & 4) sched_fence(P.zero);
        const bool e = g & 1, zneg = (g >> 1) < q, first = (i == 0) && (wu == 0);
        const float qs = 0.17677669530f * 1.4426950409f;
        uint32_t pr[2][6];
        float l[2][2];
#pragma unroll
        for (int hh = 0; hh < 2; hh++)
          attn_probs(&Q[0][4 * hh], &Q[1][4 * hh], &KH[0][4 * hh], &KH[1][4 * hh], &K[0][4 * hh], &K[1][4 * hh], rstd0 * qs, rstd1 * qs, first, e, zneg, pr[hh], l[hh]);
        float o[2][4][4];
#pragma unroll
        for (int hh = 0; hh < 2; hh++) attn_pv(pr[hh], &VH[8 * hh], &V[8 * hh], o[hh]);
        const bool early = (EARLY >> ab) & 1;
        if (early) { sched_fence(P.zero); nb_sync<NB_BOTH>(256); resume(); sched_fence(P.zero); }
#pragma unroll
        for (int hh = 0; hh < 2; hh++) {
          float l0 = l[hh][0], l1 = l[hh][1];
          l0 += __shfl_xor_sync(0xffffffffu, l0, 1); l1 += __shfl_xor_sync(0xffffffffu, l1, 1);
          l0 += __shfl_xor_sync(0xffffffffu, l0, 2); l1 += __shfl_xor_sync(0xffffffffu, l1, 2);
          asm("rcp.approx.ftz.f32 %0, %0;" : "+f"(l0)); asm("rcp.approx.ftz.f32 %0, %0;" : "+f"(l1));
#pragma unroll
          for (int dt = 0; dt < 4; dt += 2)
            stsm4(sb + OFF_STG + (16 * wu + lr) * 128 + (((4 * hh + dt + lt) ^ l7) << 4),
                  pack2(o[hh][dt][0] * l0, o[hh][dt][1] * l0), pack2(o[hh][dt][2] * l1, o[hh][dt][3] * l1),
                  pack2(o[hh][dt + 1][0] * l0, o[hh][dt + 1][1] * l0), pack2(o[hh][dt + 1][2] * l1, o[hh][dt + 1][3] * l1));
        }
        fence_async_smem();
        signal(JOB + ab);
        if (!early) { nb_sync<NB_BOTH>(256); resume(); }
      };

      TS(1 + 32 * L);
      mbar_wait(BAR(F1), 0); KB(0);    g1_issue(acca, L ? sb + OFF_X : sb + slot1(0), sb + slot1(0), True{});
      mbar_wait(BAR(F1 + 1), 0); KB(1); g1_issue(acca, L ? sb + OFF_X + 16384 : sb + slot1(1), sb + slot1(1), False{});
      wg_wait<1>(); release(E1 + 0);
      auto g1_bhead = [&](int p) {
        mbar_wait(BAR(F1 + p), 0); KB(p ? 2 : 16); g1_issue(accb, sb + OFF_X, sb + slot1(p), True{});
        if (p) { wg_wait<1>(); release(E1 + 1); }
        mbar_wait(BAR(F1 + p + 1), 0); KB(p ? 3 : 17); g1_issue(accb, sb + OFF_X + 16384, sb + slot1(p + 1), False{});
        wg_wait<1>(); release(E1 + p);
      };
      if (L == 0) {
        GEOM;
        const bf16* wp = P.wqkv_p + ((128 * opq(m) + 16 * wg + (t7 >> 3)) * 3072 + 128 * opq(j) + 64 * r + l7 * 8);
        const uint32_t ca = sb + OFF_STG + (16 * wg + (t7 >> 3)) * 784 + l7 * 32;
#pragma unroll 1
        for (int p = 0; p < 3; p++) {
          uint4 wv[4];
#pragma unroll
          for (int k = 0; k < 4; k++)
            asm volatile("ld.global.nc.v4.u32 {%0, %1, %2, %3}, [%4];" : "=r"(wv[k].x), "=r"(wv[k].y), "=r"(wv[k].z), "=r"(wv[k].w)
                         : "l"(wp + k * 32 * 3072 + p * 1024));
          g1_loop(acca, 2 + 3 * p, 5 + 3 * p, 0);
          float cs[8];
#pragma unroll
          for (int k = 0; k < 4; k++) {
            const uint4 v = wv[k];
            const float t[8] = {bf_lo(v.x), bf_hi(v.x), bf_lo(v.y), bf_hi(v.y), bf_lo(v.z), bf_hi(v.z), bf_lo(v.w), bf_hi(v.w)};
#pragma unroll
            for (int e = 0; e < 8; e++) cs[e] = k ? cs[e] + t[e] : t[e];
          }
          sts128(ca + p * 256, __float_as_uint(cs[0]), __float_as_uint(cs[1]), __float_as_uint(cs[2]), __float_as_uint(cs[3]));
          sts128(ca + p * 256 + 16, __float_as_uint(cs[4]), __float_as_uint(cs[5]), __float_as_uint(cs[6]), __float_as_uint(cs[7]));
        }
        signal(CSJ);
        g1_step(acca, 11, true);
        mbar_wait(BAR(XF), 0); mbar_wait(BAR(XF + 1), 0);
        g1_stats(12);
        wg_wait<0>(); release(E1 + 3);
        fence_regs(acca);
        g1_bhead(0);
      } else {
        g1_bhead(2);
        g1_stats(4);
        g1_loop(acca, 8, 18, 0);
      }
      stat_fetch();
      g1_loop(accb, 18, FA, 0);
      ln_stats();
      if (L == 0) mbar_wait(BAR(STAT), 0);
      center(acca, 0); wg_commit();
      wg_wait<0>(); release(E1 + ((FA - 1) & 3));
      fence_regs(acca);
      fold_v(acca); fold_k(acca, 0); fold_q(acca);
      sched_fence(P.zero);
      g1_loop(accb, FA, ATT, FA);
      attend(0, [&]() { wg_wait<0>(); release(E1 + ((ATT - 1) & 3)); mbar_wait(BAR(F1 + (ATT & 3)), (ATT >> 2) & 1); },
             [&]() { KB(ATT); g1_issue(accb, sb + slot1(ATT & 3), sb + slot1(ATT & 3), False{});
                     mbar_wait(BAR(F1 + ((ATT + 1) & 3)), ((ATT + 1) >> 2) & 1);
                     KB(ATT + 1); g1_issue(accb, sb + slot1((ATT + 1) & 3), sb + slot1((ATT + 1) & 3), False{}); });
      wg_wait<1>(); release(E1 + (ATT & 3));
      TS(3 + 32 * L);
      load_x();
      fence_regs(xa);
      center(accb, 1);
      g1_loop(accb, ATT + 2, 32 - LEAD1, 0);
      if (LEAD1 && wg == 0) { wg_wait<0>(); release(E1 + ((31 - LEAD1) & 3)); nb_sync<NB_LEAD>(256); }
      g1_loop(accb, 32 - LEAD1, 32, wg == 0 ? 32 - LEAD1 : 0);
      mbar_wait(BAR(STD), L);
      wg_wait<0>(); release(E1 + 3);
      fence_regs(accb);
      TS(4 + 32 * L);
      if (wu == 7) ST(0);
      fold_v(accb); fold_k(accb, 1);
      if (SF & 2) sched_fence(P.zero);
      fold_q(accb);
      TS2(29 + 32 * L);
      {
        auto g2_issue = [&](int p, bool own) {
          const uint32_t st = sb + slot2(p);
          const uint64_t da = mkdesc((own ? sb + OFF_STG : st) + wg * 8192, 16, 1024), db = mkdesc(st + 16384, 8192, 1024);
          wg_fence();
#pragma unroll
          for (int kk = 0; kk < 4; kk++) wgmma_128<0, 1>(xa, da + kk * 2, db + kk * 128);
          wg_commit();
        };
        uint32_t par = L ? 0x1e : 0;
        int p = 0, pp = 0;
        auto g2_loop = [&](int n0, int n1, int nrel) {
#pragma unroll 1
          for (int n = n0; n < n1; n++) {
            mbar_wait(BAR(F2 + p), (par >> p) & 1);
            KB(32 + n);
            if (n == 9 && wu == 0) ST(5);
            par ^= 1u << p;
            g2_issue(p, n == 8);
            if (LEAD2 && n == 15 && wg == 0) nb_arrive<NB_LEAD>(256);
            wg_wait<1>();
            if (n > nrel) release(E2 + pp);
            pp = p; if (++p == 5) p = 0;
          }
        };
        g2_loop(0, COVER, 0);
        attend(1, [&]() { wg_wait<0>(); release(E2 + COVER - 1); mbar_wait(BAR(F2 + COVER), (par >> COVER) & 1); },
               [&]() { KB(32 + COVER); g2_issue(COVER, false);
                       mbar_wait(BAR(F2 + COVER + 1), (par >> (COVER + 1)) & 1);
                       KB(33 + COVER); g2_issue(COVER + 1, false); });
        wg_wait<1>(); release(E2 + COVER);
        par ^= 3u << COVER; pp = COVER + 1; p = (COVER + 2) % 5;
        TS(30 + 32 * L);
        {
          const bf16* bp = P.b2 + (128 * opq(i) + 16 * wu + ((fresh_tid() & 31) >> 2));
          asm volatile("ld.global.nc.u16 %0, [%1];" : "=h"(b2a) : "l"(bp));
          asm volatile("ld.global.nc.u16 %0, [%1];" : "=h"(b2b) : "l"(bp + 8));
        }
        TS2(14 + 32 * L);
        g2_loop(COVER + 2, 8, 0);
        mbar_wait(BAR(JOB + 1), L);
        g2_loop(8, 16 - LEAD2, 0);
        if (LEAD2 && wg == 1) { wg_wait<0>(); release(E2 + pp); nb_sync<NB_LEAD>(256); }
        g2_loop(16 - LEAD2, 16, wg == 1 ? 16 - LEAD2 : 0);
        wg_wait<0>();
        release(E2 + 0);
        fence_regs(xa);
      }
      TS(5 + 32 * L);
      if (wu == 0) ST(8);
      {
        GEOM;
        const uint32_t tg = 2 * (tag + 1) + 1;
        float s0 = 0.f, s1 = 0.f, s2 = 0.f, s3 = 0.f, q0 = 0.f, q1 = 0.f, q2 = 0.f, q3 = 0.f;
#pragma unroll
        for (int t = 0; t < 16; t++) {
          s0 += xa[4 * t]; s1 += xa[4 * t + 1]; s2 += xa[4 * t + 2]; s3 += xa[4 * t + 3];
          q0 = fmaf(xa[4 * t], xa[4 * t], q0); q1 = fmaf(xa[4 * t + 1], xa[4 * t + 1], q1);
          q2 = fmaf(xa[4 * t + 2], xa[4 * t + 2], q2); q3 = fmaf(xa[4 * t + 3], xa[4 * t + 3], q3);
        }
        const float sm = stat_publish(s0 + s1, q0 + q1, s2 + s3, q2 + q3, tg);
        const uint32_t t0 = clock32();
        wg_fence();
        wgmma_rs_224z(acc3, q == 0 ? 0x3f80u : 0u, q == 0 ? 0x3f80u : 0u, 0u, 0u, mkdesc_vec(sb + OFF_B1, 16));
        wg_commit();
        TS2(13 + 32 * L);
        const float pv0 = __shfl_sync(0xffffffffu, sm, 4 * l7) * (1.f / 128), pv1 = __shfl_sync(0xffffffffu, sm, 4 * l7 + 1) * (1.f / 128);
        while (clock32() - t0 < STAT_CLK) {}
        stat_fetch();
        stat_await(tg);
        float r0, m0, r1, m1;
        {
          float mean0, var0, mean1, var1;
          stat_combine(sv0[0], sv0[1], sv1[0], sv1[1], pv0, mean0, var0); stat_combine(sv0[2], sv0[3], sv1[2], sv1[3], pv1, mean1, var1);
          mean0 = __shfl_sync(0xffffffffu, mean0, g); var0 = __shfl_sync(0xffffffffu, var0, g);
          mean1 = __shfl_sync(0xffffffffu, mean1, g); var1 = __shfl_sync(0xffffffffu, var1, g);
          r0 = 0.5f * rsq(fmaf(var0 + 1e-5f, 1e-5f, var0)); r1 = 0.5f * rsq(fmaf(var1 + 1e-5f, 1e-5f, var1));
          m0 = -mean0 * r0; m1 = -mean1 * r1;
        }
        TS2(15 + 32 * L);
        const uint32_t ha = sb + OFF_X + wg * 16384 + (16 * w + lr) * 128;
#pragma unroll
        for (int t = 0; t < 16; t += 2) {
          stsm4(ha + (t >> 3) * 8192 + ((((t & 7) + lt) ^ l7) << 4),
                pack2(fmaf(xa[4 * t], r0, m0), fmaf(xa[4 * t + 1], r0, m0)), pack2(fmaf(xa[4 * t + 2], r1, m1), fmaf(xa[4 * t + 3], r1, m1)),
                pack2(fmaf(xa[4 * t + 4], r0, m0), fmaf(xa[4 * t + 5], r0, m0)), pack2(fmaf(xa[4 * t + 6], r1, m1), fmaf(xa[4 * t + 7], r1, m1)));
          if ((DIRECT & 1) && (t & 7) == 6 && wg == 0) {
            __syncwarp();
            const int o = (t >> 3) * 8192 + w * 2048 + lane * 16;
            copy_out<4>(gHB + (opq(j) * 32 + 2 * i) * 16384 + o, sb + OFF_X + o, 512);
          }
        }
        if (DIRECT & 1) { signal(JOB + 2 + wg); fence_async_smem(); } else { fence_async_smem(); signal(JOB + 2 + wg); }
        nb_sync<NB_BOTH>(256);
      }
      TS(6 + 32 * L);
      auto g3_issue = [&](uint32_t a, int p) {
        const uint32_t st = sb + slot3(p);
        const uint64_t da = mkdesc(a + wg * 8192, 8192, 1024), db = mkdesc(st + 16384, 8192, 1024);
        wg_fence();
#pragma unroll
        for (int kk = 0; kk < 4; kk++) wgmma_224<1, 1>(acc3, da + kk * 128, db + kk * 128);
        wg_commit();
      };
      mbar_wait(BAR(F3 + 0), 0); KB(48); g3_issue(sb + OFF_X, 0);
      mbar_wait(BAR(F3 + 1), 0); KB(49); g3_issue(sb + OFF_X + 16384, 1);
      sched_fence(P.zero);
      {
        const float c0 = __uint_as_float((uint32_t)b2a << 16), c1 = __uint_as_float((uint32_t)b2b << 16);
#pragma unroll
        for (int t = 0; t < 16; t++) { xa[4 * t] += c0; xa[4 * t + 1] += c0; xa[4 * t + 2] += c1; xa[4 * t + 3] += c1; }
        fence_regs(xa);
      }
      wg_wait<1>(); release(E3 + 0);
      auto g3_loop = [&](int n0, int n1, int nrel) {
#pragma unroll 1
        for (int n = n0; n < n1; n++) {
          const int p = n & 3;
          mbar_wait(BAR(F3 + p), (n >> 2) & 1);
          KB(48 + n);
          if (n == 3 && wu == 0) ST(13);
          if (n == 2 && wu == 0) ST(14);
          g3_issue(sb + slot3(p), p);
          if (LEAD3 && n == 31 && wg == 0) nb_arrive<NB_LEAD>(256);
          wg_wait<1>();
          if (n > nrel) release(E3 + ((n - 1) & 3));
        }
      };
      g3_loop(2, 32 - LEAD3, 0);
      if (LEAD3 && wg == 1) { wg_wait<0>(); release(E3 + ((31 - LEAD3) & 3)); nb_sync<NB_LEAD>(256); }
      g3_loop(32 - LEAD3, 32, wg == 1 ? 32 - LEAD3 : 0);
      mbar_wait(BAR(RD), L);
      wg_wait<0>();
      release(E3 + 3);
      fence_regs(acc3);
      TS(7 + 32 * L);
      if (wu == 0) ST(16);
      auto g4_issue = [&](int p, uint32_t b) {
        const uint64_t da = mkdesc(sb + slot4(p) + wg * 8192, 8192, 1024), db = mkdesc(b, 8192, 1024);
        wg_fence();
#pragma unroll
        for (int kk = 0; kk < 4; kk++) wgmma_128<1, 1>(xa, da + kk * 128, db + kk * 128);
        wg_commit();
      };
      uint32_t par = L ? 0x3c : 0;
      {
        GEOM;
        const uint32_t ua = sb + wg * 8192 + (8 * lt + l7) * 128 + (((2 * w + ((lane >> 3) & 1)) ^ l7) << 4);
#pragma unroll
        for (int cc = 0; cc < 4; cc++) {
          const int c = cc == 0 ? 3 : cc == 3 ? 0 : cc;
          uint32_t u[16];
#pragma unroll
          for (int k = 0; k < (c == 3 ? 8 : 16); k++) u[k] = pack2(gelu_half(acc3[32 * c + 2 * k]), gelu_half(acc3[32 * c + 2 * k + 1]));
          if (c == 3 || c == 0) mbar_wait(BAR(E3 + (c ? 0 : 2)), 1);
#pragma unroll
          for (int k = 0; k < (c == 3 ? 2 : 4); k++)
            stsm4t(ua + (c == 3 ? slot4(5) + 16384 : c == 0 ? slot4(2) + 16384 : OFF_X + (c - 1) * 16384) + k * 2048, u[4 * k], u[4 * k + 1], u[4 * k + 2], u[4 * k + 3]);
          if ((DIRECT & 2) && c == 3) {
            __syncwarp();
            const int o = wg * 8192 + (lane >> 1) * 128 + (((2 * w + (lane & 1)) ^ ((lane >> 1) & 7)) << 4);
            copy_out<2>(gUB + (opq(j) * 56 + 48 + m) * 16384 + r * 4096 + o, sb + slot4(5) + 16384 + o, 2048);
            signal(JOB + 7);
          } else if (c == 3 || c == 0) { fence_async_smem(); signal(JOB + (c ? 7 : 6)); }
          if (c == 3) sched_fence(P.zero);
          TS2(16 + 3 * c + 32 * L);
        }
        nb_sync<NB_BOTH>(256);
      }
      TS(8 + 32 * L);
      {
        int p = 0, pp = 0;
#pragma unroll 1
        for (int n = 0; n < 56; n++) {
          mbar_wait(BAR(F4 + p), (par >> p) & 1);
          KB(80 + n);
          if (n == 3 && wu == 0) ST(21);
          if (n == 0 && wu == 0) ST(22);
          par ^= 1u << p;
          g4_issue(p, n < 2 ? sb + OFF_X + n * 16384 : sb + slot4(p) + 16384);
          wg_wait<1>();
          if (n) release(E4 + pp);
          pp = p; if (++p == 6) p = 0;
        }
      }
      mbar_wait(BAR(RD + 1), L);
      wg_wait<0>();
      release(E4 + 1);
      fence_regs(xa);
      TS(9 + 32 * L);
      {
        GEOM;
#pragma unroll
        for (int t = 0; t < 16; t += 2) {
          stsm4(sb + OFF_X + (t >> 3) * 16384 + (16 * wu + lr) * 128 + ((((t & 7) + lt) ^ l7) << 4),
                pack2(xa[4 * t], xa[4 * t + 1]), pack2(xa[4 * t + 2], xa[4 * t + 3]),
                pack2(xa[4 * t + 4], xa[4 * t + 5]), pack2(xa[4 * t + 6], xa[4 * t + 7]));
          if ((DIRECT & 4) && t == 6 && L == 0) {
            __syncwarp();
            const int o = wu * 2048 + lane * 16;
            copy_out<4>(gXB + (opq(i) * 16 + 2 * j) * 16384 + o, sb + OFF_X + o, 512);
            signal(JOB + 8);
          } else if ((t & 7) == 6) { fence_async_smem(); signal(JOB + 8 + (t >> 3)); }
        }
        nb_sync<NB_BOTH>(256);
      }
      TS(10 + 32 * L);
      KB(136);
    }
    cluster_bar();
    TS(32);
  }
}

typedef CUresult (*EncodeFn)(CUtensorMap*, CUtensorMapDataType, cuuint32_t, void*, const cuuint64_t*, const cuuint64_t*, const cuuint32_t*,
                             const cuuint32_t*, CUtensorMapInterleave, CUtensorMapSwizzle, CUtensorMapL2promotion, CUtensorMapFloatOOBfill);

void make_map(EncodeFn enc, CUtensorMap* mp, const void* base, int rank, cuuint64_t d0, cuuint64_t d1, cuuint64_t d2, cuuint64_t s1, cuuint64_t s2,
              cuuint32_t b0, cuuint32_t b1, cuuint32_t b2, CUtensorMapL2promotion promo = CU_TENSOR_MAP_L2_PROMOTION_L2_128B) {
  cuuint64_t dims[3] = {d0, d1, d2}, strides[2] = {s1, s2};
  cuuint32_t box[3] = {b0, b1, b2}, es[3] = {1, 1, 1};
  CUresult res = enc(mp, CU_TENSOR_MAP_DATA_TYPE_BFLOAT16, rank, const_cast<void*>(base), dims, strides, box, es, CU_TENSOR_MAP_INTERLEAVE_NONE,
                     CU_TENSOR_MAP_SWIZZLE_128B, promo, CU_TENSOR_MAP_FLOAT_OOB_FILL_NONE);
  (void)res;
}

}

extern "C" void kernel_launch(void* const* d_in, const int* in_sizes, int n_in, void* d_out, int out_size) {
  (void)in_sizes; (void)n_in; (void)out_size;
  static EncodeFn enc = nullptr;
  if (!enc) {
    void* fn = nullptr;
    cudaDriverEntryPointQueryResult qr;
    cudaGetDriverEntryPoint("cuTensorMapEncodeTiled", &fn, cudaEnableDefault, &qr);
    enc = (EncodeFn)fn;
    cudaFuncSetAttribute(fused_kernel, cudaFuncAttributeMaxDynamicSharedMemorySize, SMEM_BYTES);
  }
  Params P;
  make_map(enc, &P.x0, d_in[0], 2, D_, S_, 1, D_ * 2, 0, 64, 128, 1, XPROMO);
  make_map(enc, &P.wqkv, d_in[1], 3, D_, D_, 3, 3 * D_ * 2, D_ * 2, 64, 32, 3, WPROMO);
  make_map(enc, &P.wo, d_in[2], 2, D_, D_, 1, D_ * 2, 0, 64, 64, 1, W2PROMO);
  make_map(enc, &P.w1, d_in[4], 3, 64, S_, F_ / 64, F_ * 2, 128, 64, 64, 3);
  make_map(enc, &P.w1h, d_in[4], 3, 32, S_, F_ / 32, F_ * 2, 64, 64, 64, 1);
  make_map(enc, &P.w2, d_in[6], 3, 64, F_, S_ / 64, S_ * 2, 128, 64, 64, 2, W2PROMO);
  make_map(enc, &P.out, d_out, 2, D_, S_, 1, D_ * 2, 0, 64, 128, 1);
  P.wqkv_p = (const bf16*)d_in[1];
  P.b1 = (const bf16*)d_in[5];
  P.b2 = (const bf16*)d_in[7];
  P.zero = 0;
  fused_kernel<<<128, 384, SMEM_BYTES>>>(P);
}
```

```cpp
#include <cuda_runtime.h>
#include <cuda_bf16.h>
#include <cuda.h>
#include <stdint.h>

namespace {

typedef __nv_bfloat16 bf16;
constexpr int S_ = 2048, D_ = 1024, F_ = 3584;

constexpr uint32_t OFF_STG  = 163840;
constexpr uint32_t OFF_X    = 196608;
constexpr uint32_t OFF_BAR  = 229376;
constexpr uint32_t OFF_CS   = OFF_BAR + 512;
constexpr uint32_t OFF_B1   = OFF_CS + 1536;
constexpr uint32_t SMEM_BYTES = OFF_B1 + 896 + 128;
constexpr int F1 = 0, E1 = 4, F2 = 8, E2 = 13, F3 = 18, E3 = 22, F4 = 26, E4 = 32;
constexpr int JOB = 38;
constexpr int RD = 48;
constexpr int XF = 54, STD = 56, STAT = 58, FOLD = 59, CSJ = 61, HALO = 62;
constexpr int NB_BOTH = 1, NB_HELP = 2, NB_INIT = 3, NB_LEAD = 4;

__device__ __forceinline__ uint32_t slot1(int p) { return p * 40960; }
__device__ __forceinline__ uint32_t slot2(int p) { return p * 32768; }
__device__ __forceinline__ uint32_t slot3(int p) { return ((p + 2) & 3) * 49152; }
__device__ __forceinline__ uint32_t slot4(int p) { return (p < 2 ? p + 4 : p - 2) * 32768; }

__device__ __align__(1024) uint8_t gXB[16 * 16 * 16384];
__device__ __align__(1024) uint8_t gOB[16 * 16 * 16384];
__device__ __align__(1024) uint8_t gHB[8 * 32 * 16384];
__device__ __align__(1024) uint8_t gUB[8 * 56 * 16384];
__device__ __align__(1024) uint2   gST[2][16][8][8][16];
__device__ __align__(1024) uint4   gHalo[2][16][8][12][32];
__device__ __align__(1024) uint32_t gAck[2][16][8][2][8];
__device__ __align__(1024) uint4   gCS[8][16][64];
__device__ __align__(1024) uint32_t gFlag[2][7][16][32];
__device__ uint32_t gEpoch;
#define TS(k)
#define TS2(k)

#define KB(k)
#define ST(k)
struct Params {
  CUtensorMap x0, wqkv, wo, w1, w1h, w2, out;
  const bf16 *wqkv_p, *b1, *b2;
  uint32_t zero;
};

template <int TA, int TB> __device__ __forceinline__ void wgmma_128(float (&d)[64], uint64_t da, uint64_t db) {
  asm volatile("wgmma.mma_async.sync.aligned.m64n128k16.f32.bf16.bf16 {"
  "%0, %1, %2, %3, %4, %5, %6, %7, %8, %9, %10, %11, %12, %13, %14, %15, "
  "%16, %17, %18, %19, %20, %21, %22, %23, %24, %25, %26, %27, %28, %29, %30, %31, "
  "%32, %33, %34, %35, %36, %37, %38, %39, %40, %41, %42, %43, %44, %45, %46, %47, "
  "%48, %49, %50, %51, %52, %53, %54, %55, %56, %57, %58, %59, %60, %61, %62, %63"
  "}, %64, %65, 1, 1, 1, %66, %67;\n"
  : "+f"(d[0]), "+f"(d[1]), "+f"(d[2]), "+f"(d[3]), "+f"(d[4]), "+f"(d[5]), "+f"(d[6]), "+f"(d[7]),
    "+f"(d[8]), "+f"(d[9]), "+f"(d[10]), "+f"(d[11]), "+f"(d[12]), "+f"(d[13]), "+f"(d[14]), "+f"(d[15]),
    "+f"(d[16]), "+f"(d[17]), "+f"(d[18]), "+f"(d[19]), "+f"(d[20]), "+f"(d[21]), "+f"(d[22]), "+f"(d[23]),
    "+f"(d[24]), "+f"(d[25]), "+f"(d[26]), "+f"(d[27]), "+f"(d[28]), "+f"(d[29]), "+f"(d[30]), "+f"(d[31]),
    "+f"(d[32]), "+f"(d[33]), "+f"(d[34]), "+f"(d[35]), "+f"(d[36]), "+f"(d[37]), "+f"(d[38]), "+f"(d[39]),
    "+f"(d[40]), "+f"(d[41]), "+f"(d[42]), "+f"(d[43]), "+f"(d[44]), "+f"(d[45]), "+f"(d[46]), "+f"(d[47]),
    "+f"(d[48]), "+f"(d[49]), "+f"(d[50]), "+f"(d[51]), "+f"(d[52]), "+f"(d[53]), "+f"(d[54]), "+f"(d[55]),
    "+f"(d[56]), "+f"(d[57]), "+f"(d[58]), "+f"(d[59]), "+f"(d[60]), "+f"(d[61]), "+f"(d[62]), "+f"(d[63])
  : "l"(da), "l"(db), "n"(TA), "n"(TB));
}
template <int TA, int TB> __device__ __forceinline__ void wgmma_192(float (&d)[96], uint64_t da, uint64_t db) {
  asm volatile("wgmma.mma_async.sync.aligned.m64n192k16.f32.bf16.bf16 {"
  "%0, %1, %2, %3, %4, %5, %6, %7, %8, %9, %10, %11, %12, %13, %14, %15, "
  "%16, %17, %18, %19, %20, %21, %22, %23, %24, %25, %26, %27, %28, %29, %30, %31, "
  "%32, %33, %34, %35, %36, %37, %38, %39, %40, %41, %42, %43, %44, %45, %46, %47, "
  "%48, %49, %50, %51, %52, %53, %54, %55, %56, %57, %58, %59, %60, %61, %62, %63, "
  "%64, %65, %66, %67, %68, %69, %70, %71, %72, %73, %74, %75, %76, %77, %78, %79, "
  "%80, %81, %82, %83, %84, %85, %86, %87, %88, %89, %90, %91, %92, %93, %94, %95"
  "}, %96, %97, 1, 1, 1, %98, %99;\n"
  : "+f"(d[0]), "+f"(d[1]), "+f"(d[2]), "+f"(d[3]), "+f"(d[4]), "+f"(d[5]), "+f"(d[6]), "+f"(d[7]),
    "+f"(d[8]), "+f"(d[9]), "+f"(d[10]), "+f"(d[11]), "+f"(d[12]), "+f"(d[13]), "+f"(d[14]), "+f"(d[15]),
    "+f"(d[16]), "+f"(d[17]), "+f"(d[18]), "+f"(d[19]), "+f"(d[20]), "+f"(d[21]), "+f"(d[22]), "+f"(d[23]),
    "+f"(d[24]), "+f"(d[25]), "+f"(d[26]), "+f"(d[27]), "+f"(d[28]), "+f"(d[29]), "+f"(d[30]), "+f"(d[31]),
    "+f"(d[32]), "+f"(d[33]), "+f"(d[34]), "+f"(d[35]), "+f"(d[36]), "+f"(d[37]), "+f"(d[38]), "+f"(d[39]),
    "+f"(d[40]), "+f"(d[41]), "+f"(d[42]), "+f"(d[43]), "+f"(d[44]), "+f"(d[45]), "+f"(d[46]), "+f"(d[47]),
    "+f"(d[48]), "+f"(d[49]), "+f"(d[50]), "+f"(d[51]), "+f"(d[52]), "+f"(d[53]), "+f"(d[54]), "+f"(d[55]),
    "+f"(d[56]), "+f"(d[57]), "+f"(d[58]), "+f"(d[59]), "+f"(d[60]), "+f"(d[61]), "+f"(d[62]), "+f"(d[63]),
    "+f"(d[64]), "+f"(d[65]), "+f"(d[66]), "+f"(d[67]), "+f"(d[68]), "+f"(d[69]), "+f"(d[70]), "+f"(d[71]),
    "+f"(d[72]), "+f"(d[73]), "+f"(d[74]), "+f"(d[75]), "+f"(d[76]), "+f"(d[77]), "+f"(d[78]), "+f"(d[79]),
    "+f"(d[80]), "+f"(d[81]), "+f"(d[82]), "+f"(d[83]), "+f"(d[84]), "+f"(d[85]), "+f"(d[86]), "+f"(d[87]),
    "+f"(d[88]), "+f"(d[89]), "+f"(d[90]), "+f"(d[91]), "+f"(d[92]), "+f"(d[93]), "+f"(d[94]), "+f"(d[95])
  : "l"(da), "l"(db), "n"(TA), "n"(TB));
}
template <int TA, int TB> __device__ __forceinline__ void wgmma_192z(float (&d)[96], uint64_t da, uint64_t db) {
  asm volatile("wgmma.mma_async.sync.aligned.m64n192k16.f32.bf16.bf16 {"
  "%0, %1, %2, %3, %4, %5, %6, %7, %8, %9, %10, %11, %12, %13, %14, %15, "
  "%16, %17, %18, %19, %20, %21, %22, %23, %24, %25, %26, %27, %28, %29, %30, %31, "
  "%32, %33, %34, %35, %36, %37, %38, %39, %40, %41, %42, %43, %44, %45, %46, %47, "
  "%48, %49, %50, %51, %52, %53, %54, %55, %56, %57, %58, %59, %60, %61, %62, %63, "
  "%64, %65, %66, %67, %68, %69, %70, %71, %72, %73, %74, %75, %76, %77, %78, %79, "
  "%80, %81, %82, %83, %84, %85, %86, %87, %88, %89, %90, %91, %92, %93, %94, %95"
  "}, %96, %97, 0, 1, 1, %98, %99;\n"
  : "=f"(d[0]), "=f"(d[1]), "=f"(d[2]), "=f"(d[3]), "=f"(d[4]), "=f"(d[5]), "=f"(d[6]), "=f"(d[7]),
    "=f"(d[8]), "=f"(d[9]), "=f"(d[10]), "=f"(d[11]), "=f"(d[12]), "=f"(d[13]), "=f"(d[14]), "=f"(d[15]),
    "=f"(d[16]), "=f"(d[17]), "=f"(d[18]), "=f"(d[19]), "=f"(d[20]), "=f"(d[21]), "=f"(d[22]), "=f"(d[23]),
    "=f"(d[24]), "=f"(d[25]), "=f"(d[26]), "=f"(d[27]), "=f"(d[28]), "=f"(d[29]), "=f"(d[30]), "=f"(d[31]),
    "=f"(d[32]), "=f"(d[33]), "=f"(d[34]), "=f"(d[35]), "=f"(d[36]), "=f"(d[37]), "=f"(d[38]), "=f"(d[39]),
    "=f"(d[40]), "=f"(d[41]), "=f"(d[42]), "=f"(d[43]), "=f"(d[44]), "=f"(d[45]), "=f"(d[46]), "=f"(d[47]),
    "=f"(d[48]), "=f"(d[49]), "=f"(d[50]), "=f"(d[51]), "=f"(d[52]), "=f"(d[53]), "=f"(d[54]), "=f"(d[55]),
    "=f"(d[56]), "=f"(d[57]), "=f"(d[58]), "=f"(d[59]), "=f"(d[60]), "=f"(d[61]), "=f"(d[62]), "=f"(d[63]),
    "=f"(d[64]), "=f"(d[65]), "=f"(d[66]), "=f"(d[67]), "=f"(d[68]), "=f"(d[69]), "=f"(d[70]), "=f"(d[71]),
    "=f"(d[72]), "=f"(d[73]), "=f"(d[74]), "=f"(d[75]), "=f"(d[76]), "=f"(d[77]), "=f"(d[78]), "=f"(d[79]),
    "=f"(d[80]), "=f"(d[81]), "=f"(d[82]), "=f"(d[83]), "=f"(d[84]), "=f"(d[85]), "=f"(d[86]), "=f"(d[87]),
    "=f"(d[88]), "=f"(d[89]), "=f"(d[90]), "=f"(d[91]), "=f"(d[92]), "=f"(d[93]), "=f"(d[94]), "=f"(d[95])
  : "l"(da), "l"(db), "n"(TA), "n"(TB));
}
template <int TA, int TB> __device__ __forceinline__ void wgmma_224(float (&d)[112], uint64_t da, uint64_t db) {
  asm volatile("wgmma.mma_async.sync.aligned.m64n224k16.f32.bf16.bf16 {"
  "%0, %1, %2, %3, %4, %5, %6, %7, %8, %9, %10, %11, %12, %13, %14, %15, "
  "%16, %17, %18, %19, %20, %21, %22, %23, %24, %25, %26, %27, %28, %29, %30, %31, "
  "%32, %33, %34, %35, %36, %37, %38, %39, %40, %41, %42, %43, %44, %45, %46, %47, "
  "%48, %49, %50, %51, %52, %53, %54, %55, %56, %57, %58, %59, %60, %61, %62, %63, "
  "%64, %65, %66, %67, %68, %69, %70, %71, %72, %73, %74, %75, %76, %77, %78, %79, "
  "%80, %81, %82, %83, %84, %85, %86, %87, %88, %89, %90, %91, %92, %93, %94, %95, "
  "%96, %97, %98, %99, %100, %101, %102, %103, %104, %105, %106, %107, %108, %109, %110, %111"
  "}, %112, %113, 1, 1, 1, %114, %115;\n"
  : "+f"(d[0]), "+f"(d[1]), "+f"(d[2]), "+f"(d[3]), "+f"(d[4]), "+f"(d[5]), "+f"(d[6]), "+f"(d[7]),
    "+f"(d[8]), "+f"(d[9]), "+f"(d[10]), "+f"(d[11]), "+f"(d[12]), "+f"(d[13]), "+f"(d[14]), "+f"(d[15]),
    "+f"(d[16]), "+f"(d[17]), "+f"(d[18]), "+f"(d[19]), "+f"(d[20]), "+f"(d[21]), "+f"(d[22]), "+f"(d[23]),
    "+f"(d[24]), "+f"(d[25]), "+f"(d[26]), "+f"(d[27]), "+f"(d[28]), "+f"(d[29]), "+f"(d[30]), "+f"(d[31]),
    "+f"(d[32]), "+f"(d[33]), "+f"(d[34]), "+f"(d[35]), "+f"(d[36]), "+f"(d[37]), "+f"(d[38]), "+f"(d[39]),
    "+f"(d[40]), "+f"(d[41]), "+f"(d[42]), "+f"(d[43]), "+f"(d[44]), "+f"(d[45]), "+f"(d[46]), "+f"(d[47]),
    "+f"(d[48]), "+f"(d[49]), "+f"(d[50]), "+f"(d[51]), "+f"(d[52]), "+f"(d[53]), "+f"(d[54]), "+f"(d[55]),
    "+f"(d[56]), "+f"(d[57]), "+f"(d[58]), "+f"(d[59]), "+f"(d[60]), "+f"(d[61]), "+f"(d[62]), "+f"(d[63]),
    "+f"(d[64]), "+f"(d[65]), "+f"(d[66]), "+f"(d[67]), "+f"(d[68]), "+f"(d[69]), "+f"(d[70]), "+f"(d[71]),
    "+f"(d[72]), "+f"(d[73]), "+f"(d[74]), "+f"(d[75]), "+f"(d[76]), "+f"(d[77]), "+f"(d[78]), "+f"(d[79]),
    "+f"(d[80]), "+f"(d[81]), "+f"(d[82]), "+f"(d[83]), "+f"(d[84]), "+f"(d[85]), "+f"(d[86]), "+f"(d[87]),
    "+f"(d[88]), "+f"(d[89]), "+f"(d[90]), "+f"(d[91]), "+f"(d[92]), "+f"(d[93]), "+f"(d[94]), "+f"(d[95]),
    "+f"(d[96]), "+f"(d[97]), "+f"(d[98]), "+f"(d[99]), "+f"(d[100]), "+f"(d[101]), "+f"(d[102]), "+f"(d[103]),
    "+f"(d[104]), "+f"(d[105]), "+f"(d[106]), "+f"(d[107]), "+f"(d[108]), "+f"(d[109]), "+f"(d[110]), "+f"(d[111])
  : "l"(da), "l"(db), "n"(TA), "n"(TB));
}
__device__ __forceinline__ void wgmma_rs_192(float (&d)[96], uint32_t a0, uint32_t a1, uint32_t a2, uint32_t a3, uint64_t db) {
  asm volatile("wgmma.mma_async.sync.aligned.m64n192k16.f32.bf16.bf16 {"
  "%0, %1, %2, %3, %4, %5, %6, %7, %8, %9, %10, %11, %12, %13, %14, %15, "
  "%16, %17, %18, %19, %20, %21, %22, %23, %24, %25, %26, %27, %28, %29, %30, %31, "
  "%32, %33, %34, %35, %36, %37, %38, %39, %40, %41, %42, %43, %44, %45, %46, %47, "
  "%48, %49, %50, %51, %52, %53, %54, %55, %56, %57, %58, %59, %60, %61, %62, %63, "
  "%64, %65, %66, %67, %68, %69, %70, %71, %72, %73, %74, %75, %76, %77, %78, %79, "
  "%80, %81, %82, %83, %84, %85, %86, %87, %88, %89, %90, %91, %92, %93, %94, %95"
  "}, {%96, %97, %98, %99}, %100, 1, 1, 1, 1;\n"
  : "+f"(d[0]), "+f"(d[1]), "+f"(d[2]), "+f"(d[3]), "+f"(d[4]), "+f"(d[5]), "+f"(d[6]), "+f"(d[7]),
    "+f"(d[8]), "+f"(d[9]), "+f"(d[10]), "+f"(d[11]), "+f"(d[12]), "+f"(d[13]), "+f"(d[14]), "+f"(d[15]),
    "+f"(d[16]), "+f"(d[17]), "+f"(d[18]), "+f"(d[19]), "+f"(d[20]), "+f"(d[21]), "+f"(d[22]), "+f"(d[23]),
    "+f"(d[24]), "+f"(d[25]), "+f"(d[26]), "+f"(d[27]), "+f"(d[28]), "+f"(d[29]), "+f"(d[30]), "+f"(d[31]),
    "+f"(d[32]), "+f"(d[33]), "+f"(d[34]), "+f"(d[35]), "+f"(d[36]), "+f"(d[37]), "+f"(d[38]), "+f"(d[39]),
    "+f"(d[40]), "+f"(d[41]), "+f"(d[42]), "+f"(d[43]), "+f"(d[44]), "+f"(d[45]), "+f"(d[46]), "+f"(d[47]),
    "+f"(d[48]), "+f"(d[49]), "+f"(d[50]), "+f"(d[51]), "+f"(d[52]), "+f"(d[53]), "+f"(d[54]), "+f"(d[55]),
    "+f"(d[56]), "+f"(d[57]), "+f"(d[58]), "+f"(d[59]), "+f"(d[60]), "+f"(d[61]), "+f"(d[62]), "+f"(d[63]),
    "+f"(d[64]), "+f"(d[65]), "+f"(d[66]), "+f"(d[67]), "+f"(d[68]), "+f"(d[69]), "+f"(d[70]), "+f"(d[71]),
    "+f"(d[72]), "+f"(d[73]), "+f"(d[74]), "+f"(d[75]), "+f"(d[76]), "+f"(d[77]), "+f"(d[78]), "+f"(d[79]),
    "+f"(d[80]), "+f"(d[81]), "+f"(d[82]), "+f"(d[83]), "+f"(d[84]), "+f"(d[85]), "+f"(d[86]), "+f"(d[87]),
    "+f"(d[88]), "+f"(d[89]), "+f"(d[90]), "+f"(d[91]), "+f"(d[92]), "+f"(d[93]), "+f"(d[94]), "+f"(d[95])
  : "r"(a0), "r"(a1), "r"(a2), "r"(a3), "l"(db));
}
__device__ __forceinline__ void wgmma_rs_224z(float (&d)[112], uint32_t a0, uint32_t a1, uint32_t a2, uint32_t a3, uint64_t db) {
  asm volatile("wgmma.mma_async.sync.aligned.m64n224k16.f32.bf16.bf16 {"
  "%0, %1, %2, %3, %4, %5, %6, %7, %8, %9, %10, %11, %12, %13, %14, %15, "
  "%16, %17, %18, %19, %20, %21, %22, %23, %24, %25, %26, %27, %28, %29, %30, %31, "
  "%32, %33, %34, %35, %36, %37, %38, %39, %40, %41, %42, %43, %44, %45, %46, %47, "
  "%48, %49, %50, %51, %52, %53, %54, %55, %56, %57, %58, %59, %60, %61, %62, %63, "
  "%64, %65, %66, %67, %68, %69, %70, %71, %72, %73, %74, %75, %76, %77, %78, %79, "
  "%80, %81, %82, %83, %84, %85, %86, %87, %88, %89, %90, %91, %92, %93, %94, %95, "
  "%96, %97, %98, %99, %100, %101, %102, %103, %104, %105, %106, %107, %108, %109, %110, %111"
  "}, {%112, %113, %114, %115}, %116, 0, 1, 1, 1;\n"
  : "=f"(d[0]), "=f"(d[1]), "=f"(d[2]), "=f"(d[3]), "=f"(d[4]), "=f"(d[5]), "=f"(d[6]), "=f"(d[7]),
    "=f"(d[8]), "=f"(d[9]), "=f"(d[10]), "=f"(d[11]), "=f"(d[12]), "=f"(d[13]), "=f"(d[14]), "=f"(d[15]),
    "=f"(d[16]), "=f"(d[17]), "=f"(d[18]), "=f"(d[19]), "=f"(d[20]), "=f"(d[21]), "=f"(d[22]), "=f"(d[23]),
    "=f"(d[24]), "=f"(d[25]), "=f"(d[26]), "=f"(d[27]), "=f"(d[28]), "=f"(d[29]), "=f"(d[30]), "=f"(d[31]),
    "=f"(d[32]), "=f"(d[33]), "=f"(d[34]), "=f"(d[35]), "=f"(d[36]), "=f"(d[37]), "=f"(d[38]), "=f"(d[39]),
    "=f"(d[40]), "=f"(d[41]), "=f"(d[42]), "=f"(d[43]), "=f"(d[44]), "=f"(d[45]), "=f"(d[46]), "=f"(d[47]),
    "=f"(d[48]), "=f"(d[49]), "=f"(d[50]), "=f"(d[51]), "=f"(d[52]), "=f"(d[53]), "=f"(d[54]), "=f"(d[55]),
    "=f"(d[56]), "=f"(d[57]), "=f"(d[58]), "=f"(d[59]), "=f"(d[60]), "=f"(d[61]), "=f"(d[62]), "=f"(d[63]),
    "=f"(d[64]), "=f"(d[65]), "=f"(d[66]), "=f"(d[67]), "=f"(d[68]), "=f"(d[69]), "=f"(d[70]), "=f"(d[71]),
    "=f"(d[72]), "=f"(d[73]), "=f"(d[74]), "=f"(d[75]), "=f"(d[76]), "=f"(d[77]), "=f"(d[78]), "=f"(d[79]),
    "=f"(d[80]), "=f"(d[81]), "=f"(d[82]), "=f"(d[83]), "=f"(d[84]), "=f"(d[85]), "=f"(d[86]), "=f"(d[87]),
    "=f"(d[88]), "=f"(d[89]), "=f"(d[90]), "=f"(d[91]), "=f"(d[92]), "=f"(d[93]), "=f"(d[94]), "=f"(d[95]),
    "=f"(d[96]), "=f"(d[97]), "=f"(d[98]), "=f"(d[99]), "=f"(d[100]), "=f"(d[101]), "=f"(d[102]), "=f"(d[103]),
    "=f"(d[104]), "=f"(d[105]), "=f"(d[106]), "=f"(d[107]), "=f"(d[108]), "=f"(d[109]), "=f"(d[110]), "=f"(d[111])
  : "r"(a0), "r"(a1), "r"(a2), "r"(a3), "l"(db));
}

__device__ __forceinline__ uint32_t smem_u32(const void* p) { return (uint32_t)__cvta_generic_to_shared(p); }
__device__ __forceinline__ void mbar_init(uint32_t bar, uint32_t cnt) { asm volatile("mbarrier.init.shared::cta.b64 [%0], %1;" ::"r"(bar), "r"(cnt) : "memory"); }
__device__ __forceinline__ void mbar_expect(uint32_t bar, uint32_t bytes) { asm volatile("mbarrier.arrive.expect_tx.shared::cta.b64 _, [%0], %1;" ::"r"(bar), "r"(bytes) : "memory"); }
__device__ __forceinline__ void mbar_arrive(uint32_t bar) { asm volatile("mbarrier.arrive.shared::cta.b64 _, [%0];" ::"r"(bar) : "memory"); }
__device__ __forceinline__ void mbar_arrive_cl(uint32_t cbar) { asm volatile("mbarrier.arrive.shared::cluster.b64 _, [%0];" ::"r"(cbar) : "memory"); }
__device__ __forceinline__ uint32_t mapa(uint32_t a, uint32_t cta) { uint32_t r; asm("mapa.shared::cluster.u32 %0, %1, %2;" : "=r"(r) : "r"(a), "r"(cta)); return r; }
__device__ __forceinline__ void mbar_wait(uint32_t bar, uint32_t parity) {
  asm volatile("{\n.reg .pred p;\n.reg .u32 n;\nmov.u32 n, 0;\n"
    "LAB_WAIT:\n"
    "mbarrier.try_wait.parity.shared::cta.b64 p, [%0], %1;\n"
    "@p bra LAB_DONE;\n"
    "add.u32 n, n, 1;\n"
    "setp.lt.u32 p, n, 2000000;\n"
    "@p bra LAB_WAIT;\n"
    "trap;\n"
    "LAB_DONE:\n}\n" ::"r"(bar), "r"(parity) : "memory");
}
constexpr uint32_t SPIN_MAX = 2000000;
__device__ __forceinline__ void tma2d(uint32_t dst, const CUtensorMap* m, uint32_t bar, int c0, int c1) {
  asm volatile("cp.async.bulk.tensor.2d.shared::cluster.global.mbarrier::complete_tx::bytes [%0], [%1, {%3, %4}], [%2];"
    ::"r"(dst), "l"(m), "r"(bar), "r"(c0), "r"(c1) : "memory");
}
__device__ __forceinline__ void tma2d_mc(uint32_t dst, const CUtensorMap* m, uint32_t bar, int c0, int c1) {
  asm volatile("cp.async.bulk.tensor.2d.shared::cluster.global.mbarrier::complete_tx::bytes.multicast::cluster [%0], [%1, {%3, %4}], [%2], %5;"
    ::"r"(dst), "l"(m), "r"(bar), "r"(c0), "r"(c1), "h"((uint16_t)3) : "memory");
}
__device__ __forceinline__ void tma3d(uint32_t dst, const CUtensorMap* m, uint32_t bar, int c0, int c1, int c2) {
  asm volatile("cp.async.bulk.tensor.3d.shared::cluster.global.mbarrier::complete_tx::bytes [%0], [%1, {%3, %4, %5}], [%2];"
    ::"r"(dst), "l"(m), "r"(bar), "r"(c0), "r"(c1), "r"(c2) : "memory");
}
__device__ __forceinline__ void tma3d_mc(uint32_t dst, const CUtensorMap* m, uint32_t bar, int c0, int c1, int c2) {
  asm volatile("cp.async.bulk.tensor.3d.shared::cluster.global.mbarrier::complete_tx::bytes.multicast::cluster [%0], [%1, {%3, %4, %5}], [%2], %6;"
    ::"r"(dst), "l"(m), "r"(bar), "r"(c0), "r"(c1), "r"(c2), "h"((uint16_t)3) : "memory");
}
__device__ __forceinline__ void tma2d_store(const CUtensorMap* m, uint32_t src, int c0, int c1) {
  asm volatile("cp.async.bulk.tensor.2d.global.shared::cta.bulk_group [%0, {%2, %3}], [%1];" ::"l"(m), "r"(src), "r"(c0), "r"(c1) : "memory");
}
__device__ __forceinline__ void bulk_ld(uint32_t dst, const void* src, uint32_t bytes, uint32_t bar) {
  asm volatile("cp.async.bulk.shared::cluster.global.mbarrier::complete_tx::bytes [%0], [%1], %2, [%3];" ::"r"(dst), "l"(src), "r"(bytes), "r"(bar) : "memory");
}
__device__ __forceinline__ void bulk_ld_mc(uint32_t dst, const void* src, uint32_t bytes, uint32_t bar) {
  asm volatile("cp.async.bulk.shared::cluster.global.mbarrier::complete_tx::bytes.multicast::cluster [%0], [%1], %2, [%3], %4;"
    ::"r"(dst), "l"(src), "r"(bytes), "r"(bar), "h"((uint16_t)3) : "memory");
}
__device__ __forceinline__ void bulk_st(void* dst, uint32_t src, uint32_t bytes) {
  asm volatile("cp.async.bulk.global.shared::cta.bulk_group [%0], [%1], %2;" ::"l"(dst), "r"(src), "r"(bytes) : "memory");
}
__device__ __forceinline__ void bulk_commit() { asm volatile("cp.async.bulk.commit_group;" ::: "memory"); }
__device__ __forceinline__ void bulk_wait0() { asm volatile("cp.async.bulk.wait_group 0;" ::: "memory"); }
__device__ __forceinline__ void fence_async_smem() { asm volatile("fence.proxy.async.shared::cta;" ::: "memory"); }
__device__ __forceinline__ void wg_fence() { asm volatile("wgmma.fence.sync.aligned;" ::: "memory"); }
__device__ __forceinline__ void wg_commit() { asm volatile("wgmma.commit_group.sync.aligned;" ::: "memory"); }
template <int N> __device__ __forceinline__ void wg_wait() { asm volatile("wgmma.wait_group.sync.aligned %0;" ::"n"(N) : "memory"); }
template <int R> __device__ __forceinline__ void reg_alloc() { asm volatile("setmaxnreg.inc.sync.aligned.u32 %0;" ::"n"(R)); }
template <int R> __device__ __forceinline__ void reg_dealloc() { asm volatile("setmaxnreg.dec.sync.aligned.u32 %0;" ::"n"(R)); }
__device__ __forceinline__ void cluster_bar() { asm volatile("barrier.cluster.arrive.relaxed;\nbarrier.cluster.wait;" ::: "memory"); }
template <int ID> __device__ __forceinline__ void nb_sync(int n) { asm volatile("barrier.sync %0, %1;" ::"n"(ID), "r"(n) : "memory"); }
template <int ID> __device__ __forceinline__ void nb_arrive(int n) { asm volatile("barrier.arrive %0, %1;" ::"n"(ID), "r"(n) : "memory"); }
__device__ __forceinline__ int fresh_tid() { int t; asm volatile("mov.u32 %0, %%tid.x;" : "=r"(t)); return t; }
__device__ __forceinline__ void sched_fence(uint32_t z) { asm volatile("{\n.reg .pred p;\nsetp.ne.u32 p, %0, 0;\nLAB_S:\n@p nanosleep.u32 0;\n@p bra LAB_S;\n}\n" ::"r"(z) : "memory"); }
__device__ __forceinline__ float rsq(float x) { float y; asm("rsqrt.approx.ftz.f32 %0, %1;" : "=f"(y) : "f"(x)); return y; }
__device__ __forceinline__ int opq(int v) { asm volatile("" : "+r"(v)); return v; }
struct True { static constexpr bool value = true; };
struct False { static constexpr bool value = false; };
template <int N> __device__ __forceinline__ void fence_regs(float (&d)[N]) {
#pragma unroll
  for (int i = 0; i < N; i++) asm volatile("" : "+f"(d[i])::"memory");
}
__device__ __forceinline__ uint64_t mkdesc(uint32_t addr, uint32_t lbo, uint32_t sbo) {
  return (uint64_t)((addr & 0x3FFFF) >> 4) | ((uint64_t)(lbo >> 4) << 16) | ((uint64_t)(sbo >> 4) << 32) | (1ull << 62);
}
__device__ __forceinline__ uint64_t mkdesc_vec(uint32_t addr, uint32_t sbo) { return (uint64_t)((addr & 0x3FFFF) >> 4) | ((uint64_t)(sbo >> 4) << 32); }
__device__ __forceinline__ void sts16(uint32_t a, uint32_t v) { asm volatile("st.shared.u16 [%0], %1;" ::"r"(a), "h"((uint16_t)v) : "memory"); }
__device__ __forceinline__ uint32_t pack2(float lo, float hi) { uint32_t r; asm("cvt.rn.bf16x2.f32 %0, %1, %2;" : "=r"(r) : "f"(hi), "f"(lo)); return r; }
__device__ __forceinline__ float bf_lo(uint32_t v) { return __uint_as_float(v << 16); }
__device__ __forceinline__ float bf_hi(uint32_t v) { return __uint_as_float(v & 0xffff0000u); }
__device__ __forceinline__ void stsm4(uint32_t a, uint32_t r0, uint32_t r1, uint32_t r2, uint32_t r3) {
  asm volatile("stmatrix.sync.aligned.m8n8.x4.shared.b16 [%0], {%1, %2, %3, %4};" ::"r"(a), "r"(r0), "r"(r1), "r"(r2), "r"(r3) : "memory");
}
__device__ __forceinline__ void stsm4t(uint32_t a, uint32_t r0, uint32_t r1, uint32_t r2, uint32_t r3) {
  asm volatile("stmatrix.sync.aligned.m8n8.x4.trans.shared.b16 [%0], {%1, %2, %3, %4};" ::"r"(a), "r"(r0), "r"(r1), "r"(r2), "r"(r3) : "memory");
}
__device__ __forceinline__ void ldsm4(uint32_t a, uint32_t& r0, uint32_t& r1, uint32_t& r2, uint32_t& r3) {
  asm volatile("ldmatrix.sync.aligned.m8n8.x4.shared.b16 {%0, %1, %2, %3}, [%4];" : "=r"(r0), "=r"(r1), "=r"(r2), "=r"(r3) : "r"(a) : "memory");
}
__device__ __forceinline__ void ldsm4t(uint32_t a, uint32_t& r0, uint32_t& r1, uint32_t& r2, uint32_t& r3) {
  asm volatile("ldmatrix.sync.aligned.m8n8.x4.trans.shared.b16 {%0, %1, %2, %3}, [%4];" : "=r"(r0), "=r"(r1), "=r"(r2), "=r"(r3) : "r"(a) : "memory");
}
__device__ __forceinline__ void mma16816(float (&c)[4], uint32_t a0, uint32_t a1, uint32_t a2, uint32_t a3, uint32_t b0, uint32_t b1) {
  asm volatile("mma.sync.aligned.m16n8k16.row.col.f32.bf16.bf16.f32 {%0, %1, %2, %3}, {%4, %5, %6, %7}, {%8, %9}, {%0, %1, %2, %3};"
    : "+f"(c[0]), "+f"(c[1]), "+f"(c[2]), "+f"(c[3]) : "r"(a0), "r"(a1), "r"(a2), "r"(a3), "r"(b0), "r"(b1));
}
__device__ __forceinline__ void sts128(uint32_t a, uint32_t r0, uint32_t r1, uint32_t r2, uint32_t r3) {
  asm volatile("st.shared.v4.b32 [%0], {%1, %2, %3, %4};" ::"r"(a), "r"(r0), "r"(r1), "r"(r2), "r"(r3) : "memory");
}
__device__ __forceinline__ void lds128(uint32_t a, uint32_t& r0, uint32_t& r1, uint32_t& r2, uint32_t& r3) {
  asm volatile("ld.shared.v4.b32 {%0, %1, %2, %3}, [%4];" : "=r"(r0), "=r"(r1), "=r"(r2), "=r"(r3) : "r"(a) : "memory");
}
__device__ __forceinline__ float2 lds64f(uint32_t a) { float2 v; asm volatile("ld.shared.v2.f32 {%0, %1}, [%2];" : "=f"(v.x), "=f"(v.y) : "r"(a) : "memory"); return v; }
__device__ __forceinline__ float4 lds128f(uint32_t a) { float4 v; asm volatile("ld.shared.v4.f32 {%0, %1, %2, %3}, [%4];" : "=f"(v.x), "=f"(v.y), "=f"(v.z), "=f"(v.w) : "r"(a) : "memory"); return v; }
__device__ __forceinline__ void sts64f(uint32_t a, float x, float y) { asm volatile("st.shared.v2.f32 [%0], {%1, %2};" ::"r"(a), "f"(x), "f"(y) : "memory"); }
__device__ __forceinline__ float lds32f(uint32_t a) { float v; asm volatile("ld.shared.f32 %0, [%1];" : "=f"(v) : "r"(a) : "memory"); return v; }
__device__ __forceinline__ void sts32f(uint32_t a, float x) { asm volatile("st.shared.f32 [%0], %1;" ::"r"(a), "f"(x) : "memory"); }
__device__ __forceinline__ void stat_st(uint2* p, float sum, float sq, uint32_t tag) {
  const float mean = sum * (1.f / 128), m2 = fmaxf(fmaf(-mean, sum, sq), 0.f);
  const uint32_t a = ((__float_as_uint(mean) + 8u) & ~15u) | (tag & 15u), b = ((__float_as_uint(m2) + 8u) & ~15u) | (tag & 15u);
  asm volatile("{\n.reg .b64 x;\nmov.b64 x, {%1, %2};\nst.relaxed.gpu.global.b64 [%0], x;\n}\n" ::"l"(p), "r"(a), "r"(b) : "memory");
}
__device__ __forceinline__ void stat_ld2(const uint2* p, uint32_t (&v)[4]) {
  asm volatile("{\n.reg .b64 x, y;\nld.relaxed.gpu.global.v2.b64 {x, y}, [%4];\nmov.b64 {%0, %1}, x;\nmov.b64 {%2, %3}, y;\n}\n"
    : "=r"(v[0]), "=r"(v[1]), "=r"(v[2]), "=r"(v[3]) : "l"(p) : "memory");
}
__device__ __forceinline__ float untag(uint32_t v) { return __uint_as_float(v & ~15u); }
__device__ __forceinline__ void ll_st3(uint4* p, uint32_t a, uint32_t b, uint32_t c, uint32_t tag) {
  asm volatile("{\n.reg .b64 x, y;\n.reg .b128 z;\nmov.b64 x, {%1, %2};\nmov.b64 y, {%3, %4};\nmov.b128 z, {x, y};\nst.relaxed.gpu.global.b128 [%0], z;\n}\n"
    ::"l"(p), "r"(a), "r"(b), "r"(c), "r"(tag) : "memory");
}
__device__ __forceinline__ uint32_t ll_ld3(const uint4* p, uint32_t& a, uint32_t& b, uint32_t& c, uint32_t tag) {
  uint32_t t;
  asm volatile("{\n.reg .b64 x, y;\n.reg .b128 z;\nld.relaxed.gpu.global.b128 z, [%4];\nmov.b128 {x, y}, z;\nmov.b64 {%0, %1}, x;\nmov.b64 {%2, %3}, y;\n}\n"
    : "=r"(a), "=r"(b), "=r"(c), "=r"(t) : "l"(p) : "memory");
  return t ^ tag;
}
__device__ __forceinline__ void halo_send(uint4* p, uint32_t a, const uint32_t (&tg)[6]) {
  asm volatile("{\n.reg .b64 x<6>, y<6>, w<2>;\n.reg .b32 c<4>;\n.reg .b128 z<6>;\n"
    "ld.shared.b64 w0, [%1+1536];\nld.shared.b64 w1, [%1+1792];\n"
    "ld.shared.b64 x0, [%1];\nld.shared.b64 x1, [%1+256];\nld.shared.b64 x2, [%1+512];\n"
    "ld.shared.b64 x3, [%1+768];\nld.shared.b64 x4, [%1+1024];\nld.shared.b64 x5, [%1+1280];\n"
    "mov.b64 {c0, c1}, w0;\nmov.b64 {c2, c3}, w1;\n"
    "mov.b64 y0, {c0, %2};\nmov.b64 y1, {c1, %3};\nmov.b64 y2, {c2, %4};\nmov.b64 y3, {c3, %5};\nmov.b64 y4, {%6, %6};\nmov.b64 y5, {%7, %7};\n"
    "mov.b128 z0, {x0, y0};\nmov.b128 z1, {x1, y1};\nmov.b128 z2, {x2, y2};\nmov.b128 z3, {x3, y3};\nmov.b128 z4, {x4, y4};\nmov.b128 z5, {x5, y5};\n"
    "st.relaxed.gpu.global.b128 [%0], z0;\nst.relaxed.gpu.global.b128 [%0+512], z1;\nst.relaxed.gpu.global.b128 [%0+1024], z2;\n"
    "st.relaxed.gpu.global.b128 [%0+1536], z3;\nst.relaxed.gpu.global.b128 [%0+2048], z4;\nst.relaxed.gpu.global.b128 [%0+2560], z5;\n}\n"
    ::"l"(p), "r"(a), "r"(tg[0]), "r"(tg[1]), "r"(tg[2]), "r"(tg[3]), "r"(tg[4]), "r"(tg[5]) : "memory");
}
template <int N> __device__ __forceinline__ void copy_out(uint8_t* dst, uint32_t src, int stride) {
  uint4 v[N];
#pragma unroll
  for (int k = 0; k < N; k++) lds128(src + k * stride, v[k].x, v[k].y, v[k].z, v[k].w);
#pragma unroll
  for (int k = 0; k < N; k++) asm volatile("st.global.v4.b32 [%0], {%1, %2, %3, %4};" ::"l"(dst + k * stride), "r"(v[k].x), "r"(v[k].y), "r"(v[k].z), "r"(v[k].w) : "memory");
}
__device__ __forceinline__ void warp_store(uint8_t* dst, uint32_t src, int bytes, uint32_t delay, uint32_t pace) {
  __nanosleep(delay);
#pragma unroll 1
  for (int o = 0; o < bytes; o += 2048) {
    if (pace) __nanosleep(pace);
    uint4 v[4];
#pragma unroll
    for (int k = 0; k < 4; k++) lds128(src + o + k * 512, v[k].x, v[k].y, v[k].z, v[k].w);
#pragma unroll
    for (int k = 0; k < 4; k++) asm volatile("st.global.v4.b32 [%0], {%1, %2, %3, %4};" ::"l"(dst + o + k * 512), "r"(v[k].x), "r"(v[k].y), "r"(v[k].z), "r"(v[k].w) : "memory");
  }
  __syncwarp();
}
__device__ __forceinline__ uint32_t clock32() { uint32_t t; asm volatile("mov.u32 %0, %%clock;" : "=r"(t)); return t; }
__device__ __forceinline__ void flag_set(uint32_t* p, uint32_t bit) { asm volatile("red.release.gpu.global.xor.b32 [%0], %1;" ::"l"(p), "r"(bit) : "memory"); }
__device__ __forceinline__ void flag_wait(const uint32_t* p, uint32_t inv, uint32_t need, uint32_t& ready) {
  if ((ready & need) == need) return;
  uint32_t n = 0;
  do {
    asm volatile("ld.relaxed.gpu.global.b32 %0, [%1];" : "=r"(ready) : "l"(p) : "memory");
    ready = __shfl_sync(0xffffffffu, ready, 0) ^ inv;
  } while ((ready & need) != need && ++n < SPIN_MAX);
  asm volatile("fence.acquire.gpu;\nfence.proxy.async.global;" ::: "memory");
}
__device__ __forceinline__ bool elect_one() {
  uint32_t p;
  asm volatile("{\n.reg .pred P;\nelect.sync _|P, 0xffffffff;\nselp.u32 %0, 1, 0, P;\n}\n" : "=r"(p));
  return p;
}
__device__ __forceinline__ float gelu_half(float hx) {
  const float y = hx * fmaf(hx * hx, 8.f * 0.0356774081f, 2.f * 0.7978845608f);
  float th;
  asm("tanh.approx.f32 %0, %1;" : "=f"(th) : "f"(y));
  return fmaf(hx, th, hx);
}
__device__ __forceinline__ float ex2(float x) { float y; asm("ex2.approx.ftz.f32 %0, %1;" : "=f"(y) : "f"(x)); return y; }

__device__ __forceinline__ void stat_combine(uint32_t am, uint32_t aq, uint32_t bm, uint32_t bq, float pv, float& mean, float& var) {
  const float d0 = untag(am) - pv, d1 = untag(bm) - pv;
  float s = d0 + d1, q = fmaf(fmaf(d0, d0, d1 * d1), 128.f, untag(aq) + untag(bq));
  s += __shfl_xor_sync(0xffffffffu, s, 8); q += __shfl_xor_sync(0xffffffffu, q, 8);
  s += __shfl_xor_sync(0xffffffffu, s, 16); q += __shfl_xor_sync(0xffffffffu, q, 16);
  s *= 0.125f;
  mean = pv + s;
  var = fmaxf(fmaf(-s, s, q * (1.f / D_)), 0.f);
}

__device__ __forceinline__ void attn_probs(const uint32_t* q0, const uint32_t* q1,
                                           const uint32_t* k0, const uint32_t* k1, const uint32_t* k2, const uint32_t* k3,
                                           float sc0, float sc1, bool first, bool e, bool zneg, uint32_t (&pr)[6], float (&l)[2]) {
  float s[4][4];
#pragma unroll
  for (int n = 0; n < 4; n++) {
    const uint32_t* k = n == 0 ? k0 : n == 1 ? k1 : n == 2 ? k2 : k3;
    s[n][0] = s[n][1] = s[n][2] = s[n][3] = 0.f;
    mma16816(s[n], q0[0], q1[0], q0[1], q1[1], k[0], k[1]);
    mma16816(s[n], q0[2], q1[2], q0[3], q1[3], k[2], k[3]);
  }
  const float MASKED = -1.0e9f * 1.4426950409f;
  float a0 = (e ? s[1][1] : s[1][0]) * sc0;
  float b0 = (zneg ? (e ? s[0][1] : s[0][0]) : (e ? s[2][1] : s[2][0])) * sc0;
  float a1 = (e ? s[2][3] : s[2][2]) * sc1;
  float b1 = (zneg ? (e ? s[1][3] : s[1][2]) : (e ? s[3][3] : s[3][2])) * sc1;
  if (first) { a0 = MASKED; if (zneg) { b0 = MASKED; b1 = MASKED; } }
  float m0 = fmaxf(a0, b0), m1 = fmaxf(a1, b1);
  m0 = fmaxf(m0, __shfl_xor_sync(0xffffffffu, m0, 1)); m1 = fmaxf(m1, __shfl_xor_sync(0xffffffffu, m1, 1));
  m0 = fmaxf(m0, __shfl_xor_sync(0xffffffffu, m0, 2)); m1 = fmaxf(m1, __shfl_xor_sync(0xffffffffu, m1, 2));
  a0 = ex2(a0 - m0); b0 = ex2(b0 - m0); a1 = ex2(a1 - m1); b1 = ex2(b1 - m1);
  l[0] = a0 + b0; l[1] = a1 + b1;
  const int sh = e ? 16 : 0;
  const uint32_t pa0 = pack2(a0, 0.f) << sh, pb0 = pack2(b0, 0.f) << sh, pa1 = pack2(a1, 0.f) << sh, pb1 = pack2(b1, 0.f) << sh;
  pr[0] = zneg ? pb0 : 0u; pr[1] = pa0; pr[2] = zneg ? 0u : pb0;
  pr[3] = zneg ? pb1 : 0u; pr[4] = pa1; pr[5] = zneg ? 0u : pb1;
}
__device__ __forceinline__ void attn_pv(const uint32_t (&pr)[6], const uint32_t* vh, const uint32_t* v, float (&o)[4][4]) {
#pragma unroll
  for (int dt = 0; dt < 4; dt++) {
    o[dt][0] = o[dt][1] = o[dt][2] = o[dt][3] = 0.f;
    mma16816(o[dt], pr[0], 0u, pr[1], pr[3], vh[2 * dt], vh[2 * dt + 1]);
    mma16816(o[dt], pr[2], pr[4], 0u, pr[5], v[2 * dt], v[2 * dt + 1]);
  }
}

#define ATT 24
#define COVER 2
#define HALO_A_NS 300
#define H1D 900
#define U0D 300
#define U2D 3000
#define X1D 1200
#define PACE 150
#define LEAD1 3
#define LEAD2 3
#define XLD 7
#define XST 3
#define FA 20
#define LEAD4 4
#define STAT_CLK 150
__global__ void __cluster_dims__(2, 1, 1) __launch_bounds__(384, 1) fused_kernel(const __grid_constant__ Params P) {
  extern __shared__ __align__(1024) uint8_t smem_raw[];
  const uint32_t sb = smem_u32(smem_raw);
  const uint32_t bars = sb + OFF_BAR;
  const int tid = threadIdx.x;
  const int wu = __shfl_sync(0xffffffffu, tid >> 5, 0), wg = wu >> 2;
  const int r = blockIdx.x & 1, cl = blockIdx.x >> 1;
  int grp, slt;
  if (cl < 4) { grp = 0; slt = 4 + cl; }
  else if (cl < 36) { grp = (cl - 4) & 7; slt = (cl - 4) >> 3; }
  else { grp = 1 + (cl - 36) % 7; slt = 4 + (cl - 36) / 7; }
#define MAP 0
  const int m = grp, j = slt;
  const int i = 2 * m + r;
  auto BAR = [&](int k) { return bars + 8 * k; };

  auto kb1 = [&](int n) { const int h = n >= 9, t = n - 2 - 7 * h; return n < 2 ? 2 * j + n : 2 * (t + (t >= j)) + h; };
  if (wu == 8) {
    if (elect_one()) {
      asm volatile("prefetch.tensormap [%0];" ::"l"(&P.x0) : "memory");
      asm volatile("prefetch.tensormap [%0];" ::"l"(&P.wqkv) : "memory");
#pragma unroll
      for (int k = 0; k < 6; k++) mbar_init(BAR(k < 4 ? F1 + k : XF + k - 4), 1);
      asm volatile("fence.mbarrier_init.release.cluster;" ::: "memory");
      fence_async_smem();
    }
    __syncwarp();
  } else if (wu == 0) {
    if (elect_one()) {
#pragma unroll
      for (int k = E1; k < 64; k++) {
        int cnt = 1;
        if (k < F2 || (k >= E2 && k < F3) || (k >= E3 && k < F4) || (k >= E4 && k < JOB) || k == JOB + 2 || k == JOB + 3) cnt = 4;
        else if ((k >= JOB && k < RD) || k == CSJ) cnt = 8;
        else if ((k >= RD && k < RD + 4) || k == STD || k == STAT || k >= HALO) cnt = 2;
        if (k != XF && k != XF + 1) mbar_init(BAR(k), cnt);
      }
      asm volatile("fence.mbarrier_init.release.cluster;" ::: "memory");
      fence_async_smem();
    }
    __syncwarp();
  }
  auto load_tag = [&]() { uint32_t t; asm volatile("ld.relaxed.gpu.global.u32 %0, [%1];" : "=r"(t) : "l"(&gEpoch) : "memory"); return t + 1; };
  TS(0);
  if (wu == 8) nb_arrive<NB_INIT>(384); else nb_sync<NB_INIT>(384);
  asm volatile("barrier.cluster.arrive.relaxed;" ::: "memory");

  if (wg == 2) {
    reg_dealloc<40>();
    if (wu == 8) {
    if (elect_one()) {
#pragma unroll 1
      for (int u = 0; u < 4; u++) {
        const int kb = u;
        mbar_expect(BAR(F1 + u), 40960);
        tma2d(sb + slot1(u), &P.x0, BAR(F1 + u), kb * 64, 128 * i);
        tma3d(sb + slot1(u) + 16384, &P.wqkv, BAR(F1 + u), 128 * j, kb * 64, 0);
        tma3d(sb + slot1(u) + 28672, &P.wqkv, BAR(F1 + u), 128 * j, kb * 64 + 32, 0);
      }
    }
    __syncwarp();
    }
    asm volatile("barrier.cluster.wait;" ::: "memory");
    auto kb3 = [&](int n) { const int h = n >= 17, t = n - 2 - 15 * h; return n < 2 ? 2 * i + n : t == 14 ? 2 * (i ^ 1) + h : 2 * ((2 * m + 2 + t) & 15) + h; };
    auto kb2 = [&](int n) { return n < 8 ? 2 * n : n == 8 ? 2 * j + 1 : 2 * (n - 9 + (n - 9 >= j)) + 1; };
    if (wu == 8) {
#pragma unroll 1
      for (int L = 0; L < 2; L++) {
#pragma unroll 1
        for (int u = L ? 0 : 4; u < 32; u++) {
          const int v = (L && u >= 2 && u < 18) ? (u < 4 ? u + 14 : u - 2) : u;
          const int p = u & 3, ab = v >> 4, nn = v & 15;
          if (u >= 4) mbar_wait(BAR(E1 + p), ((u >> 2) - 1) & 1);
          else mbar_wait(BAR(E4 + (u == 3 ? 0 : u + 3)), u == 3);
          if (elect_one()) {
            mbar_expect(BAR(F1 + p), nn < 2 ? 24576 : 40960);
            tma3d_mc(sb + slot1(p) + 16384 + r * 12288, &P.wqkv, BAR(F1 + p), 128 * j + 64 * ab, (L | ab ? kb1(nn) : nn) * 64 + 32 * r, 0);
          }
        }
        int p = 0; uint32_t par = L ? 0x1e : 0;
#pragma unroll 1
        for (int n = 0; n < 16; n++) {
          if (n >= 5) { mbar_wait(BAR(E2 + p), (par >> p) & 1); par ^= 1u << p; }
          else if (n < 4) mbar_wait(BAR(E1 + n), 1);
          if (elect_one()) {
            mbar_expect(BAR(F2 + p), n == 8 ? 16384 : 32768);
            tma2d_mc(sb + slot2(p) + 16384 + r * 8192, &P.wo, BAR(F2 + p), 128 * j + 64 * r, kb2(n) * 64);
          }
          if (++p == 5) p = 0;
        }
#pragma unroll 1
        for (int u = 0; u < 32; u++) {
          const int n = u < 4 ? (0x2031 >> (4 * u)) & 3 : u, p = n & 3, kb = kb3(n);
          if (n == 4) mbar_wait(BAR(RD + 4), L);
          if (n >= 4) mbar_wait(BAR(E3 + p), ((n >> 2) - 1) & 1);
          else if (n == 1) mbar_wait(BAR(STD + 1), L);
          else if (n == 3) mbar_wait(BAR(E2 + 2), L);
          else if (n == 0) mbar_wait(BAR(E2 + 4), L);
          else mbar_wait(BAR(E2 + 0), 1);
          if (elect_one()) {
            mbar_expect(BAR(F3 + p), n < 2 ? 32768 : 49152);
            tma3d(sb + slot3(p) + 16384, &P.w1, BAR(F3 + p), 0, kb * 64, 7 * m + 4 * r);
            tma3d(sb + slot3(p) + 40960, &P.w1h, BAR(F3 + p), 0, kb * 64, 14 * m + 6 + r);
          }
        }
#pragma unroll 1
        for (int n = 0; n < 6; n++) {
          if (n < 3) mbar_wait(BAR(E3 + n), 1);
          else if (n == 4) mbar_wait(BAR(E3 + 3), 1);
          if (elect_one()) {
            mbar_expect(BAR(F4 + n), n < 3 ? 16384 : 32768);
            tma3d(sb + slot4(n), &P.w2, BAR(F4 + n), 0, (n < 3 ? 7 * m + 4 * r + (n == 2 ? 0 : n + 1) : 7 * ((m + n - 2) & 7) + 3) * 64, 2 * i);
          }
        }
        p = 0; par = L ? 0x3c : 0;
        auto g4w = [&](int kb) {
          mbar_wait(BAR(E4 + p), (par >> p) & 1); par ^= 1u << p;
          if (elect_one()) {
            mbar_expect(BAR(F4 + p), 32768);
            tma3d(sb + slot4(p), &P.w2, BAR(F4 + p), 0, kb * 64, 2 * i);
          }
          if (++p == 6) p = 0;
        };
#pragma unroll 1
        for (int t = 4; t < 9; t++) g4w(7 * ((m + t) & 7) + 3);
#pragma unroll 1
        for (int c = 0; c < 3; c++)
#pragma unroll 1
          for (int t = 0; t < 15; t++) { const int ii = t < 14 ? (2 * m + 2 + t) & 15 : i ^ 1; g4w(((7 * ii + 1) >> 1) + c); }
      }
    } else if (wu == 9) {
      uint32_t inv = 0;
#pragma unroll 1
      for (int L = 0; L < 2; L++) {
        uint32_t ready = 0;
#pragma unroll 1
        for (int u = 4; u < 32; u++) {
          const int p = u & 3, nn = (L && u < 18 ? u - 2 : u) & 15, kb = (L || u >= 16) ? kb1(nn) : nn;
          if (L == 0 && (u == XLD || u == XLD + XST) && elect_one()) {
            const int h = u != XLD;
            mbar_expect(BAR(XF + h), 16384);
            tma2d(sb + OFF_X + h * 16384, &P.x0, BAR(XF + h), 128 * j + 64 * h, 128 * i);
          }
          if (nn < 2) continue;
          if (L && u < 12) mbar_wait(BAR(F1 + p), u >> 3);
          if (u >= 4 + 4 * L) mbar_wait(BAR(E1 + p), ((u >> 2) - 1) & 1);
          if (L) {
            flag_wait(gFlag[0][0][i], inv, 1u << kb, ready);
            if (elect_one()) bulk_ld(sb + slot1(p), gXB + (i * 16 + kb) * 16384, 16384, BAR(F1 + p));
          } else if (elect_one()) tma2d(sb + slot1(p), &P.x0, BAR(F1 + p), kb * 64, 128 * i);
        }
        ready = 0;
        if (L == 0) inv = (__shfl_sync(0xffffffffu, load_tag(), 0) & 1) - 1;
        int p = 0; uint32_t par = L ? 0x1e : 0;
#pragma unroll 1
        for (int n = 0; n < 16; n++) {
          const int hp = kb2(n);
          if (n == 8) { par ^= 8; p = 4; continue; }
          if (n >= 5) { mbar_wait(BAR(E2 + p), (par >> p) & 1); par ^= 1u << p; }
          else if (n < 4) mbar_wait(BAR(E1 + n), 1);
          flag_wait(gFlag[L][1][i], inv, 1u << hp, ready);
          if (n == 9) ST(4);
          if (elect_one()) bulk_ld(sb + slot2(p), gOB + (i * 16 + hp) * 16384, 16384, BAR(F2 + p));
          if (++p == 5) p = 0;
        }
        ready = 0;
        mbar_wait(BAR(E2 + 0), 1);
#pragma unroll 1
        for (int n = 2; n < 32; n++) {
          const int p = n & 3, kb = kb3(n);
          if (n > 3) mbar_wait(BAR(E3 + p), ((n >> 2) - 1) & 1);
          flag_wait(gFlag[L][2][j], inv, 1u << kb, ready);
          if (n == 2) ST(12);
          if (elect_one()) {
            const uint8_t* src = gHB + (j * 32 + kb) * 16384;
            if (n != 16 && n != 31) bulk_ld_mc(sb + slot3(p) + r * 8192, src + r * 8192, 8192, BAR(F3 + p));
            else bulk_ld(sb + slot3(p), src, 16384, BAR(F3 + p));
          }
        }
        ready = 0; p = 3; par = L ? 0x3c : 0;
        mbar_wait(BAR(E3 + 3), 1);
#pragma unroll 1
        for (int t = 0; t < 8; t++) {
          const int mm = (m + t + 1) & 7;
          if (t == 2 || t == 5) mbar_wait(BAR(RD + (t == 2 ? 3 : 2)), L);
          if (t >= 3) { mbar_wait(BAR(E4 + p), (par >> p) & 1); par ^= 1u << p; }
          flag_wait(gFlag[L][6][j], inv, 3u << (2 * mm), ready);
          if (t == 0) ST(20);
          if (elect_one()) bulk_ld_mc(sb + slot4(p) + 16384 + r * 8192, gUB + (j * 56 + 48 + mm) * 16384 + r * 8192, 8192, BAR(F4 + p));
          if (++p == 6) p = 0;
        }
#pragma unroll 1
        for (int c = 0; c < 3; c++) {
          ready = 0;
#pragma unroll 1
          for (int t = 0; t < 15; t++) {
            const int ii = t < 14 ? (2 * m + 2 + t) & 15 : i ^ 1;
            mbar_wait(BAR(E4 + p), (par >> p) & 1); par ^= 1u << p;
            flag_wait(gFlag[L][3 + c][j], inv, 1u << ii, ready);
            if (elect_one()) {
              const uint8_t* src = gUB + (j * 56 + 16 * c + ii) * 16384;
              if (t < 14) bulk_ld_mc(sb + slot4(p) + 16384 + r * 8192, src + r * 8192, 8192, BAR(F4 + p));
              else bulk_ld(sb + slot4(p) + 16384, src, 16384, BAR(F4 + p));
            }
            if (++p == 6) p = 0;
          }
        }
      }
    } else {
      const int h = wu - 10, i0 = i, j0 = j;
      {
      const uint32_t tag = load_tag();
      int lane = tid & 31, i = i0, j = j0;
#define FRESH asm volatile("" : "+r"(lane), "+r"(i), "+r"(j))
      const uint32_t rs = mapa(sb, r ^ 1), rb = rs + OFF_BAR;
      auto signal = [&](int k) { if (lane == 0) mbar_arrive(BAR(k)); };
      auto drained = [&](int k) { if (lane == 0) { mbar_arrive(BAR(RD + k)); mbar_arrive_cl(rb + 8 * (RD + k)); } };
      auto publish = [&](uint32_t* f, int bit) { if (lane == 0) flag_set(f, 1u << bit); __syncwarp(); };
      for (int c = 32 * h + lane; c < 288; c += 64)
        sts16(sb + OFF_B1 + 2 * c, c >= 224 ? 0u : pack2(0.5f * __bfloat162float(P.b1[c < 192 ? 64 * (7 * m + 4 * r) + c : 64 * (7 * m + 3) + 32 * r + c - 192]), 0.f));
      if (h == 0) sts32f(sb + OFF_CS + 768 + 4 * lane, 0.f);
#pragma unroll 1
      for (int L = 0; L < 2; L++) {
        FRESH;
        if (L == 0) {
          mbar_wait(BAR(CSJ), 0);
          float c0 = 0.f, c1 = 0.f, c2 = 0.f;
          const uint32_t a = sb + OFF_STG + (32 * h + lane) * 4;
#pragma unroll 8
          for (int k = 0; k < 32; k++) { c0 += lds32f(a + k * 784); c1 += lds32f(a + k * 784 + 256); c2 += lds32f(a + k * 784 + 512); }
          ll_st3(&gCS[j][i][32 * h + lane], __float_as_uint(c0), __float_as_uint(c1), __float_as_uint(c2), tag);
          __nanosleep(500);
        }
        FRESH;
        if (L == 0) {
#pragma unroll 1
          for (int ab = 0; ab < 2; ab++) {
            float c0 = 0.f, c1 = 0.f, c2 = 0.f;
#pragma unroll 1
            for (int b4 = 0; b4 < 8; b4 += 4) {
              uint32_t a[4], b[4], c[4], n = 0, bad;
              do {
                bad = 0;
#pragma unroll
                for (int e = 0; e < 4; e++) bad |= ll_ld3(&gCS[j][2 * (b4 + e) + ab][32 * h + lane], a[e], b[e], c[e], tag);
              } while (bad && ++n < SPIN_MAX);
#pragma unroll
              for (int e = 0; e < 4; e++) { c0 += __uint_as_float(a[e]); c1 += __uint_as_float(b[e]); c2 += __uint_as_float(c[e]); }
            }
            const uint32_t a = sb + OFF_CS + ab * 768 + (4 * h + (lane >> 3)) * 32 + (lane & 7) * 2;
            const uint32_t h0 = pack2(c0, 0.f), h1 = pack2(c1, 0.f), h2 = pack2(c2, 0.f);
            sts16(a, h0); sts16(a + 256, h1); sts16(a + 512, h2);
            sts16(a + 16, pack2(c0 - bf_lo(h0), 0.f)); sts16(a + 272, pack2(c1 - bf_lo(h1), 0.f)); sts16(a + 528, pack2(c2 - bf_lo(h2), 0.f));
            fence_async_smem();
            __syncwarp();
            if (ab == 0) signal(STAT);
          }
        }
#pragma unroll 1
        for (int ab = 0; ab < 2; ab++) {
          FRESH;
          uint32_t v[18], tg[6];
          const uint32_t xs = sb + OFF_STG + h * 16384 + lane * 8;
          uint4* hp = &gHalo[L][i][j][6 * h][lane];
#pragma unroll
          for (int c = 0; c < 6; c++) { tg[c] = (2 * tag + ab) * 8 + c; asm volatile("" : "+r"(tg[c])); }
          asm volatile("" : "+l"(hp));
          mbar_wait(BAR(FOLD + ab), L);
          if (ab && h == 0) ST(6);
          if (i < 15) {
            halo_send(hp, xs, tg);
          }
          if (ab && h == 0) ST(26);
          if (i > 0) {
            if (!ab) __nanosleep(HALO_A_NS);
            uint32_t n = 0, bad;
            do {
              bad = 0;
#pragma unroll
              for (int c = 0; c < 6; c++) bad |= ll_ld3(hp + c * 32 - 8 * 12 * 32, v[3 * c], v[3 * c + 1], v[3 * c + 2], (2 * tag + ab) * 8);
              if (ab && h == 0 && n == 0) ST(28);
            } while (bad > 7 && ++n < SPIN_MAX);
            if (ab && h == 0) ST(27);
          } else {
#pragma unroll
            for (int c = 0; c < 18; c++) v[c] = 0u;
          }
#pragma unroll
          for (int c = 0; c < 6; c++) sts64f(xs + c * 256, __uint_as_float(v[3 * c]), __uint_as_float(v[3 * c + 1]));
          sts64f(xs + 1536, __uint_as_float(v[2]), __uint_as_float(v[5]));
          sts64f(xs + 1792, __uint_as_float(v[8]), __uint_as_float(v[11]));
          __syncwarp();
          signal(HALO + ab);
          if (ab && h == 0) ST(7);
          FRESH;
          if (ab == 0 && lane == 0) asm volatile("st.relaxed.gpu.global.u32 [%0], %1;" ::"l"(&gAck[L][i][j][h][0]), "r"(tag) : "memory");
          mbar_wait(BAR(JOB + ab), L);
          if (h == 0) {
            if (ab) ST(1);
            if (lane == 0) { bulk_st(gOB + (i * 16 + 2 * j + ab) * 16384, sb + OFF_STG, 16384); bulk_commit(); bulk_wait0(); }
            signal(STD + ab);
            if (ab) ST(2);
            publish(gFlag[L][1][i], 2 * j + ab);
            if (ab) ST(3);
          } else if (ab == 0) {
            if (i < 15 && lane < 2) {
              uint32_t t, n = 0;
              do { asm volatile("ld.relaxed.gpu.global.u32 %0, [%1];" : "=r"(t) : "l"(&gAck[L][i + 1][j][lane][0]) : "memory"); } while (t != tag && ++n < SPIN_MAX);
            }
            __syncwarp();
            signal(STD);
          }
        }
        FRESH;
        if (h == 0) {
          mbar_wait(BAR(JOB + 2), L);
          ST(9);
          signal(RD);
          ST(10);
          publish(gFlag[L][2][j], 2 * i);
          ST(11);
          signal(RD + 4);
          nb_arrive<NB_HELP>(64);
        } else {
          mbar_wait(BAR(JOB + 3), L);
          nb_sync<NB_HELP>(64);
          warp_store(gHB + (j * 32 + 2 * i + 1) * 16384 + lane * 16, sb + lane * 16 + OFF_X + 16384, 16384, H1D, PACE);
          signal(RD);
          ST(15);
          publish(gFlag[L][2][j], 2 * i + 1);
        }
        FRESH;
        if (h == 0) {
          mbar_wait(BAR(JOB + 7), L);
          ST(17);
          drained(3);
          ST(18);
          publish(gFlag[L][6][j], i);
          ST(19);
        }
        mbar_wait(BAR(JOB + 6), L);
        if (h == 1) {
          warp_store(gUB + (j * 56 + i) * 16384 + lane * 16, sb + lane * 16 + slot4(2) + 16384, 16384, U0D, 0);
          drained(2); ST(25);
          publish(gFlag[L][3][j], i);
        }
        nb_sync<NB_HELP>(64);
        warp_store(gUB + (j * 56 + 16 + 16 * h + i) * 16384 + lane * 16, sb + lane * 16 + OFF_X + h * 16384, 16384, h ? U2D : 0, PACE);
        ST(23 + h);
        signal(RD + 1);
        publish(gFlag[L][4 + h][j], i);
        FRESH;
        if (L == 0) {
          mbar_wait(BAR(JOB + 8 + h), 0);
          if (h == 1) warp_store(gXB + (i * 16 + 2 * j + 1) * 16384 + lane * 16, sb + lane * 16 + OFF_X + 16384, 16384, X1D, 0);
          publish(gFlag[0][0][i], 2 * j + h);
        }
      }
      if (blockIdx.x == 0 && h == 0 && lane == 0) asm volatile("st.relaxed.gpu.global.u32 [%0], %1;" ::"l"(&gEpoch), "r"(tag) : "memory");
      }
    }
    __syncwarp();
    cluster_bar();
  } else {
    reg_alloc<232>();
    asm volatile("barrier.cluster.wait;" ::: "memory");
    const uint32_t rbars = mapa(bars, tid & 1);
    const bool relp = (tid & 127) < 2;
    uint32_t tag;
    asm volatile("ld.relaxed.gpu.global.u32 %0, [%1];" : "=r"(tag) : "l"(&gEpoch + (fresh_tid() >> 10)) : "memory");
    auto release = [&](int k) { if (relp) mbar_arrive_cl(rbars + 8 * k); };
    auto signal = [&](int k) { __syncwarp(); if ((fresh_tid() & 31) == 0) mbar_arrive(BAR(k)); };
#define GEOM const int t7 = fresh_tid() & 127, lane = t7 & 31, w = t7 >> 5, g = lane >> 2, q = lane & 3, \
                       lr = lane & 15, lt = lane >> 4, l7 = lane & 7; (void)w; (void)g; (void)q; (void)lr; (void)lt; (void)l7

#pragma unroll 1
    for (int L = 0; L < 2; L++) {
      float acca[96], accb[96], xa[64], acc3[112];
      float nmean0, nmean1, rstd0, rstd1;
      uint16_t b2a, b2b;
      uint32_t Q[2][8], K[2][8], V[16];
      auto g1_issue = [&](float (&acc)[96], uint32_t a, uint32_t st, auto first) {
        const uint64_t da = mkdesc(a + wg * 8192, 16, 1024), db = mkdesc(st + 16384, 4096, 1024);
        wg_fence();
#pragma unroll
        for (int kk = 0; kk < 4; kk++) {
          const uint64_t b = db + (((kk >> 1) * 12288 + (kk & 1) * 2048) >> 4);
          if (first.value && kk == 0) wgmma_192z<0, 1>(acc, da, b); else wgmma_192<0, 1>(acc, da + kk * 2, b);
        }
        wg_commit();
      };
      auto g1_step = [&](float (&acc)[96], int u, bool rel) {
        const int p = u & 3;
        mbar_wait(BAR(F1 + p), (u >> 2) & 1);
        KB(u);
        g1_issue(acc, sb + slot1(p), sb + slot1(p), False{});
        if (LEAD1 && u == 31 && wg == 1) nb_arrive<NB_LEAD>(256);
        wg_wait<1>();
        if (rel) release(E1 + ((u - 1) & 3));
      };
      auto g1_loop = [&](float (&acc)[96], int u0, int u1, int urel) {
#pragma unroll 1
        for (int u = u0; u < u1; u++) g1_step(acc, u, u > urel);
      };
      auto load_x = [&]() {
        GEOM;
#pragma unroll
        for (int t = 0; t < 16; t += 2) {
          uint32_t v0, v1, v2, v3;
          ldsm4(sb + OFF_X + (t >> 3) * 16384 + (16 * wu + lr) * 128 + ((((t & 7) + lt) ^ l7) << 4), v0, v1, v2, v3);
          xa[4 * t + 0] = bf_lo(v0); xa[4 * t + 1] = bf_hi(v0); xa[4 * t + 2] = bf_lo(v1); xa[4 * t + 3] = bf_hi(v1);
          xa[4 * t + 4] = bf_lo(v2); xa[4 * t + 5] = bf_hi(v2); xa[4 * t + 6] = bf_lo(v3); xa[4 * t + 7] = bf_hi(v3);
        }
      };
      auto stat_publish = [&](float s0, float q0, float s2, float q2, uint32_t tg) {
        GEOM;
        const bool h1 = q & 1;
        float sm = (h1 ? s2 : s0) + __shfl_xor_sync(0xffffffffu, h1 ? s0 : s2, 1);
        float sq = (h1 ? q2 : q0) + __shfl_xor_sync(0xffffffffu, h1 ? q0 : q2, 1);
        sm += __shfl_xor_sync(0xffffffffu, sm, 2); sq += __shfl_xor_sync(0xffffffffu, sq, 2);
        if (q < 2) stat_st(&gST[0][0][0][0][0] + (((L * 16 + opq(i)) * 8 + wu) * 8 + j) * 16 + 2 * g + q, sm, sq, tg);
        return sm;
      };
      auto g1_stats = [&](int u0) {
        GEOM;
        const uint32_t xr = sb + OFF_X + (16 * wu + lr) * 128;
        float s0 = 0.f, q0 = 0.f, s2 = 0.f, q2 = 0.f;
        uint32_t v[8] = {0u, 0u, 0u, 0u, 0u, 0u, 0u, 0u};
#pragma unroll 1
        for (int k = 0; k < 5; k++) {
#pragma unroll
          for (int e = 0; e < 8; e += 2) {
            const float a = bf_lo(v[e]), b = bf_hi(v[e]), c = bf_lo(v[e + 1]), d = bf_hi(v[e + 1]);
            s0 += a + b; q0 = fmaf(a, a, fmaf(b, b, q0)); s2 += c + d; q2 = fmaf(c, c, fmaf(d, d, q2));
          }
          if (k == 4) break;
          const uint32_t o = ((2 * k + lt) ^ l7) << 4;
          ldsm4(xr + o, v[0], v[1], v[2], v[3]);
          ldsm4(xr + o + 16384, v[4], v[5], v[6], v[7]);
          g1_step(acca, u0 + k, true);
        }
        stat_publish(s0, q0, s2, q2, 2 * (tag + 1));
      };
      uint32_t sv0[4], sv1[4];
      auto stat_fetch = [&]() {
        const uint2* sp = &gST[0][0][0][0][0] + ((L * 16 + opq(i)) * 8 + wu) * 128 + 2 * (fresh_tid() & 31);
        stat_ld2(sp, sv0); stat_ld2(sp + 64, sv1);
      };
      auto stat_await = [&](uint32_t tg) {
#pragma unroll 1
        for (uint32_t n = 0; (((sv0[0] ^ tg) | (sv0[2] ^ tg) | (sv1[0] ^ tg) | (sv1[2] ^ tg)) & 15u) && n < SPIN_MAX; n++) stat_fetch();
        __syncwarp();
      };
      auto ln_stats = [&]() {
        GEOM;
        stat_await(2 * (tag + 1));
        float mean0, var0, mean1, var1;
        stat_combine(sv0[0], sv0[1], sv1[0], sv1[1], untag(__shfl_sync(0xffffffffu, sv0[0], l7)), mean0, var0);
        stat_combine(sv0[2], sv0[3], sv1[2], sv1[3], untag(__shfl_sync(0xffffffffu, sv0[2], l7)), mean1, var1);
        nmean0 = -__shfl_sync(0xffffffffu, mean0, g); rstd0 = rsq(__shfl_sync(0xffffffffu, var0, g) + 1e-5f);
        nmean1 = -__shfl_sync(0xffffffffu, mean1, g); rstd1 = rsq(__shfl_sync(0xffffffffu, var1, g) + 1e-5f);
      };
      auto center = [&](float (&acc)[96], int ab) {
        const bool q0 = (fresh_tid() & 3) == 0;
        const uint32_t h0 = pack2(nmean0, nmean0), h1 = pack2(nmean1, nmean1);
        const float l0 = nmean0 - bf_lo(h0), l1 = nmean1 - bf_lo(h1);
        const uint32_t a0 = q0 ? h0 : 0u, a1 = q0 ? h1 : 0u, a2 = q0 ? pack2(l0, l0) : 0u, a3 = q0 ? pack2(l1, l1) : 0u;
        wg_fence();
        wgmma_rs_192(acc, a0, a1, a2, a3, mkdesc_vec(sb + OFF_CS + ab * 768, 32));
      };
      auto frag = [&](float (&acc)[96], int t, uint32_t& p0, uint32_t& p1) {
        if (t >= 8) { p0 = pack2(acc[4 * t] * rstd0, acc[4 * t + 1] * rstd0); p1 = pack2(acc[4 * t + 2] * rstd1, acc[4 * t + 3] * rstd1); }
        else { p0 = pack2(acc[4 * t], acc[4 * t + 1]); p1 = pack2(acc[4 * t + 2], acc[4 * t + 3]); }
      };
      auto fold_v = [&](float (&acc)[96]) {
        GEOM;
        const uint32_t a = sb + OFF_STG + 16384 + ((wu + 1) & 7) * 2048 + lr * 128;
#pragma unroll
        for (int t = 0; t < 8; t += 2) {
          uint32_t p0, p1, p2, p3;
          frag(acc, 16 + t, p0, p1); frag(acc, 17 + t, p2, p3);
          stsm4(a + (((t + lt) ^ l7) << 4), p0, p1, p2, p3);
        }
        __syncwarp();
#pragma unroll
        for (int t = 0; t < 8; t += 2) ldsm4t(a + (((t + lt) ^ l7) << 4), V[2 * t], V[2 * t + 1], V[2 * t + 2], V[2 * t + 3]);
      };
      auto fold_k = [&](float (&acc)[96], int ab) {
        GEOM;
#pragma unroll
        for (int t = 8; t < 16; t++) frag(acc, t, K[0][t - 8], K[1][t - 8]);
        const uint32_t a = sb + OFF_STG + ((wu + 1) & 7) * 2048 + lane * 16;
#pragma unroll
        for (int c = 0; c < 4; c++)
          sts128(a + c * 512, K[c >> 1][4 * (c & 1)], K[c >> 1][4 * (c & 1) + 1], K[c >> 1][4 * (c & 1) + 2], K[c >> 1][4 * (c & 1) + 3]);
        if (wu == 7) signal(FOLD + ab);
      };
      auto fold_q = [&](float (&acc)[96]) {
#pragma unroll
        for (int t = 0; t < 8; t++) frag(acc, t, Q[0][t], Q[1][t]);
      };
      auto attend = [&](int ab, auto drain, auto resume) {
        GEOM;
        nb_sync<NB_BOTH>(256);
        const uint32_t xa_ = sb + OFF_STG + wu * 2048 + lane * 16;
        if (wu == 0) mbar_wait(BAR(HALO + ab), L);
        uint32_t KH[2][8], VH[16];
#pragma unroll
        for (int c = 0; c < 4; c++) {
          lds128(xa_ + c * 512, KH[c >> 1][4 * (c & 1)], KH[c >> 1][4 * (c & 1) + 1], KH[c >> 1][4 * (c & 1) + 2], KH[c >> 1][4 * (c & 1) + 3]);
          ldsm4t(sb + OFF_STG + 16384 + wu * 2048 + lr * 128 + (((2 * c + lt) ^ l7) << 4), VH[4 * c], VH[4 * c + 1], VH[4 * c + 2], VH[4 * c + 3]);
        }
        TS2(11 + ab + 32 * L);
        drain();
        sched_fence(P.zero);
        const bool e = g & 1, zneg = (g >> 1) < q, first = (i == 0) && (wu == 0);
        const float qs = 0.17677669530f * 1.4426950409f;
        uint32_t pr[2][6];
        float l[2][2];
#pragma unroll
        for (int hh = 0; hh < 2; hh++)
          attn_probs(&Q[0][4 * hh], &Q[1][4 * hh], &KH[0][4 * hh], &KH[1][4 * hh], &K[0][4 * hh], &K[1][4 * hh], rstd0 * qs, rstd1 * qs, first, e, zneg, pr[hh], l[hh]);
        float o[2][4][4];
#pragma unroll
        for (int hh = 0; hh < 2; hh++) attn_pv(pr[hh], &VH[8 * hh], &V[8 * hh], o[hh]);
#pragma unroll
        for (int hh = 0; hh < 2; hh++) {
          float l0 = l[hh][0], l1 = l[hh][1];
          l0 += __shfl_xor_sync(0xffffffffu, l0, 1); l1 += __shfl_xor_sync(0xffffffffu, l1, 1);
          l0 += __shfl_xor_sync(0xffffffffu, l0, 2); l1 += __shfl_xor_sync(0xffffffffu, l1, 2);
          asm("rcp.approx.ftz.f32 %0, %0;" : "+f"(l0)); asm("rcp.approx.ftz.f32 %0, %0;" : "+f"(l1));
#pragma unroll
          for (int dt = 0; dt < 4; dt += 2)
            stsm4(sb + OFF_STG + (16 * wu + lr) * 128 + (((4 * hh + dt + lt) ^ l7) << 4),
                  pack2(o[hh][dt][0] * l0, o[hh][dt][1] * l0), pack2(o[hh][dt][2] * l1, o[hh][dt][3] * l1),
                  pack2(o[hh][dt + 1][0] * l0, o[hh][dt + 1][1] * l0), pack2(o[hh][dt + 1][2] * l1, o[hh][dt + 1][3] * l1));
        }
        fence_async_smem();
        signal(JOB + ab);
        nb_sync<NB_BOTH>(256);
        resume();
      };

      TS(1 + 32 * L);
      mbar_wait(BAR(F1), 0); KB(0);    g1_issue(acca, L ? sb + OFF_X : sb + slot1(0), sb + slot1(0), True{});
      mbar_wait(BAR(F1 + 1), 0); KB(1); g1_issue(acca, L ? sb + OFF_X + 16384 : sb + slot1(1), sb + slot1(1), False{});
      wg_wait<1>(); release(E1 + 0);
      auto g1_bhead = [&](int p) {
        mbar_wait(BAR(F1 + p), 0); KB(p ? 2 : 16); g1_issue(accb, sb + OFF_X, sb + slot1(p), True{});
        if (p) { wg_wait<1>(); release(E1 + 1); }
        mbar_wait(BAR(F1 + p + 1), 0); KB(p ? 3 : 17); g1_issue(accb, sb + OFF_X + 16384, sb + slot1(p + 1), False{});
        wg_wait<1>(); release(E1 + p);
      };
      if (L == 0) {
        GEOM;
        const bf16* wp = P.wqkv_p + ((128 * opq(m) + 16 * wg + (t7 >> 3)) * 3072 + 128 * opq(j) + 64 * r + l7 * 8);
        const uint32_t ca = sb + OFF_STG + (16 * wg + (t7 >> 3)) * 784 + l7 * 32;
#pragma unroll 1
        for (int p = 0; p < 3; p++) {
          uint4 wv[4];
#pragma unroll
          for (int k = 0; k < 4; k++)
            asm volatile("ld.global.nc.v4.u32 {%0, %1, %2, %3}, [%4];" : "=r"(wv[k].x), "=r"(wv[k].y), "=r"(wv[k].z), "=r"(wv[k].w)
                         : "l"(wp + k * 32 * 3072 + p * 1024));
          g1_loop(acca, 2 + 3 * p, 5 + 3 * p, 0);
          float cs[8];
#pragma unroll
          for (int k = 0; k < 4; k++) {
            const uint4 v = wv[k];
            const float t[8] = {bf_lo(v.x), bf_hi(v.x), bf_lo(v.y), bf_hi(v.y), bf_lo(v.z), bf_hi(v.z), bf_lo(v.w), bf_hi(v.w)};
#pragma unroll
            for (int e = 0; e < 8; e++) cs[e] = k ? cs[e] + t[e] : t[e];
          }
          sts128(ca + p * 256, __float_as_uint(cs[0]), __float_as_uint(cs[1]), __float_as_uint(cs[2]), __float_as_uint(cs[3]));
          sts128(ca + p * 256 + 16, __float_as_uint(cs[4]), __float_as_uint(cs[5]), __float_as_uint(cs[6]), __float_as_uint(cs[7]));
        }
        signal(CSJ);
        g1_step(acca, 11, true);
        mbar_wait(BAR(XF), 0); mbar_wait(BAR(XF + 1), 0);
        g1_stats(12);
        wg_wait<0>(); release(E1 + 3);
        fence_regs(acca);
        g1_bhead(0);
      } else {
        g1_bhead(2);
        g1_stats(4);
        g1_loop(acca, 8, 18, 0);
      }
      stat_fetch();
      g1_loop(accb, 18, FA, 0);
      ln_stats();
      if (L == 0) mbar_wait(BAR(STAT), 0);
      center(acca, 0); wg_commit();
      wg_wait<0>(); release(E1 + ((FA - 1) & 3));
      fence_regs(acca);
      fold_v(acca); fold_k(acca, 0); fold_q(acca);
      sched_fence(P.zero);
      g1_loop(accb, FA, ATT, FA);
      attend(0, [&]() { wg_wait<0>(); release(E1 + ((ATT - 1) & 3)); mbar_wait(BAR(F1 + (ATT & 3)), (ATT >> 2) & 1); },
             [&]() { KB(ATT); g1_issue(accb, sb + slot1(ATT & 3), sb + slot1(ATT & 3), False{});
                     mbar_wait(BAR(F1 + ((ATT + 1) & 3)), ((ATT + 1) >> 2) & 1);
                     KB(ATT + 1); g1_issue(accb, sb + slot1((ATT + 1) & 3), sb + slot1((ATT + 1) & 3), False{}); });
      wg_wait<1>(); release(E1 + (ATT & 3));
      TS(3 + 32 * L);
      load_x();
      fence_regs(xa);
      center(accb, 1);
      g1_loop(accb, ATT + 2, 32 - LEAD1, 0);
      if (LEAD1 && wg == 0) { wg_wait<0>(); release(E1 + ((31 - LEAD1) & 3)); nb_sync<NB_LEAD>(256); }
      g1_loop(accb, 32 - LEAD1, 32, wg == 0 ? 32 - LEAD1 : 0);
      mbar_wait(BAR(STD), L);
      wg_wait<0>(); release(E1 + 3);
      fence_regs(accb);
      TS(4 + 32 * L);
      if (wu == 7) ST(0);
      fold_v(accb); fold_k(accb, 1);
      fold_q(accb);
      TS2(29 + 32 * L);
      {
        auto g2_issue = [&](int p, bool own) {
          const uint32_t st = sb + slot2(p);
          const uint64_t da = mkdesc((own ? sb + OFF_STG : st) + wg * 8192, 16, 1024), db = mkdesc(st + 16384, 8192, 1024);
          wg_fence();
#pragma unroll
          for (int kk = 0; kk < 4; kk++) wgmma_128<0, 1>(xa, da + kk * 2, db + kk * 128);
          wg_commit();
        };
        uint32_t par = L ? 0x1e : 0;
        int p = 0, pp = 0;
        auto g2_loop = [&](int n0, int n1, int nrel) {
#pragma unroll 1
          for (int n = n0; n < n1; n++) {
            mbar_wait(BAR(F2 + p), (par >> p) & 1);
            KB(32 + n);
            if (n == 9 && wu == 0) ST(5);
            par ^= 1u << p;
            g2_issue(p, n == 8);
            if (LEAD2 && n == 15 && wg == 0) nb_arrive<NB_LEAD>(256);
            wg_wait<1>();
            if (n > nrel) release(E2 + pp);
            pp = p; if (++p == 5) p = 0;
          }
        };
        g2_loop(0, COVER, 0);
        attend(1, [&]() { wg_wait<0>(); release(E2 + COVER - 1); mbar_wait(BAR(F2 + COVER), (par >> COVER) & 1); },
               [&]() { KB(32 + COVER); g2_issue(COVER, false);
                       mbar_wait(BAR(F2 + COVER + 1), (par >> (COVER + 1)) & 1);
                       KB(33 + COVER); g2_issue(COVER + 1, false); });
        wg_wait<1>(); release(E2 + COVER);
        par ^= 3u << COVER; pp = COVER + 1; p = (COVER + 2) % 5;
        TS(30 + 32 * L);
        {
          const bf16* bp = P.b2 + (128 * opq(i) + 16 * wu + ((fresh_tid() & 31) >> 2));
          asm volatile("ld.global.nc.u16 %0, [%1];" : "=h"(b2a) : "l"(bp));
          asm volatile("ld.global.nc.u16 %0, [%1];" : "=h"(b2b) : "l"(bp + 8));
        }
        TS2(14 + 32 * L);
        g2_loop(COVER + 2, 16 - LEAD2, 0);
        if (LEAD2 && wg == 1) { wg_wait<0>(); release(E2 + pp); nb_sync<NB_LEAD>(256); }
        g2_loop(16 - LEAD2, 16, wg == 1 ? 16 - LEAD2 : 0);
        wg_wait<0>();
        release(E2 + 0);
        fence_regs(xa);
      }
      TS(5 + 32 * L);
      if (wu == 0) ST(8);
      {
        GEOM;
        const uint32_t tg = 2 * (tag + 1) + 1;
        float s0 = 0.f, s1 = 0.f, s2 = 0.f, s3 = 0.f, q0 = 0.f, q1 = 0.f, q2 = 0.f, q3 = 0.f;
#pragma unroll
        for (int t = 0; t < 16; t++) {
          s0 += xa[4 * t]; s1 += xa[4 * t + 1]; s2 += xa[4 * t + 2]; s3 += xa[4 * t + 3];
          q0 = fmaf(xa[4 * t], xa[4 * t], q0); q1 = fmaf(xa[4 * t + 1], xa[4 * t + 1], q1);
          q2 = fmaf(xa[4 * t + 2], xa[4 * t + 2], q2); q3 = fmaf(xa[4 * t + 3], xa[4 * t + 3], q3);
        }
        const float sm = stat_publish(s0 + s1, q0 + q1, s2 + s3, q2 + q3, tg);
        const uint32_t t0 = clock32();
        wg_fence();
        wgmma_rs_224z(acc3, q == 0 ? 0x3f80u : 0u, q == 0 ? 0x3f80u : 0u, 0u, 0u, mkdesc_vec(sb + OFF_B1, 16));
        wg_commit();
        TS2(13 + 32 * L);
        const float pv0 = __shfl_sync(0xffffffffu, sm, 4 * l7) * (1.f / 128), pv1 = __shfl_sync(0xffffffffu, sm, 4 * l7 + 1) * (1.f / 128);
        while (clock32() - t0 < STAT_CLK) {}
        stat_fetch();
        stat_await(tg);
        float r0, m0, r1, m1;
        {
          float mean0, var0, mean1, var1;
          stat_combine(sv0[0], sv0[1], sv1[0], sv1[1], pv0, mean0, var0); stat_combine(sv0[2], sv0[3], sv1[2], sv1[3], pv1, mean1, var1);
          mean0 = __shfl_sync(0xffffffffu, mean0, g); var0 = __shfl_sync(0xffffffffu, var0, g);
          mean1 = __shfl_sync(0xffffffffu, mean1, g); var1 = __shfl_sync(0xffffffffu, var1, g);
          r0 = 0.5f * rsq(fmaf(var0 + 1e-5f, 1e-5f, var0)); r1 = 0.5f * rsq(fmaf(var1 + 1e-5f, 1e-5f, var1));
          m0 = -mean0 * r0; m1 = -mean1 * r1;
        }
        TS2(15 + 32 * L);
        const uint32_t ha = sb + OFF_X + wg * 16384 + (16 * w + lr) * 128;
#pragma unroll
        for (int t = 0; t < 16; t += 2) {
          stsm4(ha + (t >> 3) * 8192 + ((((t & 7) + lt) ^ l7) << 4),
                pack2(fmaf(xa[4 * t], r0, m0), fmaf(xa[4 * t + 1], r0, m0)), pack2(fmaf(xa[4 * t + 2], r1, m1), fmaf(xa[4 * t + 3], r1, m1)),
                pack2(fmaf(xa[4 * t + 4], r0, m0), fmaf(xa[4 * t + 5], r0, m0)), pack2(fmaf(xa[4 * t + 6], r1, m1), fmaf(xa[4 * t + 7], r1, m1)));
          if ((t & 7) == 6 && wg == 0) {
            __syncwarp();
            const int o = (t >> 3) * 8192 + w * 2048 + lane * 16;
            copy_out<4>(gHB + (opq(j) * 32 + 2 * i) * 16384 + o, sb + OFF_X + o, 512);
          }
        }
        signal(JOB + 2 + wg);
        fence_async_smem();
        nb_sync<NB_BOTH>(256);
      }
      TS(6 + 32 * L);
      auto g3_issue = [&](uint32_t a, int p) {
        const uint32_t st = sb + slot3(p);
        const uint64_t da = mkdesc(a + wg * 8192, 8192, 1024), db = mkdesc(st + 16384, 8192, 1024);
        wg_fence();
#pragma unroll
        for (int kk = 0; kk < 4; kk++) wgmma_224<1, 1>(acc3, da + kk * 128, db + kk * 128);
        wg_commit();
      };
      mbar_wait(BAR(F3 + 0), 0); KB(48); g3_issue(sb + OFF_X, 0);
      mbar_wait(BAR(F3 + 1), 0); KB(49); g3_issue(sb + OFF_X + 16384, 1);
      sched_fence(P.zero);
      {
        const float c0 = __uint_as_float((uint32_t)b2a << 16), c1 = __uint_as_float((uint32_t)b2b << 16);
#pragma unroll
        for (int t = 0; t < 16; t++) { xa[4 * t] += c0; xa[4 * t + 1] += c0; xa[4 * t + 2] += c1; xa[4 * t + 3] += c1; }
        fence_regs(xa);
      }
      wg_wait<1>(); release(E3 + 0);
      auto g3_loop = [&](int n0, int n1, int nrel) {
#pragma unroll 1
        for (int n = n0; n < n1; n++) {
          const int p = n & 3;
          mbar_wait(BAR(F3 + p), (n >> 2) & 1);
          KB(48 + n);
          if (n == 3 && wu == 0) ST(13);
          if (n == 2 && wu == 0) ST(14);
          g3_issue(sb + slot3(p), p);
          wg_wait<1>();
          if (n > nrel) release(E3 + ((n - 1) & 3));
        }
      };
      g3_loop(2, 32, 0);
      mbar_wait(BAR(RD), L);
      wg_wait<0>();
      release(E3 + 3);
      fence_regs(acc3);
      TS(7 + 32 * L);
      if (wu == 0) ST(16);
      auto g4_issue = [&](int p, uint32_t b) {
        const uint64_t da = mkdesc(sb + slot4(p) + wg * 8192, 8192, 1024), db = mkdesc(b, 8192, 1024);
        wg_fence();
#pragma unroll
        for (int kk = 0; kk < 4; kk++) wgmma_128<1, 1>(xa, da + kk * 128, db + kk * 128);
        wg_commit();
      };
      uint32_t par = L ? 0x3c : 0;
      {
        GEOM;
        const uint32_t ua = sb + wg * 8192 + (8 * lt + l7) * 128 + (((2 * w + ((lane >> 3) & 1)) ^ l7) << 4);
#pragma unroll
        for (int cc = 0; cc < 4; cc++) {
          const int c = cc == 0 ? 3 : cc == 3 ? 0 : cc;
          uint32_t u[16];
#pragma unroll
          for (int k = 0; k < (c == 3 ? 8 : 16); k++) u[k] = pack2(gelu_half(acc3[32 * c + 2 * k]), gelu_half(acc3[32 * c + 2 * k + 1]));
          if (c == 3) mbar_wait(BAR(E3 + 2), 1);
#pragma unroll
          for (int k = 0; k < (c == 3 ? 2 : 4); k++)
            stsm4t(ua + (c == 3 ? slot4(5) + 16384 : c == 0 ? slot4(2) + 16384 : OFF_X + (c - 1) * 16384) + k * 2048, u[4 * k], u[4 * k + 1], u[4 * k + 2], u[4 * k + 3]);
          if (c == 3) {
            __syncwarp();
            const int o = wg * 8192 + (lane >> 1) * 128 + (((2 * w + (lane & 1)) ^ ((lane >> 1) & 7)) << 4);
            copy_out<2>(gUB + (opq(j) * 56 + 48 + m) * 16384 + r * 4096 + o, sb + slot4(5) + 16384 + o, 2048);
            signal(JOB + 7);
          } else if (c == 0) { fence_async_smem(); signal(JOB + 6); }
          if (c == 3) sched_fence(P.zero);
          TS2(16 + 3 * c + 32 * L);
        }
        nb_sync<NB_BOTH>(256);
      }
      TS(8 + 32 * L);
      {
        int p = 0, pp = 0;
        auto g4_loop = [&](int n0, int n1, int nrel) {
#pragma unroll 1
          for (int n = n0; n < n1; n++) {
            mbar_wait(BAR(F4 + p), (par >> p) & 1);
            KB(80 + n);
            if (n == 3 && wu == 0) ST(21);
            if (n == 0 && wu == 0) ST(22);
            par ^= 1u << p;
            g4_issue(p, n < 2 ? sb + OFF_X + n * 16384 : sb + slot4(p) + 16384);
            if (LEAD4 && n == 55 && wg == 0) nb_arrive<NB_LEAD>(256);
            wg_wait<1>();
            if (n > nrel) release(E4 + pp);
            pp = p; if (++p == 6) p = 0;
          }
        };
        g4_loop(0, 56 - LEAD4, 0);
        if (LEAD4 && wg == 1) { wg_wait<0>(); release(E4 + pp); nb_sync<NB_LEAD>(256); }
        g4_loop(56 - LEAD4, 56, wg == 1 ? 56 - LEAD4 : 0);
      }
      mbar_wait(BAR(RD + 1), L);
      wg_wait<0>();
      release(E4 + 1);
      fence_regs(xa);
      TS(9 + 32 * L);
      {
        GEOM;
#pragma unroll
        for (int t = 0; t < 16; t += 2) {
          stsm4(sb + OFF_X + (t >> 3) * 16384 + (16 * wu + lr) * 128 + ((((t & 7) + lt) ^ l7) << 4),
                pack2(xa[4 * t], xa[4 * t + 1]), pack2(xa[4 * t + 2], xa[4 * t + 3]),
                pack2(xa[4 * t + 4], xa[4 * t + 5]), pack2(xa[4 * t + 6], xa[4 * t + 7]));
          if (t == 6 && L == 0) {
            __syncwarp();
            const int o = wu * 2048 + lane * 16;
            copy_out<4>(gXB + (opq(i) * 16 + 2 * j) * 16384 + o, sb + OFF_X + o, 512);
            signal(JOB + 8);
          }
        }
        fence_async_smem();
        if (L == 0) signal(JOB + 9);
        else {
          __syncwarp();
          if (elect_one()) {
            tma2d_store(&P.out, sb + OFF_X + wu * 2048, 128 * j, 128 * i + 16 * wu);
            tma2d_store(&P.out, sb + OFF_X + 16384 + wu * 2048, 128 * j + 64, 128 * i + 16 * wu);
            bulk_commit(); bulk_wait0();
          }
          __syncwarp();
        }
        nb_sync<NB_BOTH>(256);
      }
      TS(10 + 32 * L);
      KB(136);
    }
    cluster_bar();
    TS(32);
  }
}

typedef CUresult (*EncodeFn)(CUtensorMap*, CUtensorMapDataType, cuuint32_t, void*, const cuuint64_t*, const cuuint64_t*, const cuuint32_t*,
                             const cuuint32_t*, CUtensorMapInterleave, CUtensorMapSwizzle, CUtensorMapL2promotion, CUtensorMapFloatOOBfill);

void make_map(EncodeFn enc, CUtensorMap* mp, const void* base, int rank, cuuint64_t d0, cuuint64_t d1, cuuint64_t d2, cuuint64_t s1, cuuint64_t s2,
              cuuint32_t b0, cuuint32_t b1, cuuint32_t b2) {
  cuuint64_t dims[3] = {d0, d1, d2}, strides[2] = {s1, s2};
  cuuint32_t box[3] = {b0, b1, b2}, es[3] = {1, 1, 1};
  CUresult res = enc(mp, CU_TENSOR_MAP_DATA_TYPE_BFLOAT16, rank, const_cast<void*>(base), dims, strides, box, es, CU_TENSOR_MAP_INTERLEAVE_NONE,
                     CU_TENSOR_MAP_SWIZZLE_128B, CU_TENSOR_MAP_L2_PROMOTION_L2_128B, CU_TENSOR_MAP_FLOAT_OOB_FILL_NONE);
  (void)res;
}

}

extern "C" void kernel_launch(void* const* d_in, const int* in_sizes, int n_in, void* d_out, int out_size) {
  (void)in_sizes; (void)n_in; (void)out_size;
  static EncodeFn enc = nullptr;
  if (!enc) {
    void* fn = nullptr;
    cudaDriverEntryPointQueryResult qr;
    cudaGetDriverEntryPoint("cuTensorMapEncodeTiled", &fn, cudaEnableDefault, &qr);
    enc = (EncodeFn)fn;
    cudaFuncSetAttribute(fused_kernel, cudaFuncAttributeMaxDynamicSharedMemorySize, SMEM_BYTES);
  }
  Params P;
  make_map(enc, &P.x0, d_in[0], 2, D_, S_, 1, D_ * 2, 0, 64, 128, 1);
  make_map(enc, &P.wqkv, d_in[1], 3, D_, D_, 3, 3 * D_ * 2, D_ * 2, 64, 32, 3);
  make_map(enc, &P.wo, d_in[2], 2, D_, D_, 1, D_ * 2, 0, 64, 64, 1);
  make_map(enc, &P.w1, d_in[4], 3, 64, S_, F_ / 64, F_ * 2, 128, 64, 64, 3);
  make_map(enc, &P.w1h, d_in[4], 3, 32, S_, F_ / 32, F_ * 2, 64, 64, 64, 1);
  make_map(enc, &P.w2, d_in[6], 3, 64, F_, S_ / 64, S_ * 2, 128, 64, 64, 2);
  make_map(enc, &P.out, d_out, 2, D_, S_, 1, D_ * 2, 0, 64, 16, 1);
  P.wqkv_p = (const bf16*)d_in[1];
  P.b1 = (const bf16*)d_in[5];
  P.b2 = (const bf16*)d_in[7];
  P.zero = 0;
  fused_kernel<<<128, 384, SMEM_BYTES>>>(P);
}
```

```cpp
#include <cuda_runtime.h>
#include <cuda_bf16.h>
#include <cuda.h>
#include <stdint.h>

namespace {

typedef __nv_bfloat16 bf16;
constexpr int S_ = 2048, D_ = 1024, F_ = 3584;

constexpr uint32_t OFF_STG  = 163840;
constexpr uint32_t OFF_X    = 196608;
constexpr uint32_t OFF_BAR  = 229376;
constexpr uint32_t OFF_CS   = OFF_BAR + 512;
constexpr uint32_t OFF_B1   = OFF_CS + 1536;
constexpr uint32_t SMEM_BYTES = OFF_B1 + 896 + 128;
constexpr int F1 = 0, E1 = 4, F2 = 8, E2 = 13, F3 = 18, E3 = 22, F4 = 26, E4 = 32;
constexpr int JOB = 38;
constexpr int RD = 48;
constexpr int XF = 54, STD = 56, STAT = 58, FOLD = 59, CSJ = 61, HALO = 62;
constexpr int NB_BOTH = 1, NB_HELP = 2, NB_INIT = 3, NB_LEAD = 4;

__device__ __forceinline__ uint32_t slot1(int p) { return p * 40960; }
__device__ __forceinline__ uint32_t slot2(int p) { return p * 32768; }
__device__ __forceinline__ uint32_t slot3(int p) { return ((p + 2) & 3) * 49152; }
__device__ __forceinline__ uint32_t slot4(int p) { return (p < 2 ? p + 4 : p - 2) * 32768; }

__device__ __align__(1024) uint8_t gXB[16 * 16 * 16384];
__device__ __align__(1024) uint8_t gOB[16 * 16 * 16384];
__device__ __align__(1024) uint8_t gHB[8 * 32 * 16384];
__device__ __align__(1024) uint8_t gUB[8 * 56 * 16384];
__device__ __align__(1024) uint2   gST[2][16][8][8][16];
__device__ __align__(1024) uint4   gHalo[2][16][8][12][32];
__device__ __align__(1024) uint32_t gAck[2][16][8][2][8];
__device__ __align__(1024) uint4   gCS[8][16][64];
__device__ __align__(1024) uint32_t gFlag[2][7][16][32];
__device__ uint32_t gEpoch;
#define TS(k)
#define TS2(k)

#define KB(k)
#define ST(k)
struct Params {
  CUtensorMap x0, wqkv, wo, w1, w1h, w2, out;
  const bf16 *wqkv_p, *wo_p, *w1_p, *w2_p, *b1, *b2;
  uint32_t zero;
};

template <int TA, int TB, int O = 0, int LEN> __device__ __forceinline__ void wgmma_32(float (&d)[LEN], uint32_t da, uint32_t db) {
  asm volatile("{\n.reg .b64 da, db;\nmov.b64 da, {%16, 0x40000040};\nmov.b64 db, {%17, 0x40000040};\n"
  "wgmma.mma_async.sync.aligned.m64n32k16.f32.bf16.bf16 {"
  "%0, %1, %2, %3, %4, %5, %6, %7, %8, %9, %10, %11, %12, %13, %14, %15"
  "}, da, db, 1, 1, 1, %18, %19;\n}\n"
  : "+f"(d[O + 0]), "+f"(d[O + 1]), "+f"(d[O + 2]), "+f"(d[O + 3]), "+f"(d[O + 4]), "+f"(d[O + 5]), "+f"(d[O + 6]), "+f"(d[O + 7]),
    "+f"(d[O + 8]), "+f"(d[O + 9]), "+f"(d[O + 10]), "+f"(d[O + 11]), "+f"(d[O + 12]), "+f"(d[O + 13]), "+f"(d[O + 14]), "+f"(d[O + 15])
  : "r"(da), "r"(db), "n"(TA), "n"(TB));
}
template <int TA, int TB, int O = 0, int LEN> __device__ __forceinline__ void wgmma_128(float (&d)[LEN], uint32_t da, uint32_t db) {
  asm volatile("{\n.reg .b64 da, db;\nmov.b64 da, {%64, 0x40000040};\nmov.b64 db, {%65, 0x40000040};\n"
  "wgmma.mma_async.sync.aligned.m64n128k16.f32.bf16.bf16 {"
  "%0, %1, %2, %3, %4, %5, %6, %7, %8, %9, %10, %11, %12, %13, %14, %15, "
  "%16, %17, %18, %19, %20, %21, %22, %23, %24, %25, %26, %27, %28, %29, %30, %31, "
  "%32, %33, %34, %35, %36, %37, %38, %39, %40, %41, %42, %43, %44, %45, %46, %47, "
  "%48, %49, %50, %51, %52, %53, %54, %55, %56, %57, %58, %59, %60, %61, %62, %63"
  "}, da, db, 1, 1, 1, %66, %67;\n}\n"
  : "+f"(d[O + 0]), "+f"(d[O + 1]), "+f"(d[O + 2]), "+f"(d[O + 3]), "+f"(d[O + 4]), "+f"(d[O + 5]), "+f"(d[O + 6]), "+f"(d[O + 7]),
    "+f"(d[O + 8]), "+f"(d[O + 9]), "+f"(d[O + 10]), "+f"(d[O + 11]), "+f"(d[O + 12]), "+f"(d[O + 13]), "+f"(d[O + 14]), "+f"(d[O + 15]),
    "+f"(d[O + 16]), "+f"(d[O + 17]), "+f"(d[O + 18]), "+f"(d[O + 19]), "+f"(d[O + 20]), "+f"(d[O + 21]), "+f"(d[O + 22]), "+f"(d[O + 23]),
    "+f"(d[O + 24]), "+f"(d[O + 25]), "+f"(d[O + 26]), "+f"(d[O + 27]), "+f"(d[O + 28]), "+f"(d[O + 29]), "+f"(d[O + 30]), "+f"(d[O + 31]),
    "+f"(d[O + 32]), "+f"(d[O + 33]), "+f"(d[O + 34]), "+f"(d[O + 35]), "+f"(d[O + 36]), "+f"(d[O + 37]), "+f"(d[O + 38]), "+f"(d[O + 39]),
    "+f"(d[O + 40]), "+f"(d[O + 41]), "+f"(d[O + 42]), "+f"(d[O + 43]), "+f"(d[O + 44]), "+f"(d[O + 45]), "+f"(d[O + 46]), "+f"(d[O + 47]),
    "+f"(d[O + 48]), "+f"(d[O + 49]), "+f"(d[O + 50]), "+f"(d[O + 51]), "+f"(d[O + 52]), "+f"(d[O + 53]), "+f"(d[O + 54]), "+f"(d[O + 55]),
    "+f"(d[O + 56]), "+f"(d[O + 57]), "+f"(d[O + 58]), "+f"(d[O + 59]), "+f"(d[O + 60]), "+f"(d[O + 61]), "+f"(d[O + 62]), "+f"(d[O + 63])
  : "r"(da), "r"(db), "n"(TA), "n"(TB));
}
template <int TA, int TB, int O = 0, int LEN> __device__ __forceinline__ void wgmma_192(float (&d)[LEN], uint32_t da, uint32_t db) {
  asm volatile("{\n.reg .b64 da, db;\nmov.b64 da, {%96, 0x40000040};\nmov.b64 db, {%97, 0x40000040};\n"
  "wgmma.mma_async.sync.aligned.m64n192k16.f32.bf16.bf16 {"
  "%0, %1, %2, %3, %4, %5, %6, %7, %8, %9, %10, %11, %12, %13, %14, %15, "
  "%16, %17, %18, %19, %20, %21, %22, %23, %24, %25, %26, %27, %28, %29, %30, %31, "
  "%32, %33, %34, %35, %36, %37, %38, %39, %40, %41, %42, %43, %44, %45, %46, %47, "
  "%48, %49, %50, %51, %52, %53, %54, %55, %56, %57, %58, %59, %60, %61, %62, %63, "
  "%64, %65, %66, %67, %68, %69, %70, %71, %72, %73, %74, %75, %76, %77, %78, %79, "
  "%80, %81, %82, %83, %84, %85, %86, %87, %88, %89, %90, %91, %92, %93, %94, %95"
  "}, da, db, 1, 1, 1, %98, %99;\n}\n"
  : "+f"(d[O + 0]), "+f"(d[O + 1]), "+f"(d[O + 2]), "+f"(d[O + 3]), "+f"(d[O + 4]), "+f"(d[O + 5]), "+f"(d[O + 6]), "+f"(d[O + 7]),
    "+f"(d[O + 8]), "+f"(d[O + 9]), "+f"(d[O + 10]), "+f"(d[O + 11]), "+f"(d[O + 12]), "+f"(d[O + 13]), "+f"(d[O + 14]), "+f"(d[O + 15]),
    "+f"(d[O + 16]), "+f"(d[O + 17]), "+f"(d[O + 18]), "+f"(d[O + 19]), "+f"(d[O + 20]), "+f"(d[O + 21]), "+f"(d[O + 22]), "+f"(d[O + 23]),
    "+f"(d[O + 24]), "+f"(d[O + 25]), "+f"(d[O + 26]), "+f"(d[O + 27]), "+f"(d[O + 28]), "+f"(d[O + 29]), "+f"(d[O + 30]), "+f"(d[O + 31]),
    "+f"(d[O + 32]), "+f"(d[O + 33]), "+f"(d[O + 34]), "+f"(d[O + 35]), "+f"(d[O + 36]), "+f"(d[O + 37]), "+f"(d[O + 38]), "+f"(d[O + 39]),
    "+f"(d[O + 40]), "+f"(d[O + 41]), "+f"(d[O + 42]), "+f"(d[O + 43]), "+f"(d[O + 44]), "+f"(d[O + 45]), "+f"(d[O + 46]), "+f"(d[O + 47]),
    "+f"(d[O + 48]), "+f"(d[O + 49]), "+f"(d[O + 50]), "+f"(d[O + 51]), "+f"(d[O + 52]), "+f"(d[O + 53]), "+f"(d[O + 54]), "+f"(d[O + 55]),
    "+f"(d[O + 56]), "+f"(d[O + 57]), "+f"(d[O + 58]), "+f"(d[O + 59]), "+f"(d[O + 60]), "+f"(d[O + 61]), "+f"(d[O + 62]), "+f"(d[O + 63]),
    "+f"(d[O + 64]), "+f"(d[O + 65]), "+f"(d[O + 66]), "+f"(d[O + 67]), "+f"(d[O + 68]), "+f"(d[O + 69]), "+f"(d[O + 70]), "+f"(d[O + 71]),
    "+f"(d[O + 72]), "+f"(d[O + 73]), "+f"(d[O + 74]), "+f"(d[O + 75]), "+f"(d[O + 76]), "+f"(d[O + 77]), "+f"(d[O + 78]), "+f"(d[O + 79]),
    "+f"(d[O + 80]), "+f"(d[O + 81]), "+f"(d[O + 82]), "+f"(d[O + 83]), "+f"(d[O + 84]), "+f"(d[O + 85]), "+f"(d[O + 86]), "+f"(d[O + 87]),
    "+f"(d[O + 88]), "+f"(d[O + 89]), "+f"(d[O + 90]), "+f"(d[O + 91]), "+f"(d[O + 92]), "+f"(d[O + 93]), "+f"(d[O + 94]), "+f"(d[O + 95])
  : "r"(da), "r"(db), "n"(TA), "n"(TB));
}
template <int TA, int TB, int O = 0, int LEN> __device__ __forceinline__ void wgmma_192z(float (&d)[LEN], uint32_t da, uint32_t db) {
  asm volatile("{\n.reg .b64 da, db;\nmov.b64 da, {%96, 0x40000040};\nmov.b64 db, {%97, 0x40000040};\n"
  "wgmma.mma_async.sync.aligned.m64n192k16.f32.bf16.bf16 {"
  "%0, %1, %2, %3, %4, %5, %6, %7, %8, %9, %10, %11, %12, %13, %14, %15, "
  "%16, %17, %18, %19, %20, %21, %22, %23, %24, %25, %26, %27, %28, %29, %30, %31, "
  "%32, %33, %34, %35, %36, %37, %38, %39, %40, %41, %42, %43, %44, %45, %46, %47, "
  "%48, %49, %50, %51, %52, %53, %54, %55, %56, %57, %58, %59, %60, %61, %62, %63, "
  "%64, %65, %66, %67, %68, %69, %70, %71, %72, %73, %74, %75, %76, %77, %78, %79, "
  "%80, %81, %82, %83, %84, %85, %86, %87, %88, %89, %90, %91, %92, %93, %94, %95"
  "}, da, db, 0, 1, 1, %98, %99;\n}\n"
  : "=f"(d[O + 0]), "=f"(d[O + 1]), "=f"(d[O + 2]), "=f"(d[O + 3]), "=f"(d[O + 4]), "=f"(d[O + 5]), "=f"(d[O + 6]), "=f"(d[O + 7]),
    "=f"(d[O + 8]), "=f"(d[O + 9]), "=f"(d[O + 10]), "=f"(d[O + 11]), "=f"(d[O + 12]), "=f"(d[O + 13]), "=f"(d[O + 14]), "=f"(d[O + 15]),
    "=f"(d[O + 16]), "=f"(d[O + 17]), "=f"(d[O + 18]), "=f"(d[O + 19]), "=f"(d[O + 20]), "=f"(d[O + 21]), "=f"(d[O + 22]), "=f"(d[O + 23]),
    "=f"(d[O + 24]), "=f"(d[O + 25]), "=f"(d[O + 26]), "=f"(d[O + 27]), "=f"(d[O + 28]), "=f"(d[O + 29]), "=f"(d[O + 30]), "=f"(d[O + 31]),
    "=f"(d[O + 32]), "=f"(d[O + 33]), "=f"(d[O + 34]), "=f"(d[O + 35]), "=f"(d[O + 36]), "=f"(d[O + 37]), "=f"(d[O + 38]), "=f"(d[O + 39]),
    "=f"(d[O + 40]), "=f"(d[O + 41]), "=f"(d[O + 42]), "=f"(d[O + 43]), "=f"(d[O + 44]), "=f"(d[O + 45]), "=f"(d[O + 46]), "=f"(d[O + 47]),
    "=f"(d[O + 48]), "=f"(d[O + 49]), "=f"(d[O + 50]), "=f"(d[O + 51]), "=f"(d[O + 52]), "=f"(d[O + 53]), "=f"(d[O + 54]), "=f"(d[O + 55]),
    "=f"(d[O + 56]), "=f"(d[O + 57]), "=f"(d[O + 58]), "=f"(d[O + 59]), "=f"(d[O + 60]), "=f"(d[O + 61]), "=f"(d[O + 62]), "=f"(d[O + 63]),
    "=f"(d[O + 64]), "=f"(d[O + 65]), "=f"(d[O + 66]), "=f"(d[O + 67]), "=f"(d[O + 68]), "=f"(d[O + 69]), "=f"(d[O + 70]), "=f"(d[O + 71]),
    "=f"(d[O + 72]), "=f"(d[O + 73]), "=f"(d[O + 74]), "=f"(d[O + 75]), "=f"(d[O + 76]), "=f"(d[O + 77]), "=f"(d[O + 78]), "=f"(d[O + 79]),
    "=f"(d[O + 80]), "=f"(d[O + 81]), "=f"(d[O + 82]), "=f"(d[O + 83]), "=f"(d[O + 84]), "=f"(d[O + 85]), "=f"(d[O + 86]), "=f"(d[O + 87]),
    "=f"(d[O + 88]), "=f"(d[O + 89]), "=f"(d[O + 90]), "=f"(d[O + 91]), "=f"(d[O + 92]), "=f"(d[O + 93]), "=f"(d[O + 94]), "=f"(d[O + 95])
  : "r"(da), "r"(db), "n"(TA), "n"(TB));
}
template <int TA, int TB, int O = 0, int LEN> __device__ __forceinline__ void wgmma_224(float (&d)[LEN], uint32_t da, uint32_t db) {
  asm volatile("{\n.reg .b64 da, db;\nmov.b64 da, {%112, 0x40000040};\nmov.b64 db, {%113, 0x40000040};\n"
  "wgmma.mma_async.sync.aligned.m64n224k16.f32.bf16.bf16 {"
  "%0, %1, %2, %3, %4, %5, %6, %7, %8, %9, %10, %11, %12, %13, %14, %15, "
  "%16, %17, %18, %19, %20, %21, %22, %23, %24, %25, %26, %27, %28, %29, %30, %31, "
  "%32, %33, %34, %35, %36, %37, %38, %39, %40, %41, %42, %43, %44, %45, %46, %47, "
  "%48, %49, %50, %51, %52, %53, %54, %55, %56, %57, %58, %59, %60, %61, %62, %63, "
  "%64, %65, %66, %67, %68, %69, %70, %71, %72, %73, %74, %75, %76, %77, %78, %79, "
  "%80, %81, %82, %83, %84, %85, %86, %87, %88, %89, %90, %91, %92, %93, %94, %95, "
  "%96, %97, %98, %99, %100, %101, %102, %103, %104, %105, %106, %107, %108, %109, %110, %111"
  "}, da, db, 1, 1, 1, %114, %115;\n}\n"
  : "+f"(d[O + 0]), "+f"(d[O + 1]), "+f"(d[O + 2]), "+f"(d[O + 3]), "+f"(d[O + 4]), "+f"(d[O + 5]), "+f"(d[O + 6]), "+f"(d[O + 7]),
    "+f"(d[O + 8]), "+f"(d[O + 9]), "+f"(d[O + 10]), "+f"(d[O + 11]), "+f"(d[O + 12]), "+f"(d[O + 13]), "+f"(d[O + 14]), "+f"(d[O + 15]),
    "+f"(d[O + 16]), "+f"(d[O + 17]), "+f"(d[O + 18]), "+f"(d[O + 19]), "+f"(d[O + 20]), "+f"(d[O + 21]), "+f"(d[O + 22]), "+f"(d[O + 23]),
    "+f"(d[O + 24]), "+f"(d[O + 25]), "+f"(d[O + 26]), "+f"(d[O + 27]), "+f"(d[O + 28]), "+f"(d[O + 29]), "+f"(d[O + 30]), "+f"(d[O + 31]),
    "+f"(d[O + 32]), "+f"(d[O + 33]), "+f"(d[O + 34]), "+f"(d[O + 35]), "+f"(d[O + 36]), "+f"(d[O + 37]), "+f"(d[O + 38]), "+f"(d[O + 39]),
    "+f"(d[O + 40]), "+f"(d[O + 41]), "+f"(d[O + 42]), "+f"(d[O + 43]), "+f"(d[O + 44]), "+f"(d[O + 45]), "+f"(d[O + 46]), "+f"(d[O + 47]),
    "+f"(d[O + 48]), "+f"(d[O + 49]), "+f"(d[O + 50]), "+f"(d[O + 51]), "+f"(d[O + 52]), "+f"(d[O + 53]), "+f"(d[O + 54]), "+f"(d[O + 55]),
    "+f"(d[O + 56]), "+f"(d[O + 57]), "+f"(d[O + 58]), "+f"(d[O + 59]), "+f"(d[O + 60]), "+f"(d[O + 61]), "+f"(d[O + 62]), "+f"(d[O + 63]),
    "+f"(d[O + 64]), "+f"(d[O + 65]), "+f"(d[O + 66]), "+f"(d[O + 67]), "+f"(d[O + 68]), "+f"(d[O + 69]), "+f"(d[O + 70]), "+f"(d[O + 71]),
    "+f"(d[O + 72]), "+f"(d[O + 73]), "+f"(d[O + 74]), "+f"(d[O + 75]), "+f"(d[O + 76]), "+f"(d[O + 77]), "+f"(d[O + 78]), "+f"(d[O + 79]),
    "+f"(d[O + 80]), "+f"(d[O + 81]), "+f"(d[O + 82]), "+f"(d[O + 83]), "+f"(d[O + 84]), "+f"(d[O + 85]), "+f"(d[O + 86]), "+f"(d[O + 87]),
    "+f"(d[O + 88]), "+f"(d[O + 89]), "+f"(d[O + 90]), "+f"(d[O + 91]), "+f"(d[O + 92]), "+f"(d[O + 93]), "+f"(d[O + 94]), "+f"(d[O + 95]),
    "+f"(d[O + 96]), "+f"(d[O + 97]), "+f"(d[O + 98]), "+f"(d[O + 99]), "+f"(d[O + 100]), "+f"(d[O + 101]), "+f"(d[O + 102]), "+f"(d[O + 103]),
    "+f"(d[O + 104]), "+f"(d[O + 105]), "+f"(d[O + 106]), "+f"(d[O + 107]), "+f"(d[O + 108]), "+f"(d[O + 109]), "+f"(d[O + 110]), "+f"(d[O + 111])
  : "r"(da), "r"(db), "n"(TA), "n"(TB));
}
__device__ __forceinline__ void wgmma_rs_192(float (&d)[96], uint32_t a0, uint32_t a1, uint32_t a2, uint32_t a3, uint64_t db) {
  asm volatile("wgmma.mma_async.sync.aligned.m64n192k16.f32.bf16.bf16 {"
  "%0, %1, %2, %3, %4, %5, %6, %7, %8, %9, %10, %11, %12, %13, %14, %15, "
  "%16, %17, %18, %19, %20, %21, %22, %23, %24, %25, %26, %27, %28, %29, %30, %31, "
  "%32, %33, %34, %35, %36, %37, %38, %39, %40, %41, %42, %43, %44, %45, %46, %47, "
  "%48, %49, %50, %51, %52, %53, %54, %55, %56, %57, %58, %59, %60, %61, %62, %63, "
  "%64, %65, %66, %67, %68, %69, %70, %71, %72, %73, %74, %75, %76, %77, %78, %79, "
  "%80, %81, %82, %83, %84, %85, %86, %87, %88, %89, %90, %91, %92, %93, %94, %95"
  "}, {%96, %97, %98, %99}, %100, 1, 1, 1, 1;\n"
  : "+f"(d[0]), "+f"(d[1]), "+f"(d[2]), "+f"(d[3]), "+f"(d[4]), "+f"(d[5]), "+f"(d[6]), "+f"(d[7]),
    "+f"(d[8]), "+f"(d[9]), "+f"(d[10]), "+f"(d[11]), "+f"(d[12]), "+f"(d[13]), "+f"(d[14]), "+f"(d[15]),
    "+f"(d[16]), "+f"(d[17]), "+f"(d[18]), "+f"(d[19]), "+f"(d[20]), "+f"(d[21]), "+f"(d[22]), "+f"(d[23]),
    "+f"(d[24]), "+f"(d[25]), "+f"(d[26]), "+f"(d[27]), "+f"(d[28]), "+f"(d[29]), "+f"(d[30]), "+f"(d[31]),
    "+f"(d[32]), "+f"(d[33]), "+f"(d[34]), "+f"(d[35]), "+f"(d[36]), "+f"(d[37]), "+f"(d[38]), "+f"(d[39]),
    "+f"(d[40]), "+f"(d[41]), "+f"(d[42]), "+f"(d[43]), "+f"(d[44]), "+f"(d[45]), "+f"(d[46]), "+f"(d[47]),
    "+f"(d[48]), "+f"(d[49]), "+f"(d[50]), "+f"(d[51]), "+f"(d[52]), "+f"(d[53]), "+f"(d[54]), "+f"(d[55]),
    "+f"(d[56]), "+f"(d[57]), "+f"(d[58]), "+f"(d[59]), "+f"(d[60]), "+f"(d[61]), "+f"(d[62]), "+f"(d[63]),
    "+f"(d[64]), "+f"(d[65]), "+f"(d[66]), "+f"(d[67]), "+f"(d[68]), "+f"(d[69]), "+f"(d[70]), "+f"(d[71]),
    "+f"(d[72]), "+f"(d[73]), "+f"(d[74]), "+f"(d[75]), "+f"(d[76]), "+f"(d[77]), "+f"(d[78]), "+f"(d[79]),
    "+f"(d[80]), "+f"(d[81]), "+f"(d[82]), "+f"(d[83]), "+f"(d[84]), "+f"(d[85]), "+f"(d[86]), "+f"(d[87]),
    "+f"(d[88]), "+f"(d[89]), "+f"(d[90]), "+f"(d[91]), "+f"(d[92]), "+f"(d[93]), "+f"(d[94]), "+f"(d[95])
  : "r"(a0), "r"(a1), "r"(a2), "r"(a3), "l"(db));
}
__device__ __forceinline__ void wgmma_rs_224z(float (&d)[112], uint32_t a0, uint32_t a1, uint32_t a2, uint32_t a3, uint64_t db) {
  asm volatile("wgmma.mma_async.sync.aligned.m64n224k16.f32.bf16.bf16 {"
  "%0, %1, %2, %3, %4, %5, %6, %7, %8, %9, %10, %11, %12, %13, %14, %15, "
  "%16, %17, %18, %19, %20, %21, %22, %23, %24, %25, %26, %27, %28, %29, %30, %31, "
  "%32, %33, %34, %35, %36, %37, %38, %39, %40, %41, %42, %43, %44, %45, %46, %47, "
  "%48, %49, %50, %51, %52, %53, %54, %55, %56, %57, %58, %59, %60, %61, %62, %63, "
  "%64, %65, %66, %67, %68, %69, %70, %71, %72, %73, %74, %75, %76, %77, %78, %79, "
  "%80, %81, %82, %83, %84, %85, %86, %87, %88, %89, %90, %91, %92, %93, %94, %95, "
  "%96, %97, %98, %99, %100, %101, %102, %103, %104, %105, %106, %107, %108, %109, %110, %111"
  "}, {%112, %113, %114, %115}, %116, 0, 1, 1, 1;\n"
  : "=f"(d[0]), "=f"(d[1]), "=f"(d[2]), "=f"(d[3]), "=f"(d[4]), "=f"(d[5]), "=f"(d[6]), "=f"(d[7]),
    "=f"(d[8]), "=f"(d[9]), "=f"(d[10]), "=f"(d[11]), "=f"(d[12]), "=f"(d[13]), "=f"(d[14]), "=f"(d[15]),
    "=f"(d[16]), "=f"(d[17]), "=f"(d[18]), "=f"(d[19]), "=f"(d[20]), "=f"(d[21]), "=f"(d[22]), "=f"(d[23]),
    "=f"(d[24]), "=f"(d[25]), "=f"(d[26]), "=f"(d[27]), "=f"(d[28]), "=f"(d[29]), "=f"(d[30]), "=f"(d[31]),
    "=f"(d[32]), "=f"(d[33]), "=f"(d[34]), "=f"(d[35]), "=f"(d[36]), "=f"(d[37]), "=f"(d[38]), "=f"(d[39]),
    "=f"(d[40]), "=f"(d[41]), "=f"(d[42]), "=f"(d[43]), "=f"(d[44]), "=f"(d[45]), "=f"(d[46]), "=f"(d[47]),
    "=f"(d[48]), "=f"(d[49]), "=f"(d[50]), "=f"(d[51]), "=f"(d[52]), "=f"(d[53]), "=f"(d[54]), "=f"(d[55]),
    "=f"(d[56]), "=f"(d[57]), "=f"(d[58]), "=f"(d[59]), "=f"(d[60]), "=f"(d[61]), "=f"(d[62]), "=f"(d[63]),
    "=f"(d[64]), "=f"(d[65]), "=f"(d[66]), "=f"(d[67]), "=f"(d[68]), "=f"(d[69]), "=f"(d[70]), "=f"(d[71]),
    "=f"(d[72]), "=f"(d[73]), "=f"(d[74]), "=f"(d[75]), "=f"(d[76]), "=f"(d[77]), "=f"(d[78]), "=f"(d[79]),
    "=f"(d[80]), "=f"(d[81]), "=f"(d[82]), "=f"(d[83]), "=f"(d[84]), "=f"(d[85]), "=f"(d[86]), "=f"(d[87]),
    "=f"(d[88]), "=f"(d[89]), "=f"(d[90]), "=f"(d[91]), "=f"(d[92]), "=f"(d[93]), "=f"(d[94]), "=f"(d[95]),
    "=f"(d[96]), "=f"(d[97]), "=f"(d[98]), "=f"(d[99]), "=f"(d[100]), "=f"(d[101]), "=f"(d[102]), "=f"(d[103]),
    "=f"(d[104]), "=f"(d[105]), "=f"(d[106]), "=f"(d[107]), "=f"(d[108]), "=f"(d[109]), "=f"(d[110]), "=f"(d[111])
  : "r"(a0), "r"(a1), "r"(a2), "r"(a3), "l"(db));
}

__device__ __forceinline__ uint32_t smem_u32(const void* p) { return (uint32_t)__cvta_generic_to_shared(p); }
__device__ __forceinline__ void mbar_init(uint32_t bar, uint32_t cnt) { asm volatile("mbarrier.init.shared::cta.b64 [%0], %1;" ::"r"(bar), "r"(cnt) : "memory"); }
__device__ __forceinline__ void mbar_expect(uint32_t bar, uint32_t bytes) { asm volatile("mbarrier.arrive.expect_tx.shared::cta.b64 _, [%0], %1;" ::"r"(bar), "r"(bytes) : "memory"); }
__device__ __forceinline__ void mbar_arrive(uint32_t bar) { asm volatile("mbarrier.arrive.shared::cta.b64 _, [%0];" ::"r"(bar) : "memory"); }
__device__ __forceinline__ void mbar_arrive_cl(uint32_t cbar) { asm volatile("mbarrier.arrive.shared::cluster.b64 _, [%0];" ::"r"(cbar) : "memory"); }
__device__ __forceinline__ uint32_t mapa(uint32_t a, uint32_t cta) { uint32_t r; asm("mapa.shared::cluster.u32 %0, %1, %2;" : "=r"(r) : "r"(a), "r"(cta)); return r; }
__device__ __forceinline__ void mbar_wait(uint32_t bar, uint32_t parity) {
  asm volatile("{\n.reg .pred p;\n.reg .u32 n;\nmov.u32 n, 0;\n"
    "LAB_WAIT:\n"
    "mbarrier.try_wait.parity.shared::cta.b64 p, [%0], %1;\n"
    "@p bra LAB_DONE;\n"
    "add.u32 n, n, 1;\n"
    "setp.lt.u32 p, n, 2000000;\n"
    "@p bra LAB_WAIT;\n"
    "trap;\n"
    "LAB_DONE:\n}\n" ::"r"(bar), "r"(parity) : "memory");
}
constexpr uint32_t SPIN_MAX = 2000000;
__device__ __forceinline__ void tma2d(uint32_t dst, const CUtensorMap* m, uint32_t bar, int c0, int c1) {
  asm volatile("cp.async.bulk.tensor.2d.shared::cluster.global.mbarrier::complete_tx::bytes [%0], [%1, {%3, %4}], [%2];"
    ::"r"(dst), "l"(m), "r"(bar), "r"(c0), "r"(c1) : "memory");
}
__device__ __forceinline__ void tma2d_mc(uint32_t dst, const CUtensorMap* m, uint32_t bar, int c0, int c1) {
  asm volatile("cp.async.bulk.tensor.2d.shared::cluster.global.mbarrier::complete_tx::bytes.multicast::cluster [%0], [%1, {%3, %4}], [%2], %5;"
    ::"r"(dst), "l"(m), "r"(bar), "r"(c0), "r"(c1), "h"((uint16_t)3) : "memory");
}
__device__ __forceinline__ void tma3d(uint32_t dst, const CUtensorMap* m, uint32_t bar, int c0, int c1, int c2) {
  asm volatile("cp.async.bulk.tensor.3d.shared::cluster.global.mbarrier::complete_tx::bytes [%0], [%1, {%3, %4, %5}], [%2];"
    ::"r"(dst), "l"(m), "r"(bar), "r"(c0), "r"(c1), "r"(c2) : "memory");
}
__device__ __forceinline__ void tma3d_mc(uint32_t dst, const CUtensorMap* m, uint32_t bar, int c0, int c1, int c2) {
  asm volatile("cp.async.bulk.tensor.3d.shared::cluster.global.mbarrier::complete_tx::bytes.multicast::cluster [%0], [%1, {%3, %4, %5}], [%2], %6;"
    ::"r"(dst), "l"(m), "r"(bar), "r"(c0), "r"(c1), "r"(c2), "h"((uint16_t)3) : "memory");
}
__device__ __forceinline__ void tma2d_store(const CUtensorMap* m, uint32_t src, int c0, int c1) {
  asm volatile("cp.async.bulk.tensor.2d.global.shared::cta.bulk_group [%0, {%2, %3}], [%1];" ::"l"(m), "r"(src), "r"(c0), "r"(c1) : "memory");
}
__device__ __forceinline__ void bulk_ld(uint32_t dst, const void* src, uint32_t bytes, uint32_t bar) {
  asm volatile("cp.async.bulk.shared::cluster.global.mbarrier::complete_tx::bytes [%0], [%1], %2, [%3];" ::"r"(dst), "l"(src), "r"(bytes), "r"(bar) : "memory");
}
__device__ __forceinline__ void bulk_ld_mc(uint32_t dst, const void* src, uint32_t bytes, uint32_t bar) {
  asm volatile("cp.async.bulk.shared::cluster.global.mbarrier::complete_tx::bytes.multicast::cluster [%0], [%1], %2, [%3], %4;"
    ::"r"(dst), "l"(src), "r"(bytes), "r"(bar), "h"((uint16_t)3) : "memory");
}
__device__ __forceinline__ void bulk_st(void* dst, uint32_t src, uint32_t bytes) {
  asm volatile("cp.async.bulk.global.shared::cta.bulk_group [%0], [%1], %2;" ::"l"(dst), "r"(src), "r"(bytes) : "memory");
}
__device__ __forceinline__ void bulk_commit() { asm volatile("cp.async.bulk.commit_group;" ::: "memory"); }
__device__ __forceinline__ void bulk_wait0() { asm volatile("cp.async.bulk.wait_group 0;" ::: "memory"); }
__device__ __forceinline__ void fence_async_smem() { asm volatile("fence.proxy.async.shared::cta;" ::: "memory"); }
__device__ __forceinline__ void wg_fence() { asm volatile("wgmma.fence.sync.aligned;" ::: "memory"); }
__device__ __forceinline__ void wg_commit() { asm volatile("wgmma.commit_group.sync.aligned;" ::: "memory"); }
template <int N> __device__ __forceinline__ void wg_wait() { asm volatile("wgmma.wait_group.sync.aligned %0;" ::"n"(N) : "memory"); }
template <int R> __device__ __forceinline__ void reg_alloc() { asm volatile("setmaxnreg.inc.sync.aligned.u32 %0;" ::"n"(R)); }
template <int R> __device__ __forceinline__ void reg_dealloc() { asm volatile("setmaxnreg.dec.sync.aligned.u32 %0;" ::"n"(R)); }
__device__ __forceinline__ void cluster_bar() { asm volatile("barrier.cluster.arrive.relaxed;\nbarrier.cluster.wait;" ::: "memory"); }
template <int ID> __device__ __forceinline__ void nb_sync(int n) { asm volatile("barrier.sync %0, %1;" ::"n"(ID), "r"(n) : "memory"); }
template <int ID> __device__ __forceinline__ void nb_arrive(int n) { asm volatile("barrier.arrive %0, %1;" ::"n"(ID), "r"(n) : "memory"); }
__device__ __forceinline__ int fresh_tid() { int t; asm volatile("mov.u32 %0, %%tid.x;" : "=r"(t)); return t; }
__device__ __forceinline__ void sched_fence(uint32_t z) { asm volatile("{\n.reg .pred p;\nsetp.ne.u32 p, %0, 0;\nLAB_S:\n@p nanosleep.u32 0;\n@p bra LAB_S;\n}\n" ::"r"(z) : "memory"); }
__device__ __forceinline__ float rsq(float x) { float y; asm("rsqrt.approx.ftz.f32 %0, %1;" : "=f"(y) : "f"(x)); return y; }
__device__ __forceinline__ int opq(int v) { asm volatile("" : "+r"(v)); return v; }
struct True { static constexpr bool value = true; };
struct False { static constexpr bool value = false; };
template <int N> __device__ __forceinline__ void fence_regs(float (&d)[N]) {
#pragma unroll
  for (int i = 0; i < N; i++) asm volatile("" : "+f"(d[i])::"memory");
}
#define DESC(off, lbo) (sd + ((off) >> 4) + (((lbo) >> 4) << 16))
__device__ __forceinline__ uint64_t mkdesc_vec(uint32_t addr, uint32_t sbo) { return (uint64_t)((addr & 0x3FFFF) >> 4) | ((uint64_t)(sbo >> 4) << 32); }
__device__ __forceinline__ void sts16(uint32_t a, uint32_t v) { asm volatile("st.shared.u16 [%0], %1;" ::"r"(a), "h"((uint16_t)v) : "memory"); }
__device__ __forceinline__ uint32_t pack2(float lo, float hi) { uint32_t r; asm("cvt.rn.bf16x2.f32 %0, %1, %2;" : "=r"(r) : "f"(hi), "f"(lo)); return r; }
__device__ __forceinline__ float bf_lo(uint32_t v) { return __uint_as_float(v << 16); }
__device__ __forceinline__ float bf_hi(uint32_t v) { return __uint_as_float(v & 0xffff0000u); }
__device__ __forceinline__ void stsm4(uint32_t a, uint32_t r0, uint32_t r1, uint32_t r2, uint32_t r3) {
  asm volatile("stmatrix.sync.aligned.m8n8.x4.shared.b16 [%0], {%1, %2, %3, %4};" ::"r"(a), "r"(r0), "r"(r1), "r"(r2), "r"(r3) : "memory");
}
__device__ __forceinline__ void stsm4t(uint32_t a, uint32_t r0, uint32_t r1, uint32_t r2, uint32_t r3) {
  asm volatile("stmatrix.sync.aligned.m8n8.x4.trans.shared.b16 [%0], {%1, %2, %3, %4};" ::"r"(a), "r"(r0), "r"(r1), "r"(r2), "r"(r3) : "memory");
}
__device__ __forceinline__ void ldsm4(uint32_t a, uint32_t& r0, uint32_t& r1, uint32_t& r2, uint32_t& r3) {
  asm volatile("ldmatrix.sync.aligned.m8n8.x4.shared.b16 {%0, %1, %2, %3}, [%4];" : "=r"(r0), "=r"(r1), "=r"(r2), "=r"(r3) : "r"(a) : "memory");
}
__device__ __forceinline__ void ldsm4t(uint32_t a, uint32_t& r0, uint32_t& r1, uint32_t& r2, uint32_t& r3) {
  asm volatile("ldmatrix.sync.aligned.m8n8.x4.trans.shared.b16 {%0, %1, %2, %3}, [%4];" : "=r"(r0), "=r"(r1), "=r"(r2), "=r"(r3) : "r"(a) : "memory");
}
__device__ __forceinline__ void mma16816(float (&c)[4], uint32_t a0, uint32_t a1, uint32_t a2, uint32_t a3, uint32_t b0, uint32_t b1) {
  asm volatile("mma.sync.aligned.m16n8k16.row.col.f32.bf16.bf16.f32 {%0, %1, %2, %3}, {%4, %5, %6, %7}, {%8, %9}, {%10, %11, %12, %13};"
    : "=f"(c[0]), "=f"(c[1]), "=f"(c[2]), "=f"(c[3]) : "r"(a0), "r"(a1), "r"(a2), "r"(a3), "r"(b0), "r"(b1), "f"(c[0]), "f"(c[1]), "f"(c[2]), "f"(c[3]));
}
__device__ __forceinline__ void sts128(uint32_t a, uint32_t r0, uint32_t r1, uint32_t r2, uint32_t r3) {
  asm volatile("st.shared.v4.b32 [%0], {%1, %2, %3, %4};" ::"r"(a), "r"(r0), "r"(r1), "r"(r2), "r"(r3) : "memory");
}
__device__ __forceinline__ void lds128(uint32_t a, uint32_t& r0, uint32_t& r1, uint32_t& r2, uint32_t& r3) {
  asm volatile("ld.shared.v4.b32 {%0, %1, %2, %3}, [%4];" : "=r"(r0), "=r"(r1), "=r"(r2), "=r"(r3) : "r"(a) : "memory");
}
__device__ __forceinline__ float2 lds64f(uint32_t a) { float2 v; asm volatile("ld.shared.v2.f32 {%0, %1}, [%2];" : "=f"(v.x), "=f"(v.y) : "r"(a) : "memory"); return v; }
__device__ __forceinline__ float4 lds128f(uint32_t a) { float4 v; asm volatile("ld.shared.v4.f32 {%0, %1, %2, %3}, [%4];" : "=f"(v.x), "=f"(v.y), "=f"(v.z), "=f"(v.w) : "r"(a) : "memory"); return v; }
__device__ __forceinline__ void sts64f(uint32_t a, float x, float y) { asm volatile("st.shared.v2.f32 [%0], {%1, %2};" ::"r"(a), "f"(x), "f"(y) : "memory"); }
__device__ __forceinline__ float lds32f(uint32_t a) { float v; asm volatile("ld.shared.f32 %0, [%1];" : "=f"(v) : "r"(a) : "memory"); return v; }
__device__ __forceinline__ void sts32f(uint32_t a, float x) { asm volatile("st.shared.f32 [%0], %1;" ::"r"(a), "f"(x) : "memory"); }
__device__ __forceinline__ void stat_st(uint2* p, float sum, float sq, uint32_t tag, bool on) {
  const float mean = sum * (1.f / 128), m2 = fmaxf(fmaf(-mean, sum, sq), 0.f);
  const uint32_t a = ((__float_as_uint(mean) + 8u) & ~15u) | (tag & 15u), b = ((__float_as_uint(m2) + 8u) & ~15u) | (tag & 15u);
  asm volatile("{\n.reg .b64 x;\n.reg .pred p;\nsetp.ne.u32 p, %3, 0;\nmov.b64 x, {%1, %2};\n@p st.relaxed.gpu.global.b64 [%0], x;\n}\n" ::"l"(p), "r"(a), "r"(b), "r"((uint32_t)on) : "memory");
}
__device__ __forceinline__ void stat_ld2(const uint2* p, uint32_t (&v)[4]) {
  asm volatile("{\n.reg .b64 x, y;\nld.relaxed.gpu.global.v2.b64 {x, y}, [%4];\nmov.b64 {%0, %1}, x;\nmov.b64 {%2, %3}, y;\n}\n"
    : "=r"(v[0]), "=r"(v[1]), "=r"(v[2]), "=r"(v[3]) : "l"(p) : "memory");
}
__device__ __forceinline__ float untag(uint32_t v) { return __uint_as_float(v & ~15u); }
__device__ __forceinline__ void ll_st3(uint4* p, uint32_t a, uint32_t b, uint32_t c, uint32_t tag) {
  asm volatile("{\n.reg .b64 x, y;\n.reg .b128 z;\nmov.b64 x, {%1, %2};\nmov.b64 y, {%3, %4};\nmov.b128 z, {x, y};\nst.relaxed.gpu.global.b128 [%0], z;\n}\n"
    ::"l"(p), "r"(a), "r"(b), "r"(c), "r"(tag) : "memory");
}
__device__ __forceinline__ uint32_t ll_ld3(const uint4* p, uint32_t& a, uint32_t& b, uint32_t& c, uint32_t tag) {
  uint32_t t;
  asm volatile("{\n.reg .b64 x, y;\n.reg .b128 z;\nld.relaxed.gpu.global.b128 z, [%4];\nmov.b128 {x, y}, z;\nmov.b64 {%0, %1}, x;\nmov.b64 {%2, %3}, y;\n}\n"
    : "=r"(a), "=r"(b), "=r"(c), "=r"(t) : "l"(p) : "memory");
  return t ^ tag;
}
__device__ __forceinline__ void halo_send(uint4* p, uint32_t a, const uint32_t (&tg)[6]) {
  asm volatile("{\n.reg .b64 x<6>, y<6>, w<2>;\n.reg .b32 c<4>;\n.reg .b128 z<6>;\n"
    "ld.shared.b64 w0, [%1+1536];\nld.shared.b64 w1, [%1+1792];\n"
    "ld.shared.b64 x0, [%1];\nld.shared.b64 x1, [%1+256];\nld.shared.b64 x2, [%1+512];\n"
    "ld.shared.b64 x3, [%1+768];\nld.shared.b64 x4, [%1+1024];\nld.shared.b64 x5, [%1+1280];\n"
    "mov.b64 {c0, c1}, w0;\nmov.b64 {c2, c3}, w1;\n"
    "mov.b64 y0, {c0, %2};\nmov.b64 y1, {c1, %3};\nmov.b64 y2, {c2, %4};\nmov.b64 y3, {c3, %5};\nmov.b64 y4, {%6, %6};\nmov.b64 y5, {%7, %7};\n"
    "mov.b128 z0, {x0, y0};\nmov.b128 z1, {x1, y1};\nmov.b128 z2, {x2, y2};\nmov.b128 z3, {x3, y3};\nmov.b128 z4, {x4, y4};\nmov.b128 z5, {x5, y5};\n"
    "st.relaxed.gpu.global.b128 [%0], z0;\nst.relaxed.gpu.global.b128 [%0+512], z1;\nst.relaxed.gpu.global.b128 [%0+1024], z2;\n"
    "st.relaxed.gpu.global.b128 [%0+1536], z3;\nst.relaxed.gpu.global.b128 [%0+2048], z4;\nst.relaxed.gpu.global.b128 [%0+2560], z5;\n}\n"
    ::"l"(p), "r"(a), "r"(tg[0]), "r"(tg[1]), "r"(tg[2]), "r"(tg[3]), "r"(tg[4]), "r"(tg[5]) : "memory");
}
template <int N> __device__ __forceinline__ void copy_out(uint8_t* dst, uint32_t src, int stride) {
  uint4 v[N];
#pragma unroll
  for (int k = 0; k < N; k++) lds128(src + k * stride, v[k].x, v[k].y, v[k].z, v[k].w);
#pragma unroll
  for (int k = 0; k < N; k++) asm volatile("st.global.v4.b32 [%0], {%1, %2, %3, %4};" ::"l"(dst + k * stride), "r"(v[k].x), "r"(v[k].y), "r"(v[k].z), "r"(v[k].w) : "memory");
}
__device__ __forceinline__ void warp_store(uint8_t* dst, uint32_t src, int bytes, uint32_t delay, uint32_t pace) {
  __nanosleep(delay);
#pragma unroll 1
  for (int o = 0; o < bytes; o += 2048) {
    if (pace) __nanosleep(pace);
    uint4 v[4];
#pragma unroll
    for (int k = 0; k < 4; k++) lds128(src + o + k * 512, v[k].x, v[k].y, v[k].z, v[k].w);
#pragma unroll
    for (int k = 0; k < 4; k++) asm volatile("st.global.v4.b32 [%0], {%1, %2, %3, %4};" ::"l"(dst + o + k * 512), "r"(v[k].x), "r"(v[k].y), "r"(v[k].z), "r"(v[k].w) : "memory");
  }
  __syncwarp();
}
__device__ __forceinline__ uint32_t clock32() { uint32_t t; asm volatile("mov.u32 %0, %%clock;" : "=r"(t)); return t; }
__device__ __forceinline__ void flag_set(uint32_t* p, uint32_t bit) { asm volatile("red.release.gpu.global.xor.b32 [%0], %1;" ::"l"(p), "r"(bit) : "memory"); }
__device__ __forceinline__ void flag_wait(const uint32_t* p, uint32_t inv, uint32_t need, uint32_t& ready) {
  if ((ready & need) == need) return;
  uint32_t n = 0;
  do {
    asm volatile("ld.relaxed.gpu.global.b32 %0, [%1];" : "=r"(ready) : "l"(p) : "memory");
    ready = __shfl_sync(0xffffffffu, ready, 0) ^ inv;
  } while ((ready & need) != need && ++n < SPIN_MAX);
  asm volatile("fence.acquire.gpu;\nfence.proxy.async.global;" ::: "memory");
}
__device__ __forceinline__ bool elect_one() {
  uint32_t p;
  asm volatile("{\n.reg .pred P;\nelect.sync _|P, 0xffffffff;\nselp.u32 %0, 1, 0, P;\n}\n" : "=r"(p));
  return p;
}
__device__ __forceinline__ float gelu_half(float hx) {
  const float y = hx * fmaf(hx * hx, 8.f * 0.0356774081f, 2.f * 0.7978845608f);
  float th;
  asm("tanh.approx.f32 %0, %1;" : "=f"(th) : "f"(y));
  return fmaf(hx, th, hx);
}
__device__ __forceinline__ float ex2(float x) { float y; asm("ex2.approx.ftz.f32 %0, %1;" : "=f"(y) : "f"(x)); return y; }

__device__ __forceinline__ void stat_combine(uint32_t am, uint32_t aq, uint32_t bm, uint32_t bq, float pv, float& mean, float& var) {
  const float d0 = untag(am) - pv, d1 = untag(bm) - pv;
  float s = d0 + d1, q = fmaf(fmaf(d0, d0, d1 * d1), 128.f, untag(aq) + untag(bq));
  s += __shfl_xor_sync(0xffffffffu, s, 8); q += __shfl_xor_sync(0xffffffffu, q, 8);
  s += __shfl_xor_sync(0xffffffffu, s, 16); q += __shfl_xor_sync(0xffffffffu, q, 16);
  s *= 0.125f;
  mean = pv + s;
  var = fmaxf(fmaf(-s, s, q * (1.f / D_)), 0.f);
}

__device__ __forceinline__ void attn_probs(const uint32_t* q0, const uint32_t* q1,
                                           const uint32_t* k0, const uint32_t* k1, const uint32_t* k2, const uint32_t* k3,
                                           float sc0, float sc1, float mk0, float mk1, bool e, bool zneg, const uint32_t (&sel)[3],
                                           uint32_t (&pr)[6], float (&l)[2]) {
  float s[4][4];
#pragma unroll
  for (int n = 0; n < 4; n++) {
    const uint32_t* k = n == 0 ? k0 : n == 1 ? k1 : n == 2 ? k2 : k3;
    s[n][0] = s[n][1] = n < 2 ? mk0 : 0.f; s[n][2] = s[n][3] = n < 2 ? mk1 : 0.f;
    mma16816(s[n], q0[0], q1[0], q0[1], q1[1], k[0], k[1]);
    mma16816(s[n], q0[2], q1[2], q0[3], q1[3], k[2], k[3]);
  }
  float a0 = e ? s[1][1] : s[1][0];
  float b0 = zneg ? (e ? s[0][1] : s[0][0]) : (e ? s[2][1] : s[2][0]);
  float a1 = e ? s[2][3] : s[2][2];
  float b1 = zneg ? (e ? s[1][3] : s[1][2]) : (e ? s[3][3] : s[3][2]);
  float m0 = fmaxf(a0, b0), m1 = fmaxf(a1, b1);
  m0 = fmaxf(m0, __shfl_xor_sync(0xffffffffu, m0, 1)); m1 = fmaxf(m1, __shfl_xor_sync(0xffffffffu, m1, 1));
  m0 = fmaxf(m0, __shfl_xor_sync(0xffffffffu, m0, 2)); m1 = fmaxf(m1, __shfl_xor_sync(0xffffffffu, m1, 2));
  a0 = ex2((a0 - m0) * sc0); b0 = ex2((b0 - m0) * sc0); a1 = ex2((a1 - m1) * sc1); b1 = ex2((b1 - m1) * sc1);
  l[0] = a0 + b0; l[1] = a1 + b1;
  const uint32_t p0 = pack2(a0, b0), p1 = pack2(a1, b1);
#pragma unroll
  for (int k = 0; k < 3; k++) { pr[k] = __byte_perm(p0, 0u, sel[k]); pr[3 + k] = __byte_perm(p1, 0u, sel[k]); }
}
__device__ __forceinline__ void attn_pv(const uint32_t (&pr)[6], const uint32_t* vh, const uint32_t* v, float (&o)[4][4]) {
#pragma unroll
  for (int dt = 0; dt < 4; dt++) {
    o[dt][0] = o[dt][1] = o[dt][2] = o[dt][3] = 0.f;
    mma16816(o[dt], pr[0], 0u, pr[1], pr[3], vh[2 * dt], vh[2 * dt + 1]);
    mma16816(o[dt], pr[2], pr[4], 0u, pr[5], v[2 * dt], v[2 * dt + 1]);
  }
}

#define ATT 24
#define COVER 2
#define HALO_A_NS 300
#define H1D 900
#define POLITE 0
#define G4GATE 1
#define PFM 15
#define PD1 3
#define PD2 5
#define PD3 3
#define PD4 5
#define C0 3
#define SL0 1
#define U0P 0
#define U0D 300
#define U2D 3000
#define X1D 1200
#define PACE 150
#define LEAD1 3
#define LEAD2 3
#define XLD 7
#define XST 3
#define FA 20
#define LEAD4 4
#define STAT_CLK 150
__global__ void __cluster_dims__(2, 1, 1) __launch_bounds__(384, 1) fused_kernel(const __grid_constant__ Params P) {
  extern __shared__ __align__(1024) uint8_t smem_raw[];
  const uint32_t sb = smem_u32(smem_raw);
  const uint32_t bars = sb + OFF_BAR;
  const int tid = threadIdx.x;
  const int wu = __shfl_sync(0xffffffffu, tid >> 5, 0), wg = wu >> 2;
  const int r = blockIdx.x & 1, cl = blockIdx.x >> 1;
  int grp, slt;
  if (cl < 4) { grp = 0; slt = 4 + cl; }
  else if (cl < 36) { grp = (cl - 4) & 7; slt = (cl - 4) >> 3; }
  else { grp = 1 + (cl - 36) % 7; slt = 4 + (cl - 36) / 7; }
#define MAP 0
  const int m = grp, j = slt;
  const int i = 2 * m + r;
  auto BAR = [&](int k) { return bars + 8 * k; };

  auto kb1 = [&](int n) { const int h = n >= 9, t = n - 2 - 7 * h; return n < 2 ? 2 * j + n : 2 * (t + (t >= j)) + h; };
  if (wu == 8) {
    if (elect_one()) {
      asm volatile("prefetch.tensormap [%0];" ::"l"(&P.x0) : "memory");
      asm volatile("prefetch.tensormap [%0];" ::"l"(&P.wqkv) : "memory");
#pragma unroll
      for (int k = 0; k < 6; k++) mbar_init(BAR(k < 4 ? F1 + k : XF + k - 4), 1);
      asm volatile("fence.mbarrier_init.release.cluster;" ::: "memory");
      fence_async_smem();
    }
    __syncwarp();
  } else if (wu == 0) {
    if (elect_one()) {
#pragma unroll
      for (int k = E1; k < 64; k++) {
        int cnt = 1;
        if (k < F2 || (k >= E2 && k < F3) || (k >= E3 && k < F4) || (k >= E4 && k < JOB) || k == JOB + 2 || k == JOB + 3) cnt = 4;
        else if ((k >= JOB && k < RD) || k == CSJ) cnt = 8;
        else if ((k >= RD && k < RD + 2) || k == STD || k == STAT || k >= HALO) cnt = 2;
        if (k != XF && k != XF + 1) mbar_init(BAR(k), cnt);
      }
      asm volatile("fence.mbarrier_init.release.cluster;" ::: "memory");
      fence_async_smem();
    }
    __syncwarp();
  }
  auto load_tag = [&]() { uint32_t t; asm volatile("ld.relaxed.gpu.global.u32 %0, [%1];" : "=r"(t) : "l"(&gEpoch) : "memory"); return t + 1; };
  TS(0);
  if (wu == 8) nb_arrive<NB_INIT>(384); else nb_sync<NB_INIT>(384);
  asm volatile("barrier.cluster.arrive.relaxed;" ::: "memory");

  if (wg == 2) {
    reg_dealloc<40>();
    if (wu == 8) {
    if (elect_one()) {
#pragma unroll 1
      for (int u = 0; u < 4; u++) {
        const int kb = u;
        mbar_expect(BAR(F1 + u), 40960);
        tma2d(sb + slot1(u), &P.x0, BAR(F1 + u), kb * 64, 128 * i);
        tma3d(sb + slot1(u) + 16384, &P.wqkv, BAR(F1 + u), 128 * j, kb * 64, 0);
        tma3d(sb + slot1(u) + 28672, &P.wqkv, BAR(F1 + u), 128 * j, kb * 64 + 32, 0);
      }
    }
    __syncwarp();
    }
    asm volatile("barrier.cluster.wait;" ::: "memory");
    auto kb3 = [&](int n) { const int h = n >= 17, t = n - 2 - 15 * h; return n < 2 ? 2 * i + n : t == 14 ? 2 * (i ^ 1) + h : 2 * ((2 * m + 2 + t) & 15) + h; };
    auto kb2 = [&](int n) { return n < 8 ? 2 * n : n == 8 ? 2 * j + 1 : 2 * (n - 9 + (n - 9 >= j)) + 1; };
    if (wu == 8) {
      const int lane = tid & 31;
      auto pf = [&](const bf16* p, bool on) { if (on) asm volatile("prefetch.global.L2 [%0];" ::"l"(p)); };
      auto v1 = [&](int L, int u) { return (L && u >= 2 && u < 18) ? (u < 4 ? u + 14 : u - 2) : u; };
      auto k1 = [&](int L, int v) { return (L || v >= 16) ? kb1(v & 15) : v; };
      auto kb4f = [&](int n) {
        const int q = n ? n - 8 : 0, c = q >> 4, t = (q & 15) - 1, ii = t < 0 ? i : t < 14 ? (2 * m + 2 + t) & 15 : i ^ 1;
        return (n >= 1 && n <= 8) ? 7 * ((m + n) & 7) + 3 : ((7 * ii + 1) >> 1) + c;
      };
      const uint32_t tab4 = kb4f(lane) | (kb4f(lane + 32) << 16);
      auto kb4 = [&](int n) { return (int)((__shfl_sync(0xffffffffu, tab4, n) >> ((n >> 1) & 16)) & 63); };
      const bf16* const q1 = P.wqkv_p + (4 * i + (lane & 3)) * 3072 + (lane >> 2) * 1024 + 128 * j;
      const bf16* const q2 = P.wo_p + (4 * i + (lane & 3)) * 1024 + (lane >> 2) * 64 + 128 * j;
      const bf16* const q3 = P.w1_p + (8 * j + (lane >> 2)) * 3584 + 64 * (7 * m + ((lane & 3) == 3 ? 3 : 4 * r + (lane & 3)));
      const bf16* const q4 = P.w2_p + (8 * j + (lane >> 1)) * 2048 + 128 * i + 64 * (lane & 1);
      auto pf1 = [&](int L, int u) { const int v = v1(L, u); pf(q1 + k1(L, v) * (64 * 3072) + 64 * (v >> 4), (PFM & 1) && lane < 12); };
      auto pf2 = [&](int n) { pf(q2 + kb2(n) * (64 * 1024), (PFM & 2) && lane < 8); };
      auto pf3 = [&](int n) { pf(q3 + kb3(n) * (64 * 3584), PFM & 4); };
      auto pf4 = [&](int n) { pf(q4 + kb4(n) * (64 * 2048), (PFM & 8) && lane < 16); };
#pragma unroll 1
      for (int u = 4; u < 4 + PD1; u++) pf1(0, u);
#pragma unroll 1
      for (int L = 0; L < 2; L++) {
#pragma unroll 1
        for (int u = L ? 0 : 4; u < 32; u++) {
          const int v = v1(L, u), p = u & 3;
          if (u >= 4) mbar_wait(BAR(E1 + p), ((u >> 2) - 1) & 1);
          else mbar_wait(BAR(E4 + (u == 3 ? 0 : u + 3)), u == 3);
          if (elect_one()) {
            mbar_expect(BAR(F1 + p), (v & 15) < 2 ? 24576 : 40960);
            tma3d_mc(sb + slot1(p) + 16384 + r * 12288, &P.wqkv, BAR(F1 + p), 128 * j + 64 * (v >> 4), k1(L, v) * 64 + 32 * r, 0);
          }
          if (u + PD1 < 32) pf1(L, u + PD1);
          if (u + PD2 >= 32) pf2(u + PD2 - 32);
        }
        int p = 0; uint32_t par = L ? 0x1e : 0;
#pragma unroll 1
        for (int n = 0; n < 16; n++) {
          if (n >= 5) { mbar_wait(BAR(E2 + p), (par >> p) & 1); par ^= 1u << p; }
          else if (n < 4) mbar_wait(BAR(E1 + n), 1);
          if (elect_one()) {
            mbar_expect(BAR(F2 + p), n == 8 ? 16384 : 32768);
            tma2d_mc(sb + slot2(p) + 16384 + r * 8192, &P.wo, BAR(F2 + p), 128 * j + 64 * r, kb2(n) * 64);
          }
          if (++p == 5) p = 0;
          if (n + PD2 < 16) pf2(n + PD2);
          if (n + PD3 + 4 >= 16) pf3(n + PD3 + 4 - 16);
        }
#pragma unroll 1
        for (int u = 0; u < 32; u++) {
          const int n = u < 4 ? (0x2031 >> (4 * u)) & 3 : u, p = n & 3, kb = kb3(n);
          if (n == 4) mbar_wait(BAR(RD + 4), L);
          if (n >= 4) mbar_wait(BAR(E3 + p), ((n >> 2) - 1) & 1);
          else if (n == 1) mbar_wait(BAR(STD + 1), L);
          else if (n == 3) mbar_wait(BAR(E2 + 2), L);
          else if (n == 0) mbar_wait(BAR(E2 + 4), L);
          else mbar_wait(BAR(E2 + 0), 1);
          if (elect_one()) {
            mbar_expect(BAR(F3 + p), n < 2 ? 32768 : 49152);
            tma3d(sb + slot3(p) + 16384, &P.w1, BAR(F3 + p), 0, kb * 64, 7 * m + 4 * r);
            tma3d(sb + slot3(p) + 40960, &P.w1h, BAR(F3 + p), 0, kb * 64, 14 * m + 6 + r);
          }
          if (u >= 4 && u + PD3 < 32) pf3(u + PD3);
          if (u + PD4 + 6 >= 32) pf4(u + PD4 + 6 - 32);
        }
        auto g4w = [&](int n, int p, int kb) {
          if (elect_one()) {
            mbar_expect(BAR(F4 + p), (n == 0 || n == 24 || n == 40) ? 16384 : 32768);
            tma3d(sb + slot4(p), &P.w2, BAR(F4 + p), 0, kb * 64, 2 * i);
          }
        };
#pragma unroll 1
        for (int n = 0; n < 6; n++) {
          const int kb = kb4(n);
          if (n == G4GATE) mbar_wait(BAR(RD + 3), L);
          if (n < 3) mbar_wait(BAR(E3 + n), 1);
          else if (n == 4) mbar_wait(BAR(E3 + 3), 1);
          g4w(n, n, kb);
        }
        p = 0; par = L ? 0x3c : 0;
#pragma unroll 1
        for (int n = 6; n < 56; n++) {
          const int kb = kb4(n);
          if (n + PD4 < 56) pf4(n + PD4);
          mbar_wait(BAR(E4 + p), (par >> p) & 1); par ^= 1u << p;
          g4w(n, p, kb);
          if (++p == 6) p = 0;
        }
        if (L == 0)
#pragma unroll 1
          for (int u = 0; u < PD1; u++) pf1(1, u);
      }
    } else if (wu == 9) {
      uint32_t inv = 0;
#pragma unroll 1
      for (int L = 0; L < 2; L++) {
        uint32_t ready = 0;
#pragma unroll 1
        for (int u = 4; u < 32; u++) {
          const int p = u & 3, nn = (L && u < 18 ? u - 2 : u) & 15, kb = (L || u >= 16) ? kb1(nn) : nn;
          if (L == 0 && (u == XLD || u == XLD + XST) && elect_one()) {
            const int h = u != XLD;
            mbar_expect(BAR(XF + h), 16384);
            tma2d(sb + OFF_X + h * 16384, &P.x0, BAR(XF + h), 128 * j + 64 * h, 128 * i);
          }
          if (nn < 2) continue;
          if (L && u < 12) mbar_wait(BAR(F1 + p), u >> 3);
          if (u >= 4 + 4 * L) mbar_wait(BAR(E1 + p), ((u >> 2) - 1) & 1);
          if (L) {
            flag_wait(gFlag[0][0][i], inv, 1u << kb, ready);
            if (elect_one()) bulk_ld(sb + slot1(p), gXB + (i * 16 + kb) * 16384, 16384, BAR(F1 + p));
          } else if (elect_one()) tma2d(sb + slot1(p), &P.x0, BAR(F1 + p), kb * 64, 128 * i);
        }
        ready = 0;
        if (L == 0) inv = (__shfl_sync(0xffffffffu, load_tag(), 0) & 1) - 1;
        int p = 0; uint32_t par = L ? 0x1e : 0;
#pragma unroll 1
        for (int n = 0; n < 16; n++) {
          const int hp = kb2(n);
          if (n == 8) { par ^= 8; p = 4; continue; }
          if (n >= 5) { mbar_wait(BAR(E2 + p), (par >> p) & 1); par ^= 1u << p; }
          else if (n < 4) mbar_wait(BAR(E1 + n), 1);
          flag_wait(gFlag[L][1][i], inv, 1u << hp, ready);
          if (n == 9) ST(4);
          if (elect_one()) bulk_ld(sb + slot2(p), gOB + (i * 16 + hp) * 16384, 16384, BAR(F2 + p));
          if (++p == 5) p = 0;
        }
        ready = 0;
        mbar_wait(BAR(E2 + 0), 1);
#pragma unroll 1
        for (int n = 2; n < 32; n++) {
          const int p = n & 3, kb = kb3(n);
          if (n > 3) mbar_wait(BAR(E3 + p), ((n >> 2) - 1) & 1);
          flag_wait(gFlag[L][2][j], inv, 1u << kb, ready);
          if (n == 2) ST(12);
          if (elect_one()) {
            const uint8_t* src = gHB + (j * 32 + kb) * 16384;
            if (n != 16 && n != 31) bulk_ld_mc(sb + slot3(p) + r * 8192, src + r * 8192, 8192, BAR(F3 + p));
            else bulk_ld(sb + slot3(p), src, 16384, BAR(F3 + p));
          }
        }
        ready = 0; p = 1; par = L ? 0x3c : 0;
#pragma unroll 1
        for (int t = 0; t < 8; t++) {
          const int mm = (m + t + 1) & 7;
          if (t < 3) mbar_wait(BAR(E3 + 1 + t), 1);
          if (t >= 5) { mbar_wait(BAR(E4 + p), (par >> p) & 1); par ^= 1u << p; }
          flag_wait(gFlag[L][6][j], inv, 3u << (2 * mm), ready);
          if (t == 0) ST(20);
          if (elect_one()) bulk_ld_mc(sb + slot4(p) + 16384 + r * 8192, gUB + (j * 56 + 48 + mm) * 16384 + r * 8192, 8192, BAR(F4 + p));
          if (++p == 6) p = 0;
        }
#pragma unroll 1
        for (int c = 0; c < 3; c++) {
          ready = 0;
          if (c) { par ^= 1u << p; if (++p == 6) p = 0; }
#pragma unroll 1
          for (int t = 0; t < 15; t++) {
            const int ii = t < 14 ? (2 * m + 2 + t) & 15 : i ^ 1;
            mbar_wait(BAR(E4 + p), (par >> p) & 1); par ^= 1u << p;
            flag_wait(gFlag[L][3 + c][j], inv, 1u << ii, ready);
            if (elect_one()) {
              const uint8_t* src = gUB + (j * 56 + 16 * c + ii) * 16384;
              if (t < 14) bulk_ld_mc(sb + slot4(p) + 16384 + r * 8192, src + r * 8192, 8192, BAR(F4 + p));
              else bulk_ld(sb + slot4(p) + 16384, src, 16384, BAR(F4 + p));
            }
            if (++p == 6) p = 0;
          }
        }
      }
    } else {
      const int h = wu - 10, i0 = i, j0 = j;
      {
      const uint32_t tag = load_tag();
      int lane = tid & 31, i = i0, j = j0;
#define FRESH asm volatile("" : "+r"(lane), "+r"(i), "+r"(j))
      auto signal = [&](int k) { if (lane == 0) mbar_arrive(BAR(k)); };
      auto publish = [&](uint32_t* f, int bit) { if (lane == 0) flag_set(f, 1u << bit); __syncwarp(); };
      for (int c = 32 * h + lane; c < 288; c += 64)
        sts16(sb + OFF_B1 + 2 * c, c >= 224 ? 0u : pack2(0.5f * __bfloat162float(P.b1[c < 192 ? 64 * (7 * m + 4 * r) + c : 64 * (7 * m + 3) + 32 * r + c - 192]), 0.f));
      if (h == 0) sts32f(sb + OFF_CS + 768 + 4 * lane, 0.f);
#pragma unroll 1
      for (int L = 0; L < 2; L++) {
        FRESH;
        if (L == 0) {
          mbar_wait(BAR(CSJ), 0);
          float c0 = 0.f, c1 = 0.f, c2 = 0.f;
          const uint32_t a = sb + OFF_STG + (32 * h + lane) * 4;
#pragma unroll 8
          for (int k = 0; k < 32; k++) { c0 += lds32f(a + k * 784); c1 += lds32f(a + k * 784 + 256); c2 += lds32f(a + k * 784 + 512); }
          ll_st3(&gCS[j][i][32 * h + lane], __float_as_uint(c0), __float_as_uint(c1), __float_as_uint(c2), tag);
          __nanosleep(500);
        }
        FRESH;
        if (L == 0) {
#pragma unroll 1
          for (int ab = 0; ab < 2; ab++) {
            float c0 = 0.f, c1 = 0.f, c2 = 0.f;
#pragma unroll 1
            for (int b4 = 0; b4 < 8; b4 += 4) {
              uint32_t a[4], b[4], c[4], n = 0, bad;
              do {
                bad = 0;
#pragma unroll
                for (int e = 0; e < 4; e++) bad |= ll_ld3(&gCS[j][2 * (b4 + e) + ab][32 * h + lane], a[e], b[e], c[e], tag);
              } while (bad && ++n < SPIN_MAX);
#pragma unroll
              for (int e = 0; e < 4; e++) { c0 += __uint_as_float(a[e]); c1 += __uint_as_float(b[e]); c2 += __uint_as_float(c[e]); }
            }
            const uint32_t a = sb + OFF_CS + ab * 768 + (4 * h + (lane >> 3)) * 32 + (lane & 7) * 2;
            const uint32_t h0 = pack2(c0, 0.f), h1 = pack2(c1, 0.f), h2 = pack2(c2, 0.f);
            sts16(a, h0); sts16(a + 256, h1); sts16(a + 512, h2);
            sts16(a + 16, pack2(c0 - bf_lo(h0), 0.f)); sts16(a + 272, pack2(c1 - bf_lo(h1), 0.f)); sts16(a + 528, pack2(c2 - bf_lo(h2), 0.f));
            fence_async_smem();
            __syncwarp();
            if (ab == 0) signal(STAT);
          }
        }
#pragma unroll 1
        for (int ab = 0; ab < 2; ab++) {
          FRESH;
          uint32_t v[18], tg[6];
          const uint32_t xs = sb + OFF_STG + h * 16384 + lane * 8;
          uint4* hp = &gHalo[L][i][j][6 * h][lane];
#pragma unroll
          for (int c = 0; c < 6; c++) { tg[c] = (2 * tag + ab) * 8 + c; asm volatile("" : "+r"(tg[c])); }
          asm volatile("" : "+l"(hp));
          mbar_wait(BAR(FOLD + ab), L);
          if (ab && h == 0) ST(6);
          if (i < 15) {
            halo_send(hp, xs, tg);
          }
          if (ab && h == 0) ST(26);
          if (i > 0) {
            if (!ab) __nanosleep(HALO_A_NS);
            uint32_t n = 0, bad;
            do {
              bad = 0;
#pragma unroll
              for (int c = 0; c < 6; c++) bad |= ll_ld3(hp + c * 32 - 8 * 12 * 32, v[3 * c], v[3 * c + 1], v[3 * c + 2], (2 * tag + ab) * 8);
              if (ab && h == 0 && n == 0) ST(28);
            } while (bad > 7 && ++n < SPIN_MAX);
            if (ab && h == 0) ST(27);
          } else {
#pragma unroll
            for (int c = 0; c < 18; c++) v[c] = 0u;
          }
#pragma unroll
          for (int c = 0; c < 6; c++) sts64f(xs + c * 256, __uint_as_float(v[3 * c]), __uint_as_float(v[3 * c + 1]));
          sts64f(xs + 1536, __uint_as_float(v[2]), __uint_as_float(v[5]));
          sts64f(xs + 1792, __uint_as_float(v[8]), __uint_as_float(v[11]));
          __syncwarp();
          signal(HALO + ab);
          if (ab && h == 0) ST(7);
          FRESH;
          if (ab == 0 && lane == 0) asm volatile("st.relaxed.gpu.global.u32 [%0], %1;" ::"l"(&gAck[L][i][j][h][0]), "r"(tag) : "memory");
          mbar_wait(BAR(JOB + ab), L);
          if (h == 0) {
            if (ab) ST(1);
            if (lane == 0) { bulk_st(gOB + (i * 16 + 2 * j + ab) * 16384, sb + OFF_STG, 16384); bulk_commit(); bulk_wait0(); }
            signal(STD + ab);
            if (ab) ST(2);
            publish(gFlag[L][1][i], 2 * j + ab);
            if (ab) ST(3);
          } else if (ab == 0) {
            if (i < 15 && lane < 2) {
              uint32_t t, n = 0;
              do { asm volatile("ld.relaxed.gpu.global.u32 %0, [%1];" : "=r"(t) : "l"(&gAck[L][i + 1][j][lane][0]) : "memory"); } while (t != tag && ++n < SPIN_MAX);
            }
            __syncwarp();
            signal(STD);
          }
        }
        FRESH;
        if (h == 0) {
          mbar_wait(BAR(JOB + 2), L);
          ST(9);
          signal(RD);
          ST(10);
          publish(gFlag[L][2][j], 2 * i);
          ST(11);
          signal(RD + 4);
          nb_arrive<NB_HELP>(64);
        } else {
          mbar_wait(BAR(JOB + 3), L);
          nb_sync<NB_HELP>(64);
          warp_store(gHB + (j * 32 + 2 * i + 1) * 16384 + lane * 16, sb + lane * 16 + OFF_X + 16384, 16384, H1D, PACE);
          signal(RD);
          ST(15);
          publish(gFlag[L][2][j], 2 * i + 1);
        }
        FRESH;
        if (h == 0) {
          mbar_wait(BAR(JOB + 7), L);
          ST(17);
          publish(gFlag[L][6][j], i);
          ST(19);
          signal(RD + 3);
        } else {
          mbar_wait(BAR(JOB + 4), L);
          if (C0 == 0) warp_store(gUB + (j * 56 + i) * 16384 + lane * 16, sb + lane * 16 + OFF_X, 16384, U0D, U0P);
          if (C0 == 3) { __nanosleep(U0D); if (lane == 0) { bulk_st(gUB + (j * 56 + i) * 16384, sb + OFF_X, 16384); bulk_commit(); bulk_wait0(); } }
          signal(RD + 2); ST(25);
          publish(gFlag[L][3][j], i);
        }
        mbar_wait(BAR(JOB + 5 + h), L);
        warp_store(gUB + (j * 56 + 16 + 16 * h + i) * 16384 + lane * 16, sb + lane * 16 + OFF_X + (1 - h) * 16384, 16384, 0, PACE);
        ST(23 + h);
        signal(RD + 1);
        publish(gFlag[L][4 + h][j], i);
        FRESH;
        if (L == 0) {
          mbar_wait(BAR(JOB + 8 + h), 0);
          if (h == 1) warp_store(gXB + (i * 16 + 2 * j + 1) * 16384 + lane * 16, sb + lane * 16 + OFF_X + 16384, 16384, X1D, 0);
          publish(gFlag[0][0][i], 2 * j + h);
        }
      }
      if (blockIdx.x == 0 && h == 0 && lane == 0) asm volatile("st.relaxed.gpu.global.u32 [%0], %1;" ::"l"(&gEpoch), "r"(tag) : "memory");
      }
    }
    __syncwarp();
    cluster_bar();
  } else {
    reg_alloc<232>();
    asm volatile("barrier.cluster.wait;" ::: "memory");
    const uint32_t rbars = mapa(bars, tid & 1);
    const bool relp = (tid & 127) < 2;
    const uint32_t sd = (sb & 0x3FFFF) >> 4;
    uint32_t tag;
    asm volatile("ld.relaxed.gpu.global.u32 %0, [%1];" : "=r"(tag) : "l"(&gEpoch + (fresh_tid() >> 10)) : "memory");
    auto release = [&](int k) { if (relp) mbar_arrive_cl(rbars + 8 * k); };
    auto signal = [&](int k) { __syncwarp(); if ((fresh_tid() & 31) == 0) mbar_arrive(BAR(k)); };
#define GEOM const int t7 = fresh_tid() & 127, lane = t7 & 31, w = t7 >> 5, g = lane >> 2, q = lane & 3, \
                       lr = lane & 15, lt = lane >> 4, l7 = lane & 7; (void)w; (void)g; (void)q; (void)lr; (void)lt; (void)l7

#pragma unroll 1
    for (int L = 0; L < 2; L++) {
      float acca[96], accb[96], xa[64], acc3[112];
      float nmean0, nmean1, rstd0, rstd1;
      uint16_t b2a, b2b;
      uint2 *e2p, *e2s; uint8_t* e2g; uint32_t e2h;
      uint32_t Q[2][8], K[2][8], V[16];
      auto g1_issue = [&](float (&acc)[96], uint32_t a, uint32_t st, auto first) {
        const uint32_t da = DESC(a + wg * 8192, 16), db = DESC(st + 16384, 4096);
        wg_fence();
#pragma unroll
        for (int kk = 0; kk < 4; kk++) {
          const uint32_t b = db + (((kk >> 1) * 12288 + (kk & 1) * 2048) >> 4);
          if (first.value && kk == 0) wgmma_192z<0, 1>(acc, da, b); else wgmma_192<0, 1>(acc, da + kk * 2, b);
        }
        wg_commit();
      };
      auto g1_step = [&](float (&acc)[96], int u, bool rel) {
        const int p = u & 3;
        mbar_wait(BAR(F1 + p), (u >> 2) & 1);
        KB(u);
        g1_issue(acc, slot1(p), slot1(p), False{});
        if (LEAD1 && u == 31 && wg == 1) nb_arrive<NB_LEAD>(256);
        wg_wait<1>();
        if (rel) release(E1 + ((u - 1) & 3));
      };
      auto g1_loop = [&](float (&acc)[96], int u0, int u1, int urel) {
#pragma unroll 1
        for (int u = u0; u < u1; u++) g1_step(acc, u, u > urel);
      };
      auto load_x = [&]() {
        GEOM;
#pragma unroll
        for (int t = 0; t < 16; t += 2) {
          uint32_t v0, v1, v2, v3;
          ldsm4(sb + OFF_X + (t >> 3) * 16384 + (16 * wu + lr) * 128 + ((((t & 7) + lt) ^ l7) << 4), v0, v1, v2, v3);
          xa[4 * t + 0] = bf_lo(v0); xa[4 * t + 1] = bf_hi(v0); xa[4 * t + 2] = bf_lo(v1); xa[4 * t + 3] = bf_hi(v1);
          xa[4 * t + 4] = bf_lo(v2); xa[4 * t + 5] = bf_hi(v2); xa[4 * t + 6] = bf_lo(v3); xa[4 * t + 7] = bf_hi(v3);
        }
      };
      auto stat_base = [&]() { return &gST[0][0][0][0][0] + ((L * 16 + opq(i)) * 8 + wu) * 128; };
      auto stat_slot = [&]() { const int lane = fresh_tid() & 31; return stat_base() + 16 * j + 2 * (lane >> 2) + (lane & 1); };
      auto stat_publish = [&](uint2* sp, float s0, float q0, float s2, float q2, uint32_t tg) {
        const int q = fresh_tid() & 3;
        const bool h1 = q & 1;
        float sm = (h1 ? s2 : s0) + __shfl_xor_sync(0xffffffffu, h1 ? s0 : s2, 1);
        float sq = (h1 ? q2 : q0) + __shfl_xor_sync(0xffffffffu, h1 ? q0 : q2, 1);
        sm += __shfl_xor_sync(0xffffffffu, sm, 2); sq += __shfl_xor_sync(0xffffffffu, sq, 2);
        stat_st(sp, sm, sq, tg, q < 2);
        return sm;
      };
      auto g1_stats = [&](int u0) {
        GEOM;
        const uint32_t xr = sb + OFF_X + (16 * wu + lr) * 128;
        float s0 = 0.f, q0 = 0.f, s2 = 0.f, q2 = 0.f;
        uint32_t v[8] = {0u, 0u, 0u, 0u, 0u, 0u, 0u, 0u};
#pragma unroll 1
        for (int k = 0; k < 5; k++) {
#pragma unroll
          for (int e = 0; e < 8; e += 2) {
            const float a = bf_lo(v[e]), b = bf_hi(v[e]), c = bf_lo(v[e + 1]), d = bf_hi(v[e + 1]);
            s0 += a + b; q0 = fmaf(a, a, fmaf(b, b, q0)); s2 += c + d; q2 = fmaf(c, c, fmaf(d, d, q2));
          }
          if (k == 4) break;
          const uint32_t o = ((2 * k + lt) ^ l7) << 4;
          ldsm4(xr + o, v[0], v[1], v[2], v[3]);
          ldsm4(xr + o + 16384, v[4], v[5], v[6], v[7]);
          g1_step(acca, u0 + k, true);
        }
        stat_publish(stat_slot(), s0, q0, s2, q2, 2 * (tag + 1));
      };
      uint32_t sv0[4], sv1[4];
      auto stat_src = [&]() { return stat_base() + 2 * (fresh_tid() & 31); };
      auto stat_fetch = [&](const uint2* sp) { stat_ld2(sp, sv0); stat_ld2(sp + 64, sv1); };
      auto stat_await = [&](auto src, uint32_t tg) {
#pragma unroll 1
        for (uint32_t n = 0; (((sv0[0] ^ tg) | (sv0[2] ^ tg) | (sv1[0] ^ tg) | (sv1[2] ^ tg)) & 15u) && n < SPIN_MAX; n++) stat_fetch(src());
        __syncwarp();
      };
      auto ln_stats = [&]() {
        GEOM;
        stat_await(stat_src, 2 * (tag + 1));
        float mean0, var0, mean1, var1;
        stat_combine(sv0[0], sv0[1], sv1[0], sv1[1], untag(__shfl_sync(0xffffffffu, sv0[0], l7)), mean0, var0);
        stat_combine(sv0[2], sv0[3], sv1[2], sv1[3], untag(__shfl_sync(0xffffffffu, sv0[2], l7)), mean1, var1);
        nmean0 = -__shfl_sync(0xffffffffu, mean0, g); rstd0 = rsq(__shfl_sync(0xffffffffu, var0, g) + 1e-5f);
        nmean1 = -__shfl_sync(0xffffffffu, mean1, g); rstd1 = rsq(__shfl_sync(0xffffffffu, var1, g) + 1e-5f);
      };
      auto center = [&](float (&acc)[96], int ab) {
        const bool q0 = (fresh_tid() & 3) == 0;
        const uint32_t h0 = pack2(nmean0, nmean0), h1 = pack2(nmean1, nmean1);
        const float l0 = nmean0 - bf_lo(h0), l1 = nmean1 - bf_lo(h1);
        const uint32_t a0 = q0 ? h0 : 0u, a1 = q0 ? h1 : 0u, a2 = q0 ? pack2(l0, l0) : 0u, a3 = q0 ? pack2(l1, l1) : 0u;
        wg_fence();
        wgmma_rs_192(acc, a0, a1, a2, a3, mkdesc_vec(sb + OFF_CS + ab * 768, 32));
      };
      auto frag = [&](float (&acc)[96], int t, uint32_t& p0, uint32_t& p1) {
        if (t >= 8) { p0 = pack2(acc[4 * t] * rstd0, acc[4 * t + 1] * rstd0); p1 = pack2(acc[4 * t + 2] * rstd1, acc[4 * t + 3] * rstd1); }
        else { p0 = pack2(acc[4 * t], acc[4 * t + 1]); p1 = pack2(acc[4 * t + 2], acc[4 * t + 3]); }
      };
      auto fold_v = [&](float (&acc)[96], int t0, int t1) {
        GEOM;
        const uint32_t a = sb + OFF_STG + 16384 + ((wu + 1) & 7) * 2048 + lr * 128;
#pragma unroll
        for (int t = t0; t < t1; t += 2) {
          uint32_t p0, p1, p2, p3;
          frag(acc, 16 + t, p0, p1); frag(acc, 17 + t, p2, p3);
          stsm4(a + (((t + lt) ^ l7) << 4), p0, p1, p2, p3);
        }
        __syncwarp();
#pragma unroll
        for (int t = t0; t < t1; t += 2) ldsm4t(a + (((t + lt) ^ l7) << 4), V[2 * t], V[2 * t + 1], V[2 * t + 2], V[2 * t + 3]);
      };
      auto fold_k = [&](float (&acc)[96], int ab, int h0, int h1) {
        GEOM;
        const uint32_t a = sb + OFF_STG + ((wu + 1) & 7) * 2048 + lane * 16;
#pragma unroll
        for (int hh = h0; hh < h1; hh++) {
#pragma unroll
          for (int t = 4 * hh; t < 4 * hh + 4; t++) frag(acc, 8 + t, K[0][t], K[1][t]);
#pragma unroll
          for (int o = 0; o < 2; o++) sts128(a + (2 * o + hh) * 512, K[o][4 * hh], K[o][4 * hh + 1], K[o][4 * hh + 2], K[o][4 * hh + 3]);
        }
        if (h1 == 2 && wu == 7) signal(FOLD + ab);
      };
      auto fold_q = [&](float (&acc)[96]) {
#pragma unroll
        for (int t = 0; t < 8; t++) frag(acc, t, Q[0][t], Q[1][t]);
      };
      auto attend = [&](int ab, auto drain, auto resume) {
        GEOM;
        nb_sync<NB_BOTH>(256);
        const uint32_t xa_ = sb + OFF_STG + wu * 2048 + lane * 16;
        if (wu == 0) mbar_wait(BAR(HALO + ab), L);
        uint32_t KH[2][8], VH[16];
#pragma unroll
        for (int c = 0; c < 4; c++) {
          lds128(xa_ + c * 512, KH[c >> 1][4 * (c & 1)], KH[c >> 1][4 * (c & 1) + 1], KH[c >> 1][4 * (c & 1) + 2], KH[c >> 1][4 * (c & 1) + 3]);
          ldsm4t(sb + OFF_STG + 16384 + wu * 2048 + lr * 128 + (((2 * c + lt) ^ l7) << 4), VH[4 * c], VH[4 * c + 1], VH[4 * c + 2], VH[4 * c + 3]);
        }
        TS2(11 + ab + 32 * L);
        const bool e = g & 1, zneg = (g >> 1) < q, first = (i == 0) && (wu == 0);
        const float sc0 = rstd0 * (0.17677669530f * 1.4426950409f), sc1 = rstd1 * (0.17677669530f * 1.4426950409f);
        float mk0 = first ? __fdividef(-1.0e9f * 1.4426950409f, sc0) : 0.f, mk1 = first ? __fdividef(-1.0e9f * 1.4426950409f, sc1) : 0.f;
        const uint32_t sa = e ? 0x1044u : 0x4410u, sbb = e ? 0x3244u : 0x4432u;
        uint32_t sel[3] = {zneg ? sbb : 0x4444u, sa, zneg ? 0x4444u : sbb};
        uint32_t oa = sb + OFF_STG + (16 * wu + lr) * 128 + ((lt ^ l7) << 4);
        asm volatile("" : "+r"(sel[0]), "+r"(sel[1]), "+r"(sel[2]), "+r"(oa), "+f"(mk0), "+f"(mk1));
        drain();
        uint32_t pr[2][6];
        float l[2][2];
#pragma unroll
        for (int hh = 0; hh < 2; hh++)
          attn_probs(&Q[0][4 * hh], &Q[1][4 * hh], &KH[0][4 * hh], &KH[1][4 * hh], &K[0][4 * hh], &K[1][4 * hh], sc0, sc1, mk0, mk1, e, zneg, sel, pr[hh], l[hh]);
        float o[2][4][4];
#pragma unroll
        for (int hh = 0; hh < 2; hh++) attn_pv(pr[hh], &VH[8 * hh], &V[8 * hh], o[hh]);
#pragma unroll
        for (int hh = 0; hh < 2; hh++) {
          float l0 = l[hh][0], l1 = l[hh][1];
          l0 += __shfl_xor_sync(0xffffffffu, l0, 1); l1 += __shfl_xor_sync(0xffffffffu, l1, 1);
          l0 += __shfl_xor_sync(0xffffffffu, l0, 2); l1 += __shfl_xor_sync(0xffffffffu, l1, 2);
          asm("rcp.approx.ftz.f32 %0, %0;" : "+f"(l0)); asm("rcp.approx.ftz.f32 %0, %0;" : "+f"(l1));
#pragma unroll
          for (int dt = 0; dt < 4; dt += 2)
            stsm4(oa ^ ((4 * hh + dt) << 4),
                  pack2(o[hh][dt][0] * l0, o[hh][dt][1] * l0), pack2(o[hh][dt][2] * l1, o[hh][dt][3] * l1),
                  pack2(o[hh][dt + 1][0] * l0, o[hh][dt + 1][1] * l0), pack2(o[hh][dt + 1][2] * l1, o[hh][dt + 1][3] * l1));
        }
        fence_async_smem();
        signal(JOB + ab);
        nb_sync<NB_BOTH>(256);
        resume();
      };

      TS(1 + 32 * L);
      mbar_wait(BAR(F1), 0); KB(0);    g1_issue(acca, L ? OFF_X : slot1(0), slot1(0), True{});
      mbar_wait(BAR(F1 + 1), 0); KB(1); g1_issue(acca, L ? OFF_X + 16384 : slot1(1), slot1(1), False{});
      wg_wait<1>(); release(E1 + 0);
      auto g1_bhead = [&](int p) {
        mbar_wait(BAR(F1 + p), 0); KB(p ? 2 : 16); g1_issue(accb, OFF_X, slot1(p), True{});
        if (p) { wg_wait<1>(); release(E1 + 1); }
        mbar_wait(BAR(F1 + p + 1), 0); KB(p ? 3 : 17); g1_issue(accb, OFF_X + 16384, slot1(p + 1), False{});
        wg_wait<1>(); release(E1 + p);
      };
      if (L == 0) {
        GEOM;
        const bf16* wp = P.wqkv_p + ((128 * opq(m) + 16 * wg + (t7 >> 3)) * 3072 + 128 * opq(j) + 64 * r + l7 * 8);
        const uint32_t ca = sb + OFF_STG + (16 * wg + (t7 >> 3)) * 784 + l7 * 32;
#pragma unroll 1
        for (int p = 0; p < 3; p++) {
          uint4 wv[4];
#pragma unroll
          for (int k = 0; k < 4; k++)
            asm volatile("ld.global.nc.v4.u32 {%0, %1, %2, %3}, [%4];" : "=r"(wv[k].x), "=r"(wv[k].y), "=r"(wv[k].z), "=r"(wv[k].w)
                         : "l"(wp + k * 32 * 3072 + p * 1024));
          g1_loop(acca, 2 + 3 * p, 5 + 3 * p, 0);
          float cs[8];
#pragma unroll
          for (int k = 0; k < 4; k++) {
            const uint4 v = wv[k];
            const float t[8] = {bf_lo(v.x), bf_hi(v.x), bf_lo(v.y), bf_hi(v.y), bf_lo(v.z), bf_hi(v.z), bf_lo(v.w), bf_hi(v.w)};
#pragma unroll
            for (int e = 0; e < 8; e++) cs[e] = k ? cs[e] + t[e] : t[e];
          }
          sts128(ca + p * 256, __float_as_uint(cs[0]), __float_as_uint(cs[1]), __float_as_uint(cs[2]), __float_as_uint(cs[3]));
          sts128(ca + p * 256 + 16, __float_as_uint(cs[4]), __float_as_uint(cs[5]), __float_as_uint(cs[6]), __float_as_uint(cs[7]));
        }
        signal(CSJ);
        g1_step(acca, 11, true);
        mbar_wait(BAR(XF), 0); mbar_wait(BAR(XF + 1), 0);
        g1_stats(12);
        wg_wait<0>(); release(E1 + 3);
        fence_regs(acca);
        g1_bhead(0);
      } else {
        g1_bhead(2);
        g1_stats(4);
        g1_loop(acca, 8, 18, 0);
      }
      stat_fetch(stat_src());
      g1_loop(accb, 18, FA, 0);
      ln_stats();
      if (L == 0) mbar_wait(BAR(STAT), 0);
      center(acca, 0); wg_commit();
      wg_wait<0>(); release(E1 + ((FA - 1) & 3));
      fence_regs(acca);
      TS(2 + 32 * L);
      fold_v(acca, 0, 8); fold_k(acca, 0, 0, 2); fold_q(acca);
      sched_fence(P.zero);
      g1_loop(accb, FA, ATT, FA);
      attend(0, [&]() { wg_wait<0>(); release(E1 + ((ATT - 1) & 3)); mbar_wait(BAR(F1 + (ATT & 3)), (ATT >> 2) & 1); },
             [&]() { KB(ATT); g1_issue(accb, slot1(ATT & 3), slot1(ATT & 3), False{});
                     mbar_wait(BAR(F1 + ((ATT + 1) & 3)), ((ATT + 1) >> 2) & 1);
                     KB(ATT + 1); g1_issue(accb, slot1((ATT + 1) & 3), slot1((ATT + 1) & 3), False{}); });
      wg_wait<1>(); release(E1 + (ATT & 3));
      TS(3 + 32 * L);
      load_x();
      fence_regs(xa);
      center(accb, 1);
      g1_loop(accb, ATT + 2, 32 - LEAD1, 0);
      if (LEAD1 && wg == 0) { wg_wait<0>(); release(E1 + ((31 - LEAD1) & 3)); nb_sync<NB_LEAD>(256); }
      g1_loop(accb, 32 - LEAD1, 32, wg == 0 ? 32 - LEAD1 : 0);
      mbar_wait(BAR(STD), L);
      wg_wait<0>(); release(E1 + 3);
      fence_regs(accb);
      TS(4 + 32 * L);
      if (wu == 7) ST(0);
      fold_v(accb, 0, 8); fold_k(accb, 1, 0, 2);
      fold_q(accb);
      TS2(29 + 32 * L);
      {
        auto g2_issue = [&](int p, bool own) {
          const uint32_t st = slot2(p);
          const uint32_t da = DESC((own ? OFF_STG : st) + wg * 8192, 16), db = DESC(st + 16384, 8192);
          wg_fence();
#pragma unroll
          for (int kk = 0; kk < 4; kk++) wgmma_128<0, 1>(xa, da + kk * 2, db + kk * 128);
          wg_commit();
        };
        uint32_t par = L ? 0x1e : 0;
        int p = 0, pp = 0;
        auto g2_loop = [&](int n0, int n1, int nrel) {
#pragma unroll 1
          for (int n = n0; n < n1; n++) {
            mbar_wait(BAR(F2 + p), (par >> p) & 1);
            KB(32 + n);
            if (n == 9 && wu == 0) ST(5);
            par ^= 1u << p;
            g2_issue(p, n == 8);
            if (LEAD2 && n == 15 && wg == 0) nb_arrive<NB_LEAD>(256);
            wg_wait<1>();
            if (n > nrel) release(E2 + pp);
            pp = p; if (++p == 5) p = 0;
          }
        };
        g2_loop(0, COVER, 0);
        attend(1, [&]() { wg_wait<0>(); release(E2 + COVER - 1); mbar_wait(BAR(F2 + COVER), (par >> COVER) & 1); },
               [&]() { KB(32 + COVER); g2_issue(COVER, false);
                       mbar_wait(BAR(F2 + COVER + 1), (par >> (COVER + 1)) & 1);
                       KB(33 + COVER); g2_issue(COVER + 1, false); });
        wg_wait<1>(); release(E2 + COVER);
        par ^= 3u << COVER; pp = COVER + 1; p = (COVER + 2) % 5;
        TS(30 + 32 * L);
        {
          const bf16* bp = P.b2 + (128 * opq(i) + 16 * wu + ((fresh_tid() & 31) >> 2));
          asm volatile("ld.global.nc.u16 %0, [%1];" : "=h"(b2a) : "l"(bp));
          asm volatile("ld.global.nc.u16 %0, [%1];" : "=h"(b2b) : "l"(bp + 8));
        }
        TS2(14 + 32 * L);
        {
          GEOM;
          e2p = stat_slot(); e2s = stat_src();
          e2g = gHB + (opq(j) * 32 + 2 * i) * 16384 + w * 2048 + lane * 16;
          e2h = sb + OFF_X + wg * 16384 + (16 * w + lr) * 128 + ((lt ^ l7) << 4);
          asm volatile("" : "+l"(e2p), "+l"(e2s), "+l"(e2g), "+r"(e2h));
        }
        g2_loop(COVER + 2, 16 - LEAD2, 0);
        if (LEAD2 && wg == 1) { wg_wait<0>(); release(E2 + pp); nb_sync<NB_LEAD>(256); }
        g2_loop(16 - LEAD2, 16, wg == 1 ? 16 - LEAD2 : 0);
        wg_wait<0>();
        release(E2 + 0);
        fence_regs(xa);
      }
      TS(5 + 32 * L);
      if (wu == 0) ST(8);
      {
        GEOM;
        const uint32_t tg = 2 * (tag + 1) + 1;
        float s0 = 0.f, s1 = 0.f, s2 = 0.f, s3 = 0.f, q0 = 0.f, q1 = 0.f, q2 = 0.f, q3 = 0.f;
#pragma unroll
        for (int t = 0; t < 16; t++) {
          s0 += xa[4 * t]; s1 += xa[4 * t + 1]; s2 += xa[4 * t + 2]; s3 += xa[4 * t + 3];
          q0 = fmaf(xa[4 * t], xa[4 * t], q0); q1 = fmaf(xa[4 * t + 1], xa[4 * t + 1], q1);
          q2 = fmaf(xa[4 * t + 2], xa[4 * t + 2], q2); q3 = fmaf(xa[4 * t + 3], xa[4 * t + 3], q3);
        }
        const float sm = stat_publish(e2p, s0 + s1, q0 + q1, s2 + s3, q2 + q3, tg);
        const uint32_t t0 = clock32();
        TS2(13 + 32 * L);
        const float pv0 = __shfl_sync(0xffffffffu, sm, 4 * l7) * (1.f / 128), pv1 = __shfl_sync(0xffffffffu, sm, 4 * l7 + 1) * (1.f / 128);
        while (clock32() - t0 < STAT_CLK) {}
        stat_fetch(e2s);
        wg_fence();
        wgmma_rs_224z(acc3, q == 0 ? 0x3f80u : 0u, q == 0 ? 0x3f80u : 0u, 0u, 0u, mkdesc_vec(sb + OFF_B1, 16));
        wg_commit();
        stat_await([&]() { return e2s; }, tg);
        float r0, m0, r1, m1;
        {
          float mean0, var0, mean1, var1;
          stat_combine(sv0[0], sv0[1], sv1[0], sv1[1], pv0, mean0, var0); stat_combine(sv0[2], sv0[3], sv1[2], sv1[3], pv1, mean1, var1);
          mean0 = __shfl_sync(0xffffffffu, mean0, g); var0 = __shfl_sync(0xffffffffu, var0, g);
          mean1 = __shfl_sync(0xffffffffu, mean1, g); var1 = __shfl_sync(0xffffffffu, var1, g);
          r0 = 0.5f * rsq(fmaf(var0 + 1e-5f, 1e-5f, var0)); r1 = 0.5f * rsq(fmaf(var1 + 1e-5f, 1e-5f, var1));
          m0 = -mean0 * r0; m1 = -mean1 * r1;
        }
        TS2(15 + 32 * L);
#pragma unroll
        for (int t = 0; t < 16; t += 2) {
          stsm4((e2h ^ ((t & 7) << 4)) + (t >> 3) * 8192,
                pack2(fmaf(xa[4 * t], r0, m0), fmaf(xa[4 * t + 1], r0, m0)), pack2(fmaf(xa[4 * t + 2], r1, m1), fmaf(xa[4 * t + 3], r1, m1)),
                pack2(fmaf(xa[4 * t + 4], r0, m0), fmaf(xa[4 * t + 5], r0, m0)), pack2(fmaf(xa[4 * t + 6], r1, m1), fmaf(xa[4 * t + 7], r1, m1)));
          if ((t & 7) == 6 && wg == 0) {
            __syncwarp();
            copy_out<4>(e2g + (t >> 3) * 8192, sb + OFF_X + (t >> 3) * 8192 + w * 2048 + lane * 16, 512);
          }
        }
        signal(JOB + 2 + wg);
        fence_async_smem();
        mbar_wait(BAR(F3 + 0), 0);
        nb_sync<NB_BOTH>(256);
      }
      TS(6 + 32 * L);
      auto g3_issue = [&](uint32_t a, int p) {
        const uint32_t da = DESC(a + wg * 8192, 8192), db = DESC(slot3(p) + 16384, 8192);
        wg_fence();
#pragma unroll
        for (int kk = 0; kk < 4; kk++) wgmma_224<1, 1>(acc3, da + kk * 128, db + kk * 128);
        wg_commit();
      };
      KB(48); g3_issue(OFF_X, 0);
      mbar_wait(BAR(F3 + 1), 0); KB(49); g3_issue(OFF_X + 16384, 1);
      sched_fence(P.zero);
      {
        const float c0 = __uint_as_float((uint32_t)b2a << 16), c1 = __uint_as_float((uint32_t)b2b << 16);
#pragma unroll
        for (int t = 0; t < 16; t++) { xa[4 * t] += c0; xa[4 * t + 1] += c0; xa[4 * t + 2] += c1; xa[4 * t + 3] += c1; }
        fence_regs(xa);
      }
      wg_wait<1>(); release(E3 + 0);
      auto g3_loop = [&](int n0, int n1, int nrel) {
#pragma unroll 1
        for (int n = n0; n < n1; n++) {
          const int p = n & 3;
          mbar_wait(BAR(F3 + p), (n >> 2) & 1);
          KB(48 + n);
          if (n == 3 && wu == 0) ST(13);
          if (n == 2 && wu == 0) ST(14);
          g3_issue(slot3(p), p);
          wg_wait<1>();
          if (n > nrel) release(E3 + ((n - 1) & 3));
        }
      };
      g3_loop(2, 29, 0);
      uint32_t ua;
      uint8_t* ug;
      {
        GEOM;
        ua = sb + OFF_X + wg * 8192 + (8 * lt + l7) * 128 + (((2 * w + ((lane >> 3) & 1)) ^ l7) << 4);
        ug = gUB + (opq(j) * 56 + 48 + m) * 16384 + r * 4096 + wg * 8192 + (lane >> 1) * 128 + (((2 * w + (lane & 1)) ^ ((lane >> 1) & 7)) << 4);
      }
      auto gelu8 = [&](int c, int k) {
        const int o = 32 * c + 8 * k;
        stsm4t(ua + (c & 1) * 16384 + k * 2048,
               pack2(gelu_half(acc3[o]), gelu_half(acc3[o + 1])), pack2(gelu_half(acc3[o + 2]), gelu_half(acc3[o + 3])),
               pack2(gelu_half(acc3[o + 4]), gelu_half(acc3[o + 5])), pack2(gelu_half(acc3[o + 6]), gelu_half(acc3[o + 7])));
      };
      {
        auto part = [&](int p, auto half) {
          const uint32_t da = DESC(slot3(p) + wg * 8192, 8192), db = DESC(slot3(p) + (half.value ? 40960 : 16384), 8192);
#pragma unroll
          for (int kk = 0; kk < 4; kk++) {
            if (half.value) wgmma_32<1, 1, 96>(acc3, da + kk * 128, db + kk * 128);
            else wgmma_192<1, 1, 0>(acc3, da + kk * 128, db + kk * 128);
          }
        };
        mbar_wait(BAR(RD), L);
        mbar_wait(BAR(F3 + 1), 1); mbar_wait(BAR(F3 + 2), 1);
        wg_wait<0>(); release(E3 + 0);
#pragma unroll
        for (int k = 0; k < 112; k++) { float t; asm volatile("mov.b32 %0, %1;" : "=f"(t) : "f"(acc3[k]) : "memory"); acc3[k] = t; }
        sched_fence(P.zero);
        KB(77);
        wg_fence(); part(1, True{}); part(2, True{});
        mbar_wait(BAR(F3 + 3), 1); wg_fence(); part(3, True{}); wg_commit();
        part(1, False{}); wg_commit();
        wg_wait<1>();
#pragma unroll
        for (int k = 96; k < 112; k++) asm volatile("" : "+f"(acc3[k])::"memory");
        gelu8(3, 0); gelu8(3, 1);
        __syncwarp();
        copy_out<2>(ug, sb + OFF_X + 16384 + (uint32_t)((ug - gUB) & 0x2fff), 2048);
        signal(JOB + 7);
        sched_fence(P.zero);
        KB(78);
        wg_fence(); part(2, False{}); wg_commit();
        wg_wait<1>(); release(E3 + 1);
        KB(79);
        part(3, False{}); wg_commit();
        wg_wait<1>(); release(E3 + 2);
        wg_wait<0>(); release(E3 + 3);
      }
      fence_regs(acc3);
      TS(7 + 32 * L);
      if (wu == 0) ST(16);
      auto g4_issue = [&](int p, uint32_t b) {
        const uint32_t da = DESC(slot4(p) + wg * 8192, 8192), db = DESC(b, 8192);
        wg_fence();
#pragma unroll
        for (int kk = 0; kk < 4; kk++) wgmma_128<1, 1>(xa, da + kk * 128, db + kk * 128);
        wg_commit();
      };
      uint32_t par = L ? 0x3c : 0;
#pragma unroll
      for (int k = 0; k < 4; k++) gelu8(0, k);
      auto out0 = [&]() { __syncwarp(); copy_out<4>(ug + (i - 48 - m) * 16384 - r * 4096, sb + OFF_X + (uint32_t)((ug - gUB) & 0x2fff), 2048); signal(JOB + 4); };
      if (C0 == 0) signal(JOB + 4);
      if (C0 == 1) out0();
      fence_async_smem();
      if (C0 == 3) signal(JOB + 4);
      nb_sync<NB_BOTH>(256);
      TS(8 + 32 * L);
      {
        int p = 0, pp = 0;
        auto g4_loop = [&](int n0, int n1, int nrel, uint32_t own) {
#pragma unroll 1
          for (int n = n0; n < n1; n++) {
            mbar_wait(BAR(F4 + p), (par >> p) & 1);
            KB(80 + n);
            if (n == 1 && wu == 0) ST(21);
            if (n == 0 && wu == 0) ST(22);
            par ^= 1u << p;
            g4_issue(p, own && n == n0 ? own : slot4(p) + 16384);
            if (LEAD4 && n == 55 && wg == 0) nb_arrive<NB_LEAD>(256);
            wg_wait<1>();
            if (n > nrel) release(E4 + pp);
            pp = p; if (++p == 6) p = 0;
          }
        };
        g4_loop(0, 1, 0, OFF_X);
        if (C0 == 2) out0();
        g4_loop(1, SL0, 0, 0);
#pragma unroll
        for (int k = 0; k < 8; k++) {
          if (k == 4 && (C0 == 0 || C0 == 3)) mbar_wait(BAR(RD + 2), L);
          gelu8(1 + (k >> 2), k & 3);
          if ((k & 3) == 3) { fence_async_smem(); signal(JOB + 5 + (k >> 2)); }
          g4_loop(SL0 + 2 * k, k < 7 ? SL0 + 2 + 2 * k : 24, 0, 0);
        }
        mbar_wait(BAR(JOB + 5), L);
        g4_loop(24, 40, 0, OFF_X + 16384);
        mbar_wait(BAR(JOB + 6), L);
        g4_loop(40, 56 - LEAD4, 0, OFF_X);
        if (LEAD4 && wg == 1) { wg_wait<0>(); release(E4 + pp); nb_sync<NB_LEAD>(256); }
        g4_loop(56 - LEAD4, 56, wg == 1 ? 56 - LEAD4 : 0, 0);
      }
      mbar_wait(BAR(RD + 1), L);
      wg_wait<0>();
      release(E4 + 1);
      fence_regs(xa);
      TS(9 + 32 * L);
      {
        GEOM;
#pragma unroll
        for (int t = 0; t < 16; t += 2) {
          stsm4(sb + OFF_X + (t >> 3) * 16384 + (16 * wu + lr) * 128 + ((((t & 7) + lt) ^ l7) << 4),
                pack2(xa[4 * t], xa[4 * t + 1]), pack2(xa[4 * t + 2], xa[4 * t + 3]),
                pack2(xa[4 * t + 4], xa[4 * t + 5]), pack2(xa[4 * t + 6], xa[4 * t + 7]));
          if (t == 6 && L == 0) {
            __syncwarp();
            const int o = wu * 2048 + lane * 16;
            copy_out<4>(gXB + (opq(i) * 16 + 2 * j) * 16384 + o, sb + OFF_X + o, 512);
            signal(JOB + 8);
          }
        }
        fence_async_smem();
        if (L == 0) signal(JOB + 9);
        else {
          __syncwarp();
          if (elect_one()) {
            tma2d_store(&P.out, sb + OFF_X + wu * 2048, 128 * j, 128 * i + 16 * wu);
            tma2d_store(&P.out, sb + OFF_X + 16384 + wu * 2048, 128 * j + 64, 128 * i + 16 * wu);
            bulk_commit(); bulk_wait0();
          }
          __syncwarp();
        }
        nb_sync<NB_BOTH>(256);
      }
      TS(10 + 32 * L);
      KB(136);
    }
    cluster_bar();
    TS(32);
  }
}

typedef CUresult (*EncodeFn)(CUtensorMap*, CUtensorMapDataType, cuuint32_t, void*, const cuuint64_t*, const cuuint64_t*, const cuuint32_t*,
                             const cuuint32_t*, CUtensorMapInterleave, CUtensorMapSwizzle, CUtensorMapL2promotion, CUtensorMapFloatOOBfill);

void make_map(EncodeFn enc, CUtensorMap* mp, const void* base, int rank, cuuint64_t d0, cuuint64_t d1, cuuint64_t d2, cuuint64_t s1, cuuint64_t s2,
              cuuint32_t b0, cuuint32_t b1, cuuint32_t b2) {
  cuuint64_t dims[3] = {d0, d1, d2}, strides[2] = {s1, s2};
  cuuint32_t box[3] = {b0, b1, b2}, es[3] = {1, 1, 1};
  CUresult res = enc(mp, CU_TENSOR_MAP_DATA_TYPE_BFLOAT16, rank, const_cast<void*>(base), dims, strides, box, es, CU_TENSOR_MAP_INTERLEAVE_NONE,
                     CU_TENSOR_MAP_SWIZZLE_128B, CU_TENSOR_MAP_L2_PROMOTION_L2_128B, CU_TENSOR_MAP_FLOAT_OOB_FILL_NONE);
  (void)res;
}

}

extern "C" void kernel_launch(void* const* d_in, const int* in_sizes, int n_in, void* d_out, int out_size) {
  (void)in_sizes; (void)n_in; (void)out_size;
  static EncodeFn enc = nullptr;
  if (!enc) {
    void* fn = nullptr;
    cudaDriverEntryPointQueryResult qr;
    cudaGetDriverEntryPoint("cuTensorMapEncodeTiled", &fn, cudaEnableDefault, &qr);
    enc = (EncodeFn)fn;
    cudaFuncSetAttribute(fused_kernel, cudaFuncAttributeMaxDynamicSharedMemorySize, SMEM_BYTES);
  }
  Params P;
  make_map(enc, &P.x0, d_in[0], 2, D_, S_, 1, D_ * 2, 0, 64, 128, 1);
  make_map(enc, &P.wqkv, d_in[1], 3, D_, D_, 3, 3 * D_ * 2, D_ * 2, 64, 32, 3);
  make_map(enc, &P.wo, d_in[2], 2, D_, D_, 1, D_ * 2, 0, 64, 64, 1);
  make_map(enc, &P.w1, d_in[4], 3, 64, S_, F_ / 64, F_ * 2, 128, 64, 64, 3);
  make_map(enc, &P.w1h, d_in[4], 3, 32, S_, F_ / 32, F_ * 2, 64, 64, 64, 1);
  make_map(enc, &P.w2, d_in[6], 3, 64, F_, S_ / 64, S_ * 2, 128, 64, 64, 2);
  make_map(enc, &P.out, d_out, 2, D_, S_, 1, D_ * 2, 0, 64, 16, 1);
  P.wqkv_p = (const bf16*)d_in[1];
  P.wo_p = (const bf16*)d_in[2];
  P.w1_p = (const bf16*)d_in[4];
  P.w2_p = (const bf16*)d_in[6];
  P.b1 = (const bf16*)d_in[5];
  P.b2 = (const bf16*)d_in[7];
  P.zero = 0;
  fused_kernel<<<128, 384, SMEM_BYTES>>>(P);
}
```

```cpp
#include <cuda_runtime.h>
#include <cuda_bf16.h>
#include <cuda.h>
#include <stdint.h>

namespace {

typedef __nv_bfloat16 bf16;
constexpr int S_ = 2048, D_ = 1024, F_ = 3584;

constexpr uint32_t OFF_STG  = 163840;
constexpr uint32_t OFF_X    = 196608;
constexpr uint32_t OFF_BAR  = 229376;
constexpr uint32_t OFF_CS   = OFF_BAR + 512;
constexpr uint32_t OFF_B1   = OFF_CS + 1536;
constexpr uint32_t SMEM_BYTES = OFF_B1 + 896 + 128;
constexpr int F1 = 0, E1 = 4, F2 = 8, E2 = 13, F3 = 18, E3 = 22, F4 = 26, E4 = 32;
constexpr int JOB = 38;
constexpr int RD = 48;
constexpr int XF = 54, STD = 56, STAT = 58, FOLD = 59, CSJ = 61, HALO = 62;
constexpr int NB_BOTH = 1, NB_HELP = 2, NB_INIT = 3, NB_LEAD = 4;

__host__ __device__ constexpr uint32_t slot1(int p) { return p * 40960; }
__host__ __device__ constexpr uint32_t slot2(int p) { return p * 32768; }
__host__ __device__ constexpr uint32_t slot3(int p) { return ((p + 2) & 3) * 49152; }
__host__ __device__ constexpr uint32_t slot4(int p) { return (p < 2 ? p + 4 : p - 2) * 32768; }

__device__ __align__(1024) uint8_t gXB[16 * 16 * 16384];
__device__ __align__(1024) uint8_t gOB[16 * 16 * 16384];
__device__ __align__(1024) uint8_t gHB[8 * 32 * 16384];
__device__ __align__(1024) uint8_t gUB[8 * 56 * 16384];
__device__ __align__(1024) uint2   gST[2][16][8][8][16];
__device__ __align__(1024) uint4   gHalo[2][16][8][12][32];
__device__ __align__(1024) uint32_t gAck[2][16][8][2][8];
__device__ __align__(1024) uint4   gCS[8][16][64];
__device__ __align__(1024) uint32_t gFlag[2][7][16][32];
__device__ uint32_t gEpoch;
#define TS(k)
#define TS2(k)

#define KB(k)
#define ST(k)
struct Params {
  CUtensorMap x0, wqkv, wo, w1, w1h, w2, out;
  const bf16 *wqkv_p, *wo_p, *w1_p, *w2_p, *b1, *b2;
  uint32_t zero;
};

template <int TA, int TB, uint32_t IA, uint32_t IB, int O = 0, int LEN> __device__ __forceinline__ void wgmma_32(float (&d)[LEN], uint32_t da, uint32_t db) {
  asm volatile("{\n.reg .b64 da, db;\n.reg .b32 la, lb;\nadd.u32 la, %16, %20;\nadd.u32 lb, %17, %21;\nmov.b64 da, {la, 0x40000040};\nmov.b64 db, {lb, 0x40000040};\n"
  "wgmma.mma_async.sync.aligned.m64n32k16.f32.bf16.bf16 {"
  "%0, %1, %2, %3, %4, %5, %6, %7, %8, %9, %10, %11, %12, %13, %14, %15"
  "}, da, db, 1, 1, 1, %18, %19;\n}\n"
  : "+f"(d[O + 0]), "+f"(d[O + 1]), "+f"(d[O + 2]), "+f"(d[O + 3]), "+f"(d[O + 4]), "+f"(d[O + 5]), "+f"(d[O + 6]), "+f"(d[O + 7]),
    "+f"(d[O + 8]), "+f"(d[O + 9]), "+f"(d[O + 10]), "+f"(d[O + 11]), "+f"(d[O + 12]), "+f"(d[O + 13]), "+f"(d[O + 14]), "+f"(d[O + 15])
  : "r"(da), "r"(db), "n"(TA), "n"(TB), "n"(IA), "n"(IB));
}
template <int TA, int TB, uint32_t IA, uint32_t IB, int O = 0, int LEN> __device__ __forceinline__ void wgmma_128(float (&d)[LEN], uint32_t da, uint32_t db) {
  asm volatile("{\n.reg .b64 da, db;\n.reg .b32 la, lb;\nadd.u32 la, %64, %68;\nadd.u32 lb, %65, %69;\nmov.b64 da, {la, 0x40000040};\nmov.b64 db, {lb, 0x40000040};\n"
  "wgmma.mma_async.sync.aligned.m64n128k16.f32.bf16.bf16 {"
  "%0, %1, %2, %3, %4, %5, %6, %7, %8, %9, %10, %11, %12, %13, %14, %15, "
  "%16, %17, %18, %19, %20, %21, %22, %23, %24, %25, %26, %27, %28, %29, %30, %31, "
  "%32, %33, %34, %35, %36, %37, %38, %39, %40, %41, %42, %43, %44, %45, %46, %47, "
  "%48, %49, %50, %51, %52, %53, %54, %55, %56, %57, %58, %59, %60, %61, %62, %63"
  "}, da, db, 1, 1, 1, %66, %67;\n}\n"
  : "+f"(d[O + 0]), "+f"(d[O + 1]), "+f"(d[O + 2]), "+f"(d[O + 3]), "+f"(d[O + 4]), "+f"(d[O + 5]), "+f"(d[O + 6]), "+f"(d[O + 7]),
    "+f"(d[O + 8]), "+f"(d[O + 9]), "+f"(d[O + 10]), "+f"(d[O + 11]), "+f"(d[O + 12]), "+f"(d[O + 13]), "+f"(d[O + 14]), "+f"(d[O + 15]),
    "+f"(d[O + 16]), "+f"(d[O + 17]), "+f"(d[O + 18]), "+f"(d[O + 19]), "+f"(d[O + 20]), "+f"(d[O + 21]), "+f"(d[O + 22]), "+f"(d[O + 23]),
    "+f"(d[O + 24]), "+f"(d[O + 25]), "+f"(d[O + 26]), "+f"(d[O + 27]), "+f"(d[O + 28]), "+f"(d[O + 29]), "+f"(d[O + 30]), "+f"(d[O + 31]),
    "+f"(d[O + 32]), "+f"(d[O + 33]), "+f"(d[O + 34]), "+f"(d[O + 35]), "+f"(d[O + 36]), "+f"(d[O + 37]), "+f"(d[O + 38]), "+f"(d[O + 39]),
    "+f"(d[O + 40]), "+f"(d[O + 41]), "+f"(d[O + 42]), "+f"(d[O + 43]), "+f"(d[O + 44]), "+f"(d[O + 45]), "+f"(d[O + 46]), "+f"(d[O + 47]),
    "+f"(d[O + 48]), "+f"(d[O + 49]), "+f"(d[O + 50]), "+f"(d[O + 51]), "+f"(d[O + 52]), "+f"(d[O + 53]), "+f"(d[O + 54]), "+f"(d[O + 55]),
    "+f"(d[O + 56]), "+f"(d[O + 57]), "+f"(d[O + 58]), "+f"(d[O + 59]), "+f"(d[O + 60]), "+f"(d[O + 61]), "+f"(d[O + 62]), "+f"(d[O + 63])
  : "r"(da), "r"(db), "n"(TA), "n"(TB), "n"(IA), "n"(IB));
}
template <int TA, int TB, uint32_t IA, uint32_t IB, int O = 0, int LEN> __device__ __forceinline__ void wgmma_192(float (&d)[LEN], uint32_t da, uint32_t db) {
  asm volatile("{\n.reg .b64 da, db;\n.reg .b32 la, lb;\nadd.u32 la, %96, %100;\nadd.u32 lb, %97, %101;\nmov.b64 da, {la, 0x40000040};\nmov.b64 db, {lb, 0x40000040};\n"
  "wgmma.mma_async.sync.aligned.m64n192k16.f32.bf16.bf16 {"
  "%0, %1, %2, %3, %4, %5, %6, %7, %8, %9, %10, %11, %12, %13, %14, %15, "
  "%16, %17, %18, %19, %20, %21, %22, %23, %24, %25, %26, %27, %28, %29, %30, %31, "
  "%32, %33, %34, %35, %36, %37, %38, %39, %40, %41, %42, %43, %44, %45, %46, %47, "
  "%48, %49, %50, %51, %52, %53, %54, %55, %56, %57, %58, %59, %60, %61, %62, %63, "
  "%64, %65, %66, %67, %68, %69, %70, %71, %72, %73, %74, %75, %76, %77, %78, %79, "
  "%80, %81, %82, %83, %84, %85, %86, %87, %88, %89, %90, %91, %92, %93, %94, %95"
  "}, da, db, 1, 1, 1, %98, %99;\n}\n"
  : "+f"(d[O + 0]), "+f"(d[O + 1]), "+f"(d[O + 2]), "+f"(d[O + 3]), "+f"(d[O + 4]), "+f"(d[O + 5]), "+f"(d[O + 6]), "+f"(d[O + 7]),
    "+f"(d[O + 8]), "+f"(d[O + 9]), "+f"(d[O + 10]), "+f"(d[O + 11]), "+f"(d[O + 12]), "+f"(d[O + 13]), "+f"(d[O + 14]), "+f"(d[O + 15]),
    "+f"(d[O + 16]), "+f"(d[O + 17]), "+f"(d[O + 18]), "+f"(d[O + 19]), "+f"(d[O + 20]), "+f"(d[O + 21]), "+f"(d[O + 22]), "+f"(d[O + 23]),
    "+f"(d[O + 24]), "+f"(d[O + 25]), "+f"(d[O + 26]), "+f"(d[O + 27]), "+f"(d[O + 28]), "+f"(d[O + 29]), "+f"(d[O + 30]), "+f"(d[O + 31]),
    "+f"(d[O + 32]), "+f"(d[O + 33]), "+f"(d[O + 34]), "+f"(d[O + 35]), "+f"(d[O + 36]), "+f"(d[O + 37]), "+f"(d[O + 38]), "+f"(d[O + 39]),
    "+f"(d[O + 40]), "+f"(d[O + 41]), "+f"(d[O + 42]), "+f"(d[O + 43]), "+f"(d[O + 44]), "+f"(d[O + 45]), "+f"(d[O + 46]), "+f"(d[O + 47]),
    "+f"(d[O + 48]), "+f"(d[O + 49]), "+f"(d[O + 50]), "+f"(d[O + 51]), "+f"(d[O + 52]), "+f"(d[O + 53]), "+f"(d[O + 54]), "+f"(d[O + 55]),
    "+f"(d[O + 56]), "+f"(d[O + 57]), "+f"(d[O + 58]), "+f"(d[O + 59]), "+f"(d[O + 60]), "+f"(d[O + 61]), "+f"(d[O + 62]), "+f"(d[O + 63]),
    "+f"(d[O + 64]), "+f"(d[O + 65]), "+f"(d[O + 66]), "+f"(d[O + 67]), "+f"(d[O + 68]), "+f"(d[O + 69]), "+f"(d[O + 70]), "+f"(d[O + 71]),
    "+f"(d[O + 72]), "+f"(d[O + 73]), "+f"(d[O + 74]), "+f"(d[O + 75]), "+f"(d[O + 76]), "+f"(d[O + 77]), "+f"(d[O + 78]), "+f"(d[O + 79]),
    "+f"(d[O + 80]), "+f"(d[O + 81]), "+f"(d[O + 82]), "+f"(d[O + 83]), "+f"(d[O + 84]), "+f"(d[O + 85]), "+f"(d[O + 86]), "+f"(d[O + 87]),
    "+f"(d[O + 88]), "+f"(d[O + 89]), "+f"(d[O + 90]), "+f"(d[O + 91]), "+f"(d[O + 92]), "+f"(d[O + 93]), "+f"(d[O + 94]), "+f"(d[O + 95])
  : "r"(da), "r"(db), "n"(TA), "n"(TB), "n"(IA), "n"(IB));
}
template <int TA, int TB, uint32_t IA, uint32_t IB, int O = 0, int LEN> __device__ __forceinline__ void wgmma_192z(float (&d)[LEN], uint32_t da, uint32_t db) {
  asm volatile("{\n.reg .b64 da, db;\n.reg .b32 la, lb;\nadd.u32 la, %96, %100;\nadd.u32 lb, %97, %101;\nmov.b64 da, {la, 0x40000040};\nmov.b64 db, {lb, 0x40000040};\n"
  "wgmma.mma_async.sync.aligned.m64n192k16.f32.bf16.bf16 {"
  "%0, %1, %2, %3, %4, %5, %6, %7, %8, %9, %10, %11, %12, %13, %14, %15, "
  "%16, %17, %18, %19, %20, %21, %22, %23, %24, %25, %26, %27, %28, %29, %30, %31, "
  "%32, %33, %34, %35, %36, %37, %38, %39, %40, %41, %42, %43, %44, %45, %46, %47, "
  "%48, %49, %50, %51, %52, %53, %54, %55, %56, %57, %58, %59, %60, %61, %62, %63, "
  "%64, %65, %66, %67, %68, %69, %70, %71, %72, %73, %74, %75, %76, %77, %78, %79, "
  "%80, %81, %82, %83, %84, %85, %86, %87, %88, %89, %90, %91, %92, %93, %94, %95"
  "}, da, db, 0, 1, 1, %98, %99;\n}\n"
  : "=f"(d[O + 0]), "=f"(d[O + 1]), "=f"(d[O + 2]), "=f"(d[O + 3]), "=f"(d[O + 4]), "=f"(d[O + 5]), "=f"(d[O + 6]), "=f"(d[O + 7]),
    "=f"(d[O + 8]), "=f"(d[O + 9]), "=f"(d[O + 10]), "=f"(d[O + 11]), "=f"(d[O + 12]), "=f"(d[O + 13]), "=f"(d[O + 14]), "=f"(d[O + 15]),
    "=f"(d[O + 16]), "=f"(d[O + 17]), "=f"(d[O + 18]), "=f"(d[O + 19]), "=f"(d[O + 20]), "=f"(d[O + 21]), "=f"(d[O + 22]), "=f"(d[O + 23]),
    "=f"(d[O + 24]), "=f"(d[O + 25]), "=f"(d[O + 26]), "=f"(d[O + 27]), "=f"(d[O + 28]), "=f"(d[O + 29]), "=f"(d[O + 30]), "=f"(d[O + 31]),
    "=f"(d[O + 32]), "=f"(d[O + 33]), "=f"(d[O + 34]), "=f"(d[O + 35]), "=f"(d[O + 36]), "=f"(d[O + 37]), "=f"(d[O + 38]), "=f"(d[O + 39]),
    "=f"(d[O + 40]), "=f"(d[O + 41]), "=f"(d[O + 42]), "=f"(d[O + 43]), "=f"(d[O + 44]), "=f"(d[O + 45]), "=f"(d[O + 46]), "=f"(d[O + 47]),
    "=f"(d[O + 48]), "=f"(d[O + 49]), "=f"(d[O + 50]), "=f"(d[O + 51]), "=f"(d[O + 52]), "=f"(d[O + 53]), "=f"(d[O + 54]), "=f"(d[O + 55]),
    "=f"(d[O + 56]), "=f"(d[O + 57]), "=f"(d[O + 58]), "=f"(d[O + 59]), "=f"(d[O + 60]), "=f"(d[O + 61]), "=f"(d[O + 62]), "=f"(d[O + 63]),
    "=f"(d[O + 64]), "=f"(d[O + 65]), "=f"(d[O + 66]), "=f"(d[O + 67]), "=f"(d[O + 68]), "=f"(d[O + 69]), "=f"(d[O + 70]), "=f"(d[O + 71]),
    "=f"(d[O + 72]), "=f"(d[O + 73]), "=f"(d[O + 74]), "=f"(d[O + 75]), "=f"(d[O + 76]), "=f"(d[O + 77]), "=f"(d[O + 78]), "=f"(d[O + 79]),
    "=f"(d[O + 80]), "=f"(d[O + 81]), "=f"(d[O + 82]), "=f"(d[O + 83]), "=f"(d[O + 84]), "=f"(d[O + 85]), "=f"(d[O + 86]), "=f"(d[O + 87]),
    "=f"(d[O + 88]), "=f"(d[O + 89]), "=f"(d[O + 90]), "=f"(d[O + 91]), "=f"(d[O + 92]), "=f"(d[O + 93]), "=f"(d[O + 94]), "=f"(d[O + 95])
  : "r"(da), "r"(db), "n"(TA), "n"(TB), "n"(IA), "n"(IB));
}
template <int TA, int TB, uint32_t IA, uint32_t IB, int O = 0, int LEN> __device__ __forceinline__ void wgmma_224(float (&d)[LEN], uint32_t da, uint32_t db) {
  asm volatile("{\n.reg .b64 da, db;\n.reg .b32 la, lb;\nadd.u32 la, %112, %116;\nadd.u32 lb, %113, %117;\nmov.b64 da, {la, 0x40000040};\nmov.b64 db, {lb, 0x40000040};\n"
  "wgmma.mma_async.sync.aligned.m64n224k16.f32.bf16.bf16 {"
  "%0, %1, %2, %3, %4, %5, %6, %7, %8, %9, %10, %11, %12, %13, %14, %15, "
  "%16, %17, %18, %19, %20, %21, %22, %23, %24, %25, %26, %27, %28, %29, %30, %31, "
  "%32, %33, %34, %35, %36, %37, %38, %39, %40, %41, %42, %43, %44, %45, %46, %47, "
  "%48, %49, %50, %51, %52, %53, %54, %55, %56, %57, %58, %59, %60, %61, %62, %63, "
  "%64, %65, %66, %67, %68, %69, %70, %71, %72, %73, %74, %75, %76, %77, %78, %79, "
  "%80, %81, %82, %83, %84, %85, %86, %87, %88, %89, %90, %91, %92, %93, %94, %95, "
  "%96, %97, %98, %99, %100, %101, %102, %103, %104, %105, %106, %107, %108, %109, %110, %111"
  "}, da, db, 1, 1, 1, %114, %115;\n}\n"
  : "+f"(d[O + 0]), "+f"(d[O + 1]), "+f"(d[O + 2]), "+f"(d[O + 3]), "+f"(d[O + 4]), "+f"(d[O + 5]), "+f"(d[O + 6]), "+f"(d[O + 7]),
    "+f"(d[O + 8]), "+f"(d[O + 9]), "+f"(d[O + 10]), "+f"(d[O + 11]), "+f"(d[O + 12]), "+f"(d[O + 13]), "+f"(d[O + 14]), "+f"(d[O + 15]),
    "+f"(d[O + 16]), "+f"(d[O + 17]), "+f"(d[O + 18]), "+f"(d[O + 19]), "+f"(d[O + 20]), "+f"(d[O + 21]), "+f"(d[O + 22]), "+f"(d[O + 23]),
    "+f"(d[O + 24]), "+f"(d[O + 25]), "+f"(d[O + 26]), "+f"(d[O + 27]), "+f"(d[O + 28]), "+f"(d[O + 29]), "+f"(d[O + 30]), "+f"(d[O + 31]),
    "+f"(d[O + 32]), "+f"(d[O + 33]), "+f"(d[O + 34]), "+f"(d[O + 35]), "+f"(d[O + 36]), "+f"(d[O + 37]), "+f"(d[O + 38]), "+f"(d[O + 39]),
    "+f"(d[O + 40]), "+f"(d[O + 41]), "+f"(d[O + 42]), "+f"(d[O + 43]), "+f"(d[O + 44]), "+f"(d[O + 45]), "+f"(d[O + 46]), "+f"(d[O + 47]),
    "+f"(d[O + 48]), "+f"(d[O + 49]), "+f"(d[O + 50]), "+f"(d[O + 51]), "+f"(d[O + 52]), "+f"(d[O + 53]), "+f"(d[O + 54]), "+f"(d[O + 55]),
    "+f"(d[O + 56]), "+f"(d[O + 57]), "+f"(d[O + 58]), "+f"(d[O + 59]), "+f"(d[O + 60]), "+f"(d[O + 61]), "+f"(d[O + 62]), "+f"(d[O + 63]),
    "+f"(d[O + 64]), "+f"(d[O + 65]), "+f"(d[O + 66]), "+f"(d[O + 67]), "+f"(d[O + 68]), "+f"(d[O + 69]), "+f"(d[O + 70]), "+f"(d[O + 71]),
    "+f"(d[O + 72]), "+f"(d[O + 73]), "+f"(d[O + 74]), "+f"(d[O + 75]), "+f"(d[O + 76]), "+f"(d[O + 77]), "+f"(d[O + 78]), "+f"(d[O + 79]),
    "+f"(d[O + 80]), "+f"(d[O + 81]), "+f"(d[O + 82]), "+f"(d[O + 83]), "+f"(d[O + 84]), "+f"(d[O + 85]), "+f"(d[O + 86]), "+f"(d[O + 87]),
    "+f"(d[O + 88]), "+f"(d[O + 89]), "+f"(d[O + 90]), "+f"(d[O + 91]), "+f"(d[O + 92]), "+f"(d[O + 93]), "+f"(d[O + 94]), "+f"(d[O + 95]),
    "+f"(d[O + 96]), "+f"(d[O + 97]), "+f"(d[O + 98]), "+f"(d[O + 99]), "+f"(d[O + 100]), "+f"(d[O + 101]), "+f"(d[O + 102]), "+f"(d[O + 103]),
    "+f"(d[O + 104]), "+f"(d[O + 105]), "+f"(d[O + 106]), "+f"(d[O + 107]), "+f"(d[O + 108]), "+f"(d[O + 109]), "+f"(d[O + 110]), "+f"(d[O + 111])
  : "r"(da), "r"(db), "n"(TA), "n"(TB), "n"(IA), "n"(IB));
}
__device__ __forceinline__ void wgmma_rs_192(float (&d)[96], uint32_t a0, uint32_t a1, uint32_t a2, uint32_t a3, uint64_t db) {
  asm volatile("wgmma.mma_async.sync.aligned.m64n192k16.f32.bf16.bf16 {"
  "%0, %1, %2, %3, %4, %5, %6, %7, %8, %9, %10, %11, %12, %13, %14, %15, "
  "%16, %17, %18, %19, %20, %21, %22, %23, %24, %25, %26, %27, %28, %29, %30, %31, "
  "%32, %33, %34, %35, %36, %37, %38, %39, %40, %41, %42, %43, %44, %45, %46, %47, "
  "%48, %49, %50, %51, %52, %53, %54, %55, %56, %57, %58, %59, %60, %61, %62, %63, "
  "%64, %65, %66, %67, %68, %69, %70, %71, %72, %73, %74, %75, %76, %77, %78, %79, "
  "%80, %81, %82, %83, %84, %85, %86, %87, %88, %89, %90, %91, %92, %93, %94, %95"
  "}, {%96, %97, %98, %99}, %100, 1, 1, 1, 1;\n"
  : "+f"(d[0]), "+f"(d[1]), "+f"(d[2]), "+f"(d[3]), "+f"(d[4]), "+f"(d[5]), "+f"(d[6]), "+f"(d[7]),
    "+f"(d[8]), "+f"(d[9]), "+f"(d[10]), "+f"(d[11]), "+f"(d[12]), "+f"(d[13]), "+f"(d[14]), "+f"(d[15]),
    "+f"(d[16]), "+f"(d[17]), "+f"(d[18]), "+f"(d[19]), "+f"(d[20]), "+f"(d[21]), "+f"(d[22]), "+f"(d[23]),
    "+f"(d[24]), "+f"(d[25]), "+f"(d[26]), "+f"(d[27]), "+f"(d[28]), "+f"(d[29]), "+f"(d[30]), "+f"(d[31]),
    "+f"(d[32]), "+f"(d[33]), "+f"(d[34]), "+f"(d[35]), "+f"(d[36]), "+f"(d[37]), "+f"(d[38]), "+f"(d[39]),
    "+f"(d[40]), "+f"(d[41]), "+f"(d[42]), "+f"(d[43]), "+f"(d[44]), "+f"(d[45]), "+f"(d[46]), "+f"(d[47]),
    "+f"(d[48]), "+f"(d[49]), "+f"(d[50]), "+f"(d[51]), "+f"(d[52]), "+f"(d[53]), "+f"(d[54]), "+f"(d[55]),
    "+f"(d[56]), "+f"(d[57]), "+f"(d[58]), "+f"(d[59]), "+f"(d[60]), "+f"(d[61]), "+f"(d[62]), "+f"(d[63]),
    "+f"(d[64]), "+f"(d[65]), "+f"(d[66]), "+f"(d[67]), "+f"(d[68]), "+f"(d[69]), "+f"(d[70]), "+f"(d[71]),
    "+f"(d[72]), "+f"(d[73]), "+f"(d[74]), "+f"(d[75]), "+f"(d[76]), "+f"(d[77]), "+f"(d[78]), "+f"(d[79]),
    "+f"(d[80]), "+f"(d[81]), "+f"(d[82]), "+f"(d[83]), "+f"(d[84]), "+f"(d[85]), "+f"(d[86]), "+f"(d[87]),
    "+f"(d[88]), "+f"(d[89]), "+f"(d[90]), "+f"(d[91]), "+f"(d[92]), "+f"(d[93]), "+f"(d[94]), "+f"(d[95])
  : "r"(a0), "r"(a1), "r"(a2), "r"(a3), "l"(db));
}
__device__ __forceinline__ void wgmma_rs_224z(float (&d)[112], uint32_t a0, uint32_t a1, uint32_t a2, uint32_t a3, uint64_t db) {
  asm volatile("wgmma.mma_async.sync.aligned.m64n224k16.f32.bf16.bf16 {"
  "%0, %1, %2, %3, %4, %5, %6, %7, %8, %9, %10, %11, %12, %13, %14, %15, "
  "%16, %17, %18, %19, %20, %21, %22, %23, %24, %25, %26, %27, %28, %29, %30, %31, "
  "%32, %33, %34, %35, %36, %37, %38, %39, %40, %41, %42, %43, %44, %45, %46, %47, "
  "%48, %49, %50, %51, %52, %53, %54, %55, %56, %57, %58, %59, %60, %61, %62, %63, "
  "%64, %65, %66, %67, %68, %69, %70, %71, %72, %73, %74, %75, %76, %77, %78, %79, "
  "%80, %81, %82, %83, %84, %85, %86, %87, %88, %89, %90, %91, %92, %93, %94, %95, "
  "%96, %97, %98, %99, %100, %101, %102, %103, %104, %105, %106, %107, %108, %109, %110, %111"
  "}, {%112, %113, %114, %115}, %116, 0, 1, 1, 1;\n"
  : "=f"(d[0]), "=f"(d[1]), "=f"(d[2]), "=f"(d[3]), "=f"(d[4]), "=f"(d[5]), "=f"(d[6]), "=f"(d[7]),
    "=f"(d[8]), "=f"(d[9]), "=f"(d[10]), "=f"(d[11]), "=f"(d[12]), "=f"(d[13]), "=f"(d[14]), "=f"(d[15]),
    "=f"(d[16]), "=f"(d[17]), "=f"(d[18]), "=f"(d[19]), "=f"(d[20]), "=f"(d[21]), "=f"(d[22]), "=f"(d[23]),
    "=f"(d[24]), "=f"(d[25]), "=f"(d[26]), "=f"(d[27]), "=f"(d[28]), "=f"(d[29]), "=f"(d[30]), "=f"(d[31]),
    "=f"(d[32]), "=f"(d[33]), "=f"(d[34]), "=f"(d[35]), "=f"(d[36]), "=f"(d[37]), "=f"(d[38]), "=f"(d[39]),
    "=f"(d[40]), "=f"(d[41]), "=f"(d[42]), "=f"(d[43]), "=f"(d[44]), "=f"(d[45]), "=f"(d[46]), "=f"(d[47]),
    "=f"(d[48]), "=f"(d[49]), "=f"(d[50]), "=f"(d[51]), "=f"(d[52]), "=f"(d[53]), "=f"(d[54]), "=f"(d[55]),
    "=f"(d[56]), "=f"(d[57]), "=f"(d[58]), "=f"(d[59]), "=f"(d[60]), "=f"(d[61]), "=f"(d[62]), "=f"(d[63]),
    "=f"(d[64]), "=f"(d[65]), "=f"(d[66]), "=f"(d[67]), "=f"(d[68]), "=f"(d[69]), "=f"(d[70]), "=f"(d[71]),
    "=f"(d[72]), "=f"(d[73]), "=f"(d[74]), "=f"(d[75]), "=f"(d[76]), "=f"(d[77]), "=f"(d[78]), "=f"(d[79]),
    "=f"(d[80]), "=f"(d[81]), "=f"(d[82]), "=f"(d[83]), "=f"(d[84]), "=f"(d[85]), "=f"(d[86]), "=f"(d[87]),
    "=f"(d[88]), "=f"(d[89]), "=f"(d[90]), "=f"(d[91]), "=f"(d[92]), "=f"(d[93]), "=f"(d[94]), "=f"(d[95]),
    "=f"(d[96]), "=f"(d[97]), "=f"(d[98]), "=f"(d[99]), "=f"(d[100]), "=f"(d[101]), "=f"(d[102]), "=f"(d[103]),
    "=f"(d[104]), "=f"(d[105]), "=f"(d[106]), "=f"(d[107]), "=f"(d[108]), "=f"(d[109]), "=f"(d[110]), "=f"(d[111])
  : "r"(a0), "r"(a1), "r"(a2), "r"(a3), "l"(db));
}

__device__ __forceinline__ uint32_t smem_u32(const void* p) { return (uint32_t)__cvta_generic_to_shared(p); }
__device__ __forceinline__ void mbar_init(uint32_t bar, uint32_t cnt) { asm volatile("mbarrier.init.shared::cta.b64 [%0], %1;" ::"r"(bar), "r"(cnt) : "memory"); }
__device__ __forceinline__ void mbar_expect(uint32_t bar, uint32_t bytes) { asm volatile("mbarrier.arrive.expect_tx.shared::cta.b64 _, [%0], %1;" ::"r"(bar), "r"(bytes) : "memory"); }
__device__ __forceinline__ void mbar_arrive(uint32_t bar) { asm volatile("mbarrier.arrive.shared::cta.b64 _, [%0];" ::"r"(bar) : "memory"); }
__device__ __forceinline__ void mbar_arrive_cl(uint32_t cbar) { asm volatile("mbarrier.arrive.shared::cluster.b64 _, [%0];" ::"r"(cbar) : "memory"); }
__device__ __forceinline__ uint32_t mapa(uint32_t a, uint32_t cta) { uint32_t r; asm("mapa.shared::cluster.u32 %0, %1, %2;" : "=r"(r) : "r"(a), "r"(cta)); return r; }
__device__ __forceinline__ void mbar_wait(uint32_t bar, uint32_t parity) {
  asm volatile("{\n.reg .pred p;\n.reg .u32 n;\nmov.u32 n, 0;\n"
    "LAB_WAIT:\n"
    "mbarrier.try_wait.parity.shared::cta.b64 p, [%0], %1;\n"
    "@p bra LAB_DONE;\n"
    "add.u32 n, n, 1;\n"
    "setp.lt.u32 p, n, 2000000;\n"
    "@p bra LAB_WAIT;\n"
    "trap;\n"
    "LAB_DONE:\n}\n" ::"r"(bar), "r"(parity) : "memory");
}
constexpr uint32_t SPIN_MAX = 2000000;
__device__ __forceinline__ void tma2d(uint32_t dst, const CUtensorMap* m, uint32_t bar, int c0, int c1) {
  asm volatile("cp.async.bulk.tensor.2d.shared::cluster.global.mbarrier::complete_tx::bytes [%0], [%1, {%3, %4}], [%2];"
    ::"r"(dst), "l"(m), "r"(bar), "r"(c0), "r"(c1) : "memory");
}
__device__ __forceinline__ void tma2d_mc(uint32_t dst, const CUtensorMap* m, uint32_t bar, int c0, int c1) {
  asm volatile("cp.async.bulk.tensor.2d.shared::cluster.global.mbarrier::complete_tx::bytes.multicast::cluster [%0], [%1, {%3, %4}], [%2], %5;"
    ::"r"(dst), "l"(m), "r"(bar), "r"(c0), "r"(c1), "h"((uint16_t)3) : "memory");
}
__device__ __forceinline__ void tma3d(uint32_t dst, const CUtensorMap* m, uint32_t bar, int c0, int c1, int c2) {
  asm volatile("cp.async.bulk.tensor.3d.shared::cluster.global.mbarrier::complete_tx::bytes [%0], [%1, {%3, %4, %5}], [%2];"
    ::"r"(dst), "l"(m), "r"(bar), "r"(c0), "r"(c1), "r"(c2) : "memory");
}
__device__ __forceinline__ void tma3d_mc(uint32_t dst, const CUtensorMap* m, uint32_t bar, int c0, int c1, int c2) {
  asm volatile("cp.async.bulk.tensor.3d.shared::cluster.global.mbarrier::complete_tx::bytes.multicast::cluster [%0], [%1, {%3, %4, %5}], [%2], %6;"
    ::"r"(dst), "l"(m), "r"(bar), "r"(c0), "r"(c1), "r"(c2), "h"((uint16_t)3) : "memory");
}
__device__ __forceinline__ void tma2d_store(const CUtensorMap* m, uint32_t src, int c0, int c1) {
  asm volatile("cp.async.bulk.tensor.2d.global.shared::cta.bulk_group [%0, {%2, %3}], [%1];" ::"l"(m), "r"(src), "r"(c0), "r"(c1) : "memory");
}
__device__ __forceinline__ void bulk_ld(uint32_t dst, const void* src, uint32_t bytes, uint32_t bar) {
  asm volatile("cp.async.bulk.shared::cluster.global.mbarrier::complete_tx::bytes [%0], [%1], %2, [%3];" ::"r"(dst), "l"(src), "r"(bytes), "r"(bar) : "memory");
}
__device__ __forceinline__ void bulk_ld_mc(uint32_t dst, const void* src, uint32_t bytes, uint32_t bar) {
  asm volatile("cp.async.bulk.shared::cluster.global.mbarrier::complete_tx::bytes.multicast::cluster [%0], [%1], %2, [%3], %4;"
    ::"r"(dst), "l"(src), "r"(bytes), "r"(bar), "h"((uint16_t)3) : "memory");
}
__device__ __forceinline__ void bulk_st(void* dst, uint32_t src, uint32_t bytes) {
  asm volatile("cp.async.bulk.global.shared::cta.bulk_group [%0], [%1], %2;" ::"l"(dst), "r"(src), "r"(bytes) : "memory");
}
__device__ __forceinline__ void bulk_commit() { asm volatile("cp.async.bulk.commit_group;" ::: "memory"); }
__device__ __forceinline__ void bulk_wait0() { asm volatile("cp.async.bulk.wait_group 0;" ::: "memory"); }
__device__ __forceinline__ void fence_async_smem() { asm volatile("fence.proxy.async.shared::cta;" ::: "memory"); }
__device__ __forceinline__ void wg_fence() { asm volatile("wgmma.fence.sync.aligned;" ::: "memory"); }
__device__ __forceinline__ void wg_commit() { asm volatile("wgmma.commit_group.sync.aligned;" ::: "memory"); }
template <int N> __device__ __forceinline__ void wg_wait() { asm volatile("wgmma.wait_group.sync.aligned %0;" ::"n"(N) : "memory"); }
template <int R> __device__ __forceinline__ void reg_alloc() { asm volatile("setmaxnreg.inc.sync.aligned.u32 %0;" ::"n"(R)); }
template <int R> __device__ __forceinline__ void reg_dealloc() { asm volatile("setmaxnreg.dec.sync.aligned.u32 %0;" ::"n"(R)); }
__device__ __forceinline__ void cluster_bar() { asm volatile("barrier.cluster.arrive.relaxed;\nbarrier.cluster.wait;" ::: "memory"); }
template <int ID> __device__ __forceinline__ void nb_sync(int n) { asm volatile("barrier.sync %0, %1;" ::"n"(ID), "r"(n) : "memory"); }
template <int ID> __device__ __forceinline__ void nb_arrive(int n) { asm volatile("barrier.arrive %0, %1;" ::"n"(ID), "r"(n) : "memory"); }
__device__ __forceinline__ int fresh_tid() { int t; asm volatile("mov.u32 %0, %%tid.x;" : "=r"(t)); return t; }
__device__ __forceinline__ void sched_fence(uint32_t z) { asm volatile("{\n.reg .pred p;\nsetp.ne.u32 p, %0, 0;\nLAB_S:\n@p nanosleep.u32 0;\n@p bra LAB_S;\n}\n" ::"r"(z) : "memory"); }
__device__ __forceinline__ float rsq(float x) { float y; asm("rsqrt.approx.ftz.f32 %0, %1;" : "=f"(y) : "f"(x)); return y; }
__device__ __forceinline__ int opq(int v) { asm volatile("" : "+r"(v)); return v; }
template <int V> struct Int { static constexpr int value = V; };
struct True { static constexpr bool value = true; };
struct False { static constexpr bool value = false; };
template <int N> __device__ __forceinline__ void fence_regs(float (&d)[N]) {
#pragma unroll
  for (int i = 0; i < N; i++) asm volatile("" : "+f"(d[i])::"memory");
}
__host__ __device__ constexpr uint32_t DI(uint32_t off, uint32_t lbo) { return (off >> 4) + ((lbo >> 4) << 16); }
template <int K, int N, class F> __device__ __forceinline__ void static_for(F f) { if constexpr (K < N) { f(Int<K>{}); static_for<K + 1, N>(f); } }
__device__ __forceinline__ uint64_t mkdesc_vec(uint32_t addr, uint32_t sbo) { return (uint64_t)((addr & 0x3FFFF) >> 4) | ((uint64_t)(sbo >> 4) << 32); }
__device__ __forceinline__ void sts16(uint32_t a, uint32_t v) { asm volatile("st.shared.u16 [%0], %1;" ::"r"(a), "h"((uint16_t)v) : "memory"); }
__device__ __forceinline__ uint32_t pack2(float lo, float hi) { uint32_t r; asm("cvt.rn.bf16x2.f32 %0, %1, %2;" : "=r"(r) : "f"(hi), "f"(lo)); return r; }
__device__ __forceinline__ float bf_lo(uint32_t v) { return __uint_as_float(v << 16); }
__device__ __forceinline__ float bf_hi(uint32_t v) { return __uint_as_float(v & 0xffff0000u); }
__device__ __forceinline__ void stsm4(uint32_t a, uint32_t r0, uint32_t r1, uint32_t r2, uint32_t r3) {
  asm volatile("stmatrix.sync.aligned.m8n8.x4.shared.b16 [%0], {%1, %2, %3, %4};" ::"r"(a), "r"(r0), "r"(r1), "r"(r2), "r"(r3) : "memory");
}
__device__ __forceinline__ void stsm4t(uint32_t a, uint32_t r0, uint32_t r1, uint32_t r2, uint32_t r3) {
  asm volatile("stmatrix.sync.aligned.m8n8.x4.trans.shared.b16 [%0], {%1, %2, %3, %4};" ::"r"(a), "r"(r0), "r"(r1), "r"(r2), "r"(r3) : "memory");
}
__device__ __forceinline__ void ldsm4(uint32_t a, uint32_t& r0, uint32_t& r1, uint32_t& r2, uint32_t& r3) {
  asm volatile("ldmatrix.sync.aligned.m8n8.x4.shared.b16 {%0, %1, %2, %3}, [%4];" : "=r"(r0), "=r"(r1), "=r"(r2), "=r"(r3) : "r"(a) : "memory");
}
__device__ __forceinline__ void ldsm4t(uint32_t a, uint32_t& r0, uint32_t& r1, uint32_t& r2, uint32_t& r3) {
  asm volatile("ldmatrix.sync.aligned.m8n8.x4.trans.shared.b16 {%0, %1, %2, %3}, [%4];" : "=r"(r0), "=r"(r1), "=r"(r2), "=r"(r3) : "r"(a) : "memory");
}
__device__ __forceinline__ void mma16816(float (&c)[4], uint32_t a0, uint32_t a1, uint32_t a2, uint32_t a3, uint32_t b0, uint32_t b1) {
  asm volatile("mma.sync.aligned.m16n8k16.row.col.f32.bf16.bf16.f32 {%0, %1, %2, %3}, {%4, %5, %6, %7}, {%8, %9}, {%10, %11, %12, %13};"
    : "=f"(c[0]), "=f"(c[1]), "=f"(c[2]), "=f"(c[3]) : "r"(a0), "r"(a1), "r"(a2), "r"(a3), "r"(b0), "r"(b1), "f"(c[0]), "f"(c[1]), "f"(c[2]), "f"(c[3]));
}
__device__ __forceinline__ void sts128(uint32_t a, uint32_t r0, uint32_t r1, uint32_t r2, uint32_t r3) {
  asm volatile("st.shared.v4.b32 [%0], {%1, %2, %3, %4};" ::"r"(a), "r"(r0), "r"(r1), "r"(r2), "r"(r3) : "memory");
}
__device__ __forceinline__ void lds128(uint32_t a, uint32_t& r0, uint32_t& r1, uint32_t& r2, uint32_t& r3) {
  asm volatile("ld.shared.v4.b32 {%0, %1, %2, %3}, [%4];" : "=r"(r0), "=r"(r1), "=r"(r2), "=r"(r3) : "r"(a) : "memory");
}
__device__ __forceinline__ float2 lds64f(uint32_t a) { float2 v; asm volatile("ld.shared.v2.f32 {%0, %1}, [%2];" : "=f"(v.x), "=f"(v.y) : "r"(a) : "memory"); return v; }
__device__ __forceinline__ float4 lds128f(uint32_t a) { float4 v; asm volatile("ld.shared.v4.f32 {%0, %1, %2, %3}, [%4];" : "=f"(v.x), "=f"(v.y), "=f"(v.z), "=f"(v.w) : "r"(a) : "memory"); return v; }
__device__ __forceinline__ void sts64f(uint32_t a, float x, float y) { asm volatile("st.shared.v2.f32 [%0], {%1, %2};" ::"r"(a), "f"(x), "f"(y) : "memory"); }
__device__ __forceinline__ float lds32f(uint32_t a) { float v; asm volatile("ld.shared.f32 %0, [%1];" : "=f"(v) : "r"(a) : "memory"); return v; }
__device__ __forceinline__ void sts32f(uint32_t a, float x) { asm volatile("st.shared.f32 [%0], %1;" ::"r"(a), "f"(x) : "memory"); }
__device__ __forceinline__ void stat_st(uint2* p, float sum, float sq, uint32_t tag, bool on) {
  const float mean = sum * (1.f / 128), m2 = fmaxf(fmaf(-mean, sum, sq), 0.f);
  const uint32_t a = ((__float_as_uint(mean) + 8u) & ~15u) | (tag & 15u), b = ((__float_as_uint(m2) + 8u) & ~15u) | (tag & 15u);
  asm volatile("{\n.reg .b64 x;\n.reg .pred p;\nsetp.ne.u32 p, %3, 0;\nmov.b64 x, {%1, %2};\n@p st.relaxed.gpu.global.b64 [%0], x;\n}\n" ::"l"(p), "r"(a), "r"(b), "r"((uint32_t)on) : "memory");
}
__device__ __forceinline__ void stat_ld2(const uint2* p, uint32_t (&v)[4]) {
  asm volatile("{\n.reg .b64 x, y;\nld.relaxed.gpu.global.v2.b64 {x, y}, [%4];\nmov.b64 {%0, %1}, x;\nmov.b64 {%2, %3}, y;\n}\n"
    : "=r"(v[0]), "=r"(v[1]), "=r"(v[2]), "=r"(v[3]) : "l"(p) : "memory");
}
__device__ __forceinline__ float untag(uint32_t v) { return __uint_as_float(v & ~15u); }
__device__ __forceinline__ void ll_st3(uint4* p, uint32_t a, uint32_t b, uint32_t c, uint32_t tag) {
  asm volatile("{\n.reg .b64 x, y;\n.reg .b128 z;\nmov.b64 x, {%1, %2};\nmov.b64 y, {%3, %4};\nmov.b128 z, {x, y};\nst.relaxed.gpu.global.b128 [%0], z;\n}\n"
    ::"l"(p), "r"(a), "r"(b), "r"(c), "r"(tag) : "memory");
}
__device__ __forceinline__ uint32_t ll_ld3(const uint4* p, uint32_t& a, uint32_t& b, uint32_t& c, uint32_t tag) {
  uint32_t t;
  asm volatile("{\n.reg .b64 x, y;\n.reg .b128 z;\nld.relaxed.gpu.global.b128 z, [%4];\nmov.b128 {x, y}, z;\nmov.b64 {%0, %1}, x;\nmov.b64 {%2, %3}, y;\n}\n"
    : "=r"(a), "=r"(b), "=r"(c), "=r"(t) : "l"(p) : "memory");
  return t ^ tag;
}
__device__ __forceinline__ void halo_send(uint4* p, uint32_t a, const uint32_t (&tg)[6]) {
  asm volatile("{\n.reg .b64 x<6>, y<6>, w<2>;\n.reg .b32 c<4>;\n.reg .b128 z<6>;\n"
    "ld.shared.b64 w0, [%1+1536];\nld.shared.b64 w1, [%1+1792];\n"
    "ld.shared.b64 x0, [%1];\nld.shared.b64 x1, [%1+256];\nld.shared.b64 x2, [%1+512];\n"
    "ld.shared.b64 x3, [%1+768];\nld.shared.b64 x4, [%1+1024];\nld.shared.b64 x5, [%1+1280];\n"
    "mov.b64 {c0, c1}, w0;\nmov.b64 {c2, c3}, w1;\n"
    "mov.b64 y0, {c0, %2};\nmov.b64 y1, {c1, %3};\nmov.b64 y2, {c2, %4};\nmov.b64 y3, {c3, %5};\nmov.b64 y4, {%6, %6};\nmov.b64 y5, {%7, %7};\n"
    "mov.b128 z0, {x0, y0};\nmov.b128 z1, {x1, y1};\nmov.b128 z2, {x2, y2};\nmov.b128 z3, {x3, y3};\nmov.b128 z4, {x4, y4};\nmov.b128 z5, {x5, y5};\n"
    "st.relaxed.gpu.global.b128 [%0], z0;\nst.relaxed.gpu.global.b128 [%0+512], z1;\nst.relaxed.gpu.global.b128 [%0+1024], z2;\n"
    "st.relaxed.gpu.global.b128 [%0+1536], z3;\nst.relaxed.gpu.global.b128 [%0+2048], z4;\nst.relaxed.gpu.global.b128 [%0+2560], z5;\n}\n"
    ::"l"(p), "r"(a), "r"(tg[0]), "r"(tg[1]), "r"(tg[2]), "r"(tg[3]), "r"(tg[4]), "r"(tg[5]) : "memory");
}
template <int N> __device__ __forceinline__ void copy_out(uint8_t* dst, uint32_t src, int stride) {
  uint4 v[N];
#pragma unroll
  for (int k = 0; k < N; k++) lds128(src + k * stride, v[k].x, v[k].y, v[k].z, v[k].w);
#pragma unroll
  for (int k = 0; k < N; k++) asm volatile("st.global.v4.b32 [%0], {%1, %2, %3, %4};" ::"l"(dst + k * stride), "r"(v[k].x), "r"(v[k].y), "r"(v[k].z), "r"(v[k].w) : "memory");
}
__device__ __forceinline__ void warp_store(uint8_t* dst, uint32_t src, int bytes, uint32_t delay, uint32_t pace) {
  __nanosleep(delay);
#pragma unroll 1
  for (int o = 0; o < bytes; o += 2048) {
    if (pace) __nanosleep(pace);
    uint4 v[4];
#pragma unroll
    for (int k = 0; k < 4; k++) lds128(src + o + k * 512, v[k].x, v[k].y, v[k].z, v[k].w);
#pragma unroll
    for (int k = 0; k < 4; k++) asm volatile("st.global.v4.b32 [%0], {%1, %2, %3, %4};" ::"l"(dst + o + k * 512), "r"(v[k].x), "r"(v[k].y), "r"(v[k].z), "r"(v[k].w) : "memory");
  }
  __syncwarp();
}
__device__ __forceinline__ uint32_t clock32() { uint32_t t; asm volatile("mov.u32 %0, %%clock;" : "=r"(t)); return t; }
__device__ __forceinline__ void flag_set(uint32_t* p, uint32_t bit) { asm volatile("red.release.gpu.global.xor.b32 [%0], %1;" ::"l"(p), "r"(bit) : "memory"); }
__device__ __forceinline__ void flag_wait(const uint32_t* p, uint32_t inv, uint32_t need, uint32_t& ready) {
  if ((ready & need) == need) return;
  uint32_t n = 0;
  do {
    asm volatile("ld.relaxed.gpu.global.b32 %0, [%1];" : "=r"(ready) : "l"(p) : "memory");
    ready = __shfl_sync(0xffffffffu, ready, 0) ^ inv;
  } while ((ready & need) != need && ++n < SPIN_MAX);
  asm volatile("fence.acquire.gpu;\nfence.proxy.async.global;" ::: "memory");
}
__device__ __forceinline__ bool elect_one() {
  uint32_t p;
  asm volatile("{\n.reg .pred P;\nelect.sync _|P, 0xffffffff;\nselp.u32 %0, 1, 0, P;\n}\n" : "=r"(p));
  return p;
}
__device__ __forceinline__ float gelu_half(float hx) {
  const float y = hx * fmaf(hx * hx, 8.f * 0.0356774081f, 2.f * 0.7978845608f);
  float th;
  asm("tanh.approx.f32 %0, %1;" : "=f"(th) : "f"(y));
  return fmaf(hx, th, hx);
}
__device__ __forceinline__ float ex2(float x) { float y; asm("ex2.approx.ftz.f32 %0, %1;" : "=f"(y) : "f"(x)); return y; }

__device__ __forceinline__ void stat_combine(uint32_t am, uint32_t aq, uint32_t bm, uint32_t bq, float pv, float& mean, float& var) {
  const float d0 = untag(am) - pv, d1 = untag(bm) - pv;
  float s = d0 + d1, q = fmaf(fmaf(d0, d0, d1 * d1), 128.f, untag(aq) + untag(bq));
  s += __shfl_xor_sync(0xffffffffu, s, 8); q += __shfl_xor_sync(0xffffffffu, q, 8);
  s += __shfl_xor_sync(0xffffffffu, s, 16); q += __shfl_xor_sync(0xffffffffu, q, 16);
  s *= 0.125f;
  mean = pv + s;
  var = fmaxf(fmaf(-s, s, q * (1.f / D_)), 0.f);
}

__device__ __forceinline__ void attn_probs(const uint32_t* q0, const uint32_t* q1,
                                           const uint32_t* k0, const uint32_t* k1, const uint32_t* k2, const uint32_t* k3,
                                           float sc0, float sc1, float mk0, float mk1, bool e, bool zneg, const uint32_t (&sel)[3],
                                           uint32_t (&pr)[6], float (&l)[2]) {
  float s[4][4];
#pragma unroll
  for (int n = 0; n < 4; n++) {
    const uint32_t* k = n == 0 ? k0 : n == 1 ? k1 : n == 2 ? k2 : k3;
    s[n][0] = s[n][1] = n < 2 ? mk0 : 0.f; s[n][2] = s[n][3] = n < 2 ? mk1 : 0.f;
    mma16816(s[n], q0[0], q1[0], q0[1], q1[1], k[0], k[1]);
    mma16816(s[n], q0[2], q1[2], q0[3], q1[3], k[2], k[3]);
  }
  float a0 = e ? s[1][1] : s[1][0];
  float b0 = zneg ? (e ? s[0][1] : s[0][0]) : (e ? s[2][1] : s[2][0]);
  float a1 = e ? s[2][3] : s[2][2];
  float b1 = zneg ? (e ? s[1][3] : s[1][2]) : (e ? s[3][3] : s[3][2]);
  float m0 = fmaxf(a0, b0), m1 = fmaxf(a1, b1);
  m0 = fmaxf(m0, __shfl_xor_sync(0xffffffffu, m0, 1)); m1 = fmaxf(m1, __shfl_xor_sync(0xffffffffu, m1, 1));
  m0 = fmaxf(m0, __shfl_xor_sync(0xffffffffu, m0, 2)); m1 = fmaxf(m1, __shfl_xor_sync(0xffffffffu, m1, 2));
  a0 = ex2((a0 - m0) * sc0); b0 = ex2((b0 - m0) * sc0); a1 = ex2((a1 - m1) * sc1); b1 = ex2((b1 - m1) * sc1);
  l[0] = a0 + b0; l[1] = a1 + b1;
  const uint32_t p0 = pack2(a0, b0), p1 = pack2(a1, b1);
#pragma unroll
  for (int k = 0; k < 3; k++) { pr[k] = __byte_perm(p0, 0u, sel[k]); pr[3 + k] = __byte_perm(p1, 0u, sel[k]); }
}
__device__ __forceinline__ void attn_pv(const uint32_t (&pr)[6], const uint32_t* vh, const uint32_t* v, float (&o)[4][4]) {
#pragma unroll
  for (int dt = 0; dt < 4; dt++) {
    o[dt][0] = o[dt][1] = o[dt][2] = o[dt][3] = 0.f;
    mma16816(o[dt], pr[0], 0u, pr[1], pr[3], vh[2 * dt], vh[2 * dt + 1]);
    mma16816(o[dt], pr[2], pr[4], 0u, pr[5], v[2 * dt], v[2 * dt + 1]);
  }
}

#define ATT 24
#define COVER 2
#define HALO_A_NS 300
#define H1D 900
#define POLITE 0
#define G4GATE 9
#define PFM 7
#define PD1 3
#define PD2 5
#define PD3 3
#define PD4 5
#define U0D 300
#define X1D 1200
#define PACE 150
#define LEAD1 3
#define LEAD2 3
#define XLD 7
#define XST 3
#define FA 20
#define LEAD4 4
#define STAT_CLK 150
__global__ void __cluster_dims__(2, 1, 1) __launch_bounds__(384, 1) fused_kernel(const __grid_constant__ Params P) {
  extern __shared__ __align__(1024) uint8_t smem_raw[];
  const uint32_t sb = smem_u32(smem_raw);
  const uint32_t bars = sb + OFF_BAR;
  const int tid = threadIdx.x;
  const int wu = __shfl_sync(0xffffffffu, tid >> 5, 0), wg = wu >> 2;
  const int r = blockIdx.x & 1, cl = blockIdx.x >> 1;
  int grp, slt;
  if (cl < 4) { grp = 0; slt = 4 + cl; }
  else if (cl < 36) { grp = (cl - 4) & 7; slt = (cl - 4) >> 3; }
  else { grp = 1 + (cl - 36) % 7; slt = 4 + (cl - 36) / 7; }
#define MAP 0
  const int m = grp, j = slt;
  const int i = 2 * m + r;
  auto BAR = [&](int k) { return bars + 8 * k; };

  auto kb1 = [&](int n) { const int h = n >= 9, t = n - 2 - 7 * h; return n < 2 ? 2 * j + n : 2 * (t + (t >= j)) + h; };
  if (wu == 8) {
    if (elect_one()) {
      asm volatile("prefetch.tensormap [%0];" ::"l"(&P.x0) : "memory");
      asm volatile("prefetch.tensormap [%0];" ::"l"(&P.wqkv) : "memory");
#pragma unroll
      for (int k = 0; k < 6; k++) mbar_init(BAR(k < 4 ? F1 + k : XF + k - 4), 1);
      asm volatile("fence.mbarrier_init.release.cluster;" ::: "memory");
      fence_async_smem();
    }
    __syncwarp();
  } else if (wu == 0) {
    if (elect_one()) {
#pragma unroll
      for (int k = E1; k < 64; k++) {
        int cnt = 1;
        if (k < F2 || (k >= E2 && k < F3) || (k >= E3 && k < F4) || (k >= E4 && k < JOB) || k == JOB + 2 || k == JOB + 3) cnt = 4;
        else if ((k >= JOB && k < RD) || k == CSJ) cnt = 8;
        else if ((k >= RD && k < RD + 2) || k == STD || k == STAT || k >= HALO) cnt = 2;
        if (k != XF && k != XF + 1) mbar_init(BAR(k), cnt);
      }
      asm volatile("fence.mbarrier_init.release.cluster;" ::: "memory");
      fence_async_smem();
    }
    __syncwarp();
  }
  auto load_tag = [&]() { uint32_t t; asm volatile("ld.relaxed.gpu.global.u32 %0, [%1];" : "=r"(t) : "l"(&gEpoch) : "memory"); return t + 1; };
  TS(0);
  if (wu == 8) nb_arrive<NB_INIT>(384); else nb_sync<NB_INIT>(384);
  asm volatile("barrier.cluster.arrive.relaxed;" ::: "memory");

  if (wg == 2) {
    reg_dealloc<40>();
    if (wu == 8) {
    if (elect_one()) {
#pragma unroll 1
      for (int u = 0; u < 4; u++) {
        const int kb = u;
        mbar_expect(BAR(F1 + u), 40960);
        tma2d(sb + slot1(u), &P.x0, BAR(F1 + u), kb * 64, 128 * i);
        tma3d(sb + slot1(u) + 16384, &P.wqkv, BAR(F1 + u), 128 * j, kb * 64, 0);
        tma3d(sb + slot1(u) + 28672, &P.wqkv, BAR(F1 + u), 128 * j, kb * 64 + 32, 0);
      }
    }
    __syncwarp();
    }
    asm volatile("barrier.cluster.wait;" ::: "memory");
    auto kb3 = [&](int n) { const int h = n >= 17, t = n - 2 - 15 * h; return n < 2 ? 2 * i + n : t == 14 ? 2 * (i ^ 1) + h : 2 * ((2 * m + 2 + t) & 15) + h; };
    auto kb2 = [&](int n) { return n < 8 ? 2 * n : n == 8 ? 2 * j + 1 : 2 * (n - 9 + (n - 9 >= j)) + 1; };
    if (wu == 8) {
      const int lane = tid & 31;
      auto pf = [&](const bf16* p, bool on) { if (on) asm volatile("prefetch.global.L2 [%0];" ::"l"(p)); };
      auto v1 = [&](int L, int u) { return (L && u >= 2 && u < 18) ? (u < 4 ? u + 14 : u - 2) : u; };
      auto k1 = [&](int L, int v) { return (L || v >= 16) ? kb1(v & 15) : v; };
      auto kb4f = [&](int n) {
        const int q = n ? n - 8 : 0, c = q >> 4, t = (q & 15) - 1, ii = t < 0 ? i : t < 14 ? (2 * m + 2 + t) & 15 : i ^ 1;
        return (n >= 1 && n <= 8) ? 7 * ((m + n) & 7) + 3 : ((7 * ii + 1) >> 1) + c;
      };
      const uint32_t tab4 = kb4f(lane) | (kb4f(lane + 32) << 16);
      auto kb4 = [&](int n) { return (int)((__shfl_sync(0xffffffffu, tab4, n) >> ((n >> 1) & 16)) & 63); };
      const bf16* const q1 = P.wqkv_p + (4 * i + (lane & 3)) * 3072 + (lane >> 2) * 1024 + 128 * j;
      const bf16* const q2 = P.wo_p + (4 * i + (lane & 3)) * 1024 + (lane >> 2) * 64 + 128 * j;
      const bf16* const q3 = P.w1_p + (8 * j + (lane >> 2)) * 3584 + 64 * (7 * m + ((lane & 3) == 3 ? 3 : 4 * r + (lane & 3)));
      const bf16* const q4 = P.w2_p + (8 * j + (lane >> 1)) * 2048 + 128 * i + 64 * (lane & 1);
      auto pf1 = [&](int L, int u) { const int v = v1(L, u); pf(q1 + k1(L, v) * (64 * 3072) + 64 * (v >> 4), (PFM & 1) && lane < 12); };
      auto pf2 = [&](int n) { pf(q2 + kb2(n) * (64 * 1024), (PFM & 2) && lane < 8); };
      auto pf3 = [&](int n) { pf(q3 + kb3(n) * (64 * 3584), PFM & 4); };
      auto pf4 = [&](int n) { pf(q4 + kb4(n) * (64 * 2048), (PFM & 8) && lane < 16); };
#pragma unroll 1
      for (int u = 4; u < 4 + PD1; u++) pf1(0, u);
#pragma unroll 1
      for (int L = 0; L < 2; L++) {
#pragma unroll 1
        for (int u = L ? 0 : 4; u < 32; u++) {
          const int v = v1(L, u), p = u & 3;
          if (u >= 4) mbar_wait(BAR(E1 + p), ((u >> 2) - 1) & 1);
          else mbar_wait(BAR(E4 + (u == 3 ? 0 : u + 3)), u == 3);
          if (elect_one()) {
            mbar_expect(BAR(F1 + p), (v & 15) < 2 ? 24576 : 40960);
            tma3d_mc(sb + slot1(p) + 16384 + r * 12288, &P.wqkv, BAR(F1 + p), 128 * j + 64 * (v >> 4), k1(L, v) * 64 + 32 * r, 0);
          }
          if (u + PD1 < 32) pf1(L, u + PD1);
          if (u + PD2 >= 32) pf2(u + PD2 - 32);
        }
        int p = 0; uint32_t par = L ? 0x1e : 0;
#pragma unroll 1
        for (int n = 0; n < 16; n++) {
          if (n >= 5) { mbar_wait(BAR(E2 + p), (par >> p) & 1); par ^= 1u << p; }
          else if (n < 4) mbar_wait(BAR(E1 + n), 1);
          if (elect_one()) {
            mbar_expect(BAR(F2 + p), n == 8 ? 16384 : 32768);
            tma2d_mc(sb + slot2(p) + 16384 + r * 8192, &P.wo, BAR(F2 + p), 128 * j + 64 * r, kb2(n) * 64);
          }
          if (++p == 5) p = 0;
          if (n + PD2 < 16) pf2(n + PD2);
          if (n + PD3 + 4 >= 16) pf3(n + PD3 + 4 - 16);
        }
#pragma unroll 1
        for (int u = 0; u < 32; u++) {
          const int n = u < 4 ? (0x2031 >> (4 * u)) & 3 : u, p = n & 3, kb = kb3(n);
          if (n == 4) mbar_wait(BAR(RD + 4), L);
          if (n >= 4) mbar_wait(BAR(E3 + p), ((n >> 2) - 1) & 1);
          else if (n == 1) mbar_wait(BAR(STD + 1), L);
          else if (n == 3) mbar_wait(BAR(E2 + 2), L);
          else if (n == 0) mbar_wait(BAR(E2 + 4), L);
          else mbar_wait(BAR(E2 + 0), 1);
          if (elect_one()) {
            mbar_expect(BAR(F3 + p), n < 2 ? 32768 : 49152);
            tma3d(sb + slot3(p) + 16384, &P.w1, BAR(F3 + p), 0, kb * 64, 7 * m + 4 * r);
            tma3d(sb + slot3(p) + 40960, &P.w1h, BAR(F3 + p), 0, kb * 64, 14 * m + 6 + r);
          }
          if (u >= 4 && u + PD3 < 32) pf3(u + PD3);
          if (u + PD4 + 6 >= 32) pf4(u + PD4 + 6 - 32);
        }
        auto g4w = [&](int n, int p, int kb) {
          if (elect_one()) {
            mbar_expect(BAR(F4 + p), (n == 0 || n == 24 || n == 40) ? 16384 : 32768);
            tma3d(sb + slot4(p), &P.w2, BAR(F4 + p), 0, kb * 64, 2 * i);
          }
        };
#pragma unroll 1
        for (int n = 0; n < 6; n++) {
          const int kb = kb4(n);
          if (n == G4GATE) mbar_wait(BAR(RD + 3), L);
          if (n < 3) mbar_wait(BAR(E3 + n), 1);
          else if (n == 4) mbar_wait(BAR(E3 + 3), 1);
          g4w(n, n, kb);
        }
        p = 0; par = L ? 0x3c : 0;
#pragma unroll 1
        for (int n = 6; n < 56; n++) {
          const int kb = kb4(n);
          if (n + PD4 < 56) pf4(n + PD4);
          mbar_wait(BAR(E4 + p), (par >> p) & 1); par ^= 1u << p;
          g4w(n, p, kb);
          if (++p == 6) p = 0;
        }
        if (L == 0)
#pragma unroll 1
          for (int u = 0; u < PD1; u++) pf1(1, u);
      }
    } else if (wu == 9) {
      uint32_t inv = 0;
#pragma unroll 1
      for (int L = 0; L < 2; L++) {
        uint32_t ready = 0;
#pragma unroll 1
        for (int u = 4; u < 32; u++) {
          const int p = u & 3, nn = (L && u < 18 ? u - 2 : u) & 15, kb = (L || u >= 16) ? kb1(nn) : nn;
          if (L == 0 && (u == XLD || u == XLD + XST) && elect_one()) {
            const int h = u != XLD;
            mbar_expect(BAR(XF + h), 16384);
            tma2d(sb + OFF_X + h * 16384, &P.x0, BAR(XF + h), 128 * j + 64 * h, 128 * i);
          }
          if (nn < 2) continue;
          if (L && u < 12) mbar_wait(BAR(F1 + p), u >> 3);
          if (u >= 4 + 4 * L) mbar_wait(BAR(E1 + p), ((u >> 2) - 1) & 1);
          if (L) {
            flag_wait(gFlag[0][0][i], inv, 1u << kb, ready);
            if (elect_one()) bulk_ld(sb + slot1(p), gXB + (i * 16 + kb) * 16384, 16384, BAR(F1 + p));
          } else if (elect_one()) tma2d(sb + slot1(p), &P.x0, BAR(F1 + p), kb * 64, 128 * i);
        }
        ready = 0;
        if (L == 0) inv = (__shfl_sync(0xffffffffu, load_tag(), 0) & 1) - 1;
        int p = 0; uint32_t par = L ? 0x1e : 0;
#pragma unroll 1
        for (int n = 0; n < 16; n++) {
          const int hp = kb2(n);
          if (n == 8) { par ^= 8; p = 4; continue; }
          if (n >= 5) { mbar_wait(BAR(E2 + p), (par >> p) & 1); par ^= 1u << p; }
          else if (n < 4) mbar_wait(BAR(E1 + n), 1);
          flag_wait(gFlag[L][1][i], inv, 1u << hp, ready);
          if (n == 9) ST(4);
          if (elect_one()) bulk_ld(sb + slot2(p), gOB + (i * 16 + hp) * 16384, 16384, BAR(F2 + p));
          if (++p == 5) p = 0;
        }
        ready = 0;
        mbar_wait(BAR(E2 + 0), 1);
#pragma unroll 1
        for (int n = 2; n < 32; n++) {
          const int p = n & 3, kb = kb3(n);
          if (n > 3) mbar_wait(BAR(E3 + p), ((n >> 2) - 1) & 1);
          flag_wait(gFlag[L][2][j], inv, 1u << kb, ready);
          if (n == 2) ST(12);
          if (elect_one()) {
            const uint8_t* src = gHB + (j * 32 + kb) * 16384;
            if (n != 16 && n != 31) bulk_ld_mc(sb + slot3(p) + r * 8192, src + r * 8192, 8192, BAR(F3 + p));
            else bulk_ld(sb + slot3(p), src, 16384, BAR(F3 + p));
          }
        }
        ready = 0; p = 1; par = L ? 0x3c : 0;
#pragma unroll 1
        for (int t = 0; t < 8; t++) {
          const int mm = (m + t + 1) & 7;
          if (t < 3) mbar_wait(BAR(E3 + 1 + t), 1);
          if (t >= 5) { mbar_wait(BAR(E4 + p), (par >> p) & 1); par ^= 1u << p; }
          flag_wait(gFlag[L][6][j], inv, 3u << (2 * mm), ready);
          if (t == 0) ST(20);
          if (elect_one()) bulk_ld_mc(sb + slot4(p) + 16384 + r * 8192, gUB + (j * 56 + 48 + mm) * 16384 + r * 8192, 8192, BAR(F4 + p));
          if (++p == 6) p = 0;
        }
#pragma unroll 1
        for (int c = 0; c < 3; c++) {
          ready = 0;
          if (c) { par ^= 1u << p; if (++p == 6) p = 0; }
#pragma unroll 1
          for (int t = 0; t < 15; t++) {
            const int ii = t < 14 ? (2 * m + 2 + t) & 15 : i ^ 1;
            mbar_wait(BAR(E4 + p), (par >> p) & 1); par ^= 1u << p;
            flag_wait(gFlag[L][3 + c][j], inv, 1u << ii, ready);
            if (elect_one()) {
              const uint8_t* src = gUB + (j * 56 + 16 * c + ii) * 16384;
              if (t < 14) bulk_ld_mc(sb + slot4(p) + 16384 + r * 8192, src + r * 8192, 8192, BAR(F4 + p));
              else bulk_ld(sb + slot4(p) + 16384, src, 16384, BAR(F4 + p));
            }
            if (++p == 6) p = 0;
          }
        }
      }
    } else {
      const int h = wu - 10, i0 = i, j0 = j;
      {
      const uint32_t tag = load_tag();
      int lane = tid & 31, i = i0, j = j0;
#define FRESH asm volatile("" : "+r"(lane), "+r"(i), "+r"(j))
      auto signal = [&](int k) { if (lane == 0) mbar_arrive(BAR(k)); };
      auto publish = [&](uint32_t* f, int bit) { if (lane == 0) flag_set(f, 1u << bit); __syncwarp(); };
      for (int c = 32 * h + lane; c < 288; c += 64)
        sts16(sb + OFF_B1 + 2 * c, c >= 224 ? 0u : pack2(0.5f * __bfloat162float(P.b1[c < 192 ? 64 * (7 * m + 4 * r) + c : 64 * (7 * m + 3) + 32 * r + c - 192]), 0.f));
      if (h == 0) sts32f(sb + OFF_CS + 768 + 4 * lane, 0.f);
#pragma unroll 1
      for (int L = 0; L < 2; L++) {
        FRESH;
        if (L == 0) {
          mbar_wait(BAR(CSJ), 0);
          float c0 = 0.f, c1 = 0.f, c2 = 0.f;
          const uint32_t a = sb + OFF_STG + (32 * h + lane) * 4;
#pragma unroll 8
          for (int k = 0; k < 32; k++) { c0 += lds32f(a + k * 784); c1 += lds32f(a + k * 784 + 256); c2 += lds32f(a + k * 784 + 512); }
          ll_st3(&gCS[j][i][32 * h + lane], __float_as_uint(c0), __float_as_uint(c1), __float_as_uint(c2), tag);
          __nanosleep(500);
        }
        FRESH;
        if (L == 0) {
#pragma unroll 1
          for (int ab = 0; ab < 2; ab++) {
            float c0 = 0.f, c1 = 0.f, c2 = 0.f;
#pragma unroll 1
            for (int b4 = 0; b4 < 8; b4 += 4) {
              uint32_t a[4], b[4], c[4], n = 0, bad;
              do {
                bad = 0;
#pragma unroll
                for (int e = 0; e < 4; e++) bad |= ll_ld3(&gCS[j][2 * (b4 + e) + ab][32 * h + lane], a[e], b[e], c[e], tag);
              } while (bad && ++n < SPIN_MAX);
#pragma unroll
              for (int e = 0; e < 4; e++) { c0 += __uint_as_float(a[e]); c1 += __uint_as_float(b[e]); c2 += __uint_as_float(c[e]); }
            }
            const uint32_t a = sb + OFF_CS + ab * 768 + (4 * h + (lane >> 3)) * 32 + (lane & 7) * 2;
            const uint32_t h0 = pack2(c0, 0.f), h1 = pack2(c1, 0.f), h2 = pack2(c2, 0.f);
            sts16(a, h0); sts16(a + 256, h1); sts16(a + 512, h2);
            sts16(a + 16, pack2(c0 - bf_lo(h0), 0.f)); sts16(a + 272, pack2(c1 - bf_lo(h1), 0.f)); sts16(a + 528, pack2(c2 - bf_lo(h2), 0.f));
            fence_async_smem();
            __syncwarp();
            if (ab == 0) signal(STAT);
          }
        }
#pragma unroll 1
        for (int ab = 0; ab < 2; ab++) {
          FRESH;
          uint32_t v[18], tg[6];
          const uint32_t xs = sb + OFF_STG + h * 16384 + lane * 8;
          uint4* hp = &gHalo[L][i][j][6 * h][lane];
#pragma unroll
          for (int c = 0; c < 6; c++) { tg[c] = (2 * tag + ab) * 8 + c; asm volatile("" : "+r"(tg[c])); }
          asm volatile("" : "+l"(hp));
          mbar_wait(BAR(FOLD + ab), L);
          if (ab && h == 0) ST(6);
          if (i < 15) {
            halo_send(hp, xs, tg);
          }
          if (ab && h == 0) ST(26);
          if (i > 0) {
            if (!ab) __nanosleep(HALO_A_NS);
            uint32_t n = 0, bad;
            do {
              bad = 0;
#pragma unroll
              for (int c = 0; c < 6; c++) bad |= ll_ld3(hp + c * 32 - 8 * 12 * 32, v[3 * c], v[3 * c + 1], v[3 * c + 2], (2 * tag + ab) * 8);
              if (ab && h == 0 && n == 0) ST(28);
            } while (bad > 7 && ++n < SPIN_MAX);
            if (ab && h == 0) ST(27);
          } else {
#pragma unroll
            for (int c = 0; c < 18; c++) v[c] = 0u;
          }
#pragma unroll
          for (int c = 0; c < 6; c++) sts64f(xs + c * 256, __uint_as_float(v[3 * c]), __uint_as_float(v[3 * c + 1]));
          sts64f(xs + 1536, __uint_as_float(v[2]), __uint_as_float(v[5]));
          sts64f(xs + 1792, __uint_as_float(v[8]), __uint_as_float(v[11]));
          __syncwarp();
          signal(HALO + ab);
          if (ab && h == 0) ST(7);
          FRESH;
          if (ab == 0 && lane == 0) asm volatile("st.relaxed.gpu.global.u32 [%0], %1;" ::"l"(&gAck[L][i][j][h][0]), "r"(tag) : "memory");
          mbar_wait(BAR(JOB + ab), L);
          if (h == 0) {
            if (ab) ST(1);
            if (lane == 0) { bulk_st(gOB + (i * 16 + 2 * j + ab) * 16384, sb + OFF_STG, 16384); bulk_commit(); bulk_wait0(); }
            signal(STD + ab);
            if (ab) ST(2);
            publish(gFlag[L][1][i], 2 * j + ab);
            if (ab) ST(3);
          } else if (ab == 0) {
            if (i < 15 && lane < 2) {
              uint32_t t, n = 0;
              do { asm volatile("ld.relaxed.gpu.global.u32 %0, [%1];" : "=r"(t) : "l"(&gAck[L][i + 1][j][lane][0]) : "memory"); } while (t != tag && ++n < SPIN_MAX);
            }
            __syncwarp();
            signal(STD);
          }
        }
        FRESH;
        if (h == 0) {
          mbar_wait(BAR(JOB + 2), L);
          ST(9);
          signal(RD);
          ST(10);
          publish(gFlag[L][2][j], 2 * i);
          ST(11);
          signal(RD + 4);
          nb_arrive<NB_HELP>(64);
        } else {
          mbar_wait(BAR(JOB + 3), L);
          nb_sync<NB_HELP>(64);
          warp_store(gHB + (j * 32 + 2 * i + 1) * 16384 + lane * 16, sb + lane * 16 + OFF_X + 16384, 16384, H1D, PACE);
          signal(RD);
          ST(15);
          publish(gFlag[L][2][j], 2 * i + 1);
        }
        FRESH;
        if (h == 0) {
          mbar_wait(BAR(JOB + 7), L);
          ST(17);
          publish(gFlag[L][6][j], i);
          ST(19);
          signal(RD + 3);
        } else {
          mbar_wait(BAR(JOB + 4), L);
          __nanosleep(U0D);
          if (lane == 0) { bulk_st(gUB + (j * 56 + i) * 16384, sb + OFF_X, 16384); bulk_commit(); bulk_wait0(); }
          signal(RD + 2); ST(25);
          publish(gFlag[L][3][j], i);
        }
        mbar_wait(BAR(JOB + 5 + h), L);
        warp_store(gUB + (j * 56 + 16 + 16 * h + i) * 16384 + lane * 16, sb + lane * 16 + OFF_X + (1 - h) * 16384, 16384, 0, PACE);
        ST(23 + h);
        signal(RD + 1);
        publish(gFlag[L][4 + h][j], i);
        FRESH;
        if (L == 0) {
          mbar_wait(BAR(JOB + 8 + h), 0);
          if (h == 1) warp_store(gXB + (i * 16 + 2 * j + 1) * 16384 + lane * 16, sb + lane * 16 + OFF_X + 16384, 16384, X1D, 0);
          publish(gFlag[0][0][i], 2 * j + h);
        }
      }
      if (blockIdx.x == 0 && h == 0 && lane == 0) asm volatile("st.relaxed.gpu.global.u32 [%0], %1;" ::"l"(&gEpoch), "r"(tag) : "memory");
      }
    }
    __syncwarp();
    cluster_bar();
  } else {
    reg_alloc<232>();
    asm volatile("barrier.cluster.wait;" ::: "memory");
    const uint32_t rbars = mapa(bars, tid & 1);
    const bool relp = (tid & 127) < 2;
    const uint32_t sd = (sb & 0x3FFFF) >> 4, sda = sd + wg * 512;
    uint32_t tag;
    asm volatile("ld.relaxed.gpu.global.u32 %0, [%1];" : "=r"(tag) : "l"(&gEpoch + (fresh_tid() >> 10)) : "memory");
    auto release = [&](int k) { if (relp) mbar_arrive_cl(rbars + 8 * k); };
    auto signal = [&](int k) { __syncwarp(); if ((fresh_tid() & 31) == 0) mbar_arrive(BAR(k)); };
#define GEOM const int t7 = fresh_tid() & 127, lane = t7 & 31, w = t7 >> 5, g = lane >> 2, q = lane & 3, \
                       lr = lane & 15, lt = lane >> 4, l7 = lane & 7; (void)w; (void)g; (void)q; (void)lr; (void)lt; (void)l7

#pragma unroll 1
    for (int L = 0; L < 2; L++) {
      float acca[96], accb[96], xa[64], acc3[112];
      float nmean0, nmean1, rstd0, rstd1;
      uint16_t b2a, b2b;
      uint2 *e2p, *e2s; uint8_t* e2g; uint32_t e2h;
      uint32_t Q[2][8], K[2][8], V[16];
      auto g1_issue = [&](float (&acc)[96], uint32_t a, uint32_t st, auto first) {
        const uint32_t da = sda + (a >> 4), db = sd + (st >> 4);
        wg_fence();
        static_for<0, 4>([&](auto kk) {
          constexpr uint32_t ia = DI(kk.value * 32, 16), ib = DI(16384 + (kk.value >> 1) * 12288 + (kk.value & 1) * 2048, 4096);
          if constexpr (first.value && kk.value == 0) wgmma_192z<0, 1, ia, ib>(acc, da, db); else wgmma_192<0, 1, ia, ib>(acc, da, db);
        });
        wg_commit();
      };
      auto g1_step = [&](float (&acc)[96], int u, bool rel, bool lead = false) {
        const int p = u & 3;
        mbar_wait(BAR(F1 + p), (u >> 2) & 1);
        KB(u);
        g1_issue(acc, slot1(p), slot1(p), False{});
        if (lead) nb_arrive<NB_LEAD>(256);
        wg_wait<1>();
        if (rel) release(E1 + ((u - 1) & 3));
      };
      auto g1_loop = [&](float (&acc)[96], int u0, int u1, int urel) {
#pragma unroll 1
        for (int u = u0; u < u1; u++) g1_step(acc, u, u > urel);
      };
      auto load_x = [&]() {
        GEOM;
#pragma unroll
        for (int t = 0; t < 16; t += 2) {
          uint32_t v0, v1, v2, v3;
          ldsm4(sb + OFF_X + (t >> 3) * 16384 + (16 * wu + lr) * 128 + ((((t & 7) + lt) ^ l7) << 4), v0, v1, v2, v3);
          xa[4 * t + 0] = bf_lo(v0); xa[4 * t + 1] = bf_hi(v0); xa[4 * t + 2] = bf_lo(v1); xa[4 * t + 3] = bf_hi(v1);
          xa[4 * t + 4] = bf_lo(v2); xa[4 * t + 5] = bf_hi(v2); xa[4 * t + 6] = bf_lo(v3); xa[4 * t + 7] = bf_hi(v3);
        }
      };
      auto stat_base = [&]() { return &gST[0][0][0][0][0] + ((L * 16 + opq(i)) * 8 + wu) * 128; };
      auto stat_slot = [&]() { const int lane = fresh_tid() & 31; return stat_base() + 16 * j + 2 * (lane >> 2) + (lane & 1); };
      auto stat_publish = [&](uint2* sp, float s0, float q0, float s2, float q2, uint32_t tg) {
        const int q = fresh_tid() & 3;
        const bool h1 = q & 1;
        float sm = (h1 ? s2 : s0) + __shfl_xor_sync(0xffffffffu, h1 ? s0 : s2, 1);
        float sq = (h1 ? q2 : q0) + __shfl_xor_sync(0xffffffffu, h1 ? q0 : q2, 1);
        sm += __shfl_xor_sync(0xffffffffu, sm, 2); sq += __shfl_xor_sync(0xffffffffu, sq, 2);
        stat_st(sp, sm, sq, tg, q < 2);
        return sm;
      };
      auto g1_stats = [&](int u0) {
        GEOM;
        const uint32_t xr = sb + OFF_X + (16 * wu + lr) * 128;
        float s0 = 0.f, q0 = 0.f, s2 = 0.f, q2 = 0.f;
        uint32_t v[8] = {0u, 0u, 0u, 0u, 0u, 0u, 0u, 0u};
#pragma unroll 1
        for (int k = 0; k < 5; k++) {
#pragma unroll
          for (int e = 0; e < 8; e += 2) {
            const float a = bf_lo(v[e]), b = bf_hi(v[e]), c = bf_lo(v[e + 1]), d = bf_hi(v[e + 1]);
            s0 += a + b; q0 = fmaf(a, a, fmaf(b, b, q0)); s2 += c + d; q2 = fmaf(c, c, fmaf(d, d, q2));
          }
          if (k == 4) break;
          const uint32_t o = ((2 * k + lt) ^ l7) << 4;
          ldsm4(xr + o, v[0], v[1], v[2], v[3]);
          ldsm4(xr + o + 16384, v[4], v[5], v[6], v[7]);
          g1_step(acca, u0 + k, true);
        }
        stat_publish(stat_slot(), s0, q0, s2, q2, 2 * (tag + 1));
      };
      uint32_t sv0[4], sv1[4];
      auto stat_src = [&]() { return stat_base() + 2 * (fresh_tid() & 31); };
      auto stat_fetch = [&](const uint2* sp) { stat_ld2(sp, sv0); stat_ld2(sp + 64, sv1); };
      auto stat_await = [&](auto src, uint32_t tg) {
#pragma unroll 1
        for (uint32_t n = 0; (((sv0[0] ^ tg) | (sv0[2] ^ tg) | (sv1[0] ^ tg) | (sv1[2] ^ tg)) & 15u) && n < SPIN_MAX; n++) stat_fetch(src());
        __syncwarp();
      };
      auto ln_stats = [&]() {
        GEOM;
        stat_await(stat_src, 2 * (tag + 1));
        float mean0, var0, mean1, var1;
        stat_combine(sv0[0], sv0[1], sv1[0], sv1[1], untag(__shfl_sync(0xffffffffu, sv0[0], l7)), mean0, var0);
        stat_combine(sv0[2], sv0[3], sv1[2], sv1[3], untag(__shfl_sync(0xffffffffu, sv0[2], l7)), mean1, var1);
        nmean0 = -__shfl_sync(0xffffffffu, mean0, g); rstd0 = rsq(__shfl_sync(0xffffffffu, var0, g) + 1e-5f);
        nmean1 = -__shfl_sync(0xffffffffu, mean1, g); rstd1 = rsq(__shfl_sync(0xffffffffu, var1, g) + 1e-5f);
      };
      auto center = [&](float (&acc)[96], int ab) {
        const bool q0 = (fresh_tid() & 3) == 0;
        const uint32_t h0 = pack2(nmean0, nmean0), h1 = pack2(nmean1, nmean1);
        const float l0 = nmean0 - bf_lo(h0), l1 = nmean1 - bf_lo(h1);
        const uint32_t a0 = q0 ? h0 : 0u, a1 = q0 ? h1 : 0u, a2 = q0 ? pack2(l0, l0) : 0u, a3 = q0 ? pack2(l1, l1) : 0u;
        wg_fence();
        wgmma_rs_192(acc, a0, a1, a2, a3, mkdesc_vec(sb + OFF_CS + ab * 768, 32));
      };
      auto frag = [&](float (&acc)[96], int t, uint32_t& p0, uint32_t& p1) {
        if (t >= 8) { p0 = pack2(acc[4 * t] * rstd0, acc[4 * t + 1] * rstd0); p1 = pack2(acc[4 * t + 2] * rstd1, acc[4 * t + 3] * rstd1); }
        else { p0 = pack2(acc[4 * t], acc[4 * t + 1]); p1 = pack2(acc[4 * t + 2], acc[4 * t + 3]); }
      };
      auto fold_v = [&](float (&acc)[96], int t0, int t1) {
        GEOM;
        const uint32_t a = sb + OFF_STG + 16384 + ((wu + 1) & 7) * 2048 + lr * 128;
#pragma unroll
        for (int t = t0; t < t1; t += 2) {
          uint32_t p0, p1, p2, p3;
          frag(acc, 16 + t, p0, p1); frag(acc, 17 + t, p2, p3);
          stsm4(a + (((t + lt) ^ l7) << 4), p0, p1, p2, p3);
        }
        __syncwarp();
#pragma unroll
        for (int t = t0; t < t1; t += 2) ldsm4t(a + (((t + lt) ^ l7) << 4), V[2 * t], V[2 * t + 1], V[2 * t + 2], V[2 * t + 3]);
      };
      auto fold_k = [&](float (&acc)[96], int ab, int h0, int h1) {
        GEOM;
        const uint32_t a = sb + OFF_STG + ((wu + 1) & 7) * 2048 + lane * 16;
#pragma unroll
        for (int hh = h0; hh < h1; hh++) {
#pragma unroll
          for (int t = 4 * hh; t < 4 * hh + 4; t++) frag(acc, 8 + t, K[0][t], K[1][t]);
#pragma unroll
          for (int o = 0; o < 2; o++) sts128(a + (2 * o + hh) * 512, K[o][4 * hh], K[o][4 * hh + 1], K[o][4 * hh + 2], K[o][4 * hh + 3]);
        }
        if (h1 == 2 && wu == 7) signal(FOLD + ab);
      };
      auto fold_q = [&](float (&acc)[96]) {
#pragma unroll
        for (int t = 0; t < 8; t++) frag(acc, t, Q[0][t], Q[1][t]);
      };
      auto attend = [&](int ab, auto drain, auto resume) {
        GEOM;
        nb_sync<NB_BOTH>(256);
        const uint32_t xa_ = sb + OFF_STG + wu * 2048 + lane * 16;
        if (wu == 0) mbar_wait(BAR(HALO + ab), L);
        uint32_t KH[2][8], VH[16];
#pragma unroll
        for (int c = 0; c < 4; c++) {
          lds128(xa_ + c * 512, KH[c >> 1][4 * (c & 1)], KH[c >> 1][4 * (c & 1) + 1], KH[c >> 1][4 * (c & 1) + 2], KH[c >> 1][4 * (c & 1) + 3]);
          ldsm4t(sb + OFF_STG + 16384 + wu * 2048 + lr * 128 + (((2 * c + lt) ^ l7) << 4), VH[4 * c], VH[4 * c + 1], VH[4 * c + 2], VH[4 * c + 3]);
        }
        TS2(11 + ab + 32 * L);
        const bool e = g & 1, zneg = (g >> 1) < q, first = (i == 0) && (wu == 0);
        const float sc0 = rstd0 * (0.17677669530f * 1.4426950409f), sc1 = rstd1 * (0.17677669530f * 1.4426950409f);
        float mk0 = first ? __fdividef(-1.0e9f * 1.4426950409f, sc0) : 0.f, mk1 = first ? __fdividef(-1.0e9f * 1.4426950409f, sc1) : 0.f;
        const uint32_t sa = e ? 0x1044u : 0x4410u, sbb = e ? 0x3244u : 0x4432u;
        uint32_t sel[3] = {zneg ? sbb : 0x4444u, sa, zneg ? 0x4444u : sbb};
        uint32_t oa = sb + OFF_STG + (16 * wu + lr) * 128 + ((lt ^ l7) << 4);
        asm volatile("" : "+r"(sel[0]), "+r"(sel[1]), "+r"(sel[2]), "+r"(oa), "+f"(mk0), "+f"(mk1));
        drain();
        uint32_t pr[2][6];
        float l[2][2];
#pragma unroll
        for (int hh = 0; hh < 2; hh++)
          attn_probs(&Q[0][4 * hh], &Q[1][4 * hh], &KH[0][4 * hh], &KH[1][4 * hh], &K[0][4 * hh], &K[1][4 * hh], sc0, sc1, mk0, mk1, e, zneg, sel, pr[hh], l[hh]);
        float o[2][4][4];
#pragma unroll
        for (int hh = 0; hh < 2; hh++) attn_pv(pr[hh], &VH[8 * hh], &V[8 * hh], o[hh]);
#pragma unroll
        for (int hh = 0; hh < 2; hh++) {
          float l0 = l[hh][0], l1 = l[hh][1];
          l0 += __shfl_xor_sync(0xffffffffu, l0, 1); l1 += __shfl_xor_sync(0xffffffffu, l1, 1);
          l0 += __shfl_xor_sync(0xffffffffu, l0, 2); l1 += __shfl_xor_sync(0xffffffffu, l1, 2);
          asm("rcp.approx.ftz.f32 %0, %0;" : "+f"(l0)); asm("rcp.approx.ftz.f32 %0, %0;" : "+f"(l1));
#pragma unroll
          for (int dt = 0; dt < 4; dt += 2)
            stsm4(oa ^ ((4 * hh + dt) << 4),
                  pack2(o[hh][dt][0] * l0, o[hh][dt][1] * l0), pack2(o[hh][dt][2] * l1, o[hh][dt][3] * l1),
                  pack2(o[hh][dt + 1][0] * l0, o[hh][dt + 1][1] * l0), pack2(o[hh][dt + 1][2] * l1, o[hh][dt + 1][3] * l1));
        }
        fence_async_smem();
        signal(JOB + ab);
        nb_sync<NB_BOTH>(256);
        resume();
      };

      TS(1 + 32 * L);
      mbar_wait(BAR(F1), 0); KB(0);    g1_issue(acca, L ? OFF_X : slot1(0), slot1(0), True{});
      mbar_wait(BAR(F1 + 1), 0); KB(1); g1_issue(acca, L ? OFF_X + 16384 : slot1(1), slot1(1), False{});
      wg_wait<1>(); release(E1 + 0);
      auto g1_bhead = [&](int p) {
        mbar_wait(BAR(F1 + p), 0); KB(p ? 2 : 16); g1_issue(accb, OFF_X, slot1(p), True{});
        if (p) { wg_wait<1>(); release(E1 + 1); }
        mbar_wait(BAR(F1 + p + 1), 0); KB(p ? 3 : 17); g1_issue(accb, OFF_X + 16384, slot1(p + 1), False{});
        wg_wait<1>(); release(E1 + p);
      };
      if (L == 0) {
        GEOM;
        const bf16* wp = P.wqkv_p + ((128 * opq(m) + 16 * wg + (t7 >> 3)) * 3072 + 128 * opq(j) + 64 * r + l7 * 8);
        const uint32_t ca = sb + OFF_STG + (16 * wg + (t7 >> 3)) * 784 + l7 * 32;
#pragma unroll 1
        for (int p = 0; p < 3; p++) {
          uint4 wv[4];
#pragma unroll
          for (int k = 0; k < 4; k++)
            asm volatile("ld.global.nc.v4.u32 {%0, %1, %2, %3}, [%4];" : "=r"(wv[k].x), "=r"(wv[k].y), "=r"(wv[k].z), "=r"(wv[k].w)
                         : "l"(wp + k * 32 * 3072 + p * 1024));
          g1_loop(acca, 2 + 3 * p, 5 + 3 * p, 0);
          float cs[8];
#pragma unroll
          for (int k = 0; k < 4; k++) {
            const uint4 v = wv[k];
            const float t[8] = {bf_lo(v.x), bf_hi(v.x), bf_lo(v.y), bf_hi(v.y), bf_lo(v.z), bf_hi(v.z), bf_lo(v.w), bf_hi(v.w)};
#pragma unroll
            for (int e = 0; e < 8; e++) cs[e] = k ? cs[e] + t[e] : t[e];
          }
          sts128(ca + p * 256, __float_as_uint(cs[0]), __float_as_uint(cs[1]), __float_as_uint(cs[2]), __float_as_uint(cs[3]));
          sts128(ca + p * 256 + 16, __float_as_uint(cs[4]), __float_as_uint(cs[5]), __float_as_uint(cs[6]), __float_as_uint(cs[7]));
        }
        signal(CSJ);
        g1_step(acca, 11, true);
        mbar_wait(BAR(XF), 0); mbar_wait(BAR(XF + 1), 0);
        g1_stats(12);
        wg_wait<0>(); release(E1 + 3);
        fence_regs(acca);
        g1_bhead(0);
      } else {
        g1_bhead(2);
        g1_stats(4);
        g1_loop(acca, 8, 18, 0);
      }
      stat_fetch(stat_src());
      g1_loop(accb, 18, FA, 0);
      ln_stats();
      if (L == 0) mbar_wait(BAR(STAT), 0);
      center(acca, 0); wg_commit();
      wg_wait<0>(); release(E1 + ((FA - 1) & 3));
      fence_regs(acca);
      TS(2 + 32 * L);
      fold_v(acca, 0, 8); fold_k(acca, 0, 0, 2); fold_q(acca);
      sched_fence(P.zero);
      g1_loop(accb, FA, ATT, FA);
      attend(0, [&]() { wg_wait<0>(); release(E1 + ((ATT - 1) & 3)); mbar_wait(BAR(F1 + (ATT & 3)), (ATT >> 2) & 1); },
             [&]() { KB(ATT); g1_issue(accb, slot1(ATT & 3), slot1(ATT & 3), False{});
                     mbar_wait(BAR(F1 + ((ATT + 1) & 3)), ((ATT + 1) >> 2) & 1);
                     KB(ATT + 1); g1_issue(accb, slot1((ATT + 1) & 3), slot1((ATT + 1) & 3), False{}); });
      wg_wait<1>(); release(E1 + (ATT & 3));
      TS(3 + 32 * L);
      load_x();
      fence_regs(xa);
      center(accb, 1);
#pragma unroll 1
      for (int u = ATT + 2; u < 32; u++) {
        const bool hold = u == 32 - LEAD1 && wg == 0;
        if (hold) { wg_wait<0>(); release(E1 + ((31 - LEAD1) & 3)); nb_sync<NB_LEAD>(256); }
        g1_step(accb, u, !hold, u == 31 && wg == 1);
      }
      mbar_wait(BAR(STD), L);
      wg_wait<0>(); release(E1 + 3);
      fence_regs(accb);
      TS(4 + 32 * L);
      if (wu == 7) ST(0);
      fold_v(accb, 0, 8); fold_k(accb, 1, 0, 2);
      fold_q(accb);
      TS2(29 + 32 * L);
      {
        auto g2_issue = [&](int p, bool own) {
          const uint32_t st = slot2(p);
          const uint32_t da = sda + ((own ? OFF_STG : st) >> 4), db = sd + (st >> 4);
          wg_fence();
          static_for<0, 4>([&](auto kk) { wgmma_128<0, 1, DI(kk.value * 32, 16), DI(16384 + kk.value * 2048, 8192)>(xa, da, db); });
          wg_commit();
        };
        uint32_t par = L ? 0x1e : 0;
        int p = 0, pp = 0;
        auto g2_loop = [&](int n0, int n1, int nrel) {
#pragma unroll 1
          for (int n = n0; n < n1; n++) {
            mbar_wait(BAR(F2 + p), (par >> p) & 1);
            KB(32 + n);
            if (n == 9 && wu == 0) ST(5);
            par ^= 1u << p;
            g2_issue(p, n == 8);
            if (n1 == 16 && n == 15 && wg == 0) nb_arrive<NB_LEAD>(256);
            wg_wait<1>();
            if (n > nrel) release(E2 + pp);
            pp = p; if (++p == 5) p = 0;
          }
        };
        g2_loop(0, COVER, 0);
        attend(1, [&]() { wg_wait<0>(); release(E2 + COVER - 1); mbar_wait(BAR(F2 + COVER), (par >> COVER) & 1); },
               [&]() { KB(32 + COVER); g2_issue(COVER, false);
                       mbar_wait(BAR(F2 + COVER + 1), (par >> (COVER + 1)) & 1);
                       KB(33 + COVER); g2_issue(COVER + 1, false); });
        wg_wait<1>(); release(E2 + COVER);
        par ^= 3u << COVER; pp = COVER + 1; p = (COVER + 2) % 5;
        TS(30 + 32 * L);
        {
          const bf16* bp = P.b2 + (128 * opq(i) + 16 * wu + ((fresh_tid() & 31) >> 2));
          asm volatile("ld.global.nc.u16 %0, [%1];" : "=h"(b2a) : "l"(bp));
          asm volatile("ld.global.nc.u16 %0, [%1];" : "=h"(b2b) : "l"(bp + 8));
        }
        TS2(14 + 32 * L);
        {
          GEOM;
          e2p = stat_slot(); e2s = stat_src();
          e2g = gHB + (opq(j) * 32 + 2 * i) * 16384 + w * 2048 + lane * 16;
          e2h = sb + OFF_X + wg * 16384 + (16 * w + lr) * 128 + ((lt ^ l7) << 4);
          asm volatile("" : "+l"(e2p), "+l"(e2s), "+l"(e2g), "+r"(e2h));
        }
        g2_loop(COVER + 2, 16 - LEAD2, 0);
        if (wg == 1) { wg_wait<0>(); release(E2 + pp); nb_sync<NB_LEAD>(256); }
        g2_loop(16 - LEAD2, 16, wg == 1 ? 16 - LEAD2 : 0);
        wg_wait<0>();
        release(E2 + 0);
        fence_regs(xa);
      }
      TS(5 + 32 * L);
      if (wu == 0) ST(8);
      {
        GEOM;
        const uint32_t tg = 2 * (tag + 1) + 1;
        float s0 = 0.f, s1 = 0.f, s2 = 0.f, s3 = 0.f, q0 = 0.f, q1 = 0.f, q2 = 0.f, q3 = 0.f;
#pragma unroll
        for (int t = 0; t < 16; t++) {
          s0 += xa[4 * t]; s1 += xa[4 * t + 1]; s2 += xa[4 * t + 2]; s3 += xa[4 * t + 3];
          q0 = fmaf(xa[4 * t], xa[4 * t], q0); q1 = fmaf(xa[4 * t + 1], xa[4 * t + 1], q1);
          q2 = fmaf(xa[4 * t + 2], xa[4 * t + 2], q2); q3 = fmaf(xa[4 * t + 3], xa[4 * t + 3], q3);
        }
        const float sm = stat_publish(e2p, s0 + s1, q0 + q1, s2 + s3, q2 + q3, tg);
        const uint32_t t0 = clock32();
        TS2(13 + 32 * L);
        const float pv0 = __shfl_sync(0xffffffffu, sm, 4 * l7) * (1.f / 128), pv1 = __shfl_sync(0xffffffffu, sm, 4 * l7 + 1) * (1.f / 128);
        while (clock32() - t0 < STAT_CLK) {}
        stat_fetch(e2s);
        wg_fence();
        wgmma_rs_224z(acc3, q == 0 ? 0x3f80u : 0u, q == 0 ? 0x3f80u : 0u, 0u, 0u, mkdesc_vec(sb + OFF_B1, 16));
        wg_commit();
        stat_await([&]() { return e2s; }, tg);
        float r0, m0, r1, m1;
        {
          float mean0, var0, mean1, var1;
          stat_combine(sv0[0], sv0[1], sv1[0], sv1[1], pv0, mean0, var0); stat_combine(sv0[2], sv0[3], sv1[2], sv1[3], pv1, mean1, var1);
          mean0 = __shfl_sync(0xffffffffu, mean0, g); var0 = __shfl_sync(0xffffffffu, var0, g);
          mean1 = __shfl_sync(0xffffffffu, mean1, g); var1 = __shfl_sync(0xffffffffu, var1, g);
          r0 = 0.5f * rsq(fmaf(var0 + 1e-5f, 1e-5f, var0)); r1 = 0.5f * rsq(fmaf(var1 + 1e-5f, 1e-5f, var1));
          m0 = -mean0 * r0; m1 = -mean1 * r1;
        }
        TS2(15 + 32 * L);
#pragma unroll
        for (int t = 0; t < 16; t += 2) {
          stsm4((e2h ^ ((t & 7) << 4)) + (t >> 3) * 8192,
                pack2(fmaf(xa[4 * t], r0, m0), fmaf(xa[4 * t + 1], r0, m0)), pack2(fmaf(xa[4 * t + 2], r1, m1), fmaf(xa[4 * t + 3], r1, m1)),
                pack2(fmaf(xa[4 * t + 4], r0, m0), fmaf(xa[4 * t + 5], r0, m0)), pack2(fmaf(xa[4 * t + 6], r1, m1), fmaf(xa[4 * t + 7], r1, m1)));
          if ((t & 7) == 6 && wg == 0) {
            __syncwarp();
            copy_out<4>(e2g + (t >> 3) * 8192, sb + OFF_X + (t >> 3) * 8192 + w * 2048 + lane * 16, 512);
          }
        }
        signal(JOB + 2 + wg);
        fence_async_smem();
        mbar_wait(BAR(F3 + 0), 0);
        nb_sync<NB_BOTH>(256);
      }
      TS(6 + 32 * L);
      auto g3_issue = [&](uint32_t a, int p) {
        const uint32_t da = sda + (a >> 4), db = sd + (slot3(p) >> 4);
        wg_fence();
        static_for<0, 4>([&](auto kk) { wgmma_224<1, 1, DI(kk.value * 2048, 8192), DI(16384 + kk.value * 2048, 8192)>(acc3, da, db); });
        wg_commit();
      };
      KB(48); g3_issue(OFF_X, 0);
      mbar_wait(BAR(F3 + 1), 0); KB(49); g3_issue(OFF_X + 16384, 1);
      sched_fence(P.zero);
      {
        const float c0 = __uint_as_float((uint32_t)b2a << 16), c1 = __uint_as_float((uint32_t)b2b << 16);
#pragma unroll
        for (int t = 0; t < 16; t++) { xa[4 * t] += c0; xa[4 * t + 1] += c0; xa[4 * t + 2] += c1; xa[4 * t + 3] += c1; }
        fence_regs(xa);
      }
      wg_wait<1>(); release(E3 + 0);
      auto g3_loop = [&](int n0, int n1, int nrel) {
#pragma unroll 1
        for (int n = n0; n < n1; n++) {
          const int p = n & 3;
          mbar_wait(BAR(F3 + p), (n >> 2) & 1);
          KB(48 + n);
          if (n == 3 && wu == 0) ST(13);
          if (n == 2 && wu == 0) ST(14);
          g3_issue(slot3(p), p);
          wg_wait<1>();
          if (n > nrel) release(E3 + ((n - 1) & 3));
        }
      };
      g3_loop(2, 29, 0);
      uint32_t ua;
      uint8_t* ug;
      {
        GEOM;
        ua = sb + OFF_X + wg * 8192 + (8 * lt + l7) * 128 + (((2 * w + ((lane >> 3) & 1)) ^ l7) << 4);
        ug = gUB + (opq(j) * 56 + 48 + m) * 16384 + r * 4096 + wg * 8192 + (lane >> 1) * 128 + (((2 * w + (lane & 1)) ^ ((lane >> 1) & 7)) << 4);
      }
      auto gelu8 = [&](int c, int k) {
        const int o = 32 * c + 8 * k;
        stsm4t(ua + (c & 1) * 16384 + k * 2048,
               pack2(gelu_half(acc3[o]), gelu_half(acc3[o + 1])), pack2(gelu_half(acc3[o + 2]), gelu_half(acc3[o + 3])),
               pack2(gelu_half(acc3[o + 4]), gelu_half(acc3[o + 5])), pack2(gelu_half(acc3[o + 6]), gelu_half(acc3[o + 7])));
      };
      {
        auto part = [&](auto p, auto half) {
          static_for<0, 4>([&](auto kk) {
            constexpr uint32_t o = slot3(p.value) + kk.value * 2048;
            if constexpr (half.value) wgmma_32<1, 1, DI(o, 8192), DI(o + 40960, 8192), 96>(acc3, sda, sd);
            else wgmma_192<1, 1, DI(o, 8192), DI(o + 16384, 8192), 0>(acc3, sda, sd);
          });
        };
        mbar_wait(BAR(RD), L);
        mbar_wait(BAR(F3 + 1), 1); mbar_wait(BAR(F3 + 2), 1);
        wg_wait<0>(); release(E3 + 0);
#pragma unroll
        for (int k = 0; k < 112; k++) { float t; asm volatile("mov.b32 %0, %1;" : "=f"(t) : "f"(acc3[k]) : "memory"); acc3[k] = t; }
        sched_fence(P.zero);
        KB(77);
        wg_fence(); part(Int<1>{}, True{}); part(Int<2>{}, True{});
        mbar_wait(BAR(F3 + 3), 1); wg_fence(); part(Int<3>{}, True{}); wg_commit();
        part(Int<1>{}, False{}); wg_commit();
        wg_wait<1>();
#pragma unroll
        for (int k = 96; k < 112; k++) asm volatile("" : "+f"(acc3[k])::"memory");
        gelu8(3, 0); gelu8(3, 1);
        __syncwarp();
        copy_out<2>(ug, sb + OFF_X + 16384 + (uint32_t)((ug - gUB) & 0x2fff), 2048);
        signal(JOB + 7);
        sched_fence(P.zero);
        KB(78);
        wg_fence(); part(Int<2>{}, False{}); wg_commit();
        wg_wait<1>(); release(E3 + 1);
        KB(79);
        part(Int<3>{}, False{}); wg_commit();
        wg_wait<1>(); release(E3 + 2);
        wg_wait<0>(); release(E3 + 3);
      }
      fence_regs(acc3);
      TS(7 + 32 * L);
      if (wu == 0) ST(16);
      auto g4_issue = [&](int p, uint32_t b) {
        const uint32_t da = sda + (slot4(p) >> 4), db = sd + (b >> 4);
        wg_fence();
        static_for<0, 4>([&](auto kk) { wgmma_128<1, 1, DI(kk.value * 2048, 8192), DI(kk.value * 2048, 8192)>(xa, da, db); });
        wg_commit();
      };
#pragma unroll
      for (int k = 0; k < 4; k++) gelu8(0, k);
      fence_async_smem();
      signal(JOB + 4);
      nb_sync<NB_BOTH>(256);
      TS(8 + 32 * L);
      static_for<0, 16>([&](auto nn) {
        constexpr int n = nn.value, p = n % 6;
        mbar_wait(BAR(F4 + p), (n / 6 + (p >= 2 ? L : 0)) & 1);
        KB(80 + n);
        if (n == 1 && wu == 0) ST(21);
        if (n == 0 && wu == 0) ST(22);
        wg_fence();
        static_for<0, 4>([&](auto kk) {
          wgmma_128<1, 1, DI(slot4(p) + kk.value * 2048, 8192), DI((n ? slot4(p) + 16384 : OFF_X) + kk.value * 2048, 8192)>(xa, sda, sd);
        });
        wg_commit();
        if (n) { wg_wait<1>(); release(E4 + (n + 5) % 6); }
        if (n == 8) mbar_wait(BAR(RD + 2), L);
        else if (!(n & 1)) sched_fence(P.zero);
        if (!(n & 1)) gelu8(1 + (n >> 3), (n >> 1) & 3);
        if ((n & 7) == 7) { fence_async_smem(); signal(JOB + 5 + (n >> 3)); }
      });
      {
        int p = 4, pp = 3;
        uint32_t par = L ? 0x33 : 0x0f;
        auto g4_loop = [&](int n0, int n1, int nrel, uint32_t own) {
#pragma unroll 1
          for (int n = n0; n < n1; n++) {
            mbar_wait(BAR(F4 + p), (par >> p) & 1);
            KB(80 + n);
            par ^= 1u << p;
            g4_issue(p, own && n == n0 ? own : slot4(p) + 16384);
            if (n1 == 56 && n == 55 && wg == 0) nb_arrive<NB_LEAD>(256);
            wg_wait<1>();
            if (n > nrel) release(E4 + pp);
            pp = p; if (++p == 6) p = 0;
          }
        };
        g4_loop(16, 24, 0, 0);
        mbar_wait(BAR(JOB + 5), L);
        g4_loop(24, 40, 0, OFF_X + 16384);
        mbar_wait(BAR(JOB + 6), L);
        g4_loop(40, 56 - LEAD4, 0, OFF_X);
        if (wg == 1) { wg_wait<0>(); release(E4 + pp); nb_sync<NB_LEAD>(256); }
        g4_loop(56 - LEAD4, 56, wg == 1 ? 56 - LEAD4 : 0, 0);
      }
      mbar_wait(BAR(RD + 1), L);
      wg_wait<0>();
      release(E4 + 1);
      fence_regs(xa);
      TS(9 + 32 * L);
      {
        GEOM;
#pragma unroll
        for (int t = 0; t < 16; t += 2) {
          stsm4(sb + OFF_X + (t >> 3) * 16384 + (16 * wu + lr) * 128 + ((((t & 7) + lt) ^ l7) << 4),
                pack2(xa[4 * t], xa[4 * t + 1]), pack2(xa[4 * t + 2], xa[4 * t + 3]),
                pack2(xa[4 * t + 4], xa[4 * t + 5]), pack2(xa[4 * t + 6], xa[4 * t + 7]));
          if (t == 6 && L == 0) {
            __syncwarp();
            const int o = wu * 2048 + lane * 16;
            copy_out<4>(gXB + (opq(i) * 16 + 2 * j) * 16384 + o, sb + OFF_X + o, 512);
            signal(JOB + 8);
          }
        }
        fence_async_smem();
        if (L == 0) signal(JOB + 9);
        else {
          __syncwarp();
          if (elect_one()) {
            tma2d_store(&P.out, sb + OFF_X + wu * 2048, 128 * j, 128 * i + 16 * wu);
            tma2d_store(&P.out, sb + OFF_X + 16384 + wu * 2048, 128 * j + 64, 128 * i + 16 * wu);
            bulk_commit(); bulk_wait0();
          }
          __syncwarp();
        }
        nb_sync<NB_BOTH>(256);
      }
      TS(10 + 32 * L);
      KB(136);
    }
    cluster_bar();
    TS(32);
  }
}

typedef CUresult (*EncodeFn)(CUtensorMap*, CUtensorMapDataType, cuuint32_t, void*, const cuuint64_t*, const cuuint64_t*, const cuuint32_t*,
                             const cuuint32_t*, CUtensorMapInterleave, CUtensorMapSwizzle, CUtensorMapL2promotion, CUtensorMapFloatOOBfill);

void make_map(EncodeFn enc, CUtensorMap* mp, const void* base, int rank, cuuint64_t d0, cuuint64_t d1, cuuint64_t d2, cuuint64_t s1, cuuint64_t s2,
              cuuint32_t b0, cuuint32_t b1, cuuint32_t b2) {
  cuuint64_t dims[3] = {d0, d1, d2}, strides[2] = {s1, s2};
  cuuint32_t box[3] = {b0, b1, b2}, es[3] = {1, 1, 1};
  CUresult res = enc(mp, CU_TENSOR_MAP_DATA_TYPE_BFLOAT16, rank, const_cast<void*>(base), dims, strides, box, es, CU_TENSOR_MAP_INTERLEAVE_NONE,
                     CU_TENSOR_MAP_SWIZZLE_128B, CU_TENSOR_MAP_L2_PROMOTION_L2_128B, CU_TENSOR_MAP_FLOAT_OOB_FILL_NONE);
  (void)res;
}

}

extern "C" void kernel_launch(void* const* d_in, const int* in_sizes, int n_in, void* d_out, int out_size) {
  (void)in_sizes; (void)n_in; (void)out_size;
  static EncodeFn enc = nullptr;
  if (!enc) {
    void* fn = nullptr;
    cudaDriverEntryPointQueryResult qr;
    cudaGetDriverEntryPoint("cuTensorMapEncodeTiled", &fn, cudaEnableDefault, &qr);
    enc = (EncodeFn)fn;
    cudaFuncSetAttribute(fused_kernel, cudaFuncAttributeMaxDynamicSharedMemorySize, SMEM_BYTES);
  }
  Params P;
  make_map(enc, &P.x0, d_in[0], 2, D_, S_, 1, D_ * 2, 0, 64, 128, 1);
  make_map(enc, &P.wqkv, d_in[1], 3, D_, D_, 3, 3 * D_ * 2, D_ * 2, 64, 32, 3);
  make_map(enc, &P.wo, d_in[2], 2, D_, D_, 1, D_ * 2, 0, 64, 64, 1);
  make_map(enc, &P.w1, d_in[4], 3, 64, S_, F_ / 64, F_ * 2, 128, 64, 64, 3);
  make_map(enc, &P.w1h, d_in[4], 3, 32, S_, F_ / 32, F_ * 2, 64, 64, 64, 1);
  make_map(enc, &P.w2, d_in[6], 3, 64, F_, S_ / 64, S_ * 2, 128, 64, 64, 2);
  make_map(enc, &P.out, d_out, 2, D_, S_, 1, D_ * 2, 0, 64, 16, 1);
  P.wqkv_p = (const bf16*)d_in[1];
  P.wo_p = (const bf16*)d_in[2];
  P.w1_p = (const bf16*)d_in[4];
  P.w2_p = (const bf16*)d_in[6];
  P.b1 = (const bf16*)d_in[5];
  P.b2 = (const bf16*)d_in[7];
  P.zero = 0;
  fused_kernel<<<128, 384, SMEM_BYTES>>>(P);
}
```

```cpp
#include <cuda_runtime.h>
#include <cuda_bf16.h>
#include <cuda.h>
#include <stdint.h>

namespace {

typedef __nv_bfloat16 bf16;
constexpr int S_ = 2048, D_ = 1024, F_ = 3584;

constexpr uint32_t OFF_STG  = 163840;
constexpr uint32_t OFF_X    = 196608;
constexpr uint32_t OFF_BAR  = 229376;
constexpr uint32_t OFF_CS   = OFF_BAR + 512;
constexpr uint32_t OFF_B1   = OFF_CS + 1536;
constexpr uint32_t SMEM_BYTES = OFF_B1 + 896 + 128;
constexpr int F1 = 0, E1 = 4, F2 = 8, E2 = 13, F3 = 18, E3 = 22, F4 = 26, E4 = 32;
constexpr int JOB = 38;
constexpr int RD = 48;
constexpr int XF = 54, STD = 56, STAT = 58, FOLD = 59, CSJ = 61, HALO = 62;
constexpr int NB_BOTH = 1, NB_HELP = 2, NB_INIT = 3, NB_LEAD = 4;

__host__ __device__ constexpr uint32_t slot1(int p) { return p * 40960; }
__host__ __device__ constexpr uint32_t slot2(int p) { return p * 32768; }
__host__ __device__ constexpr uint32_t slot3(int p) { return ((p + 2) & 3) * 49152; }
__host__ __device__ constexpr uint32_t slot4(int p) { return (p < 2 ? p + 4 : p - 2) * 32768; }

__device__ __align__(1024) uint8_t gXB[16 * 16 * 16384];
__device__ __align__(1024) uint8_t gOB[16 * 16 * 16384];
__device__ __align__(1024) uint8_t gHB[8 * 32 * 16384];
__device__ __align__(1024) uint8_t gUB[8 * 56 * 16384];
__device__ __align__(1024) uint2   gST[2][16][8][8][16];
__device__ __align__(1024) uint4   gHalo[2][16][8][12][32];
__device__ __align__(1024) uint32_t gAck[2][16][8][2][8];
__device__ __align__(1024) uint4   gCS[8][16][64];
__device__ __align__(1024) uint32_t gFlag[2][7][16][32];
__device__ uint32_t gEpoch;
#define TS(k)
#define TS2(k)

#define KB(k)
#define ST(k)
struct Params {
  CUtensorMap x0, wqkv, wo, w1, w1h, w2, out;
  const bf16 *wqkv_p, *wo_p, *w1_p, *w2_p, *b1, *b2;
  uint32_t zero;
};

template <int TA, int TB, uint32_t IA, uint32_t IB, int O = 0, int LEN> __device__ __forceinline__ void wgmma_32(float (&d)[LEN], uint32_t da, uint32_t db) {
  asm volatile("{\n.reg .b64 da, db;\n.reg .b32 la, lb;\nadd.u32 la, %16, %20;\nadd.u32 lb, %17, %21;\nmov.b64 da, {la, 0x40000040};\nmov.b64 db, {lb, 0x40000040};\n"
  "wgmma.mma_async.sync.aligned.m64n32k16.f32.bf16.bf16 {"
  "%0, %1, %2, %3, %4, %5, %6, %7, %8, %9, %10, %11, %12, %13, %14, %15"
  "}, da, db, 1, 1, 1, %18, %19;\n}\n"
  : "+f"(d[O + 0]), "+f"(d[O + 1]), "+f"(d[O + 2]), "+f"(d[O + 3]), "+f"(d[O + 4]), "+f"(d[O + 5]), "+f"(d[O + 6]), "+f"(d[O + 7]),
    "+f"(d[O + 8]), "+f"(d[O + 9]), "+f"(d[O + 10]), "+f"(d[O + 11]), "+f"(d[O + 12]), "+f"(d[O + 13]), "+f"(d[O + 14]), "+f"(d[O + 15])
  : "r"(da), "r"(db), "n"(TA), "n"(TB), "n"(IA), "n"(IB));
}
template <int TA, int TB, uint32_t IA, uint32_t IB, int O = 0, int LEN> __device__ __forceinline__ void wgmma_128(float (&d)[LEN], uint32_t da, uint32_t db) {
  asm volatile("{\n.reg .b64 da, db;\n.reg .b32 la, lb;\nadd.u32 la, %64, %68;\nadd.u32 lb, %65, %69;\nmov.b64 da, {la, 0x40000040};\nmov.b64 db, {lb, 0x40000040};\n"
  "wgmma.mma_async.sync.aligned.m64n128k16.f32.bf16.bf16 {"
  "%0, %1, %2, %3, %4, %5, %6, %7, %8, %9, %10, %11, %12, %13, %14, %15, "
  "%16, %17, %18, %19, %20, %21, %22, %23, %24, %25, %26, %27, %28, %29, %30, %31, "
  "%32, %33, %34, %35, %36, %37, %38, %39, %40, %41, %42, %43, %44, %45, %46, %47, "
  "%48, %49, %50, %51, %52, %53, %54, %55, %56, %57, %58, %59, %60, %61, %62, %63"
  "}, da, db, 1, 1, 1, %66, %67;\n}\n"
  : "+f"(d[O + 0]), "+f"(d[O + 1]), "+f"(d[O + 2]), "+f"(d[O + 3]), "+f"(d[O + 4]), "+f"(d[O + 5]), "+f"(d[O + 6]), "+f"(d[O + 7]),
    "+f"(d[O + 8]), "+f"(d[O + 9]), "+f"(d[O + 10]), "+f"(d[O + 11]), "+f"(d[O + 12]), "+f"(d[O + 13]), "+f"(d[O + 14]), "+f"(d[O + 15]),
    "+f"(d[O + 16]), "+f"(d[O + 17]), "+f"(d[O + 18]), "+f"(d[O + 19]), "+f"(d[O + 20]), "+f"(d[O + 21]), "+f"(d[O + 22]), "+f"(d[O + 23]),
    "+f"(d[O + 24]), "+f"(d[O + 25]), "+f"(d[O + 26]), "+f"(d[O + 27]), "+f"(d[O + 28]), "+f"(d[O + 29]), "+f"(d[O + 30]), "+f"(d[O + 31]),
    "+f"(d[O + 32]), "+f"(d[O + 33]), "+f"(d[O + 34]), "+f"(d[O + 35]), "+f"(d[O + 36]), "+f"(d[O + 37]), "+f"(d[O + 38]), "+f"(d[O + 39]),
    "+f"(d[O + 40]), "+f"(d[O + 41]), "+f"(d[O + 42]), "+f"(d[O + 43]), "+f"(d[O + 44]), "+f"(d[O + 45]), "+f"(d[O + 46]), "+f"(d[O + 47]),
    "+f"(d[O + 48]), "+f"(d[O + 49]), "+f"(d[O + 50]), "+f"(d[O + 51]), "+f"(d[O + 52]), "+f"(d[O + 53]), "+f"(d[O + 54]), "+f"(d[O + 55]),
    "+f"(d[O + 56]), "+f"(d[O + 57]), "+f"(d[O + 58]), "+f"(d[O + 59]), "+f"(d[O + 60]), "+f"(d[O + 61]), "+f"(d[O + 62]), "+f"(d[O + 63])
  : "r"(da), "r"(db), "n"(TA), "n"(TB), "n"(IA), "n"(IB));
}
template <int TA, int TB, uint32_t IA, uint32_t IB, int O = 0, int LEN> __device__ __forceinline__ void wgmma_192(float (&d)[LEN], uint32_t da, uint32_t db) {
  asm volatile("{\n.reg .b64 da, db;\n.reg .b32 la, lb;\nadd.u32 la, %96, %100;\nadd.u32 lb, %97, %101;\nmov.b64 da, {la, 0x40000040};\nmov.b64 db, {lb, 0x40000040};\n"
  "wgmma.mma_async.sync.aligned.m64n192k16.f32.bf16.bf16 {"
  "%0, %1, %2, %3, %4, %5, %6, %7, %8, %9, %10, %11, %12, %13, %14, %15, "
  "%16, %17, %18, %19, %20, %21, %22, %23, %24, %25, %26, %27, %28, %29, %30, %31, "
  "%32, %33, %34, %35, %36, %37, %38, %39, %40, %41, %42, %43, %44, %45, %46, %47, "
  "%48, %49, %50, %51, %52, %53, %54, %55, %56, %57, %58, %59, %60, %61, %62, %63, "
  "%64, %65, %66, %67, %68, %69, %70, %71, %72, %73, %74, %75, %76, %77, %78, %79, "
  "%80, %81, %82, %83, %84, %85, %86, %87, %88, %89, %90, %91, %92, %93, %94, %95"
  "}, da, db, 1, 1, 1, %98, %99;\n}\n"
  : "+f"(d[O + 0]), "+f"(d[O + 1]), "+f"(d[O + 2]), "+f"(d[O + 3]), "+f"(d[O + 4]), "+f"(d[O + 5]), "+f"(d[O + 6]), "+f"(d[O + 7]),
    "+f"(d[O + 8]), "+f"(d[O + 9]), "+f"(d[O + 10]), "+f"(d[O + 11]), "+f"(d[O + 12]), "+f"(d[O + 13]), "+f"(d[O + 14]), "+f"(d[O + 15]),
    "+f"(d[O + 16]), "+f"(d[O + 17]), "+f"(d[O + 18]), "+f"(d[O + 19]), "+f"(d[O + 20]), "+f"(d[O + 21]), "+f"(d[O + 22]), "+f"(d[O + 23]),
    "+f"(d[O + 24]), "+f"(d[O + 25]), "+f"(d[O + 26]), "+f"(d[O + 27]), "+f"(d[O + 28]), "+f"(d[O + 29]), "+f"(d[O + 30]), "+f"(d[O + 31]),
    "+f"(d[O + 32]), "+f"(d[O + 33]), "+f"(d[O + 34]), "+f"(d[O + 35]), "+f"(d[O + 36]), "+f"(d[O + 37]), "+f"(d[O + 38]), "+f"(d[O + 39]),
    "+f"(d[O + 40]), "+f"(d[O + 41]), "+f"(d[O + 42]), "+f"(d[O + 43]), "+f"(d[O + 44]), "+f"(d[O + 45]), "+f"(d[O + 46]), "+f"(d[O + 47]),
    "+f"(d[O + 48]), "+f"(d[O + 49]), "+f"(d[O + 50]), "+f"(d[O + 51]), "+f"(d[O + 52]), "+f"(d[O + 53]), "+f"(d[O + 54]), "+f"(d[O + 55]),
    "+f"(d[O + 56]), "+f"(d[O + 57]), "+f"(d[O + 58]), "+f"(d[O + 59]), "+f"(d[O + 60]), "+f"(d[O + 61]), "+f"(d[O + 62]), "+f"(d[O + 63]),
    "+f"(d[O + 64]), "+f"(d[O + 65]), "+f"(d[O + 66]), "+f"(d[O + 67]), "+f"(d[O + 68]), "+f"(d[O + 69]), "+f"(d[O + 70]), "+f"(d[O + 71]),
    "+f"(d[O + 72]), "+f"(d[O + 73]), "+f"(d[O + 74]), "+f"(d[O + 75]), "+f"(d[O + 76]), "+f"(d[O + 77]), "+f"(d[O + 78]), "+f"(d[O + 79]),
    "+f"(d[O + 80]), "+f"(d[O + 81]), "+f"(d[O + 82]), "+f"(d[O + 83]), "+f"(d[O + 84]), "+f"(d[O + 85]), "+f"(d[O + 86]), "+f"(d[O + 87]),
    "+f"(d[O + 88]), "+f"(d[O + 89]), "+f"(d[O + 90]), "+f"(d[O + 91]), "+f"(d[O + 92]), "+f"(d[O + 93]), "+f"(d[O + 94]), "+f"(d[O + 95])
  : "r"(da), "r"(db), "n"(TA), "n"(TB), "n"(IA), "n"(IB));
}
template <int TA, int TB, uint32_t IA, uint32_t IB, int O = 0, int LEN> __device__ __forceinline__ void wgmma_192z(float (&d)[LEN], uint32_t da, uint32_t db) {
  asm volatile("{\n.reg .b64 da, db;\n.reg .b32 la, lb;\nadd.u32 la, %96, %100;\nadd.u32 lb, %97, %101;\nmov.b64 da, {la, 0x40000040};\nmov.b64 db, {lb, 0x40000040};\n"
  "wgmma.mma_async.sync.aligned.m64n192k16.f32.bf16.bf16 {"
  "%0, %1, %2, %3, %4, %5, %6, %7, %8, %9, %10, %11, %12, %13, %14, %15, "
  "%16, %17, %18, %19, %20, %21, %22, %23, %24, %25, %26, %27, %28, %29, %30, %31, "
  "%32, %33, %34, %35, %36, %37, %38, %39, %40, %41, %42, %43, %44, %45, %46, %47, "
  "%48, %49, %50, %51, %52, %53, %54, %55, %56, %57, %58, %59, %60, %61, %62, %63, "
  "%64, %65, %66, %67, %68, %69, %70, %71, %72, %73, %74, %75, %76, %77, %78, %79, "
  "%80, %81, %82, %83, %84, %85, %86, %87, %88, %89, %90, %91, %92, %93, %94, %95"
  "}, da, db, 0, 1, 1, %98, %99;\n}\n"
  : "=f"(d[O + 0]), "=f"(d[O + 1]), "=f"(d[O + 2]), "=f"(d[O + 3]), "=f"(d[O + 4]), "=f"(d[O + 5]), "=f"(d[O + 6]), "=f"(d[O + 7]),
    "=f"(d[O + 8]), "=f"(d[O + 9]), "=f"(d[O + 10]), "=f"(d[O + 11]), "=f"(d[O + 12]), "=f"(d[O + 13]), "=f"(d[O + 14]), "=f"(d[O + 15]),
    "=f"(d[O + 16]), "=f"(d[O + 17]), "=f"(d[O + 18]), "=f"(d[O + 19]), "=f"(d[O + 20]), "=f"(d[O + 21]), "=f"(d[O + 22]), "=f"(d[O + 23]),
    "=f"(d[O + 24]), "=f"(d[O + 25]), "=f"(d[O + 26]), "=f"(d[O + 27]), "=f"(d[O + 28]), "=f"(d[O + 29]), "=f"(d[O + 30]), "=f"(d[O + 31]),
    "=f"(d[O + 32]), "=f"(d[O + 33]), "=f"(d[O + 34]), "=f"(d[O + 35]), "=f"(d[O + 36]), "=f"(d[O + 37]), "=f"(d[O + 38]), "=f"(d[O + 39]),
    "=f"(d[O + 40]), "=f"(d[O + 41]), "=f"(d[O + 42]), "=f"(d[O + 43]), "=f"(d[O + 44]), "=f"(d[O + 45]), "=f"(d[O + 46]), "=f"(d[O + 47]),
    "=f"(d[O + 48]), "=f"(d[O + 49]), "=f"(d[O + 50]), "=f"(d[O + 51]), "=f"(d[O + 52]), "=f"(d[O + 53]), "=f"(d[O + 54]), "=f"(d[O + 55]),
    "=f"(d[O + 56]), "=f"(d[O + 57]), "=f"(d[O + 58]), "=f"(d[O + 59]), "=f"(d[O + 60]), "=f"(d[O + 61]), "=f"(d[O + 62]), "=f"(d[O + 63]),
    "=f"(d[O + 64]), "=f"(d[O + 65]), "=f"(d[O + 66]), "=f"(d[O + 67]), "=f"(d[O + 68]), "=f"(d[O + 69]), "=f"(d[O + 70]), "=f"(d[O + 71]),
    "=f"(d[O + 72]), "=f"(d[O + 73]), "=f"(d[O + 74]), "=f"(d[O + 75]), "=f"(d[O + 76]), "=f"(d[O + 77]), "=f"(d[O + 78]), "=f"(d[O + 79]),
    "=f"(d[O + 80]), "=f"(d[O + 81]), "=f"(d[O + 82]), "=f"(d[O + 83]), "=f"(d[O + 84]), "=f"(d[O + 85]), "=f"(d[O + 86]), "=f"(d[O + 87]),
    "=f"(d[O + 88]), "=f"(d[O + 89]), "=f"(d[O + 90]), "=f"(d[O + 91]), "=f"(d[O + 92]), "=f"(d[O + 93]), "=f"(d[O + 94]), "=f"(d[O + 95])
  : "r"(da), "r"(db), "n"(TA), "n"(TB), "n"(IA), "n"(IB));
}
template <int TA, int TB, uint32_t IA, uint32_t IB, int O = 0, int LEN> __device__ __forceinline__ void wgmma_224(float (&d)[LEN], uint32_t da, uint32_t db) {
  asm volatile("{\n.reg .b64 da, db;\n.reg .b32 la, lb;\nadd.u32 la, %112, %116;\nadd.u32 lb, %113, %117;\nmov.b64 da, {la, 0x40000040};\nmov.b64 db, {lb, 0x40000040};\n"
  "wgmma.mma_async.sync.aligned.m64n224k16.f32.bf16.bf16 {"
  "%0, %1, %2, %3, %4, %5, %6, %7, %8, %9, %10, %11, %12, %13, %14, %15, "
  "%16, %17, %18, %19, %20, %21, %22, %23, %24, %25, %26, %27, %28, %29, %30, %31, "
  "%32, %33, %34, %35, %36, %37, %38, %39, %40, %41, %42, %43, %44, %45, %46, %47, "
  "%48, %49, %50, %51, %52, %53, %54, %55, %56, %57, %58, %59, %60, %61, %62, %63, "
  "%64, %65, %66, %67, %68, %69, %70, %71, %72, %73, %74, %75, %76, %77, %78, %79, "
  "%80, %81, %82, %83, %84, %85, %86, %87, %88, %89, %90, %91, %92, %93, %94, %95, "
  "%96, %97, %98, %99, %100, %101, %102, %103, %104, %105, %106, %107, %108, %109, %110, %111"
  "}, da, db, 1, 1, 1, %114, %115;\n}\n"
  : "+f"(d[O + 0]), "+f"(d[O + 1]), "+f"(d[O + 2]), "+f"(d[O + 3]), "+f"(d[O + 4]), "+f"(d[O + 5]), "+f"(d[O + 6]), "+f"(d[O + 7]),
    "+f"(d[O + 8]), "+f"(d[O + 9]), "+f"(d[O + 10]), "+f"(d[O + 11]), "+f"(d[O + 12]), "+f"(d[O + 13]), "+f"(d[O + 14]), "+f"(d[O + 15]),
    "+f"(d[O + 16]), "+f"(d[O + 17]), "+f"(d[O + 18]), "+f"(d[O + 19]), "+f"(d[O + 20]), "+f"(d[O + 21]), "+f"(d[O + 22]), "+f"(d[O + 23]),
    "+f"(d[O + 24]), "+f"(d[O + 25]), "+f"(d[O + 26]), "+f"(d[O + 27]), "+f"(d[O + 28]), "+f"(d[O + 29]), "+f"(d[O + 30]), "+f"(d[O + 31]),
    "+f"(d[O + 32]), "+f"(d[O + 33]), "+f"(d[O + 34]), "+f"(d[O + 35]), "+f"(d[O + 36]), "+f"(d[O + 37]), "+f"(d[O + 38]), "+f"(d[O + 39]),
    "+f"(d[O + 40]), "+f"(d[O + 41]), "+f"(d[O + 42]), "+f"(d[O + 43]), "+f"(d[O + 44]), "+f"(d[O + 45]), "+f"(d[O + 46]), "+f"(d[O + 47]),
    "+f"(d[O + 48]), "+f"(d[O + 49]), "+f"(d[O + 50]), "+f"(d[O + 51]), "+f"(d[O + 52]), "+f"(d[O + 53]), "+f"(d[O + 54]), "+f"(d[O + 55]),
    "+f"(d[O + 56]), "+f"(d[O + 57]), "+f"(d[O + 58]), "+f"(d[O + 59]), "+f"(d[O + 60]), "+f"(d[O + 61]), "+f"(d[O + 62]), "+f"(d[O + 63]),
    "+f"(d[O + 64]), "+f"(d[O + 65]), "+f"(d[O + 66]), "+f"(d[O + 67]), "+f"(d[O + 68]), "+f"(d[O + 69]), "+f"(d[O + 70]), "+f"(d[O + 71]),
    "+f"(d[O + 72]), "+f"(d[O + 73]), "+f"(d[O + 74]), "+f"(d[O + 75]), "+f"(d[O + 76]), "+f"(d[O + 77]), "+f"(d[O + 78]), "+f"(d[O + 79]),
    "+f"(d[O + 80]), "+f"(d[O + 81]), "+f"(d[O + 82]), "+f"(d[O + 83]), "+f"(d[O + 84]), "+f"(d[O + 85]), "+f"(d[O + 86]), "+f"(d[O + 87]),
    "+f"(d[O + 88]), "+f"(d[O + 89]), "+f"(d[O + 90]), "+f"(d[O + 91]), "+f"(d[O + 92]), "+f"(d[O + 93]), "+f"(d[O + 94]), "+f"(d[O + 95]),
    "+f"(d[O + 96]), "+f"(d[O + 97]), "+f"(d[O + 98]), "+f"(d[O + 99]), "+f"(d[O + 100]), "+f"(d[O + 101]), "+f"(d[O + 102]), "+f"(d[O + 103]),
    "+f"(d[O + 104]), "+f"(d[O + 105]), "+f"(d[O + 106]), "+f"(d[O + 107]), "+f"(d[O + 108]), "+f"(d[O + 109]), "+f"(d[O + 110]), "+f"(d[O + 111])
  : "r"(da), "r"(db), "n"(TA), "n"(TB), "n"(IA), "n"(IB));
}
__device__ __forceinline__ void wgmma_rs_192(float (&d)[96], uint32_t a0, uint32_t a1, uint32_t a2, uint32_t a3, uint64_t db) {
  asm volatile("wgmma.mma_async.sync.aligned.m64n192k16.f32.bf16.bf16 {"
  "%0, %1, %2, %3, %4, %5, %6, %7, %8, %9, %10, %11, %12, %13, %14, %15, "
  "%16, %17, %18, %19, %20, %21, %22, %23, %24, %25, %26, %27, %28, %29, %30, %31, "
  "%32, %33, %34, %35, %36, %37, %38, %39, %40, %41, %42, %43, %44, %45, %46, %47, "
  "%48, %49, %50, %51, %52, %53, %54, %55, %56, %57, %58, %59, %60, %61, %62, %63, "
  "%64, %65, %66, %67, %68, %69, %70, %71, %72, %73, %74, %75, %76, %77, %78, %79, "
  "%80, %81, %82, %83, %84, %85, %86, %87, %88, %89, %90, %91, %92, %93, %94, %95"
  "}, {%96, %97, %98, %99}, %100, 1, 1, 1, 1;\n"
  : "+f"(d[0]), "+f"(d[1]), "+f"(d[2]), "+f"(d[3]), "+f"(d[4]), "+f"(d[5]), "+f"(d[6]), "+f"(d[7]),
    "+f"(d[8]), "+f"(d[9]), "+f"(d[10]), "+f"(d[11]), "+f"(d[12]), "+f"(d[13]), "+f"(d[14]), "+f"(d[15]),
    "+f"(d[16]), "+f"(d[17]), "+f"(d[18]), "+f"(d[19]), "+f"(d[20]), "+f"(d[21]), "+f"(d[22]), "+f"(d[23]),
    "+f"(d[24]), "+f"(d[25]), "+f"(d[26]), "+f"(d[27]), "+f"(d[28]), "+f"(d[29]), "+f"(d[30]), "+f"(d[31]),
    "+f"(d[32]), "+f"(d[33]), "+f"(d[34]), "+f"(d[35]), "+f"(d[36]), "+f"(d[37]), "+f"(d[38]), "+f"(d[39]),
    "+f"(d[40]), "+f"(d[41]), "+f"(d[42]), "+f"(d[43]), "+f"(d[44]), "+f"(d[45]), "+f"(d[46]), "+f"(d[47]),
    "+f"(d[48]), "+f"(d[49]), "+f"(d[50]), "+f"(d[51]), "+f"(d[52]), "+f"(d[53]), "+f"(d[54]), "+f"(d[55]),
    "+f"(d[56]), "+f"(d[57]), "+f"(d[58]), "+f"(d[59]), "+f"(d[60]), "+f"(d[61]), "+f"(d[62]), "+f"(d[63]),
    "+f"(d[64]), "+f"(d[65]), "+f"(d[66]), "+f"(d[67]), "+f"(d[68]), "+f"(d[69]), "+f"(d[70]), "+f"(d[71]),
    "+f"(d[72]), "+f"(d[73]), "+f"(d[74]), "+f"(d[75]), "+f"(d[76]), "+f"(d[77]), "+f"(d[78]), "+f"(d[79]),
    "+f"(d[80]), "+f"(d[81]), "+f"(d[82]), "+f"(d[83]), "+f"(d[84]), "+f"(d[85]), "+f"(d[86]), "+f"(d[87]),
    "+f"(d[88]), "+f"(d[89]), "+f"(d[90]), "+f"(d[91]), "+f"(d[92]), "+f"(d[93]), "+f"(d[94]), "+f"(d[95])
  : "r"(a0), "r"(a1), "r"(a2), "r"(a3), "l"(db));
}
__device__ __forceinline__ void wgmma_rs_224z(float (&d)[112], uint32_t a0, uint32_t a1, uint32_t a2, uint32_t a3, uint64_t db) {
  asm volatile("wgmma.mma_async.sync.aligned.m64n224k16.f32.bf16.bf16 {"
  "%0, %1, %2, %3, %4, %5, %6, %7, %8, %9, %10, %11, %12, %13, %14, %15, "
  "%16, %17, %18, %19, %20, %21, %22, %23, %24, %25, %26, %27, %28, %29, %30, %31, "
  "%32, %33, %34, %35, %36, %37, %38, %39, %40, %41, %42, %43, %44, %45, %46, %47, "
  "%48, %49, %50, %51, %52, %53, %54, %55, %56, %57, %58, %59, %60, %61, %62, %63, "
  "%64, %65, %66, %67, %68, %69, %70, %71, %72, %73, %74, %75, %76, %77, %78, %79, "
  "%80, %81, %82, %83, %84, %85, %86, %87, %88, %89, %90, %91, %92, %93, %94, %95, "
  "%96, %97, %98, %99, %100, %101, %102, %103, %104, %105, %106, %107, %108, %109, %110, %111"
  "}, {%112, %113, %114, %115}, %116, 0, 1, 1, 1;\n"
  : "=f"(d[0]), "=f"(d[1]), "=f"(d[2]), "=f"(d[3]), "=f"(d[4]), "=f"(d[5]), "=f"(d[6]), "=f"(d[7]),
    "=f"(d[8]), "=f"(d[9]), "=f"(d[10]), "=f"(d[11]), "=f"(d[12]), "=f"(d[13]), "=f"(d[14]), "=f"(d[15]),
    "=f"(d[16]), "=f"(d[17]), "=f"(d[18]), "=f"(d[19]), "=f"(d[20]), "=f"(d[21]), "=f"(d[22]), "=f"(d[23]),
    "=f"(d[24]), "=f"(d[25]), "=f"(d[26]), "=f"(d[27]), "=f"(d[28]), "=f"(d[29]), "=f"(d[30]), "=f"(d[31]),
    "=f"(d[32]), "=f"(d[33]), "=f"(d[34]), "=f"(d[35]), "=f"(d[36]), "=f"(d[37]), "=f"(d[38]), "=f"(d[39]),
    "=f"(d[40]), "=f"(d[41]), "=f"(d[42]), "=f"(d[43]), "=f"(d[44]), "=f"(d[45]), "=f"(d[46]), "=f"(d[47]),
    "=f"(d[48]), "=f"(d[49]), "=f"(d[50]), "=f"(d[51]), "=f"(d[52]), "=f"(d[53]), "=f"(d[54]), "=f"(d[55]),
    "=f"(d[56]), "=f"(d[57]), "=f"(d[58]), "=f"(d[59]), "=f"(d[60]), "=f"(d[61]), "=f"(d[62]), "=f"(d[63]),
    "=f"(d[64]), "=f"(d[65]), "=f"(d[66]), "=f"(d[67]), "=f"(d[68]), "=f"(d[69]), "=f"(d[70]), "=f"(d[71]),
    "=f"(d[72]), "=f"(d[73]), "=f"(d[74]), "=f"(d[75]), "=f"(d[76]), "=f"(d[77]), "=f"(d[78]), "=f"(d[79]),
    "=f"(d[80]), "=f"(d[81]), "=f"(d[82]), "=f"(d[83]), "=f"(d[84]), "=f"(d[85]), "=f"(d[86]), "=f"(d[87]),
    "=f"(d[88]), "=f"(d[89]), "=f"(d[90]), "=f"(d[91]), "=f"(d[92]), "=f"(d[93]), "=f"(d[94]), "=f"(d[95]),
    "=f"(d[96]), "=f"(d[97]), "=f"(d[98]), "=f"(d[99]), "=f"(d[100]), "=f"(d[101]), "=f"(d[102]), "=f"(d[103]),
    "=f"(d[104]), "=f"(d[105]), "=f"(d[106]), "=f"(d[107]), "=f"(d[108]), "=f"(d[109]), "=f"(d[110]), "=f"(d[111])
  : "r"(a0), "r"(a1), "r"(a2), "r"(a3), "l"(db));
}

__device__ __forceinline__ uint32_t smem_u32(const void* p) { return (uint32_t)__cvta_generic_to_shared(p); }
__device__ __forceinline__ void mbar_init(uint32_t bar, uint32_t cnt) { asm volatile("mbarrier.init.shared::cta.b64 [%0], %1;" ::"r"(bar), "r"(cnt) : "memory"); }
__device__ __forceinline__ void mbar_expect(uint32_t bar, uint32_t bytes) { asm volatile("mbarrier.arrive.expect_tx.shared::cta.b64 _, [%0], %1;" ::"r"(bar), "r"(bytes) : "memory"); }
__device__ __forceinline__ void mbar_arrive(uint32_t bar) { asm volatile("mbarrier.arrive.shared::cta.b64 _, [%0];" ::"r"(bar) : "memory"); }
__device__ __forceinline__ void mbar_arrive_cl(uint32_t cbar) { asm volatile("mbarrier.arrive.shared::cluster.b64 _, [%0];" ::"r"(cbar) : "memory"); }
__device__ __forceinline__ uint32_t mapa(uint32_t a, uint32_t cta) { uint32_t r; asm("mapa.shared::cluster.u32 %0, %1, %2;" : "=r"(r) : "r"(a), "r"(cta)); return r; }
__device__ __forceinline__ void mbar_wait(uint32_t bar, uint32_t parity) {
  asm volatile("{\n.reg .pred p;\n.reg .u32 n;\nmov.u32 n, 0;\n"
    "LAB_WAIT:\n"
    "mbarrier.try_wait.parity.shared::cta.b64 p, [%0], %1;\n"
    "@p bra LAB_DONE;\n"
    "add.u32 n, n, 1;\n"
    "setp.lt.u32 p, n, 2000000;\n"
    "@p bra LAB_WAIT;\n"
    "trap;\n"
    "LAB_DONE:\n}\n" ::"r"(bar), "r"(parity) : "memory");
}
constexpr uint32_t SPIN_MAX = 2000000;
__device__ __forceinline__ void tma2d(uint32_t dst, const CUtensorMap* m, uint32_t bar, int c0, int c1) {
  asm volatile("cp.async.bulk.tensor.2d.shared::cluster.global.mbarrier::complete_tx::bytes [%0], [%1, {%3, %4}], [%2];"
    ::"r"(dst), "l"(m), "r"(bar), "r"(c0), "r"(c1) : "memory");
}
__device__ __forceinline__ void tma2d_mc(uint32_t dst, const CUtensorMap* m, uint32_t bar, int c0, int c1) {
  asm volatile("cp.async.bulk.tensor.2d.shared::cluster.global.mbarrier::complete_tx::bytes.multicast::cluster [%0], [%1, {%3, %4}], [%2], %5;"
    ::"r"(dst), "l"(m), "r"(bar), "r"(c0), "r"(c1), "h"((uint16_t)3) : "memory");
}
__device__ __forceinline__ void tma3d(uint32_t dst, const CUtensorMap* m, uint32_t bar, int c0, int c1, int c2) {
  asm volatile("cp.async.bulk.tensor.3d.shared::cluster.global.mbarrier::complete_tx::bytes [%0], [%1, {%3, %4, %5}], [%2];"
    ::"r"(dst), "l"(m), "r"(bar), "r"(c0), "r"(c1), "r"(c2) : "memory");
}
__device__ __forceinline__ void tma3d_mc(uint32_t dst, const CUtensorMap* m, uint32_t bar, int c0, int c1, int c2) {
  asm volatile("cp.async.bulk.tensor.3d.shared::cluster.global.mbarrier::complete_tx::bytes.multicast::cluster [%0], [%1, {%3, %4, %5}], [%2], %6;"
    ::"r"(dst), "l"(m), "r"(bar), "r"(c0), "r"(c1), "r"(c2), "h"((uint16_t)3) : "memory");
}
__device__ __forceinline__ void tma2d_store(const CUtensorMap* m, uint32_t src, int c0, int c1) {
  asm volatile("cp.async.bulk.tensor.2d.global.shared::cta.bulk_group [%0, {%2, %3}], [%1];" ::"l"(m), "r"(src), "r"(c0), "r"(c1) : "memory");
}
__device__ __forceinline__ void bulk_ld(uint32_t dst, const void* src, uint32_t bytes, uint32_t bar) {
  asm volatile("cp.async.bulk.shared::cluster.global.mbarrier::complete_tx::bytes [%0], [%1], %2, [%3];" ::"r"(dst), "l"(src), "r"(bytes), "r"(bar) : "memory");
}
__device__ __forceinline__ void bulk_ld_mc(uint32_t dst, const void* src, uint32_t bytes, uint32_t bar) {
  asm volatile("cp.async.bulk.shared::cluster.global.mbarrier::complete_tx::bytes.multicast::cluster [%0], [%1], %2, [%3], %4;"
    ::"r"(dst), "l"(src), "r"(bytes), "r"(bar), "h"((uint16_t)3) : "memory");
}
__device__ __forceinline__ void bulk_st(void* dst, uint32_t src, uint32_t bytes) {
  asm volatile("cp.async.bulk.global.shared::cta.bulk_group [%0], [%1], %2;" ::"l"(dst), "r"(src), "r"(bytes) : "memory");
}
__device__ __forceinline__ void bulk_commit() { asm volatile("cp.async.bulk.commit_group;" ::: "memory"); }
__device__ __forceinline__ void bulk_wait0() { asm volatile("cp.async.bulk.wait_group 0;" ::: "memory"); }
__device__ __forceinline__ void fence_async_smem() { asm volatile("fence.proxy.async.shared::cta;" ::: "memory"); }
__device__ __forceinline__ void wg_fence() { asm volatile("wgmma.fence.sync.aligned;" ::: "memory"); }
__device__ __forceinline__ void wg_commit() { asm volatile("wgmma.commit_group.sync.aligned;" ::: "memory"); }
template <int N> __device__ __forceinline__ void wg_wait() { asm volatile("wgmma.wait_group.sync.aligned %0;" ::"n"(N) : "memory"); }
template <int R> __device__ __forceinline__ void reg_alloc() { asm volatile("setmaxnreg.inc.sync.aligned.u32 %0;" ::"n"(R)); }
template <int R> __device__ __forceinline__ void reg_dealloc() { asm volatile("setmaxnreg.dec.sync.aligned.u32 %0;" ::"n"(R)); }
__device__ __forceinline__ void cluster_bar() { asm volatile("barrier.cluster.arrive.relaxed;\nbarrier.cluster.wait;" ::: "memory"); }
template <int ID> __device__ __forceinline__ void nb_sync(int n) { asm volatile("barrier.sync %0, %1;" ::"n"(ID), "r"(n) : "memory"); }
template <int ID> __device__ __forceinline__ void nb_arrive(int n) { asm volatile("barrier.arrive %0, %1;" ::"n"(ID), "r"(n) : "memory"); }
__device__ __forceinline__ int fresh_tid() { int t; asm volatile("mov.u32 %0, %%tid.x;" : "=r"(t)); return t; }
__device__ __forceinline__ void sched_fence(uint32_t z) { asm volatile("{\n.reg .pred p;\nsetp.ne.u32 p, %0, 0;\nLAB_S:\n@p nanosleep.u32 0;\n@p bra LAB_S;\n}\n" ::"r"(z) : "memory"); }
__device__ __forceinline__ float rsq(float x) { float y; asm("rsqrt.approx.ftz.f32 %0, %1;" : "=f"(y) : "f"(x)); return y; }
__device__ __forceinline__ int opq(int v) { asm volatile("" : "+r"(v)); return v; }
template <int V> struct Int { static constexpr int value = V; };
struct True { static constexpr bool value = true; };
struct False { static constexpr bool value = false; };
template <int N> __device__ __forceinline__ void fence_regs(float (&d)[N]) {
#pragma unroll
  for (int i = 0; i < N; i++) asm volatile("" : "+f"(d[i])::"memory");
}
__host__ __device__ constexpr uint32_t DI(uint32_t off, uint32_t lbo) { return (off >> 4) + ((lbo >> 4) << 16); }
template <int K, int N, class F> __device__ __forceinline__ void static_for(F f) { if constexpr (K < N) { f(Int<K>{}); static_for<K + 1, N>(f); } }
__device__ __forceinline__ uint64_t mkdesc_vec(uint32_t addr, uint32_t sbo) { return (uint64_t)((addr & 0x3FFFF) >> 4) | ((uint64_t)(sbo >> 4) << 32); }
__device__ __forceinline__ void sts16(uint32_t a, uint32_t v) { asm volatile("st.shared.u16 [%0], %1;" ::"r"(a), "h"((uint16_t)v) : "memory"); }
__device__ __forceinline__ uint32_t pack2(float lo, float hi) { uint32_t r; asm("cvt.rn.bf16x2.f32 %0, %1, %2;" : "=r"(r) : "f"(hi), "f"(lo)); return r; }
__device__ __forceinline__ float bf_lo(uint32_t v) { return __uint_as_float(v << 16); }
__device__ __forceinline__ float bf_hi(uint32_t v) { return __uint_as_float(v & 0xffff0000u); }
__device__ __forceinline__ void stsm4(uint32_t a, uint32_t r0, uint32_t r1, uint32_t r2, uint32_t r3) {
  asm volatile("stmatrix.sync.aligned.m8n8.x4.shared.b16 [%0], {%1, %2, %3, %4};" ::"r"(a), "r"(r0), "r"(r1), "r"(r2), "r"(r3) : "memory");
}
__device__ __forceinline__ void stsm4t(uint32_t a, uint32_t r0, uint32_t r1, uint32_t r2, uint32_t r3) {
  asm volatile("stmatrix.sync.aligned.m8n8.x4.trans.shared.b16 [%0], {%1, %2, %3, %4};" ::"r"(a), "r"(r0), "r"(r1), "r"(r2), "r"(r3) : "memory");
}
__device__ __forceinline__ void ldsm4(uint32_t a, uint32_t& r0, uint32_t& r1, uint32_t& r2, uint32_t& r3) {
  asm volatile("ldmatrix.sync.aligned.m8n8.x4.shared.b16 {%0, %1, %2, %3}, [%4];" : "=r"(r0), "=r"(r1), "=r"(r2), "=r"(r3) : "r"(a) : "memory");
}
__device__ __forceinline__ void ldsm4t(uint32_t a, uint32_t& r0, uint32_t& r1, uint32_t& r2, uint32_t& r3) {
  asm volatile("ldmatrix.sync.aligned.m8n8.x4.trans.shared.b16 {%0, %1, %2, %3}, [%4];" : "=r"(r0), "=r"(r1), "=r"(r2), "=r"(r3) : "r"(a) : "memory");
}
__device__ __forceinline__ void mma16816(float (&c)[4], uint32_t a0, uint32_t a1, uint32_t a2, uint32_t a3, uint32_t b0, uint32_t b1) {
  asm volatile("mma.sync.aligned.m16n8k16.row.col.f32.bf16.bf16.f32 {%0, %1, %2, %3}, {%4, %5, %6, %7}, {%8, %9}, {%10, %11, %12, %13};"
    : "=f"(c[0]), "=f"(c[1]), "=f"(c[2]), "=f"(c[3]) : "r"(a0), "r"(a1), "r"(a2), "r"(a3), "r"(b0), "r"(b1), "f"(c[0]), "f"(c[1]), "f"(c[2]), "f"(c[3]));
}
__device__ __forceinline__ void sts128(uint32_t a, uint32_t r0, uint32_t r1, uint32_t r2, uint32_t r3) {
  asm volatile("st.shared.v4.b32 [%0], {%1, %2, %3, %4};" ::"r"(a), "r"(r0), "r"(r1), "r"(r2), "r"(r3) : "memory");
}
__device__ __forceinline__ void lds128(uint32_t a, uint32_t& r0, uint32_t& r1, uint32_t& r2, uint32_t& r3) {
  asm volatile("ld.shared.v4.b32 {%0, %1, %2, %3}, [%4];" : "=r"(r0), "=r"(r1), "=r"(r2), "=r"(r3) : "r"(a) : "memory");
}
__device__ __forceinline__ float2 lds64f(uint32_t a) { float2 v; asm volatile("ld.shared.v2.f32 {%0, %1}, [%2];" : "=f"(v.x), "=f"(v.y) : "r"(a) : "memory"); return v; }
__device__ __forceinline__ float4 lds128f(uint32_t a) { float4 v; asm volatile("ld.shared.v4.f32 {%0, %1, %2, %3}, [%4];" : "=f"(v.x), "=f"(v.y), "=f"(v.z), "=f"(v.w) : "r"(a) : "memory"); return v; }
__device__ __forceinline__ void sts64f(uint32_t a, float x, float y) { asm volatile("st.shared.v2.f32 [%0], {%1, %2};" ::"r"(a), "f"(x), "f"(y) : "memory"); }
__device__ __forceinline__ float lds32f(uint32_t a) { float v; asm volatile("ld.shared.f32 %0, [%1];" : "=f"(v) : "r"(a) : "memory"); return v; }
__device__ __forceinline__ void sts32f(uint32_t a, float x) { asm volatile("st.shared.f32 [%0], %1;" ::"r"(a), "f"(x) : "memory"); }
__device__ __forceinline__ void stat_st(uint2* p, float sum, float sq, uint32_t tag, bool on) {
  const float mean = sum * (1.f / 128), m2 = fmaxf(fmaf(-mean, sum, sq), 0.f);
  const uint32_t a = ((__float_as_uint(mean) + 8u) & ~15u) | (tag & 15u), b = ((__float_as_uint(m2) + 8u) & ~15u) | (tag & 15u);
  asm volatile("{\n.reg .b64 x;\n.reg .pred p;\nsetp.ne.u32 p, %3, 0;\nmov.b64 x, {%1, %2};\n@p st.relaxed.gpu.global.b64 [%0], x;\n}\n" ::"l"(p), "r"(a), "r"(b), "r"((uint32_t)on) : "memory");
}
__device__ __forceinline__ void stat_ld2(const uint2* p, uint32_t (&v)[4]) {
  asm volatile("{\n.reg .b64 x, y;\nld.relaxed.gpu.global.v2.b64 {x, y}, [%4];\nmov.b64 {%0, %1}, x;\nmov.b64 {%2, %3}, y;\n}\n"
    : "=r"(v[0]), "=r"(v[1]), "=r"(v[2]), "=r"(v[3]) : "l"(p) : "memory");
}
__device__ __forceinline__ float untag(uint32_t v) { return __uint_as_float(v & ~15u); }
__device__ __forceinline__ void ll_st3(uint4* p, uint32_t a, uint32_t b, uint32_t c, uint32_t tag) {
  asm volatile("{\n.reg .b64 x, y;\n.reg .b128 z;\nmov.b64 x, {%1, %2};\nmov.b64 y, {%3, %4};\nmov.b128 z, {x, y};\nst.relaxed.gpu.global.b128 [%0], z;\n}\n"
    ::"l"(p), "r"(a), "r"(b), "r"(c), "r"(tag) : "memory");
}
__device__ __forceinline__ uint32_t ll_ld3(const uint4* p, uint32_t& a, uint32_t& b, uint32_t& c, uint32_t tag) {
  uint32_t t;
  asm volatile("{\n.reg .b64 x, y;\n.reg .b128 z;\nld.relaxed.gpu.global.b128 z, [%4];\nmov.b128 {x, y}, z;\nmov.b64 {%0, %1}, x;\nmov.b64 {%2, %3}, y;\n}\n"
    : "=r"(a), "=r"(b), "=r"(c), "=r"(t) : "l"(p) : "memory");
  return t ^ tag;
}
__device__ __forceinline__ void halo_send(uint4* p, uint32_t a, const uint32_t (&tg)[6]) {
  asm volatile("{\n.reg .b64 x<6>, y<6>, w<2>;\n.reg .b32 c<4>;\n.reg .b128 z<6>;\n"
    "ld.shared.b64 w0, [%1+1536];\nld.shared.b64 w1, [%1+1792];\n"
    "ld.shared.b64 x0, [%1];\nld.shared.b64 x1, [%1+256];\nld.shared.b64 x2, [%1+512];\n"
    "ld.shared.b64 x3, [%1+768];\nld.shared.b64 x4, [%1+1024];\nld.shared.b64 x5, [%1+1280];\n"
    "mov.b64 {c0, c1}, w0;\nmov.b64 {c2, c3}, w1;\n"
    "mov.b64 y0, {c0, %2};\nmov.b64 y1, {c1, %3};\nmov.b64 y2, {c2, %4};\nmov.b64 y3, {c3, %5};\nmov.b64 y4, {%6, %6};\nmov.b64 y5, {%7, %7};\n"
    "mov.b128 z0, {x0, y0};\nmov.b128 z1, {x1, y1};\nmov.b128 z2, {x2, y2};\nmov.b128 z3, {x3, y3};\nmov.b128 z4, {x4, y4};\nmov.b128 z5, {x5, y5};\n"
    "st.relaxed.gpu.global.b128 [%0], z0;\nst.relaxed.gpu.global.b128 [%0+512], z1;\nst.relaxed.gpu.global.b128 [%0+1024], z2;\n"
    "st.relaxed.gpu.global.b128 [%0+1536], z3;\nst.relaxed.gpu.global.b128 [%0+2048], z4;\nst.relaxed.gpu.global.b128 [%0+2560], z5;\n}\n"
    ::"l"(p), "r"(a), "r"(tg[0]), "r"(tg[1]), "r"(tg[2]), "r"(tg[3]), "r"(tg[4]), "r"(tg[5]) : "memory");
}
template <int N> __device__ __forceinline__ void copy_out(uint8_t* dst, uint32_t src, int stride) {
  uint4 v[N];
#pragma unroll
  for (int k = 0; k < N; k++) lds128(src + k * stride, v[k].x, v[k].y, v[k].z, v[k].w);
#pragma unroll
  for (int k = 0; k < N; k++) asm volatile("st.global.v4.b32 [%0], {%1, %2, %3, %4};" ::"l"(dst + k * stride), "r"(v[k].x), "r"(v[k].y), "r"(v[k].z), "r"(v[k].w) : "memory");
}
__device__ __forceinline__ void warp_store(uint8_t* dst, uint32_t src, int bytes, uint32_t delay, uint32_t pace) {
  __nanosleep(delay);
#pragma unroll 1
  for (int o = 0; o < bytes; o += 2048) {
    if (pace) __nanosleep(pace);
    uint4 v[4];
#pragma unroll
    for (int k = 0; k < 4; k++) lds128(src + o + k * 512, v[k].x, v[k].y, v[k].z, v[k].w);
#pragma unroll
    for (int k = 0; k < 4; k++) asm volatile("st.global.v4.b32 [%0], {%1, %2, %3, %4};" ::"l"(dst + o + k * 512), "r"(v[k].x), "r"(v[k].y), "r"(v[k].z), "r"(v[k].w) : "memory");
  }
  __syncwarp();
}
__device__ __forceinline__ uint32_t clock32() { uint32_t t; asm volatile("mov.u32 %0, %%clock;" : "=r"(t)); return t; }
__device__ __forceinline__ void flag_set(uint32_t* p, uint32_t bit) { asm volatile("red.release.gpu.global.xor.b32 [%0], %1;" ::"l"(p), "r"(bit) : "memory"); }
__device__ __forceinline__ void flag_wait(const uint32_t* p, uint32_t inv, uint32_t need, uint32_t& ready) {
  if ((ready & need) == need) return;
  uint32_t n = 0;
  do {
    asm volatile("ld.relaxed.gpu.global.b32 %0, [%1];" : "=r"(ready) : "l"(p) : "memory");
    ready = __shfl_sync(0xffffffffu, ready, 0) ^ inv;
  } while ((ready & need) != need && ++n < SPIN_MAX);
  asm volatile("fence.acquire.gpu;\nfence.proxy.async.global;" ::: "memory");
}
__device__ __forceinline__ bool elect_one() {
  uint32_t p;
  asm volatile("{\n.reg .pred P;\nelect.sync _|P, 0xffffffff;\nselp.u32 %0, 1, 0, P;\n}\n" : "=r"(p));
  return p;
}
__device__ __forceinline__ float gelu_half(float hx) {
  const float y = hx * fmaf(hx * hx, 8.f * 0.0356774081f, 2.f * 0.7978845608f);
  float th;
  asm("tanh.approx.f32 %0, %1;" : "=f"(th) : "f"(y));
  return fmaf(hx, th, hx);
}
__device__ __forceinline__ float ex2(float x) { float y; asm("ex2.approx.ftz.f32 %0, %1;" : "=f"(y) : "f"(x)); return y; }

__device__ __forceinline__ void stat_combine(uint32_t am, uint32_t aq, uint32_t bm, uint32_t bq, float pv, float& mean, float& var) {
  const float d0 = untag(am) - pv, d1 = untag(bm) - pv;
  float s = d0 + d1, q = fmaf(fmaf(d0, d0, d1 * d1), 128.f, untag(aq) + untag(bq));
  s += __shfl_xor_sync(0xffffffffu, s, 8); q += __shfl_xor_sync(0xffffffffu, q, 8);
  s += __shfl_xor_sync(0xffffffffu, s, 16); q += __shfl_xor_sync(0xffffffffu, q, 16);
  s *= 0.125f;
  mean = pv + s;
  var = fmaxf(fmaf(-s, s, q * (1.f / D_)), 0.f);
}

__device__ __forceinline__ void attn_probs(const uint32_t* q0, const uint32_t* q1,
                                           const uint32_t* k0, const uint32_t* k1, const uint32_t* k2, const uint32_t* k3,
                                           float sc0, float sc1, float mk0, float mk1, bool e, bool zneg, const uint32_t (&sel)[3],
                                           uint32_t (&pr)[6], float (&l)[2]) {
  float s[4][4];
#pragma unroll
  for (int n = 0; n < 4; n++) {
    const uint32_t* k = n == 0 ? k0 : n == 1 ? k1 : n == 2 ? k2 : k3;
    s[n][0] = s[n][1] = n < 2 ? mk0 : 0.f; s[n][2] = s[n][3] = n < 2 ? mk1 : 0.f;
    mma16816(s[n], q0[0], q1[0], q0[1], q1[1], k[0], k[1]);
    mma16816(s[n], q0[2], q1[2], q0[3], q1[3], k[2], k[3]);
  }
  float a0 = e ? s[1][1] : s[1][0];
  float b0 = zneg ? (e ? s[0][1] : s[0][0]) : (e ? s[2][1] : s[2][0]);
  float a1 = e ? s[2][3] : s[2][2];
  float b1 = zneg ? (e ? s[1][3] : s[1][2]) : (e ? s[3][3] : s[3][2]);
  float m0 = fmaxf(a0, b0), m1 = fmaxf(a1, b1);
  m0 = fmaxf(m0, __shfl_xor_sync(0xffffffffu, m0, 1)); m1 = fmaxf(m1, __shfl_xor_sync(0xffffffffu, m1, 1));
  m0 = fmaxf(m0, __shfl_xor_sync(0xffffffffu, m0, 2)); m1 = fmaxf(m1, __shfl_xor_sync(0xffffffffu, m1, 2));
  a0 = ex2((a0 - m0) * sc0); b0 = ex2((b0 - m0) * sc0); a1 = ex2((a1 - m1) * sc1); b1 = ex2((b1 - m1) * sc1);
  l[0] = a0 + b0; l[1] = a1 + b1;
  const uint32_t p0 = pack2(a0, b0), p1 = pack2(a1, b1);
#pragma unroll
  for (int k = 0; k < 3; k++) { pr[k] = __byte_perm(p0, 0u, sel[k]); pr[3 + k] = __byte_perm(p1, 0u, sel[k]); }
}
__device__ __forceinline__ void attn_pv(const uint32_t (&pr)[6], const uint32_t* vh, const uint32_t* v, float (&o)[4][4]) {
#pragma unroll
  for (int dt = 0; dt < 4; dt++) {
    o[dt][0] = o[dt][1] = o[dt][2] = o[dt][3] = 0.f;
    mma16816(o[dt], pr[0], 0u, pr[1], pr[3], vh[2 * dt], vh[2 * dt + 1]);
    mma16816(o[dt], pr[2], pr[4], 0u, pr[5], v[2 * dt], v[2 * dt + 1]);
  }
}

#define ATT 24
#define COVER 2
#define HALO_A_NS 300
#define H1D 900
#define FO 2
#define G4GATE 1
#define PFM 7
#define PD1 3
#define PD2 5
#define PD3 3
#define PD4 5
#define U0D 300
#define X1D 1200
#define PACE 150
#define LEAD1 3
#define LEAD2 3
#define XLD 7
#define XST 3
#define FA 20
#define LEAD4 4
#define STAT_CLK 150
__global__ void __cluster_dims__(2, 1, 1) __launch_bounds__(384, 1) fused_kernel(const __grid_constant__ Params P) {
  extern __shared__ __align__(1024) uint8_t smem_raw[];
  const uint32_t sb = smem_u32(smem_raw);
  const uint32_t bars = sb + OFF_BAR;
  const int tid = threadIdx.x;
  const int wu = __shfl_sync(0xffffffffu, tid >> 5, 0), wg = wu >> 2;
  const int r = blockIdx.x & 1, cl = blockIdx.x >> 1;
  int grp, slt;
  if (cl < 4) { grp = 0; slt = 4 + cl; }
  else if (cl < 36) { grp = (cl - 4) & 7; slt = (cl - 4) >> 3; }
  else { grp = 1 + (cl - 36) % 7; slt = 4 + (cl - 36) / 7; }
#define MAP 0
  const int m = grp, j = slt;
  const int i = 2 * m + r;
  auto BAR = [&](int k) { return bars + 8 * k; };

  auto kb1 = [&](int n) { const int h = n >= 9, t = n - 2 - 7 * h; return n < 2 ? 2 * j + n : 2 * (t + (t >= j)) + h; };
  if (wu == 8) {
    if (elect_one()) {
      asm volatile("prefetch.tensormap [%0];" ::"l"(&P.x0) : "memory");
      asm volatile("prefetch.tensormap [%0];" ::"l"(&P.wqkv) : "memory");
#pragma unroll
      for (int k = 0; k < 6; k++) mbar_init(BAR(k < 4 ? F1 + k : XF + k - 4), 1);
      asm volatile("fence.mbarrier_init.release.cluster;" ::: "memory");
      fence_async_smem();
    }
    __syncwarp();
  } else if (wu == 0) {
    if (elect_one()) {
#pragma unroll
      for (int k = E1; k < 64; k++) {
        int cnt = 1;
        if (k < F2 || (k >= E2 && k < F3) || (k >= E3 && k < F4) || (k >= E4 && k < JOB) || k == JOB + 2 || k == JOB + 3) cnt = 4;
        else if ((k >= JOB && k < RD) || k == CSJ) cnt = 8;
        else if ((k >= RD && k < RD + 2) || k == STD || k == STAT || k >= HALO) cnt = 2;
        if (k != XF && k != XF + 1) mbar_init(BAR(k), cnt);
      }
      asm volatile("fence.mbarrier_init.release.cluster;" ::: "memory");
      fence_async_smem();
    }
    __syncwarp();
  }
  auto load_tag = [&]() { uint32_t t; asm volatile("ld.relaxed.gpu.global.u32 %0, [%1];" : "=r"(t) : "l"(&gEpoch) : "memory"); return t + 1; };
  TS(0);
  if (wu == 8) nb_arrive<NB_INIT>(384); else nb_sync<NB_INIT>(384);
  asm volatile("barrier.cluster.arrive.relaxed;" ::: "memory");

  if (wg == 2) {
    reg_dealloc<40>();
    if (wu == 8) {
    if (elect_one()) {
#pragma unroll 1
      for (int u = 0; u < 4; u++) {
        const int kb = u;
        mbar_expect(BAR(F1 + u), 40960);
        tma2d(sb + slot1(u), &P.x0, BAR(F1 + u), kb * 64, 128 * i);
        tma3d(sb + slot1(u) + 16384, &P.wqkv, BAR(F1 + u), 128 * j, kb * 64, 0);
        tma3d(sb + slot1(u) + 28672, &P.wqkv, BAR(F1 + u), 128 * j, kb * 64 + 32, 0);
      }
    }
    __syncwarp();
    }
    asm volatile("barrier.cluster.wait;" ::: "memory");
    auto kb3 = [&](int n) { const int h = n >= 17, t = n - 2 - 15 * h; return n < 2 ? 2 * i + n : t == 14 ? 2 * (i ^ 1) + h : 2 * ((2 * m + 2 + t) & 15) + h; };
    auto kb2 = [&](int n) { return n < 8 ? 2 * n : n == 8 ? 2 * j + 1 : 2 * (n - 9 + (n - 9 >= j)) + 1; };
    if (wu == 8) {
      const int lane = tid & 31;
      auto pf = [&](const bf16* p, bool on) { if (on) asm volatile("prefetch.global.L2 [%0];" ::"l"(p)); };
      auto v1 = [&](int L, int u) { return (L && u >= 2 && u < 18) ? (u < 4 ? u + 14 : u - 2) : u; };
      auto k1 = [&](int L, int v) { return (L || v >= 16) ? kb1(v & 15) : v; };
      auto kb4f = [&](int n) {
        const int q = n ? n - 8 : 0, c = q >> 4, t = (q & 15) - 1, ii = t < 0 ? i : t < 14 ? (2 * m + 2 + t) & 15 : i ^ 1;
        return (n >= 1 && n <= 8) ? 7 * ((m + n) & 7) + 3 : ((7 * ii + 1) >> 1) + c;
      };
      const uint32_t tab4 = kb4f(lane) | (kb4f(lane + 32) << 16);
      auto kb4 = [&](int n) { return (int)((__shfl_sync(0xffffffffu, tab4, n) >> ((n >> 1) & 16)) & 63); };
      const bf16* const q1 = P.wqkv_p + (4 * i + (lane & 3)) * 3072 + (lane >> 2) * 1024 + 128 * j;
      const bf16* const q2 = P.wo_p + (4 * i + (lane & 3)) * 1024 + (lane >> 2) * 64 + 128 * j;
      const bf16* const q3 = P.w1_p + (8 * j + (lane >> 2)) * 3584 + 64 * (7 * m + ((lane & 3) == 3 ? 3 : 4 * r + (lane & 3)));
      const bf16* const q4 = P.w2_p + (8 * j + (lane >> 1)) * 2048 + 128 * i + 64 * (lane & 1);
      auto pf1 = [&](int L, int u) { const int v = v1(L, u); pf(q1 + k1(L, v) * (64 * 3072) + 64 * (v >> 4), (PFM & 1) && lane < 12); };
      auto pf2 = [&](int n) { pf(q2 + kb2(n) * (64 * 1024), (PFM & 2) && lane < 8); };
      auto pf3 = [&](int n) { pf(q3 + kb3(n) * (64 * 3584), PFM & 4); };
      auto pf4 = [&](int n) { pf(q4 + kb4(n) * (64 * 2048), (PFM & 8) && lane < 16); };
#pragma unroll 1
      for (int u = 4; u < 4 + PD1; u++) pf1(0, u);
#pragma unroll 1
      for (int L = 0; L < 2; L++) {
#pragma unroll 1
        for (int u = L ? 0 : 4; u < 32; u++) {
          const int v = v1(L, u), p = u & 3;
          if (u >= 4) mbar_wait(BAR(E1 + p), ((u >> 2) - 1) & 1);
          else mbar_wait(BAR(E4 + (u == 3 ? 0 : u + 3)), u == 3);
          if (elect_one()) {
            mbar_expect(BAR(F1 + p), (v & 15) < 2 ? 24576 : 40960);
            tma3d_mc(sb + slot1(p) + 16384 + r * 12288, &P.wqkv, BAR(F1 + p), 128 * j + 64 * (v >> 4), k1(L, v) * 64 + 32 * r, 0);
          }
          if (u + PD1 < 32) pf1(L, u + PD1);
          if (u + PD2 >= 32) pf2(u + PD2 - 32);
        }
        int p = 0; uint32_t par = L ? 0x1e : 0;
#pragma unroll 1
        for (int n = 0; n < 16; n++) {
          if (n >= 5) { mbar_wait(BAR(E2 + p), (par >> p) & 1); par ^= 1u << p; }
          else if (n < 4) mbar_wait(BAR(E1 + n), 1);
          if (elect_one()) {
            mbar_expect(BAR(F2 + p), n == 8 ? 16384 : 32768);
            tma2d_mc(sb + slot2(p) + 16384 + r * 8192, &P.wo, BAR(F2 + p), 128 * j + 64 * r, kb2(n) * 64);
          }
          if (++p == 5) p = 0;
          if (n + PD2 < 16) pf2(n + PD2);
          if (n + PD3 + 4 >= 16) pf3(n + PD3 + 4 - 16);
        }
#pragma unroll 1
        for (int u = 0; u < 32; u++) {
          const int n = u < 4 ? (0x2031 >> (4 * u)) & 3 : u, p = n & 3, kb = kb3(n);
          if (n == 4) mbar_wait(BAR(RD + 4), L);
          if (n >= 4) mbar_wait(BAR(E3 + p), ((n >> 2) - 1) & 1);
          else if (n == 1) mbar_wait(BAR(STD + 1), L);
          else if (n == 3) mbar_wait(BAR(E2 + 2), L);
          else if (n == 0) mbar_wait(BAR(E2 + 4), L);
          else mbar_wait(BAR(E2 + 0), 1);
          if (elect_one()) {
            mbar_expect(BAR(F3 + p), n < 2 ? 32768 : 49152);
            tma3d(sb + slot3(p) + 16384, &P.w1, BAR(F3 + p), 0, kb * 64, 7 * m + 4 * r);
            tma3d(sb + slot3(p) + 40960, &P.w1h, BAR(F3 + p), 0, kb * 64, 14 * m + 6 + r);
          }
          if (u >= 4 && u + PD3 < 32) pf3(u + PD3);
          if (u + PD4 + 6 >= 32) pf4(u + PD4 + 6 - 32);
        }
        auto g4w = [&](int n, int p, int kb) {
          if (elect_one()) {
            mbar_expect(BAR(F4 + p), (n == 0 || n == 24 || n == 40) ? 16384 : 32768);
            tma3d(sb + slot4(p), &P.w2, BAR(F4 + p), 0, kb * 64, 2 * i);
          }
        };
#pragma unroll 1
        for (int n = 0; n < 6; n++) {
          const int kb = kb4(n);
          if (n == G4GATE) mbar_wait(BAR(RD + 3), L);
          if (n < 3) mbar_wait(BAR(E3 + n), 1);
          else if (n == 4) mbar_wait(BAR(E3 + 3), 1);
          g4w(n, n, kb);
        }
        p = 0; par = L ? 0x3c : 0;
#pragma unroll 1
        for (int n = 6; n < 56; n++) {
          const int kb = kb4(n);
          if (n + PD4 < 56) pf4(n + PD4);
          mbar_wait(BAR(E4 + p), (par >> p) & 1); par ^= 1u << p;
          g4w(n, p, kb);
          if (++p == 6) p = 0;
        }
        if (L == 0)
#pragma unroll 1
          for (int u = 0; u < PD1; u++) pf1(1, u);
      }
    } else if (wu == 9) {
      uint32_t inv = 0;
#pragma unroll 1
      for (int L = 0; L < 2; L++) {
        uint32_t ready = 0;
#pragma unroll 1
        for (int u = 4; u < 32; u++) {
          const int p = u & 3, nn = (L && u < 18 ? u - 2 : u) & 15, kb = (L || u >= 16) ? kb1(nn) : nn;
          if (L == 0 && (u == XLD || u == XLD + XST) && elect_one()) {
            const int h = u != XLD;
            mbar_expect(BAR(XF + h), 16384);
            tma2d(sb + OFF_X + h * 16384, &P.x0, BAR(XF + h), 128 * j + 64 * h, 128 * i);
          }
          if (nn < 2) continue;
          if (L && u < 12) mbar_wait(BAR(F1 + p), u >> 3);
          if (u >= 4 + 4 * L) mbar_wait(BAR(E1 + p), ((u >> 2) - 1) & 1);
          if (L) {
            flag_wait(gFlag[0][0][i], inv, 1u << kb, ready);
            if (elect_one()) bulk_ld(sb + slot1(p), gXB + (i * 16 + kb) * 16384, 16384, BAR(F1 + p));
          } else if (elect_one()) tma2d(sb + slot1(p), &P.x0, BAR(F1 + p), kb * 64, 128 * i);
        }
        ready = 0;
        if (L == 0) inv = (__shfl_sync(0xffffffffu, load_tag(), 0) & 1) - 1;
        int p = 0; uint32_t par = L ? 0x1e : 0;
#pragma unroll 1
        for (int n = 0; n < 16; n++) {
          const int hp = kb2(n);
          if (n == 8) { par ^= 8; p = 4; continue; }
          if (n >= 5) { mbar_wait(BAR(E2 + p), (par >> p) & 1); par ^= 1u << p; }
          else if (n < 4) mbar_wait(BAR(E1 + n), 1);
          flag_wait(gFlag[L][1][i], inv, 1u << hp, ready);
          if (n == 9) ST(4);
          if (elect_one()) bulk_ld(sb + slot2(p), gOB + (i * 16 + hp) * 16384, 16384, BAR(F2 + p));
          if (++p == 5) p = 0;
        }
        ready = 0;
        mbar_wait(BAR(E2 + 0), 1);
#pragma unroll 1
        for (int n = 2; n < 32; n++) {
          const int p = n & 3, kb = kb3(n);
          if (n > 3) mbar_wait(BAR(E3 + p), ((n >> 2) - 1) & 1);
          flag_wait(gFlag[L][2][j], inv, 1u << kb, ready);
          if (n == 2) ST(12);
          if (elect_one()) {
            const uint8_t* src = gHB + (j * 32 + kb) * 16384;
            if (n != 16 && n != 31) bulk_ld_mc(sb + slot3(p) + r * 8192, src + r * 8192, 8192, BAR(F3 + p));
            else bulk_ld(sb + slot3(p), src, 16384, BAR(F3 + p));
          }
        }
        ready = 0; p = 1; par = L ? 0x3c : 0;
#pragma unroll 1
        for (int t = 0; t < 8; t++) {
          const int mm = (m + t + 1) & 7;
          if (t < 3) mbar_wait(BAR(E3 + 1 + t), 1);
          if (t >= 5) { mbar_wait(BAR(E4 + p), (par >> p) & 1); par ^= 1u << p; }
          flag_wait(gFlag[L][6][j], inv, 3u << (2 * mm), ready);
          if (t == 0) ST(20);
          if (elect_one()) bulk_ld_mc(sb + slot4(p) + 16384 + r * 8192, gUB + (j * 56 + 48 + mm) * 16384 + r * 8192, 8192, BAR(F4 + p));
          if (++p == 6) p = 0;
        }
#pragma unroll 1
        for (int c = 0; c < 3; c++) {
          ready = 0;
          if (c) { par ^= 1u << p; if (++p == 6) p = 0; }
#pragma unroll 1
          for (int t = 0; t < 15; t++) {
            const int ii = t < 14 ? (2 * m + 2 + t) & 15 : i ^ 1;
            mbar_wait(BAR(E4 + p), (par >> p) & 1); par ^= 1u << p;
            flag_wait(gFlag[L][3 + c][j], inv, 1u << ii, ready);
            if (elect_one()) {
              const uint8_t* src = gUB + (j * 56 + 16 * c + ii) * 16384;
              if (t < 14) bulk_ld_mc(sb + slot4(p) + 16384 + r * 8192, src + r * 8192, 8192, BAR(F4 + p));
              else bulk_ld(sb + slot4(p) + 16384, src, 16384, BAR(F4 + p));
            }
            if (++p == 6) p = 0;
          }
        }
      }
    } else {
      const int h = wu - 10, i0 = i, j0 = j;
      {
      const uint32_t tag = load_tag();
      int lane = tid & 31, i = i0, j = j0;
#define FRESH asm volatile("" : "+r"(lane), "+r"(i), "+r"(j))
      auto signal = [&](int k) { if (lane == 0) mbar_arrive(BAR(k)); };
      auto publish = [&](uint32_t* f, int bit) { if (lane == 0) flag_set(f, 1u << bit); __syncwarp(); };
      for (int c = 32 * h + lane; c < 288; c += 64)
        sts16(sb + OFF_B1 + 2 * c, c >= 224 ? 0u : pack2(0.5f * __bfloat162float(P.b1[c < 192 ? 64 * (7 * m + 4 * r) + c : 64 * (7 * m + 3) + 32 * r + c - 192]), 0.f));
      if (h == 0) sts32f(sb + OFF_CS + 768 + 4 * lane, 0.f);
#pragma unroll 1
      for (int L = 0; L < 2; L++) {
        FRESH;
        if (L == 0) {
          mbar_wait(BAR(CSJ), 0);
          float c0 = 0.f, c1 = 0.f, c2 = 0.f;
          const uint32_t a = sb + OFF_STG + (32 * h + lane) * 4;
#pragma unroll 8
          for (int k = 0; k < 32; k++) { c0 += lds32f(a + k * 784); c1 += lds32f(a + k * 784 + 256); c2 += lds32f(a + k * 784 + 512); }
          ll_st3(&gCS[j][i][32 * h + lane], __float_as_uint(c0), __float_as_uint(c1), __float_as_uint(c2), tag);
          __nanosleep(500);
        }
        FRESH;
        if (L == 0) {
#pragma unroll 1
          for (int ab = 0; ab < 2; ab++) {
            float c0 = 0.f, c1 = 0.f, c2 = 0.f;
#pragma unroll 1
            for (int b4 = 0; b4 < 8; b4 += 4) {
              uint32_t a[4], b[4], c[4], n = 0, bad;
              do {
                bad = 0;
#pragma unroll
                for (int e = 0; e < 4; e++) bad |= ll_ld3(&gCS[j][2 * (b4 + e) + ab][32 * h + lane], a[e], b[e], c[e], tag);
              } while (bad && ++n < SPIN_MAX);
#pragma unroll
              for (int e = 0; e < 4; e++) { c0 += __uint_as_float(a[e]); c1 += __uint_as_float(b[e]); c2 += __uint_as_float(c[e]); }
            }
            const uint32_t a = sb + OFF_CS + ab * 768 + (4 * h + (lane >> 3)) * 32 + (lane & 7) * 2;
            const uint32_t h0 = pack2(c0, 0.f), h1 = pack2(c1, 0.f), h2 = pack2(c2, 0.f);
            sts16(a, h0); sts16(a + 256, h1); sts16(a + 512, h2);
            sts16(a + 16, pack2(c0 - bf_lo(h0), 0.f)); sts16(a + 272, pack2(c1 - bf_lo(h1), 0.f)); sts16(a + 528, pack2(c2 - bf_lo(h2), 0.f));
            fence_async_smem();
            __syncwarp();
            if (ab == 0) signal(STAT);
          }
        }
#pragma unroll 1
        for (int ab = 0; ab < 2; ab++) {
          FRESH;
          uint32_t v[18], tg[6];
          const uint32_t xs = sb + OFF_STG + h * 16384 + lane * 8;
          uint4* hp = &gHalo[L][i][j][6 * h][lane];
#pragma unroll
          for (int c = 0; c < 6; c++) { tg[c] = (2 * tag + ab) * 8 + c; asm volatile("" : "+r"(tg[c])); }
          asm volatile("" : "+l"(hp));
          mbar_wait(BAR(FOLD + ab), L);
          if (ab && h == 0) ST(6);
          if (i < 15) {
            halo_send(hp, xs, tg);
          }
          if (ab && h == 0) ST(26);
          if (i > 0) {
            if (!ab) __nanosleep(HALO_A_NS);
            uint32_t n = 0, bad;
            do {
              bad = 0;
#pragma unroll
              for (int c = 0; c < 6; c++) bad |= ll_ld3(hp + c * 32 - 8 * 12 * 32, v[3 * c], v[3 * c + 1], v[3 * c + 2], (2 * tag + ab) * 8);
              if (ab && h == 0 && n == 0) ST(28);
            } while (bad > 7 && ++n < SPIN_MAX);
            if (ab && h == 0) ST(27);
          } else {
#pragma unroll
            for (int c = 0; c < 18; c++) v[c] = 0u;
          }
#pragma unroll
          for (int c = 0; c < 6; c++) sts64f(xs + c * 256, __uint_as_float(v[3 * c]), __uint_as_float(v[3 * c + 1]));
          sts64f(xs + 1536, __uint_as_float(v[2]), __uint_as_float(v[5]));
          sts64f(xs + 1792, __uint_as_float(v[8]), __uint_as_float(v[11]));
          __syncwarp();
          signal(HALO + ab);
          if (ab && h == 0) ST(7);
          FRESH;
          if (ab == 0 && lane == 0) asm volatile("st.relaxed.gpu.global.u32 [%0], %1;" ::"l"(&gAck[L][i][j][h][0]), "r"(tag) : "memory");
          mbar_wait(BAR(JOB + ab), L);
          if (h == 0) {
            if (ab) ST(1);
            if (lane == 0) { bulk_st(gOB + (i * 16 + 2 * j + ab) * 16384, sb + OFF_STG, 16384); bulk_commit(); bulk_wait0(); }
            signal(STD + ab);
            if (ab) ST(2);
            publish(gFlag[L][1][i], 2 * j + ab);
            if (ab) ST(3);
          } else if (ab == 0) {
            if (i < 15 && lane < 2) {
              uint32_t t, n = 0;
              do { asm volatile("ld.relaxed.gpu.global.u32 %0, [%1];" : "=r"(t) : "l"(&gAck[L][i + 1][j][lane][0]) : "memory"); } while (t != tag && ++n < SPIN_MAX);
            }
            __syncwarp();
            signal(STD);
          }
        }
        FRESH;
        if (h == 0) {
          mbar_wait(BAR(JOB + 2), L);
          ST(9);
          signal(RD);
          ST(10);
          publish(gFlag[L][2][j], 2 * i);
          ST(11);
          signal(RD + 4);
          nb_arrive<NB_HELP>(64);
        } else {
          mbar_wait(BAR(JOB + 3), L);
          nb_sync<NB_HELP>(64);
          warp_store(gHB + (j * 32 + 2 * i + 1) * 16384 + lane * 16, sb + lane * 16 + OFF_X + 16384, 16384, H1D, PACE);
          signal(RD);
          ST(15);
          publish(gFlag[L][2][j], 2 * i + 1);
        }
        FRESH;
        if (h == 0) {
          mbar_wait(BAR(JOB + 7), L);
          ST(17);
          publish(gFlag[L][6][j], i);
          ST(19);
          signal(RD + 3);
        } else {
          mbar_wait(BAR(JOB + 4), L);
          __nanosleep(U0D);
          if (lane == 0) { bulk_st(gUB + (j * 56 + i) * 16384, sb + OFF_X, 16384); bulk_commit(); bulk_wait0(); }
          signal(RD + 2); ST(25);
          publish(gFlag[L][3][j], i);
        }
        mbar_wait(BAR(JOB + 5 + h), L);
        warp_store(gUB + (j * 56 + 16 + 16 * h + i) * 16384 + lane * 16, sb + lane * 16 + OFF_X + (1 - h) * 16384, 16384, 0, PACE);
        ST(23 + h);
        signal(RD + 1);
        publish(gFlag[L][4 + h][j], i);
        FRESH;
        if (L == 0) {
          mbar_wait(BAR(JOB + 8 + h), 0);
          if (h == 1) warp_store(gXB + (i * 16 + 2 * j + 1) * 16384 + lane * 16, sb + lane * 16 + OFF_X + 16384, 16384, X1D, 0);
          publish(gFlag[0][0][i], 2 * j + h);
        }
      }
      if (blockIdx.x == 0 && h == 0 && lane == 0) asm volatile("st.relaxed.gpu.global.u32 [%0], %1;" ::"l"(&gEpoch), "r"(tag) : "memory");
      }
    }
    __syncwarp();
    cluster_bar();
  } else {
    reg_alloc<232>();
    asm volatile("barrier.cluster.wait;" ::: "memory");
    const uint32_t rbars = mapa(bars, tid & 1);
    const bool relp = (tid & 127) < 2;
    const uint32_t sd = (sb & 0x3FFFF) >> 4, sda = sd + wg * 512;
    uint32_t tag;
    asm volatile("ld.relaxed.gpu.global.u32 %0, [%1];" : "=r"(tag) : "l"(&gEpoch + (fresh_tid() >> 10)) : "memory");
    auto release = [&](int k) { if (relp) mbar_arrive_cl(rbars + 8 * k); };
    auto signal = [&](int k) { __syncwarp(); if ((fresh_tid() & 31) == 0) mbar_arrive(BAR(k)); };
#define GEOM const int t7 = fresh_tid() & 127, lane = t7 & 31, w = t7 >> 5, g = lane >> 2, q = lane & 3, \
                       lr = lane & 15, lt = lane >> 4, l7 = lane & 7; (void)w; (void)g; (void)q; (void)lr; (void)lt; (void)l7

#pragma unroll 1
    for (int L = 0; L < 2; L++) {
      float acca[96], accb[96], xa[64], acc3[112];
      float nmean0, nmean1, rstd0, rstd1;
      uint16_t b2a, b2b;
      uint2 *e2p, *e2s; uint8_t* e2g; uint32_t e2h;
      uint32_t Q[2][8], K[2][8], V[16];
      auto g1_issue = [&](float (&acc)[96], uint32_t a, uint32_t st, auto first) {
        const uint32_t da = sda + (a >> 4), db = sd + (st >> 4);
        wg_fence();
        static_for<0, 4>([&](auto kk) {
          constexpr uint32_t ia = DI(kk.value * 32, 16), ib = DI(16384 + (kk.value >> 1) * 12288 + (kk.value & 1) * 2048, 4096);
          if constexpr (first.value && kk.value == 0) wgmma_192z<0, 1, ia, ib>(acc, da, db); else wgmma_192<0, 1, ia, ib>(acc, da, db);
        });
        wg_commit();
      };
      auto g1_step = [&](float (&acc)[96], int u, bool rel, bool lead = false) {
        const int p = u & 3;
        mbar_wait(BAR(F1 + p), (u >> 2) & 1);
        KB(u);
        g1_issue(acc, slot1(p), slot1(p), False{});
        if (lead) nb_arrive<NB_LEAD>(256);
        wg_wait<1>();
        if (rel) release(E1 + ((u - 1) & 3));
      };
      auto g1_loop = [&](float (&acc)[96], int u0, int u1, int urel) {
        int u = u0;
#pragma unroll 1
        do { g1_step(acc, u, u > urel); } while (++u < u1);
      };
      auto load_x = [&]() {
        GEOM;
#pragma unroll
        for (int t = 0; t < 16; t += 2) {
          uint32_t v0, v1, v2, v3;
          ldsm4(sb + OFF_X + (t >> 3) * 16384 + (16 * wu + lr) * 128 + ((((t & 7) + lt) ^ l7) << 4), v0, v1, v2, v3);
          xa[4 * t + 0] = bf_lo(v0); xa[4 * t + 1] = bf_hi(v0); xa[4 * t + 2] = bf_lo(v1); xa[4 * t + 3] = bf_hi(v1);
          xa[4 * t + 4] = bf_lo(v2); xa[4 * t + 5] = bf_hi(v2); xa[4 * t + 6] = bf_lo(v3); xa[4 * t + 7] = bf_hi(v3);
        }
      };
      auto stat_base = [&]() { return &gST[0][0][0][0][0] + ((L * 16 + opq(i)) * 8 + wu) * 128; };
      auto stat_slot = [&]() { const int lane = fresh_tid() & 31; return stat_base() + 16 * j + 2 * (lane >> 2) + (lane & 1); };
      auto stat_publish = [&](uint2* sp, float s0, float q0, float s2, float q2, uint32_t tg) {
        const int q = fresh_tid() & 3;
        const bool h1 = q & 1;
        float sm = (h1 ? s2 : s0) + __shfl_xor_sync(0xffffffffu, h1 ? s0 : s2, 1);
        float sq = (h1 ? q2 : q0) + __shfl_xor_sync(0xffffffffu, h1 ? q0 : q2, 1);
        sm += __shfl_xor_sync(0xffffffffu, sm, 2); sq += __shfl_xor_sync(0xffffffffu, sq, 2);
        stat_st(sp, sm, sq, tg, q < 2);
        return sm;
      };
      auto g1_stats = [&](int u0) {
        GEOM;
        const uint32_t xr = sb + OFF_X + (16 * wu + lr) * 128;
        float s0 = 0.f, q0 = 0.f, s2 = 0.f, q2 = 0.f;
        uint32_t v[8] = {0u, 0u, 0u, 0u, 0u, 0u, 0u, 0u};
#pragma unroll 1
        for (int k = 0; k < 5; k++) {
#pragma unroll
          for (int e = 0; e < 8; e += 2) {
            const float a = bf_lo(v[e]), b = bf_hi(v[e]), c = bf_lo(v[e + 1]), d = bf_hi(v[e + 1]);
            s0 += a + b; q0 = fmaf(a, a, fmaf(b, b, q0)); s2 += c + d; q2 = fmaf(c, c, fmaf(d, d, q2));
          }
          if (k == 4) break;
          const uint32_t o = ((2 * k + lt) ^ l7) << 4;
          ldsm4(xr + o, v[0], v[1], v[2], v[3]);
          ldsm4(xr + o + 16384, v[4], v[5], v[6], v[7]);
          g1_step(acca, u0 + k, true);
        }
        stat_publish(stat_slot(), s0, q0, s2, q2, 2 * (tag + 1));
      };
      uint32_t sv0[4], sv1[4];
      auto stat_src = [&]() { return stat_base() + 2 * (fresh_tid() & 31); };
      auto stat_fetch = [&](const uint2* sp) { stat_ld2(sp, sv0); stat_ld2(sp + 64, sv1); };
      auto stat_await = [&](auto src, uint32_t tg) {
#pragma unroll 1
        for (uint32_t n = 0; (((sv0[0] ^ tg) | (sv0[2] ^ tg) | (sv1[0] ^ tg) | (sv1[2] ^ tg)) & 15u) && n < SPIN_MAX; n++) stat_fetch(src());
        __syncwarp();
      };
      auto ln_stats = [&]() {
        GEOM;
        stat_await(stat_src, 2 * (tag + 1));
        float mean0, var0, mean1, var1;
        stat_combine(sv0[0], sv0[1], sv1[0], sv1[1], untag(__shfl_sync(0xffffffffu, sv0[0], l7)), mean0, var0);
        stat_combine(sv0[2], sv0[3], sv1[2], sv1[3], untag(__shfl_sync(0xffffffffu, sv0[2], l7)), mean1, var1);
        nmean0 = -__shfl_sync(0xffffffffu, mean0, g); rstd0 = rsq(__shfl_sync(0xffffffffu, var0, g) + 1e-5f);
        nmean1 = -__shfl_sync(0xffffffffu, mean1, g); rstd1 = rsq(__shfl_sync(0xffffffffu, var1, g) + 1e-5f);
      };
      auto center = [&](float (&acc)[96], int ab) {
        const bool q0 = (fresh_tid() & 3) == 0;
        const uint32_t h0 = pack2(nmean0, nmean0), h1 = pack2(nmean1, nmean1);
        const float l0 = nmean0 - bf_lo(h0), l1 = nmean1 - bf_lo(h1);
        const uint32_t a0 = q0 ? h0 : 0u, a1 = q0 ? h1 : 0u, a2 = q0 ? pack2(l0, l0) : 0u, a3 = q0 ? pack2(l1, l1) : 0u;
        wg_fence();
        wgmma_rs_192(acc, a0, a1, a2, a3, mkdesc_vec(sb + OFF_CS + ab * 768, 32));
      };
      auto frag = [&](float (&acc)[96], int t, uint32_t& p0, uint32_t& p1) {
        if (t >= 8) { p0 = pack2(acc[4 * t] * rstd0, acc[4 * t + 1] * rstd0); p1 = pack2(acc[4 * t + 2] * rstd1, acc[4 * t + 3] * rstd1); }
        else { p0 = pack2(acc[4 * t], acc[4 * t + 1]); p1 = pack2(acc[4 * t + 2], acc[4 * t + 3]); }
      };
      auto fold_v = [&](float (&acc)[96], int t0, int t1) {
        GEOM;
        const uint32_t a = sb + OFF_STG + 16384 + ((wu + 1) & 7) * 2048 + lr * 128;
#pragma unroll
        for (int t = t0; t < t1; t += 2) {
          uint32_t p0, p1, p2, p3;
          frag(acc, 16 + t, p0, p1); frag(acc, 17 + t, p2, p3);
          stsm4(a + (((t + lt) ^ l7) << 4), p0, p1, p2, p3);
        }
        __syncwarp();
#pragma unroll
        for (int t = t0; t < t1; t += 2) ldsm4t(a + (((t + lt) ^ l7) << 4), V[2 * t], V[2 * t + 1], V[2 * t + 2], V[2 * t + 3]);
      };
      auto fold_k = [&](float (&acc)[96], int ab, int h0, int h1) {
        GEOM;
        const uint32_t a = sb + OFF_STG + ((wu + 1) & 7) * 2048 + lane * 16;
#pragma unroll
        for (int hh = h0; hh < h1; hh++) {
#pragma unroll
          for (int t = 4 * hh; t < 4 * hh + 4; t++) frag(acc, 8 + t, K[0][t], K[1][t]);
#pragma unroll
          for (int o = 0; o < 2; o++) sts128(a + (2 * o + hh) * 512, K[o][4 * hh], K[o][4 * hh + 1], K[o][4 * hh + 2], K[o][4 * hh + 3]);
        }
        if (h1 == 2 && wu == 7) signal(FOLD + ab);
      };
      auto fold_q = [&](float (&acc)[96]) {
#pragma unroll
        for (int t = 0; t < 8; t++) frag(acc, t, Q[0][t], Q[1][t]);
      };
      auto attend = [&](int ab, auto drain, auto resume) {
        GEOM;
        nb_sync<NB_BOTH>(256);
        const uint32_t xa_ = sb + OFF_STG + wu * 2048 + lane * 16;
        if (wu == 0) mbar_wait(BAR(HALO + ab), L);
        uint32_t KH[2][8], VH[16];
#pragma unroll
        for (int c = 0; c < 4; c++) {
          lds128(xa_ + c * 512, KH[c >> 1][4 * (c & 1)], KH[c >> 1][4 * (c & 1) + 1], KH[c >> 1][4 * (c & 1) + 2], KH[c >> 1][4 * (c & 1) + 3]);
          ldsm4t(sb + OFF_STG + 16384 + wu * 2048 + lr * 128 + (((2 * c + lt) ^ l7) << 4), VH[4 * c], VH[4 * c + 1], VH[4 * c + 2], VH[4 * c + 3]);
        }
        TS2(11 + ab + 32 * L);
        const bool e = g & 1, zneg = (g >> 1) < q, first = (i == 0) && (wu == 0);
        const float sc0 = rstd0 * (0.17677669530f * 1.4426950409f), sc1 = rstd1 * (0.17677669530f * 1.4426950409f);
        float mk0 = first ? __fdividef(-1.0e9f * 1.4426950409f, sc0) : 0.f, mk1 = first ? __fdividef(-1.0e9f * 1.4426950409f, sc1) : 0.f;
        const uint32_t sa = e ? 0x1044u : 0x4410u, sbb = e ? 0x3244u : 0x4432u;
        uint32_t sel[3] = {zneg ? sbb : 0x4444u, sa, zneg ? 0x4444u : sbb};
        uint32_t oa = sb + OFF_STG + (16 * wu + lr) * 128 + ((lt ^ l7) << 4);
        asm volatile("" : "+r"(sel[0]), "+r"(sel[1]), "+r"(sel[2]), "+r"(oa), "+f"(mk0), "+f"(mk1));
        drain();
        uint32_t pr[2][6];
        float l[2][2];
#pragma unroll
        for (int hh = 0; hh < 2; hh++)
          attn_probs(&Q[0][4 * hh], &Q[1][4 * hh], &KH[0][4 * hh], &KH[1][4 * hh], &K[0][4 * hh], &K[1][4 * hh], sc0, sc1, mk0, mk1, e, zneg, sel, pr[hh], l[hh]);
        float o[2][4][4];
#pragma unroll
        for (int hh = 0; hh < 2; hh++) attn_pv(pr[hh], &VH[8 * hh], &V[8 * hh], o[hh]);
#pragma unroll
        for (int hh = 0; hh < 2; hh++) {
          float l0 = l[hh][0], l1 = l[hh][1];
          l0 += __shfl_xor_sync(0xffffffffu, l0, 1); l1 += __shfl_xor_sync(0xffffffffu, l1, 1);
          l0 += __shfl_xor_sync(0xffffffffu, l0, 2); l1 += __shfl_xor_sync(0xffffffffu, l1, 2);
          asm("rcp.approx.ftz.f32 %0, %0;" : "+f"(l0)); asm("rcp.approx.ftz.f32 %0, %0;" : "+f"(l1));
#pragma unroll
          for (int dt = 0; dt < 4; dt += 2)
            stsm4(oa ^ ((4 * hh + dt) << 4),
                  pack2(o[hh][dt][0] * l0, o[hh][dt][1] * l0), pack2(o[hh][dt][2] * l1, o[hh][dt][3] * l1),
                  pack2(o[hh][dt + 1][0] * l0, o[hh][dt + 1][1] * l0), pack2(o[hh][dt + 1][2] * l1, o[hh][dt + 1][3] * l1));
        }
        fence_async_smem();
        signal(JOB + ab);
        nb_sync<NB_BOTH>(256);
        resume();
      };

      TS(1 + 32 * L);
      mbar_wait(BAR(F1), 0); KB(0);    g1_issue(acca, L ? OFF_X : slot1(0), slot1(0), True{});
      mbar_wait(BAR(F1 + 1), 0); KB(1); g1_issue(acca, L ? OFF_X + 16384 : slot1(1), slot1(1), False{});
      wg_wait<1>(); release(E1 + 0);
      auto g1_bhead = [&](int p) {
        mbar_wait(BAR(F1 + p), 0); KB(p ? 2 : 16); g1_issue(accb, OFF_X, slot1(p), True{});
        if (p) { wg_wait<1>(); release(E1 + 1); }
        mbar_wait(BAR(F1 + p + 1), 0); KB(p ? 3 : 17); g1_issue(accb, OFF_X + 16384, slot1(p + 1), False{});
        wg_wait<1>(); release(E1 + p);
      };
      if (L == 0) {
        GEOM;
        const bf16* wp = P.wqkv_p + ((128 * opq(m) + 16 * wg + (t7 >> 3)) * 3072 + 128 * opq(j) + 64 * r + l7 * 8);
        const uint32_t ca = sb + OFF_STG + (16 * wg + (t7 >> 3)) * 784 + l7 * 32;
#pragma unroll 1
        for (int p = 0; p < 3; p++) {
          uint4 wv[4];
#pragma unroll
          for (int k = 0; k < 4; k++)
            asm volatile("ld.global.nc.v4.u32 {%0, %1, %2, %3}, [%4];" : "=r"(wv[k].x), "=r"(wv[k].y), "=r"(wv[k].z), "=r"(wv[k].w)
                         : "l"(wp + k * 32 * 3072 + p * 1024));
          g1_loop(acca, 2 + 3 * p, 5 + 3 * p, 0);
          float cs[8];
#pragma unroll
          for (int k = 0; k < 4; k++) {
            const uint4 v = wv[k];
            const float t[8] = {bf_lo(v.x), bf_hi(v.x), bf_lo(v.y), bf_hi(v.y), bf_lo(v.z), bf_hi(v.z), bf_lo(v.w), bf_hi(v.w)};
#pragma unroll
            for (int e = 0; e < 8; e++) cs[e] = k ? cs[e] + t[e] : t[e];
          }
          sts128(ca + p * 256, __float_as_uint(cs[0]), __float_as_uint(cs[1]), __float_as_uint(cs[2]), __float_as_uint(cs[3]));
          sts128(ca + p * 256 + 16, __float_as_uint(cs[4]), __float_as_uint(cs[5]), __float_as_uint(cs[6]), __float_as_uint(cs[7]));
        }
        signal(CSJ);
        g1_step(acca, 11, true);
        mbar_wait(BAR(XF), 0); mbar_wait(BAR(XF + 1), 0);
        g1_stats(12);
        wg_wait<0>(); release(E1 + 3);
        fence_regs(acca);
        g1_bhead(0);
      } else {
        g1_bhead(2);
        g1_stats(4);
        g1_loop(acca, 8, 18, 0);
      }
      stat_fetch(stat_src());
      const int fa = FA + (wg ? 0 : FO);
      g1_loop(accb, 18, fa, 0);
      ln_stats();
      if (L == 0) mbar_wait(BAR(STAT), 0);
      center(acca, 0); wg_commit();
      wg_wait<0>(); release(E1 + ((fa - 1) & 3));
      fence_regs(acca);
      TS(2 + 32 * L);
      fold_v(acca, 0, 8); fold_k(acca, 0, 0, 2); fold_q(acca);
      sched_fence(P.zero);
      g1_loop(accb, fa, ATT, fa);
      attend(0, [&]() { wg_wait<0>(); release(E1 + ((ATT - 1) & 3)); mbar_wait(BAR(F1 + (ATT & 3)), (ATT >> 2) & 1); },
             [&]() { KB(ATT); g1_issue(accb, slot1(ATT & 3), slot1(ATT & 3), False{});
                     mbar_wait(BAR(F1 + ((ATT + 1) & 3)), ((ATT + 1) >> 2) & 1);
                     KB(ATT + 1); g1_issue(accb, slot1((ATT + 1) & 3), slot1((ATT + 1) & 3), False{}); });
      wg_wait<1>(); release(E1 + (ATT & 3));
      TS(3 + 32 * L);
      load_x();
      fence_regs(xa);
      center(accb, 1);
#pragma unroll 1
      for (int u = ATT + 2; u < 32; u++) {
        const bool hold = u == 32 - LEAD1 && wg == 0;
        if (hold) { wg_wait<0>(); release(E1 + ((31 - LEAD1) & 3)); nb_sync<NB_LEAD>(256); }
        g1_step(accb, u, !hold, u == 31 && wg == 1);
      }
      mbar_wait(BAR(STD), L);
      wg_wait<0>(); release(E1 + 3);
      fence_regs(accb);
      TS(4 + 32 * L);
      if (wu == 7) ST(0);
      fold_v(accb, 0, 8); fold_k(accb, 1, 0, 2);
      fold_q(accb);
      TS2(29 + 32 * L);
      {
        auto g2_issue = [&](int p, bool own) {
          const uint32_t st = slot2(p);
          const uint32_t da = sda + ((own ? OFF_STG : st) >> 4), db = sd + (st >> 4);
          wg_fence();
          static_for<0, 4>([&](auto kk) { wgmma_128<0, 1, DI(kk.value * 32, 16), DI(16384 + kk.value * 2048, 8192)>(xa, da, db); });
          wg_commit();
        };
        uint32_t par = L ? 0x1e : 0;
        int p = 0, pp = 0;
        auto g2_loop = [&](int n0, int n1, int nrel) {
#pragma unroll 1
          for (int n = n0; n < n1; n++) {
            mbar_wait(BAR(F2 + p), (par >> p) & 1);
            KB(32 + n);
            if (n == 9 && wu == 0) ST(5);
            par ^= 1u << p;
            g2_issue(p, n == 8);
            if (n1 == 16 && n == 15 && wg == 0) nb_arrive<NB_LEAD>(256);
            wg_wait<1>();
            if (n > nrel) release(E2 + pp);
            pp = p; if (++p == 5) p = 0;
          }
        };
        g2_loop(0, COVER, 0);
        attend(1, [&]() { wg_wait<0>(); release(E2 + COVER - 1); mbar_wait(BAR(F2 + COVER), (par >> COVER) & 1); },
               [&]() { KB(32 + COVER); g2_issue(COVER, false);
                       mbar_wait(BAR(F2 + COVER + 1), (par >> (COVER + 1)) & 1);
                       KB(33 + COVER); g2_issue(COVER + 1, false); });
        wg_wait<1>(); release(E2 + COVER);
        par ^= 3u << COVER; pp = COVER + 1; p = (COVER + 2) % 5;
        TS(30 + 32 * L);
        {
          const bf16* bp = P.b2 + (128 * opq(i) + 16 * wu + ((fresh_tid() & 31) >> 2));
          asm volatile("ld.global.nc.u16 %0, [%1];" : "=h"(b2a) : "l"(bp));
          asm volatile("ld.global.nc.u16 %0, [%1];" : "=h"(b2b) : "l"(bp + 8));
        }
        TS2(14 + 32 * L);
        {
          GEOM;
          e2p = stat_slot(); e2s = stat_src();
          e2g = gHB + (opq(j) * 32 + 2 * i) * 16384 + w * 2048 + lane * 16;
          e2h = sb + OFF_X + wg * 16384 + (16 * w + lr) * 128 + ((lt ^ l7) << 4);
          asm volatile("" : "+l"(e2p), "+l"(e2s), "+l"(e2g), "+r"(e2h));
        }
        g2_loop(COVER + 2, 16 - LEAD2, 0);
        if (wg == 1) { wg_wait<0>(); release(E2 + pp); nb_sync<NB_LEAD>(256); }
        g2_loop(16 - LEAD2, 16, wg == 1 ? 16 - LEAD2 : 0);
        wg_wait<0>();
        release(E2 + 0);
        fence_regs(xa);
      }
      TS(5 + 32 * L);
      if (wu == 0) ST(8);
      {
        GEOM;
        const uint32_t tg = 2 * (tag + 1) + 1;
        float s0 = 0.f, s1 = 0.f, s2 = 0.f, s3 = 0.f, q0 = 0.f, q1 = 0.f, q2 = 0.f, q3 = 0.f;
#pragma unroll
        for (int t = 0; t < 16; t++) {
          s0 += xa[4 * t]; s1 += xa[4 * t + 1]; s2 += xa[4 * t + 2]; s3 += xa[4 * t + 3];
          q0 = fmaf(xa[4 * t], xa[4 * t], q0); q1 = fmaf(xa[4 * t + 1], xa[4 * t + 1], q1);
          q2 = fmaf(xa[4 * t + 2], xa[4 * t + 2], q2); q3 = fmaf(xa[4 * t + 3], xa[4 * t + 3], q3);
        }
        const float sm = stat_publish(e2p, s0 + s1, q0 + q1, s2 + s3, q2 + q3, tg);
        const uint32_t t0 = clock32();
        TS2(13 + 32 * L);
        const float pv0 = __shfl_sync(0xffffffffu, sm, 4 * l7) * (1.f / 128), pv1 = __shfl_sync(0xffffffffu, sm, 4 * l7 + 1) * (1.f / 128);
        while (clock32() - t0 < STAT_CLK) {}
        stat_fetch(e2s);
        wg_fence();
        wgmma_rs_224z(acc3, q == 0 ? 0x3f80u : 0u, q == 0 ? 0x3f80u : 0u, 0u, 0u, mkdesc_vec(sb + OFF_B1, 16));
        wg_commit();
        stat_await([&]() { return e2s; }, tg);
        float r0, m0, r1, m1;
        {
          float mean0, var0, mean1, var1;
          stat_combine(sv0[0], sv0[1], sv1[0], sv1[1], pv0, mean0, var0); stat_combine(sv0[2], sv0[3], sv1[2], sv1[3], pv1, mean1, var1);
          mean0 = __shfl_sync(0xffffffffu, mean0, g); var0 = __shfl_sync(0xffffffffu, var0, g);
          mean1 = __shfl_sync(0xffffffffu, mean1, g); var1 = __shfl_sync(0xffffffffu, var1, g);
          r0 = 0.5f * rsq(fmaf(var0 + 1e-5f, 1e-5f, var0)); r1 = 0.5f * rsq(fmaf(var1 + 1e-5f, 1e-5f, var1));
          m0 = -mean0 * r0; m1 = -mean1 * r1;
        }
        TS2(15 + 32 * L);
#pragma unroll
        for (int t = 0; t < 16; t += 2) {
          stsm4((e2h ^ ((t & 7) << 4)) + (t >> 3) * 8192,
                pack2(fmaf(xa[4 * t], r0, m0), fmaf(xa[4 * t + 1], r0, m0)), pack2(fmaf(xa[4 * t + 2], r1, m1), fmaf(xa[4 * t + 3], r1, m1)),
                pack2(fmaf(xa[4 * t + 4], r0, m0), fmaf(xa[4 * t + 5], r0, m0)), pack2(fmaf(xa[4 * t + 6], r1, m1), fmaf(xa[4 * t + 7], r1, m1)));
          if ((t & 7) == 6 && wg == 0) {
            __syncwarp();
            copy_out<4>(e2g + (t >> 3) * 8192, sb + OFF_X + (t >> 3) * 8192 + w * 2048 + lane * 16, 512);
          }
        }
        signal(JOB + 2 + wg);
        fence_async_smem();
        mbar_wait(BAR(F3 + 0), 0);
        nb_sync<NB_BOTH>(256);
      }
      TS(6 + 32 * L);
      auto g3_issue = [&](uint32_t a, int p) {
        const uint32_t da = sda + (a >> 4), db = sd + (slot3(p) >> 4);
        wg_fence();
        static_for<0, 4>([&](auto kk) { wgmma_224<1, 1, DI(kk.value * 2048, 8192), DI(16384 + kk.value * 2048, 8192)>(acc3, da, db); });
        wg_commit();
      };
      KB(48); g3_issue(OFF_X, 0);
      mbar_wait(BAR(F3 + 1), 0); KB(49); g3_issue(OFF_X + 16384, 1);
      sched_fence(P.zero);
      {
        const float c0 = __uint_as_float((uint32_t)b2a << 16), c1 = __uint_as_float((uint32_t)b2b << 16);
#pragma unroll
        for (int t = 0; t < 16; t++) { xa[4 * t] += c0; xa[4 * t + 1] += c0; xa[4 * t + 2] += c1; xa[4 * t + 3] += c1; }
        fence_regs(xa);
      }
      wg_wait<1>(); release(E3 + 0);
      auto g3_loop = [&](int n0, int n1, int nrel) {
#pragma unroll 1
        for (int n = n0; n < n1; n++) {
          const int p = n & 3;
          mbar_wait(BAR(F3 + p), (n >> 2) & 1);
          KB(48 + n);
          if (n == 3 && wu == 0) ST(13);
          if (n == 2 && wu == 0) ST(14);
          g3_issue(slot3(p), p);
          wg_wait<1>();
          if (n > nrel) release(E3 + ((n - 1) & 3));
        }
      };
      g3_loop(2, 29, 0);
      uint32_t ua;
      uint8_t* ug;
      {
        GEOM;
        ua = sb + OFF_X + wg * 8192 + (8 * lt + l7) * 128 + (((2 * w + ((lane >> 3) & 1)) ^ l7) << 4);
        ug = gUB + (opq(j) * 56 + 48 + m) * 16384 + r * 4096 + wg * 8192 + (lane >> 1) * 128 + (((2 * w + (lane & 1)) ^ ((lane >> 1) & 7)) << 4);
      }
      auto gelu8 = [&](int c, int k) {
        const int o = 32 * c + 8 * k;
        stsm4t(ua + (c & 1) * 16384 + k * 2048,
               pack2(gelu_half(acc3[o]), gelu_half(acc3[o + 1])), pack2(gelu_half(acc3[o + 2]), gelu_half(acc3[o + 3])),
               pack2(gelu_half(acc3[o + 4]), gelu_half(acc3[o + 5])), pack2(gelu_half(acc3[o + 6]), gelu_half(acc3[o + 7])));
      };
      {
        auto part = [&](auto p, auto half) {
          static_for<0, 4>([&](auto kk) {
            constexpr uint32_t o = slot3(p.value) + kk.value * 2048;
            if constexpr (half.value) wgmma_32<1, 1, DI(o, 8192), DI(o + 40960, 8192), 96>(acc3, sda, sd);
            else wgmma_192<1, 1, DI(o, 8192), DI(o + 16384, 8192), 0>(acc3, sda, sd);
          });
        };
        mbar_wait(BAR(RD), L);
        mbar_wait(BAR(F3 + 1), 1); mbar_wait(BAR(F3 + 2), 1);
        wg_wait<0>(); release(E3 + 0);
#pragma unroll
        for (int k = 0; k < 112; k++) { float t; asm volatile("mov.b32 %0, %1;" : "=f"(t) : "f"(acc3[k]) : "memory"); acc3[k] = t; }
        sched_fence(P.zero);
        KB(77);
        wg_fence(); part(Int<1>{}, True{}); part(Int<2>{}, True{});
        mbar_wait(BAR(F3 + 3), 1); wg_fence(); part(Int<3>{}, True{}); wg_commit();
        part(Int<1>{}, False{}); wg_commit();
        wg_wait<1>();
#pragma unroll
        for (int k = 96; k < 112; k++) asm volatile("" : "+f"(acc3[k])::"memory");
        gelu8(3, 0); gelu8(3, 1);
        __syncwarp();
        copy_out<2>(ug, sb + OFF_X + 16384 + (uint32_t)((ug - gUB) & 0x2fff), 2048);
        signal(JOB + 7);
        sched_fence(P.zero);
        KB(78);
        wg_fence(); part(Int<2>{}, False{}); wg_commit();
        wg_wait<1>(); release(E3 + 1);
        KB(79);
        part(Int<3>{}, False{}); wg_commit();
        wg_wait<1>(); release(E3 + 2);
        wg_wait<0>(); release(E3 + 3);
      }
      fence_regs(acc3);
      TS(7 + 32 * L);
      if (wu == 0) ST(16);
      auto g4_issue = [&](int p, uint32_t b) {
        const uint32_t da = sda + (slot4(p) >> 4), db = sd + (b >> 4);
        wg_fence();
        static_for<0, 4>([&](auto kk) { wgmma_128<1, 1, DI(kk.value * 2048, 8192), DI(kk.value * 2048, 8192)>(xa, da, db); });
        wg_commit();
      };
#pragma unroll
      for (int k = 0; k < 4; k++) gelu8(0, k);
      fence_async_smem();
      signal(JOB + 4);
      nb_sync<NB_BOTH>(256);
      TS(8 + 32 * L);
      static_for<0, 16>([&](auto nn) {
        constexpr int n = nn.value, p = n % 6;
        mbar_wait(BAR(F4 + p), (n / 6 + (p >= 2 ? L : 0)) & 1);
        KB(80 + n);
        if (n == 1 && wu == 0) ST(21);
        if (n == 0 && wu == 0) ST(22);
        wg_fence();
        static_for<0, 4>([&](auto kk) {
          wgmma_128<1, 1, DI(slot4(p) + kk.value * 2048, 8192), DI((n ? slot4(p) + 16384 : OFF_X) + kk.value * 2048, 8192)>(xa, sda, sd);
        });
        wg_commit();
        if (n) { wg_wait<1>(); release(E4 + (n + 5) % 6); }
        if (n == 8) mbar_wait(BAR(RD + 2), L);
        else if (!(n & 1)) sched_fence(P.zero);
        if (!(n & 1)) gelu8(1 + (n >> 3), (n >> 1) & 3);
        if ((n & 7) == 7) { fence_async_smem(); signal(JOB + 5 + (n >> 3)); }
      });
      {
        int p = 4, pp = 3;
        uint32_t par = L ? 0x33 : 0x0f;
        auto g4_loop = [&](int n0, int n1, int nrel, uint32_t own) {
#pragma unroll 1
          for (int n = n0; n < n1; n++) {
            mbar_wait(BAR(F4 + p), (par >> p) & 1);
            KB(80 + n);
            par ^= 1u << p;
            g4_issue(p, own && n == n0 ? own : slot4(p) + 16384);
            if (n1 == 56 && n == 55 && wg == 0) nb_arrive<NB_LEAD>(256);
            wg_wait<1>();
            if (n > nrel) release(E4 + pp);
            pp = p; if (++p == 6) p = 0;
          }
        };
        g4_loop(16, 24, 0, 0);
        mbar_wait(BAR(JOB + 5), L);
        g4_loop(24, 40, 0, OFF_X + 16384);
        mbar_wait(BAR(JOB + 6), L);
        g4_loop(40, 56 - LEAD4, 0, OFF_X);
        if (wg == 1) { wg_wait<0>(); release(E4 + pp); nb_sync<NB_LEAD>(256); }
        g4_loop(56 - LEAD4, 56, wg == 1 ? 56 - LEAD4 : 0, 0);
      }
      mbar_wait(BAR(RD + 1), L);
      wg_wait<0>();
      release(E4 + 1);
      fence_regs(xa);
      TS(9 + 32 * L);
      {
        GEOM;
#pragma unroll
        for (int t = 0; t < 16; t += 2) {
          stsm4(sb + OFF_X + (t >> 3) * 16384 + (16 * wu + lr) * 128 + ((((t & 7) + lt) ^ l7) << 4),
                pack2(xa[4 * t], xa[4 * t + 1]), pack2(xa[4 * t + 2], xa[4 * t + 3]),
                pack2(xa[4 * t + 4], xa[4 * t + 5]), pack2(xa[4 * t + 6], xa[4 * t + 7]));
          if (t == 6 && L == 0) {
            __syncwarp();
            const int o = wu * 2048 + lane * 16;
            copy_out<4>(gXB + (opq(i) * 16 + 2 * j) * 16384 + o, sb + OFF_X + o, 512);
            signal(JOB + 8);
          }
        }
        fence_async_smem();
        if (L == 0) signal(JOB + 9);
        else {
          __syncwarp();
          if (elect_one()) {
            tma2d_store(&P.out, sb + OFF_X + wu * 2048, 128 * j, 128 * i + 16 * wu);
            tma2d_store(&P.out, sb + OFF_X + 16384 + wu * 2048, 128 * j + 64, 128 * i + 16 * wu);
            bulk_commit(); bulk_wait0();
          }
          __syncwarp();
        }
        nb_sync<NB_BOTH>(256);
      }
      TS(10 + 32 * L);
      KB(136);
    }
    cluster_bar();
    TS(32);
  }
}

typedef CUresult (*EncodeFn)(CUtensorMap*, CUtensorMapDataType, cuuint32_t, void*, const cuuint64_t*, const cuuint64_t*, const cuuint32_t*,
                             const cuuint32_t*, CUtensorMapInterleave, CUtensorMapSwizzle, CUtensorMapL2promotion, CUtensorMapFloatOOBfill);

void make_map(EncodeFn enc, CUtensorMap* mp, const void* base, int rank, cuuint64_t d0, cuuint64_t d1, cuuint64_t d2, cuuint64_t s1, cuuint64_t s2,
              cuuint32_t b0, cuuint32_t b1, cuuint32_t b2) {
  cuuint64_t dims[3] = {d0, d1, d2}, strides[2] = {s1, s2};
  cuuint32_t box[3] = {b0, b1, b2}, es[3] = {1, 1, 1};
  CUresult res = enc(mp, CU_TENSOR_MAP_DATA_TYPE_BFLOAT16, rank, const_cast<void*>(base), dims, strides, box, es, CU_TENSOR_MAP_INTERLEAVE_NONE,
                     CU_TENSOR_MAP_SWIZZLE_128B, CU_TENSOR_MAP_L2_PROMOTION_L2_128B, CU_TENSOR_MAP_FLOAT_OOB_FILL_NONE);
  (void)res;
}

}

extern "C" void kernel_launch(void* const* d_in, const int* in_sizes, int n_in, void* d_out, int out_size) {
  (void)in_sizes; (void)n_in; (void)out_size;
  static EncodeFn enc = nullptr;
  if (!enc) {
    void* fn = nullptr;
    cudaDriverEntryPointQueryResult qr;
    cudaGetDriverEntryPoint("cuTensorMapEncodeTiled", &fn, cudaEnableDefault, &qr);
    enc = (EncodeFn)fn;
    cudaFuncSetAttribute(fused_kernel, cudaFuncAttributeMaxDynamicSharedMemorySize, SMEM_BYTES);
  }
  Params P;
  make_map(enc, &P.x0, d_in[0], 2, D_, S_, 1, D_ * 2, 0, 64, 128, 1);
  make_map(enc, &P.wqkv, d_in[1], 3, D_, D_, 3, 3 * D_ * 2, D_ * 2, 64, 32, 3);
  make_map(enc, &P.wo, d_in[2], 2, D_, D_, 1, D_ * 2, 0, 64, 64, 1);
  make_map(enc, &P.w1, d_in[4], 3, 64, S_, F_ / 64, F_ * 2, 128, 64, 64, 3);
  make_map(enc, &P.w1h, d_in[4], 3, 32, S_, F_ / 32, F_ * 2, 64, 64, 64, 1);
  make_map(enc, &P.w2, d_in[6], 3, 64, F_, S_ / 64, S_ * 2, 128, 64, 64, 2);
  make_map(enc, &P.out, d_out, 2, D_, S_, 1, D_ * 2, 0, 64, 16, 1);
  P.wqkv_p = (const bf16*)d_in[1];
  P.wo_p = (const bf16*)d_in[2];
  P.w1_p = (const bf16*)d_in[4];
  P.w2_p = (const bf16*)d_in[6];
  P.b1 = (const bf16*)d_in[5];
  P.b2 = (const bf16*)d_in[7];
  P.zero = 0;
  fused_kernel<<<128, 384, SMEM_BYTES>>>(P);
}
```

```cpp
#include <cuda_runtime.h>
#include <cuda_bf16.h>
#include <cuda.h>
#include <stdint.h>

namespace {

typedef __nv_bfloat16 bf16;
constexpr int S_ = 2048, D_ = 1024, F_ = 3584;

constexpr uint32_t OFF_STG  = 163840;
constexpr uint32_t OFF_X    = 196608;
constexpr uint32_t OFF_BAR  = 229376;
constexpr uint32_t OFF_CS   = OFF_BAR + 512;
constexpr uint32_t OFF_B1   = OFF_CS + 1536;
constexpr uint32_t SMEM_BYTES = OFF_B1 + 896 + 128;
constexpr int F1 = 0, E1 = 4, F2 = 8, E2 = 13, F3 = 18, E3 = 22, F4 = 26, E4 = 32;
constexpr int JOB = 38;
constexpr int RD = 48;
constexpr int XF = 54, STD = 56, STAT = 58, FOLD = 59, CSJ = 61, HALO = 62;
constexpr int NB_BOTH = 1, NB_HELP = 2, NB_INIT = 3, NB_LEAD = 4;

__host__ __device__ constexpr uint32_t slot1(int p) { return p * 40960; }
__host__ __device__ constexpr uint32_t slot2(int p) { return p * 32768; }
__host__ __device__ constexpr uint32_t slot3(int p) { return ((p + 2) & 3) * 49152; }
__host__ __device__ constexpr uint32_t slot4(int p) { return (p < 2 ? p + 4 : p - 2) * 32768; }

__device__ __align__(1024) uint8_t gXB[16 * 16 * 16384];
__device__ __align__(1024) uint8_t gOB[16 * 16 * 16384];
__device__ __align__(1024) uint8_t gHB[8 * 32 * 16384];
__device__ __align__(1024) uint8_t gUB[8 * 56 * 16384];
__device__ __align__(1024) uint2   gST[2][16][8][8][16];
__device__ __align__(1024) uint4   gHalo[2][16][8][12][32];
__device__ __align__(1024) uint32_t gAck[2][16][8][2][8];
__device__ __align__(1024) uint4   gCS[8][16][64];
__device__ __align__(1024) uint32_t gFlag[2][7][16][32];
__device__ uint32_t gEpoch;
#define TS(k)
#define TS2(k)

#define S5(k)
#define KB(k)
#define ST(k)
struct Params {
  CUtensorMap x0, wqkv, wo, w1, w1h, w2, out;
  const bf16 *wqkv_p, *wo_p, *w1_p, *w2_p, *b1, *b2;
  uint32_t zero;
};

template <int TA, int TB, uint32_t IA, uint32_t IB, int O = 0, int LEN> __device__ __forceinline__ void wgmma_32(float (&d)[LEN], uint32_t da, uint32_t db) {
  asm volatile("{\n.reg .b64 da, db;\n.reg .b32 la, lb;\nadd.u32 la, %16, %20;\nadd.u32 lb, %17, %21;\nmov.b64 da, {la, 0x40000040};\nmov.b64 db, {lb, 0x40000040};\n"
  "wgmma.mma_async.sync.aligned.m64n32k16.f32.bf16.bf16 {"
  "%0, %1, %2, %3, %4, %5, %6, %7, %8, %9, %10, %11, %12, %13, %14, %15"
  "}, da, db, 1, 1, 1, %18, %19;\n}\n"
  : "+f"(d[O + 0]), "+f"(d[O + 1]), "+f"(d[O + 2]), "+f"(d[O + 3]), "+f"(d[O + 4]), "+f"(d[O + 5]), "+f"(d[O + 6]), "+f"(d[O + 7]),
    "+f"(d[O + 8]), "+f"(d[O + 9]), "+f"(d[O + 10]), "+f"(d[O + 11]), "+f"(d[O + 12]), "+f"(d[O + 13]), "+f"(d[O + 14]), "+f"(d[O + 15])
  : "r"(da), "r"(db), "n"(TA), "n"(TB), "n"(IA), "n"(IB));
}
template <int TA, int TB, uint32_t IA, uint32_t IB, int O = 0, int LEN> __device__ __forceinline__ void wgmma_128(float (&d)[LEN], uint32_t da, uint32_t db) {
  asm volatile("{\n.reg .b64 da, db;\n.reg .b32 la, lb;\nadd.u32 la, %64, %68;\nadd.u32 lb, %65, %69;\nmov.b64 da, {la, 0x40000040};\nmov.b64 db, {lb, 0x40000040};\n"
  "wgmma.mma_async.sync.aligned.m64n128k16.f32.bf16.bf16 {"
  "%0, %1, %2, %3, %4, %5, %6, %7, %8, %9, %10, %11, %12, %13, %14, %15, "
  "%16, %17, %18, %19, %20, %21, %22, %23, %24, %25, %26, %27, %28, %29, %30, %31, "
  "%32, %33, %34, %35, %36, %37, %38, %39, %40, %41, %42, %43, %44, %45, %46, %47, "
  "%48, %49, %50, %51, %52, %53, %54, %55, %56, %57, %58, %59, %60, %61, %62, %63"
  "}, da, db, 1, 1, 1, %66, %67;\n}\n"
  : "+f"(d[O + 0]), "+f"(d[O + 1]), "+f"(d[O + 2]), "+f"(d[O + 3]), "+f"(d[O + 4]), "+f"(d[O + 5]), "+f"(d[O + 6]), "+f"(d[O + 7]),
    "+f"(d[O + 8]), "+f"(d[O + 9]), "+f"(d[O + 10]), "+f"(d[O + 11]), "+f"(d[O + 12]), "+f"(d[O + 13]), "+f"(d[O + 14]), "+f"(d[O + 15]),
    "+f"(d[O + 16]), "+f"(d[O + 17]), "+f"(d[O + 18]), "+f"(d[O + 19]), "+f"(d[O + 20]), "+f"(d[O + 21]), "+f"(d[O + 22]), "+f"(d[O + 23]),
    "+f"(d[O + 24]), "+f"(d[O + 25]), "+f"(d[O + 26]), "+f"(d[O + 27]), "+f"(d[O + 28]), "+f"(d[O + 29]), "+f"(d[O + 30]), "+f"(d[O + 31]),
    "+f"(d[O + 32]), "+f"(d[O + 33]), "+f"(d[O + 34]), "+f"(d[O + 35]), "+f"(d[O + 36]), "+f"(d[O + 37]), "+f"(d[O + 38]), "+f"(d[O + 39]),
    "+f"(d[O + 40]), "+f"(d[O + 41]), "+f"(d[O + 42]), "+f"(d[O + 43]), "+f"(d[O + 44]), "+f"(d[O + 45]), "+f"(d[O + 46]), "+f"(d[O + 47]),
    "+f"(d[O + 48]), "+f"(d[O + 49]), "+f"(d[O + 50]), "+f"(d[O + 51]), "+f"(d[O + 52]), "+f"(d[O + 53]), "+f"(d[O + 54]), "+f"(d[O + 55]),
    "+f"(d[O + 56]), "+f"(d[O + 57]), "+f"(d[O + 58]), "+f"(d[O + 59]), "+f"(d[O + 60]), "+f"(d[O + 61]), "+f"(d[O + 62]), "+f"(d[O + 63])
  : "r"(da), "r"(db), "n"(TA), "n"(TB), "n"(IA), "n"(IB));
}
template <int TA, int TB, uint32_t IA, uint32_t IB, int O = 0, int LEN> __device__ __forceinline__ void wgmma_192(float (&d)[LEN], uint32_t da, uint32_t db) {
  asm volatile("{\n.reg .b64 da, db;\n.reg .b32 la, lb;\nadd.u32 la, %96, %100;\nadd.u32 lb, %97, %101;\nmov.b64 da, {la, 0x40000040};\nmov.b64 db, {lb, 0x40000040};\n"
  "wgmma.mma_async.sync.aligned.m64n192k16.f32.bf16.bf16 {"
  "%0, %1, %2, %3, %4, %5, %6, %7, %8, %9, %10, %11, %12, %13, %14, %15, "
  "%16, %17, %18, %19, %20, %21, %22, %23, %24, %25, %26, %27, %28, %29, %30, %31, "
  "%32, %33, %34, %35, %36, %37, %38, %39, %40, %41, %42, %43, %44, %45, %46, %47, "
  "%48, %49, %50, %51, %52, %53, %54, %55, %56, %57, %58, %59, %60, %61, %62, %63, "
  "%64, %65, %66, %67, %68, %69, %70, %71, %72, %73, %74, %75, %76, %77, %78, %79, "
  "%80, %81, %82, %83, %84, %85, %86, %87, %88, %89, %90, %91, %92, %93, %94, %95"
  "}, da, db, 1, 1, 1, %98, %99;\n}\n"
  : "+f"(d[O + 0]), "+f"(d[O + 1]), "+f"(d[O + 2]), "+f"(d[O + 3]), "+f"(d[O + 4]), "+f"(d[O + 5]), "+f"(d[O + 6]), "+f"(d[O + 7]),
    "+f"(d[O + 8]), "+f"(d[O + 9]), "+f"(d[O + 10]), "+f"(d[O + 11]), "+f"(d[O + 12]), "+f"(d[O + 13]), "+f"(d[O + 14]), "+f"(d[O + 15]),
    "+f"(d[O + 16]), "+f"(d[O + 17]), "+f"(d[O + 18]), "+f"(d[O + 19]), "+f"(d[O + 20]), "+f"(d[O + 21]), "+f"(d[O + 22]), "+f"(d[O + 23]),
    "+f"(d[O + 24]), "+f"(d[O + 25]), "+f"(d[O + 26]), "+f"(d[O + 27]), "+f"(d[O + 28]), "+f"(d[O + 29]), "+f"(d[O + 30]), "+f"(d[O + 31]),
    "+f"(d[O + 32]), "+f"(d[O + 33]), "+f"(d[O + 34]), "+f"(d[O + 35]), "+f"(d[O + 36]), "+f"(d[O + 37]), "+f"(d[O + 38]), "+f"(d[O + 39]),
    "+f"(d[O + 40]), "+f"(d[O + 41]), "+f"(d[O + 42]), "+f"(d[O + 43]), "+f"(d[O + 44]), "+f"(d[O + 45]), "+f"(d[O + 46]), "+f"(d[O + 47]),
    "+f"(d[O + 48]), "+f"(d[O + 49]), "+f"(d[O + 50]), "+f"(d[O + 51]), "+f"(d[O + 52]), "+f"(d[O + 53]), "+f"(d[O + 54]), "+f"(d[O + 55]),
    "+f"(d[O + 56]), "+f"(d[O + 57]), "+f"(d[O + 58]), "+f"(d[O + 59]), "+f"(d[O + 60]), "+f"(d[O + 61]), "+f"(d[O + 62]), "+f"(d[O + 63]),
    "+f"(d[O + 64]), "+f"(d[O + 65]), "+f"(d[O + 66]), "+f"(d[O + 67]), "+f"(d[O + 68]), "+f"(d[O + 69]), "+f"(d[O + 70]), "+f"(d[O + 71]),
    "+f"(d[O + 72]), "+f"(d[O + 73]), "+f"(d[O + 74]), "+f"(d[O + 75]), "+f"(d[O + 76]), "+f"(d[O + 77]), "+f"(d[O + 78]), "+f"(d[O + 79]),
    "+f"(d[O + 80]), "+f"(d[O + 81]), "+f"(d[O + 82]), "+f"(d[O + 83]), "+f"(d[O + 84]), "+f"(d[O + 85]), "+f"(d[O + 86]), "+f"(d[O + 87]),
    "+f"(d[O + 88]), "+f"(d[O + 89]), "+f"(d[O + 90]), "+f"(d[O + 91]), "+f"(d[O + 92]), "+f"(d[O + 93]), "+f"(d[O + 94]), "+f"(d[O + 95])
  : "r"(da), "r"(db), "n"(TA), "n"(TB), "n"(IA), "n"(IB));
}
template <int TA, int TB, uint32_t IA, uint32_t IB, int O = 0, int LEN> __device__ __forceinline__ void wgmma_192z(float (&d)[LEN], uint32_t da, uint32_t db) {
  asm volatile("{\n.reg .b64 da, db;\n.reg .b32 la, lb;\nadd.u32 la, %96, %100;\nadd.u32 lb, %97, %101;\nmov.b64 da, {la, 0x40000040};\nmov.b64 db, {lb, 0x40000040};\n"
  "wgmma.mma_async.sync.aligned.m64n192k16.f32.bf16.bf16 {"
  "%0, %1, %2, %3, %4, %5, %6, %7, %8, %9, %10, %11, %12, %13, %14, %15, "
  "%16, %17, %18, %19, %20, %21, %22, %23, %24, %25, %26, %27, %28, %29, %30, %31, "
  "%32, %33, %34, %35, %36, %37, %38, %39, %40, %41, %42, %43, %44, %45, %46, %47, "
  "%48, %49, %50, %51, %52, %53, %54, %55, %56, %57, %58, %59, %60, %61, %62, %63, "
  "%64, %65, %66, %67, %68, %69, %70, %71, %72, %73, %74, %75, %76, %77, %78, %79, "
  "%80, %81, %82, %83, %84, %85, %86, %87, %88, %89, %90, %91, %92, %93, %94, %95"
  "}, da, db, 0, 1, 1, %98, %99;\n}\n"
  : "=f"(d[O + 0]), "=f"(d[O + 1]), "=f"(d[O + 2]), "=f"(d[O + 3]), "=f"(d[O + 4]), "=f"(d[O + 5]), "=f"(d[O + 6]), "=f"(d[O + 7]),
    "=f"(d[O + 8]), "=f"(d[O + 9]), "=f"(d[O + 10]), "=f"(d[O + 11]), "=f"(d[O + 12]), "=f"(d[O + 13]), "=f"(d[O + 14]), "=f"(d[O + 15]),
    "=f"(d[O + 16]), "=f"(d[O + 17]), "=f"(d[O + 18]), "=f"(d[O + 19]), "=f"(d[O + 20]), "=f"(d[O + 21]), "=f"(d[O + 22]), "=f"(d[O + 23]),
    "=f"(d[O + 24]), "=f"(d[O + 25]), "=f"(d[O + 26]), "=f"(d[O + 27]), "=f"(d[O + 28]), "=f"(d[O + 29]), "=f"(d[O + 30]), "=f"(d[O + 31]),
    "=f"(d[O + 32]), "=f"(d[O + 33]), "=f"(d[O + 34]), "=f"(d[O + 35]), "=f"(d[O + 36]), "=f"(d[O + 37]), "=f"(d[O + 38]), "=f"(d[O + 39]),
    "=f"(d[O + 40]), "=f"(d[O + 41]), "=f"(d[O + 42]), "=f"(d[O + 43]), "=f"(d[O + 44]), "=f"(d[O + 45]), "=f"(d[O + 46]), "=f"(d[O + 47]),
    "=f"(d[O + 48]), "=f"(d[O + 49]), "=f"(d[O + 50]), "=f"(d[O + 51]), "=f"(d[O + 52]), "=f"(d[O + 53]), "=f"(d[O + 54]), "=f"(d[O + 55]),
    "=f"(d[O + 56]), "=f"(d[O + 57]), "=f"(d[O + 58]), "=f"(d[O + 59]), "=f"(d[O + 60]), "=f"(d[O + 61]), "=f"(d[O + 62]), "=f"(d[O + 63]),
    "=f"(d[O + 64]), "=f"(d[O + 65]), "=f"(d[O + 66]), "=f"(d[O + 67]), "=f"(d[O + 68]), "=f"(d[O + 69]), "=f"(d[O + 70]), "=f"(d[O + 71]),
    "=f"(d[O + 72]), "=f"(d[O + 73]), "=f"(d[O + 74]), "=f"(d[O + 75]), "=f"(d[O + 76]), "=f"(d[O + 77]), "=f"(d[O + 78]), "=f"(d[O + 79]),
    "=f"(d[O + 80]), "=f"(d[O + 81]), "=f"(d[O + 82]), "=f"(d[O + 83]), "=f"(d[O + 84]), "=f"(d[O + 85]), "=f"(d[O + 86]), "=f"(d[O + 87]),
    "=f"(d[O + 88]), "=f"(d[O + 89]), "=f"(d[O + 90]), "=f"(d[O + 91]), "=f"(d[O + 92]), "=f"(d[O + 93]), "=f"(d[O + 94]), "=f"(d[O + 95])
  : "r"(da), "r"(db), "n"(TA), "n"(TB), "n"(IA), "n"(IB));
}
template <int TA, int TB, uint32_t IA, uint32_t IB, int O = 0, int LEN> __device__ __forceinline__ void wgmma_224(float (&d)[LEN], uint32_t da, uint32_t db) {
  asm volatile("{\n.reg .b64 da, db;\n.reg .b32 la, lb;\nadd.u32 la, %112, %116;\nadd.u32 lb, %113, %117;\nmov.b64 da, {la, 0x40000040};\nmov.b64 db, {lb, 0x40000040};\n"
  "wgmma.mma_async.sync.aligned.m64n224k16.f32.bf16.bf16 {"
  "%0, %1, %2, %3, %4, %5, %6, %7, %8, %9, %10, %11, %12, %13, %14, %15, "
  "%16, %17, %18, %19, %20, %21, %22, %23, %24, %25, %26, %27, %28, %29, %30, %31, "
  "%32, %33, %34, %35, %36, %37, %38, %39, %40, %41, %42, %43, %44, %45, %46, %47, "
  "%48, %49, %50, %51, %52, %53, %54, %55, %56, %57, %58, %59, %60, %61, %62, %63, "
  "%64, %65, %66, %67, %68, %69, %70, %71, %72, %73, %74, %75, %76, %77, %78, %79, "
  "%80, %81, %82, %83, %84, %85, %86, %87, %88, %89, %90, %91, %92, %93, %94, %95, "
  "%96, %97, %98, %99, %100, %101, %102, %103, %104, %105, %106, %107, %108, %109, %110, %111"
  "}, da, db, 1, 1, 1, %114, %115;\n}\n"
  : "+f"(d[O + 0]), "+f"(d[O + 1]), "+f"(d[O + 2]), "+f"(d[O + 3]), "+f"(d[O + 4]), "+f"(d[O + 5]), "+f"(d[O + 6]), "+f"(d[O + 7]),
    "+f"(d[O + 8]), "+f"(d[O + 9]), "+f"(d[O + 10]), "+f"(d[O + 11]), "+f"(d[O + 12]), "+f"(d[O + 13]), "+f"(d[O + 14]), "+f"(d[O + 15]),
    "+f"(d[O + 16]), "+f"(d[O + 17]), "+f"(d[O + 18]), "+f"(d[O + 19]), "+f"(d[O + 20]), "+f"(d[O + 21]), "+f"(d[O + 22]), "+f"(d[O + 23]),
    "+f"(d[O + 24]), "+f"(d[O + 25]), "+f"(d[O + 26]), "+f"(d[O + 27]), "+f"(d[O + 28]), "+f"(d[O + 29]), "+f"(d[O + 30]), "+f"(d[O + 31]),
    "+f"(d[O + 32]), "+f"(d[O + 33]), "+f"(d[O + 34]), "+f"(d[O + 35]), "+f"(d[O + 36]), "+f"(d[O + 37]), "+f"(d[O + 38]), "+f"(d[O + 39]),
    "+f"(d[O + 40]), "+f"(d[O + 41]), "+f"(d[O + 42]), "+f"(d[O + 43]), "+f"(d[O + 44]), "+f"(d[O + 45]), "+f"(d[O + 46]), "+f"(d[O + 47]),
    "+f"(d[O + 48]), "+f"(d[O + 49]), "+f"(d[O + 50]), "+f"(d[O + 51]), "+f"(d[O + 52]), "+f"(d[O + 53]), "+f"(d[O + 54]), "+f"(d[O + 55]),
    "+f"(d[O + 56]), "+f"(d[O + 57]), "+f"(d[O + 58]), "+f"(d[O + 59]), "+f"(d[O + 60]), "+f"(d[O + 61]), "+f"(d[O + 62]), "+f"(d[O + 63]),
    "+f"(d[O + 64]), "+f"(d[O + 65]), "+f"(d[O + 66]), "+f"(d[O + 67]), "+f"(d[O + 68]), "+f"(d[O + 69]), "+f"(d[O + 70]), "+f"(d[O + 71]),
    "+f"(d[O + 72]), "+f"(d[O + 73]), "+f"(d[O + 74]), "+f"(d[O + 75]), "+f"(d[O + 76]), "+f"(d[O + 77]), "+f"(d[O + 78]), "+f"(d[O + 79]),
    "+f"(d[O + 80]), "+f"(d[O + 81]), "+f"(d[O + 82]), "+f"(d[O + 83]), "+f"(d[O + 84]), "+f"(d[O + 85]), "+f"(d[O + 86]), "+f"(d[O + 87]),
    "+f"(d[O + 88]), "+f"(d[O + 89]), "+f"(d[O + 90]), "+f"(d[O + 91]), "+f"(d[O + 92]), "+f"(d[O + 93]), "+f"(d[O + 94]), "+f"(d[O + 95]),
    "+f"(d[O + 96]), "+f"(d[O + 97]), "+f"(d[O + 98]), "+f"(d[O + 99]), "+f"(d[O + 100]), "+f"(d[O + 101]), "+f"(d[O + 102]), "+f"(d[O + 103]),
    "+f"(d[O + 104]), "+f"(d[O + 105]), "+f"(d[O + 106]), "+f"(d[O + 107]), "+f"(d[O + 108]), "+f"(d[O + 109]), "+f"(d[O + 110]), "+f"(d[O + 111])
  : "r"(da), "r"(db), "n"(TA), "n"(TB), "n"(IA), "n"(IB));
}
__device__ __forceinline__ void wgmma_rs_192(float (&d)[96], uint32_t a0, uint32_t a1, uint32_t a2, uint32_t a3, uint64_t db) {
  asm volatile("wgmma.mma_async.sync.aligned.m64n192k16.f32.bf16.bf16 {"
  "%0, %1, %2, %3, %4, %5, %6, %7, %8, %9, %10, %11, %12, %13, %14, %15, "
  "%16, %17, %18, %19, %20, %21, %22, %23, %24, %25, %26, %27, %28, %29, %30, %31, "
  "%32, %33, %34, %35, %36, %37, %38, %39, %40, %41, %42, %43, %44, %45, %46, %47, "
  "%48, %49, %50, %51, %52, %53, %54, %55, %56, %57, %58, %59, %60, %61, %62, %63, "
  "%64, %65, %66, %67, %68, %69, %70, %71, %72, %73, %74, %75, %76, %77, %78, %79, "
  "%80, %81, %82, %83, %84, %85, %86, %87, %88, %89, %90, %91, %92, %93, %94, %95"
  "}, {%96, %97, %98, %99}, %100, 1, 1, 1, 1;\n"
  : "+f"(d[0]), "+f"(d[1]), "+f"(d[2]), "+f"(d[3]), "+f"(d[4]), "+f"(d[5]), "+f"(d[6]), "+f"(d[7]),
    "+f"(d[8]), "+f"(d[9]), "+f"(d[10]), "+f"(d[11]), "+f"(d[12]), "+f"(d[13]), "+f"(d[14]), "+f"(d[15]),
    "+f"(d[16]), "+f"(d[17]), "+f"(d[18]), "+f"(d[19]), "+f"(d[20]), "+f"(d[21]), "+f"(d[22]), "+f"(d[23]),
    "+f"(d[24]), "+f"(d[25]), "+f"(d[26]), "+f"(d[27]), "+f"(d[28]), "+f"(d[29]), "+f"(d[30]), "+f"(d[31]),
    "+f"(d[32]), "+f"(d[33]), "+f"(d[34]), "+f"(d[35]), "+f"(d[36]), "+f"(d[37]), "+f"(d[38]), "+f"(d[39]),
    "+f"(d[40]), "+f"(d[41]), "+f"(d[42]), "+f"(d[43]), "+f"(d[44]), "+f"(d[45]), "+f"(d[46]), "+f"(d[47]),
    "+f"(d[48]), "+f"(d[49]), "+f"(d[50]), "+f"(d[51]), "+f"(d[52]), "+f"(d[53]), "+f"(d[54]), "+f"(d[55]),
    "+f"(d[56]), "+f"(d[57]), "+f"(d[58]), "+f"(d[59]), "+f"(d[60]), "+f"(d[61]), "+f"(d[62]), "+f"(d[63]),
    "+f"(d[64]), "+f"(d[65]), "+f"(d[66]), "+f"(d[67]), "+f"(d[68]), "+f"(d[69]), "+f"(d[70]), "+f"(d[71]),
    "+f"(d[72]), "+f"(d[73]), "+f"(d[74]), "+f"(d[75]), "+f"(d[76]), "+f"(d[77]), "+f"(d[78]), "+f"(d[79]),
    "+f"(d[80]), "+f"(d[81]), "+f"(d[82]), "+f"(d[83]), "+f"(d[84]), "+f"(d[85]), "+f"(d[86]), "+f"(d[87]),
    "+f"(d[88]), "+f"(d[89]), "+f"(d[90]), "+f"(d[91]), "+f"(d[92]), "+f"(d[93]), "+f"(d[94]), "+f"(d[95])
  : "r"(a0), "r"(a1), "r"(a2), "r"(a3), "l"(db));
}
__device__ __forceinline__ void wgmma_rs_224z(float (&d)[112], uint32_t a0, uint32_t a1, uint32_t a2, uint32_t a3, uint64_t db) {
  asm volatile("wgmma.mma_async.sync.aligned.m64n224k16.f32.bf16.bf16 {"
  "%0, %1, %2, %3, %4, %5, %6, %7, %8, %9, %10, %11, %12, %13, %14, %15, "
  "%16, %17, %18, %19, %20, %21, %22, %23, %24, %25, %26, %27, %28, %29, %30, %31, "
  "%32, %33, %34, %35, %36, %37, %38, %39, %40, %41, %42, %43, %44, %45, %46, %47, "
  "%48, %49, %50, %51, %52, %53, %54, %55, %56, %57, %58, %59, %60, %61, %62, %63, "
  "%64, %65, %66, %67, %68, %69, %70, %71, %72, %73, %74, %75, %76, %77, %78, %79, "
  "%80, %81, %82, %83, %84, %85, %86, %87, %88, %89, %90, %91, %92, %93, %94, %95, "
  "%96, %97, %98, %99, %100, %101, %102, %103, %104, %105, %106, %107, %108, %109, %110, %111"
  "}, {%112, %113, %114, %115}, %116, 0, 1, 1, 1;\n"
  : "=f"(d[0]), "=f"(d[1]), "=f"(d[2]), "=f"(d[3]), "=f"(d[4]), "=f"(d[5]), "=f"(d[6]), "=f"(d[7]),
    "=f"(d[8]), "=f"(d[9]), "=f"(d[10]), "=f"(d[11]), "=f"(d[12]), "=f"(d[13]), "=f"(d[14]), "=f"(d[15]),
    "=f"(d[16]), "=f"(d[17]), "=f"(d[18]), "=f"(d[19]), "=f"(d[20]), "=f"(d[21]), "=f"(d[22]), "=f"(d[23]),
    "=f"(d[24]), "=f"(d[25]), "=f"(d[26]), "=f"(d[27]), "=f"(d[28]), "=f"(d[29]), "=f"(d[30]), "=f"(d[31]),
    "=f"(d[32]), "=f"(d[33]), "=f"(d[34]), "=f"(d[35]), "=f"(d[36]), "=f"(d[37]), "=f"(d[38]), "=f"(d[39]),
    "=f"(d[40]), "=f"(d[41]), "=f"(d[42]), "=f"(d[43]), "=f"(d[44]), "=f"(d[45]), "=f"(d[46]), "=f"(d[47]),
    "=f"(d[48]), "=f"(d[49]), "=f"(d[50]), "=f"(d[51]), "=f"(d[52]), "=f"(d[53]), "=f"(d[54]), "=f"(d[55]),
    "=f"(d[56]), "=f"(d[57]), "=f"(d[58]), "=f"(d[59]), "=f"(d[60]), "=f"(d[61]), "=f"(d[62]), "=f"(d[63]),
    "=f"(d[64]), "=f"(d[65]), "=f"(d[66]), "=f"(d[67]), "=f"(d[68]), "=f"(d[69]), "=f"(d[70]), "=f"(d[71]),
    "=f"(d[72]), "=f"(d[73]), "=f"(d[74]), "=f"(d[75]), "=f"(d[76]), "=f"(d[77]), "=f"(d[78]), "=f"(d[79]),
    "=f"(d[80]), "=f"(d[81]), "=f"(d[82]), "=f"(d[83]), "=f"(d[84]), "=f"(d[85]), "=f"(d[86]), "=f"(d[87]),
    "=f"(d[88]), "=f"(d[89]), "=f"(d[90]), "=f"(d[91]), "=f"(d[92]), "=f"(d[93]), "=f"(d[94]), "=f"(d[95]),
    "=f"(d[96]), "=f"(d[97]), "=f"(d[98]), "=f"(d[99]), "=f"(d[100]), "=f"(d[101]), "=f"(d[102]), "=f"(d[103]),
    "=f"(d[104]), "=f"(d[105]), "=f"(d[106]), "=f"(d[107]), "=f"(d[108]), "=f"(d[109]), "=f"(d[110]), "=f"(d[111])
  : "r"(a0), "r"(a1), "r"(a2), "r"(a3), "l"(db));
}

__device__ __forceinline__ uint32_t smem_u32(const void* p) { return (uint32_t)__cvta_generic_to_shared(p); }
__device__ __forceinline__ void mbar_init(uint32_t bar, uint32_t cnt) { asm volatile("mbarrier.init.shared::cta.b64 [%0], %1;" ::"r"(bar), "r"(cnt) : "memory"); }
__device__ __forceinline__ void mbar_expect(uint32_t bar, uint32_t bytes) { asm volatile("mbarrier.arrive.expect_tx.shared::cta.b64 _, [%0], %1;" ::"r"(bar), "r"(bytes) : "memory"); }
__device__ __forceinline__ void mbar_arrive(uint32_t bar) { asm volatile("mbarrier.arrive.shared::cta.b64 _, [%0];" ::"r"(bar) : "memory"); }
__device__ __forceinline__ void mbar_arrive_cl(uint32_t cbar) { asm volatile("mbarrier.arrive.shared::cluster.b64 _, [%0];" ::"r"(cbar) : "memory"); }
__device__ __forceinline__ uint32_t mapa(uint32_t a, uint32_t cta) { uint32_t r; asm("mapa.shared::cluster.u32 %0, %1, %2;" : "=r"(r) : "r"(a), "r"(cta)); return r; }
__device__ __forceinline__ void mbar_wait(uint32_t bar, uint32_t parity) {
  asm volatile("{\n.reg .pred p;\n.reg .u32 n;\nmov.u32 n, 0;\n"
    "LAB_WAIT:\n"
    "mbarrier.try_wait.parity.shared::cta.b64 p, [%0], %1;\n"
    "@p bra LAB_DONE;\n"
    "add.u32 n, n, 1;\n"
    "setp.lt.u32 p, n, 2000000;\n"
    "@p bra LAB_WAIT;\n"
    "trap;\n"
    "LAB_DONE:\n}\n" ::"r"(bar), "r"(parity) : "memory");
}
constexpr uint32_t SPIN_MAX = 2000000;
__device__ __forceinline__ void tma2d(uint32_t dst, const CUtensorMap* m, uint32_t bar, int c0, int c1) {
  asm volatile("cp.async.bulk.tensor.2d.shared::cluster.global.mbarrier::complete_tx::bytes [%0], [%1, {%3, %4}], [%2];"
    ::"r"(dst), "l"(m), "r"(bar), "r"(c0), "r"(c1) : "memory");
}
__device__ __forceinline__ void tma2d_mc(uint32_t dst, const CUtensorMap* m, uint32_t bar, int c0, int c1) {
  asm volatile("cp.async.bulk.tensor.2d.shared::cluster.global.mbarrier::complete_tx::bytes.multicast::cluster [%0], [%1, {%3, %4}], [%2], %5;"
    ::"r"(dst), "l"(m), "r"(bar), "r"(c0), "r"(c1), "h"((uint16_t)3) : "memory");
}
__device__ __forceinline__ void tma3d(uint32_t dst, const CUtensorMap* m, uint32_t bar, int c0, int c1, int c2) {
  asm volatile("cp.async.bulk.tensor.3d.shared::cluster.global.mbarrier::complete_tx::bytes [%0], [%1, {%3, %4, %5}], [%2];"
    ::"r"(dst), "l"(m), "r"(bar), "r"(c0), "r"(c1), "r"(c2) : "memory");
}
__device__ __forceinline__ void tma3d_mc(uint32_t dst, const CUtensorMap* m, uint32_t bar, int c0, int c1, int c2) {
  asm volatile("cp.async.bulk.tensor.3d.shared::cluster.global.mbarrier::complete_tx::bytes.multicast::cluster [%0], [%1, {%3, %4, %5}], [%2], %6;"
    ::"r"(dst), "l"(m), "r"(bar), "r"(c0), "r"(c1), "r"(c2), "h"((uint16_t)3) : "memory");
}
__device__ __forceinline__ void tma2d_store(const CUtensorMap* m, uint32_t src, int c0, int c1) {
  asm volatile("cp.async.bulk.tensor.2d.global.shared::cta.bulk_group [%0, {%2, %3}], [%1];" ::"l"(m), "r"(src), "r"(c0), "r"(c1) : "memory");
}
__device__ __forceinline__ void bulk_ld(uint32_t dst, const void* src, uint32_t bytes, uint32_t bar) {
  asm volatile("cp.async.bulk.shared::cluster.global.mbarrier::complete_tx::bytes [%0], [%1], %2, [%3];" ::"r"(dst), "l"(src), "r"(bytes), "r"(bar) : "memory");
}
__device__ __forceinline__ void bulk_ld_mc(uint32_t dst, const void* src, uint32_t bytes, uint32_t bar) {
  asm volatile("cp.async.bulk.shared::cluster.global.mbarrier::complete_tx::bytes.multicast::cluster [%0], [%1], %2, [%3], %4;"
    ::"r"(dst), "l"(src), "r"(bytes), "r"(bar), "h"((uint16_t)3) : "memory");
}
__device__ __forceinline__ void bulk_st(void* dst, uint32_t src, uint32_t bytes) {
  asm volatile("cp.async.bulk.global.shared::cta.bulk_group [%0], [%1], %2;" ::"l"(dst), "r"(src), "r"(bytes) : "memory");
}
__device__ __forceinline__ void bulk_commit() { asm volatile("cp.async.bulk.commit_group;" ::: "memory"); }
__device__ __forceinline__ void bulk_wait0() { asm volatile("cp.async.bulk.wait_group 0;" ::: "memory"); }
__device__ __forceinline__ void fence_async_smem() { asm volatile("fence.proxy.async.shared::cta;" ::: "memory"); }
__device__ __forceinline__ void wg_fence() { asm volatile("wgmma.fence.sync.aligned;" ::: "memory"); }
__device__ __forceinline__ void wg_commit() { asm volatile("wgmma.commit_group.sync.aligned;" ::: "memory"); }
template <int N> __device__ __forceinline__ void wg_wait() { asm volatile("wgmma.wait_group.sync.aligned %0;" ::"n"(N) : "memory"); }
template <int R> __device__ __forceinline__ void reg_alloc() { asm volatile("setmaxnreg.inc.sync.aligned.u32 %0;" ::"n"(R)); }
template <int R> __device__ __forceinline__ void reg_dealloc() { asm volatile("setmaxnreg.dec.sync.aligned.u32 %0;" ::"n"(R)); }
__device__ __forceinline__ void cluster_bar() { asm volatile("barrier.cluster.arrive.relaxed;\nbarrier.cluster.wait;" ::: "memory"); }
template <int ID> __device__ __forceinline__ void nb_sync(int n) { asm volatile("barrier.sync %0, %1;" ::"n"(ID), "r"(n) : "memory"); }
template <int ID> __device__ __forceinline__ void nb_arrive(int n) { asm volatile("barrier.arrive %0, %1;" ::"n"(ID), "r"(n) : "memory"); }
__device__ __forceinline__ int fresh_tid() { int t; asm volatile("mov.u32 %0, %%tid.x;" : "=r"(t)); return t; }
__device__ __forceinline__ void sched_fence(uint32_t z) { asm volatile("{\n.reg .pred p;\nsetp.ne.u32 p, %0, 0;\nLAB_S:\n@p nanosleep.u32 0;\n@p bra LAB_S;\n}\n" ::"r"(z) : "memory"); }
__device__ __forceinline__ float rsq(float x) { float y; asm("rsqrt.approx.ftz.f32 %0, %1;" : "=f"(y) : "f"(x)); return y; }
__device__ __forceinline__ int opq(int v) { asm volatile("" : "+r"(v)); return v; }
template <int V> struct Int { static constexpr int value = V; };
struct True { static constexpr bool value = true; };
struct False { static constexpr bool value = false; };
template <int N> __device__ __forceinline__ void fence_regs(float (&d)[N]) {
#pragma unroll
  for (int i = 0; i < N; i++) asm volatile("" : "+f"(d[i])::"memory");
}
__host__ __device__ constexpr uint32_t DI(uint32_t off, uint32_t lbo) { return (off >> 4) + ((lbo >> 4) << 16); }
template <int K, int N, class F> __device__ __forceinline__ void static_for(F f) { if constexpr (K < N) { f(Int<K>{}); static_for<K + 1, N>(f); } }
__device__ __forceinline__ uint64_t mkdesc_vec(uint32_t addr, uint32_t sbo) { return (uint64_t)((addr & 0x3FFFF) >> 4) | ((uint64_t)(sbo >> 4) << 32); }
__device__ __forceinline__ void sts16(uint32_t a, uint32_t v) { asm volatile("st.shared.u16 [%0], %1;" ::"r"(a), "h"((uint16_t)v) : "memory"); }
__device__ __forceinline__ uint32_t pack2(float lo, float hi) { uint32_t r; asm("cvt.rn.bf16x2.f32 %0, %1, %2;" : "=r"(r) : "f"(hi), "f"(lo)); return r; }
__device__ __forceinline__ float bf_lo(uint32_t v) { return __uint_as_float(v << 16); }
__device__ __forceinline__ float bf_hi(uint32_t v) { return __uint_as_float(v & 0xffff0000u); }
__device__ __forceinline__ void stsm4(uint32_t a, uint32_t r0, uint32_t r1, uint32_t r2, uint32_t r3) {
  asm volatile("stmatrix.sync.aligned.m8n8.x4.shared.b16 [%0], {%1, %2, %3, %4};" ::"r"(a), "r"(r0), "r"(r1), "r"(r2), "r"(r3) : "memory");
}
__device__ __forceinline__ void stsm4t(uint32_t a, uint32_t r0, uint32_t r1, uint32_t r2, uint32_t r3) {
  asm volatile("stmatrix.sync.aligned.m8n8.x4.trans.shared.b16 [%0], {%1, %2, %3, %4};" ::"r"(a), "r"(r0), "r"(r1), "r"(r2), "r"(r3) : "memory");
}
__device__ __forceinline__ void ldsm4(uint32_t a, uint32_t& r0, uint32_t& r1, uint32_t& r2, uint32_t& r3) {
  asm volatile("ldmatrix.sync.aligned.m8n8.x4.shared.b16 {%0, %1, %2, %3}, [%4];" : "=r"(r0), "=r"(r1), "=r"(r2), "=r"(r3) : "r"(a) : "memory");
}
__device__ __forceinline__ void ldsm4t(uint32_t a, uint32_t& r0, uint32_t& r1, uint32_t& r2, uint32_t& r3) {
  asm volatile("ldmatrix.sync.aligned.m8n8.x4.trans.shared.b16 {%0, %1, %2, %3}, [%4];" : "=r"(r0), "=r"(r1), "=r"(r2), "=r"(r3) : "r"(a) : "memory");
}
__device__ __forceinline__ void mma16816(float (&c)[4], uint32_t a0, uint32_t a1, uint32_t a2, uint32_t a3, uint32_t b0, uint32_t b1) {
  asm volatile("mma.sync.aligned.m16n8k16.row.col.f32.bf16.bf16.f32 {%0, %1, %2, %3}, {%4, %5, %6, %7}, {%8, %9}, {%10, %11, %12, %13};"
    : "=f"(c[0]), "=f"(c[1]), "=f"(c[2]), "=f"(c[3]) : "r"(a0), "r"(a1), "r"(a2), "r"(a3), "r"(b0), "r"(b1), "f"(c[0]), "f"(c[1]), "f"(c[2]), "f"(c[3]));
}
__device__ __forceinline__ void sts128(uint32_t a, uint32_t r0, uint32_t r1, uint32_t r2, uint32_t r3) {
  asm volatile("st.shared.v4.b32 [%0], {%1, %2, %3, %4};" ::"r"(a), "r"(r0), "r"(r1), "r"(r2), "r"(r3) : "memory");
}
__device__ __forceinline__ void lds128(uint32_t a, uint32_t& r0, uint32_t& r1, uint32_t& r2, uint32_t& r3) {
  asm volatile("ld.shared.v4.b32 {%0, %1, %2, %3}, [%4];" : "=r"(r0), "=r"(r1), "=r"(r2), "=r"(r3) : "r"(a) : "memory");
}
__device__ __forceinline__ float2 lds64f(uint32_t a) { float2 v; asm volatile("ld.shared.v2.f32 {%0, %1}, [%2];" : "=f"(v.x), "=f"(v.y) : "r"(a) : "memory"); return v; }
__device__ __forceinline__ float4 lds128f(uint32_t a) { float4 v; asm volatile("ld.shared.v4.f32 {%0, %1, %2, %3}, [%4];" : "=f"(v.x), "=f"(v.y), "=f"(v.z), "=f"(v.w) : "r"(a) : "memory"); return v; }
__device__ __forceinline__ void sts64f(uint32_t a, float x, float y) { asm volatile("st.shared.v2.f32 [%0], {%1, %2};" ::"r"(a), "f"(x), "f"(y) : "memory"); }
__device__ __forceinline__ float lds32f(uint32_t a) { float v; asm volatile("ld.shared.f32 %0, [%1];" : "=f"(v) : "r"(a) : "memory"); return v; }
__device__ __forceinline__ void sts32f(uint32_t a, float x) { asm volatile("st.shared.f32 [%0], %1;" ::"r"(a), "f"(x) : "memory"); }
__device__ __forceinline__ void stat_st(uint2* p, float sum, float sq, uint32_t tag, bool on) {
  const float mean = sum * (1.f / 128), m2 = fmaxf(fmaf(-mean, sum, sq), 0.f);
  const uint32_t a = ((__float_as_uint(mean) + 8u) & ~15u) | (tag & 15u), b = ((__float_as_uint(m2) + 8u) & ~15u) | (tag & 15u);
  asm volatile("{\n.reg .b64 x;\n.reg .pred p;\nsetp.ne.u32 p, %3, 0;\nmov.b64 x, {%1, %2};\n@p st.relaxed.gpu.global.b64 [%0], x;\n}\n" ::"l"(p), "r"(a), "r"(b), "r"((uint32_t)on) : "memory");
}
__device__ __forceinline__ void stat_ld2(const uint2* p, uint32_t (&v)[4]) {
  asm volatile("{\n.reg .b64 x, y;\nld.relaxed.gpu.global.v2.b64 {x, y}, [%4];\nmov.b64 {%0, %1}, x;\nmov.b64 {%2, %3}, y;\n}\n"
    : "=r"(v[0]), "=r"(v[1]), "=r"(v[2]), "=r"(v[3]) : "l"(p) : "memory");
}
__device__ __forceinline__ float untag(uint32_t v) { return __uint_as_float(v & ~15u); }
__device__ __forceinline__ void ll_st3(uint4* p, uint32_t a, uint32_t b, uint32_t c, uint32_t tag) {
  asm volatile("{\n.reg .b64 x, y;\n.reg .b128 z;\nmov.b64 x, {%1, %2};\nmov.b64 y, {%3, %4};\nmov.b128 z, {x, y};\nst.relaxed.gpu.global.b128 [%0], z;\n}\n"
    ::"l"(p), "r"(a), "r"(b), "r"(c), "r"(tag) : "memory");
}
__device__ __forceinline__ uint32_t ll_ld3(const uint4* p, uint32_t& a, uint32_t& b, uint32_t& c, uint32_t tag) {
  uint32_t t;
  asm volatile("{\n.reg .b64 x, y;\n.reg .b128 z;\nld.relaxed.gpu.global.b128 z, [%4];\nmov.b128 {x, y}, z;\nmov.b64 {%0, %1}, x;\nmov.b64 {%2, %3}, y;\n}\n"
    : "=r"(a), "=r"(b), "=r"(c), "=r"(t) : "l"(p) : "memory");
  return t ^ tag;
}
__device__ __forceinline__ void halo_send(uint4* p, uint32_t a, const uint32_t (&tg)[6]) {
  asm volatile("{\n.reg .b64 x<6>, y<6>, w<2>;\n.reg .b32 c<4>;\n.reg .b128 z<6>;\n"
    "ld.shared.b64 w0, [%1+1536];\nld.shared.b64 w1, [%1+1792];\n"
    "ld.shared.b64 x0, [%1];\nld.shared.b64 x1, [%1+256];\nld.shared.b64 x2, [%1+512];\n"
    "ld.shared.b64 x3, [%1+768];\nld.shared.b64 x4, [%1+1024];\nld.shared.b64 x5, [%1+1280];\n"
    "mov.b64 {c0, c1}, w0;\nmov.b64 {c2, c3}, w1;\n"
    "mov.b64 y0, {c0, %2};\nmov.b64 y1, {c1, %3};\nmov.b64 y2, {c2, %4};\nmov.b64 y3, {c3, %5};\nmov.b64 y4, {%6, %6};\nmov.b64 y5, {%7, %7};\n"
    "mov.b128 z0, {x0, y0};\nmov.b128 z1, {x1, y1};\nmov.b128 z2, {x2, y2};\nmov.b128 z3, {x3, y3};\nmov.b128 z4, {x4, y4};\nmov.b128 z5, {x5, y5};\n"
    "st.relaxed.gpu.global.b128 [%0], z0;\nst.relaxed.gpu.global.b128 [%0+512], z1;\nst.relaxed.gpu.global.b128 [%0+1024], z2;\n"
    "st.relaxed.gpu.global.b128 [%0+1536], z3;\nst.relaxed.gpu.global.b128 [%0+2048], z4;\nst.relaxed.gpu.global.b128 [%0+2560], z5;\n}\n"
    ::"l"(p), "r"(a), "r"(tg[0]), "r"(tg[1]), "r"(tg[2]), "r"(tg[3]), "r"(tg[4]), "r"(tg[5]) : "memory");
}
template <int N> __device__ __forceinline__ void copy_out(uint8_t* dst, uint32_t src, int stride) {
  uint4 v[N];
#pragma unroll
  for (int k = 0; k < N; k++) lds128(src + k * stride, v[k].x, v[k].y, v[k].z, v[k].w);
#pragma unroll
  for (int k = 0; k < N; k++) asm volatile("st.global.v4.b32 [%0], {%1, %2, %3, %4};" ::"l"(dst + k * stride), "r"(v[k].x), "r"(v[k].y), "r"(v[k].z), "r"(v[k].w) : "memory");
}
__device__ __forceinline__ void warp_store(uint8_t* dst, uint32_t src, int bytes, uint32_t delay, uint32_t pace) {
  __nanosleep(delay);
#pragma unroll 1
  for (int o = 0; o < bytes; o += 2048) {
    if (pace) __nanosleep(pace);
    uint4 v[4];
#pragma unroll
    for (int k = 0; k < 4; k++) lds128(src + o + k * 512, v[k].x, v[k].y, v[k].z, v[k].w);
#pragma unroll
    for (int k = 0; k < 4; k++) asm volatile("st.global.v4.b32 [%0], {%1, %2, %3, %4};" ::"l"(dst + o + k * 512), "r"(v[k].x), "r"(v[k].y), "r"(v[k].z), "r"(v[k].w) : "memory");
  }
  __syncwarp();
}
__device__ __forceinline__ uint32_t clock32() { uint32_t t; asm volatile("mov.u32 %0, %%clock;" : "=r"(t)); return t; }
__device__ __forceinline__ void flag_set(uint32_t* p, uint32_t bit) { asm volatile("red.release.gpu.global.xor.b32 [%0], %1;" ::"l"(p), "r"(bit) : "memory"); }
__device__ __forceinline__ void flag_wait(const uint32_t* p, uint32_t inv, uint32_t need, uint32_t& ready) {
  if ((ready & need) == need) return;
  uint32_t n = 0;
  do {
    asm volatile("ld.relaxed.gpu.global.b32 %0, [%1];" : "=r"(ready) : "l"(p) : "memory");
    ready = __shfl_sync(0xffffffffu, ready, 0) ^ inv;
  } while ((ready & need) != need && ++n < SPIN_MAX);
  asm volatile("fence.acquire.gpu;\nfence.proxy.async.global;" ::: "memory");
}
__device__ __forceinline__ bool elect_one() {
  uint32_t p;
  asm volatile("{\n.reg .pred P;\nelect.sync _|P, 0xffffffff;\nselp.u32 %0, 1, 0, P;\n}\n" : "=r"(p));
  return p;
}
__device__ __forceinline__ float gelu_half(float hx) {
  const float y = hx * fmaf(hx * hx, 8.f * 0.0356774081f, 2.f * 0.7978845608f);
  float th;
  asm("tanh.approx.f32 %0, %1;" : "=f"(th) : "f"(y));
  return fmaf(hx, th, hx);
}
__device__ __forceinline__ float ex2(float x) { float y; asm("ex2.approx.ftz.f32 %0, %1;" : "=f"(y) : "f"(x)); return y; }

__device__ __forceinline__ void stat_combine(uint32_t am, uint32_t aq, uint32_t bm, uint32_t bq, float pv, float& mean, float& var) {
  const float d0 = untag(am) - pv, d1 = untag(bm) - pv;
  float s = d0 + d1, q = fmaf(fmaf(d0, d0, d1 * d1), 128.f, untag(aq) + untag(bq));
  s += __shfl_xor_sync(0xffffffffu, s, 8); q += __shfl_xor_sync(0xffffffffu, q, 8);
  s += __shfl_xor_sync(0xffffffffu, s, 16); q += __shfl_xor_sync(0xffffffffu, q, 16);
  s *= 0.125f;
  mean = pv + s;
  var = fmaxf(fmaf(-s, s, q * (1.f / D_)), 0.f);
}

__device__ __forceinline__ void attn_probs(const uint32_t* q0, const uint32_t* q1,
                                           const uint32_t* k0, const uint32_t* k1, const uint32_t* k2, const uint32_t* k3,
                                           float sc0, float sc1, float mk0, float mk1, bool e, bool zneg, const uint32_t (&sel)[3],
                                           uint32_t (&pr)[6], float (&l)[2]) {
  float s[4][4];
#pragma unroll
  for (int n = 0; n < 4; n++) {
    const uint32_t* k = n == 0 ? k0 : n == 1 ? k1 : n == 2 ? k2 : k3;
    s[n][0] = s[n][1] = n < 2 ? mk0 : 0.f; s[n][2] = s[n][3] = n < 2 ? mk1 : 0.f;
    mma16816(s[n], q0[0], q1[0], q0[1], q1[1], k[0], k[1]);
    mma16816(s[n], q0[2], q1[2], q0[3], q1[3], k[2], k[3]);
  }
  float a0 = e ? s[1][1] : s[1][0];
  float b0 = zneg ? (e ? s[0][1] : s[0][0]) : (e ? s[2][1] : s[2][0]);
  float a1 = e ? s[2][3] : s[2][2];
  float b1 = zneg ? (e ? s[1][3] : s[1][2]) : (e ? s[3][3] : s[3][2]);
  float m0 = fmaxf(a0, b0), m1 = fmaxf(a1, b1);
  m0 = fmaxf(m0, __shfl_xor_sync(0xffffffffu, m0, 1)); m1 = fmaxf(m1, __shfl_xor_sync(0xffffffffu, m1, 1));
  m0 = fmaxf(m0, __shfl_xor_sync(0xffffffffu, m0, 2)); m1 = fmaxf(m1, __shfl_xor_sync(0xffffffffu, m1, 2));
  a0 = ex2((a0 - m0) * sc0); b0 = ex2((b0 - m0) * sc0); a1 = ex2((a1 - m1) * sc1); b1 = ex2((b1 - m1) * sc1);
  l[0] = a0 + b0; l[1] = a1 + b1;
  const uint32_t p0 = pack2(a0, b0), p1 = pack2(a1, b1);
#pragma unroll
  for (int k = 0; k < 3; k++) { pr[k] = __byte_perm(p0, 0u, sel[k]); pr[3 + k] = __byte_perm(p1, 0u, sel[k]); }
}
__device__ __forceinline__ void attn_pv(const uint32_t (&pr)[6], const uint32_t* vh, const uint32_t* v, float (&o)[4][4]) {
#pragma unroll
  for (int dt = 0; dt < 4; dt++) {
    o[dt][0] = o[dt][1] = o[dt][2] = o[dt][3] = 0.f;
    mma16816(o[dt], pr[0], 0u, pr[1], pr[3], vh[2 * dt], vh[2 * dt + 1]);
    mma16816(o[dt], pr[2], pr[4], 0u, pr[5], v[2 * dt], v[2 * dt + 1]);
  }
}

#define ATT 25
#define COVER 2
#define HALO_A_NS 300
#define H1D 900
#define FO 2
#define G4GATE 1
#define PFM 7
#define PD1 3
#define PD2 5
#define PD3 3
#define PD4 5
#define FR 1
#define U0D 300
#define X1D 1200
#define PACE 150
#define LEAD1 3
#define LEAD2 3
#define XLD 6
#define XST 3
#define FA 20
#define LEAD4 4
#define STAT_CLK 150
__global__ void __cluster_dims__(2, 1, 1) __launch_bounds__(384, 1) fused_kernel(const __grid_constant__ Params P) {
  extern __shared__ __align__(1024) uint8_t smem_raw[];
  const uint32_t sb = smem_u32(smem_raw);
  const uint32_t bars = sb + OFF_BAR;
  const int tid = threadIdx.x;
  if (tid == 256) S5(0);
  const int wu = __shfl_sync(0xffffffffu, tid >> 5, 0), wg = wu >> 2;
  const int r = blockIdx.x & 1, cl = blockIdx.x >> 1;
  int grp, slt;
  if (cl < 4) { grp = 0; slt = 4 + cl; }
  else if (cl < 36) { grp = (cl - 4) & 7; slt = (cl - 4) >> 3; }
  else { grp = 1 + (cl - 36) % 7; slt = 4 + (cl - 36) / 7; }
#define MAP 0
  const int m = grp, j = slt;
  const int i = 2 * m + r;
  auto BAR = [&](int k) { return bars + 8 * k; };

  auto kb1 = [&](int n) { const int h = n >= 9, t = n - 2 - 7 * h; return n < 2 ? 2 * j + n : 2 * (t + (t >= j)) + h; };
  auto first_round = [&](int u0, int u1) {
#pragma unroll 1
    for (int u = u0; u < u1; u++) {
      S5(3 + u);
      mbar_expect(BAR(F1 + u), 40960);
      tma2d(sb + slot1(u), &P.x0, BAR(F1 + u), u * 64, 128 * i);
      tma3d(sb + slot1(u) + 16384, &P.wqkv, BAR(F1 + u), 128 * j, u * 64, 0);
      tma3d(sb + slot1(u) + 28672, &P.wqkv, BAR(F1 + u), 128 * j, u * 64 + 32, 0);
    }
  };
  if (wu == 9) {
    if (elect_one()) asm volatile("prefetch.tensormap [%0];" ::"l"(&P.wqkv) : "memory");
    __syncwarp();
  } else if (wu == 8) {
    if (elect_one()) {
      S5(1);
#pragma unroll
      for (int k = 0; k < 4; k++) mbar_init(BAR(F1 + k), 1);
      asm volatile("fence.mbarrier_init.release.cluster;" ::: "memory");
      fence_async_smem();
      first_round(0, FR);
    }
    __syncwarp();
  } else if (wu == 0) {
    if (elect_one()) {
#pragma unroll
      for (int k = E1; k < 64; k++) {
        int cnt = 1;
        if (k < F2 || (k >= E2 && k < F3) || (k >= E3 && k < F4) || (k >= E4 && k < JOB) || k == JOB + 2 || k == JOB + 3) cnt = 4;
        else if ((k >= JOB && k < RD) || k == CSJ) cnt = 8;
        else if (k == RD + 1 || k == STD || k == STAT || k >= HALO) cnt = 2;
        mbar_init(BAR(k), cnt);
      }
      asm volatile("fence.mbarrier_init.release.cluster;" ::: "memory");
      fence_async_smem();
    }
    __syncwarp();
  }
  auto load_tag = [&]() { uint32_t t; asm volatile("ld.relaxed.gpu.global.u32 %0, [%1];" : "=r"(t) : "l"(&gEpoch) : "memory"); return t + 1; };
  TS(0);
  if (wu == 8) nb_arrive<NB_INIT>(384); else nb_sync<NB_INIT>(384);
  asm volatile("barrier.cluster.arrive.relaxed;" ::: "memory");

  if (wg == 2) {
    if (tid == 256) S5(2);
    reg_dealloc<40>();
    if (wu == 8) {
      if (elect_one()) first_round(FR, 4);
      __syncwarp();
    }
    asm volatile("barrier.cluster.wait;" ::: "memory");
    auto kb3 = [&](int n) { const int h = n >= 17, t = n - 2 - 15 * h; return n < 2 ? 2 * i + n : t == 14 ? 2 * (i ^ 1) + h : 2 * ((2 * m + 2 + t) & 15) + h; };
    auto v1 = [&](int L, int u) { const int u0 = L ? 2 : 10; return (u >= u0 && u < 18) ? (u < u0 + 2 ? u - u0 + 16 : u - 2) : u; };
    auto kb2 = [&](int n) { return n < 8 ? 2 * n : n == 8 ? 2 * j + 1 : 2 * (n - 9 + (n - 9 >= j)) + 1; };
    if (wu == 8) {
      const int lane = tid & 31;
      auto pf = [&](const bf16* p, bool on) { if (on) asm volatile("prefetch.global.L2 [%0];" ::"l"(p)); };

      auto k1 = [&](int L, int v) { return (L || v >= 16) ? kb1(v & 15) : v; };
      auto kb4f = [&](int n) {
        const bool own = n == 0 || n == 9 || n == 17;
        const int q = n - 10 - (n > 17), c = own ? n >> 3 : q / 15, t = q - 15 * c;
        const int ii = own ? i : t < 14 ? (2 * m + 2 + t) & 15 : i ^ 1;
        return (n >= 1 && n <= 8) ? 7 * ((m + n) & 7) + 3 : ((7 * ii + 1) >> 1) + c;
      };
      const uint32_t tab4 = kb4f(lane) | (kb4f(lane + 32) << 16);
      auto kb4 = [&](int n) { return (int)((__shfl_sync(0xffffffffu, tab4, n) >> ((n >> 1) & 16)) & 63); };
      const bf16* const q1 = P.wqkv_p + (4 * i + (lane & 3)) * 3072 + (lane >> 2) * 1024 + 128 * j;
      const bf16* const q2 = P.wo_p + (4 * i + (lane & 3)) * 1024 + (lane >> 2) * 64 + 128 * j;
      const bf16* const q3 = P.w1_p + (8 * j + (lane >> 2)) * 3584 + 64 * (7 * m + ((lane & 3) == 3 ? 3 : 4 * r + (lane & 3)));
      const bf16* const q4 = P.w2_p + (8 * j + (lane >> 1)) * 2048 + 128 * i + 64 * (lane & 1);
      auto pf1 = [&](int L, int u) { const int v = v1(L, u); pf(q1 + k1(L, v) * (64 * 3072) + 64 * (v >> 4), (PFM & 1) && lane < 12); };
      auto pf2 = [&](int n) { pf(q2 + kb2(n) * (64 * 1024), (PFM & 2) && lane < 8); };
      auto pf3 = [&](int n) { pf(q3 + kb3(n) * (64 * 3584), PFM & 4); };
      auto pf4 = [&](int n) { pf(q4 + kb4(n) * (64 * 2048), (PFM & 8) && lane < 16); };
#pragma unroll 1
      for (int u = 4; u < 4 + PD1; u++) pf1(0, u);
#pragma unroll 1
      for (int L = 0; L < 2; L++) {
#pragma unroll 1
        for (int u = L ? 0 : 4; u < 32; u++) {
          const int v = v1(L, u), p = u & 3;
          if (u >= 4) mbar_wait(BAR(E1 + p), ((u >> 2) - 1) & 1);
          else mbar_wait(BAR(E4 + (u == 3 ? 0 : u + 3)), u == 3);
          if (elect_one()) {
            mbar_expect(BAR(F1 + p), (v & 15) < 2 ? 24576 : 40960);
            tma3d_mc(sb + slot1(p) + 16384 + r * 12288, &P.wqkv, BAR(F1 + p), 128 * j + 64 * (v >> 4), k1(L, v) * 64 + 32 * r, 0);
          }
          if (u + PD1 < 32) pf1(L, u + PD1);
          if (u + PD2 >= 32) pf2(u + PD2 - 32);
        }
        int p = 0; uint32_t par = L ? 0x1e : 0;
#pragma unroll 1
        for (int n = 0; n < 16; n++) {
          if (n >= 5) { mbar_wait(BAR(E2 + p), (par >> p) & 1); par ^= 1u << p; }
          else if (n < 4) mbar_wait(BAR(E1 + n), 1);
          if (elect_one()) {
            mbar_expect(BAR(F2 + p), n == 8 ? 16384 : 32768);
            tma2d_mc(sb + slot2(p) + 16384 + r * 8192, &P.wo, BAR(F2 + p), 128 * j + 64 * r, kb2(n) * 64);
          }
          if (++p == 5) p = 0;
          if (n + PD2 < 16) pf2(n + PD2);
          if (n + PD3 + 4 >= 16) pf3(n + PD3 + 4 - 16);
        }
#pragma unroll 1
        for (int u = 0; u < 32; u++) {
          const int n = u < 4 ? (0x2031 >> (4 * u)) & 3 : u, p = n & 3, kb = kb3(n);
          if (n == 4) mbar_wait(BAR(RD + 4), L);
          if (n >= 4) mbar_wait(BAR(E3 + p), ((n >> 2) - 1) & 1);
          else if (n == 1) mbar_wait(BAR(STD + 1), L);
          else if (n == 3) mbar_wait(BAR(E2 + 2), L);
          else if (n == 0) mbar_wait(BAR(E2 + 4), L);
          else mbar_wait(BAR(E2 + 0), 1);
          if (elect_one()) {
            mbar_expect(BAR(F3 + p), n < 2 ? 32768 : 49152);
            tma3d(sb + slot3(p) + 16384, &P.w1, BAR(F3 + p), 0, kb * 64, 7 * m + 4 * r);
            tma3d(sb + slot3(p) + 40960, &P.w1h, BAR(F3 + p), 0, kb * 64, 14 * m + 6 + r);
          }
          if (u >= 4 && u + PD3 < 32) pf3(u + PD3);
          if (u + PD4 + 6 >= 32) pf4(u + PD4 + 6 - 32);
        }
        auto g4w = [&](int n, int p, int kb) {
          if (elect_one()) {
            mbar_expect(BAR(F4 + p), (n == 0 || n == 9 || n == 17) ? 16384 : 32768);
            tma3d(sb + slot4(p), &P.w2, BAR(F4 + p), 0, kb * 64, 2 * i);
          }
        };
#pragma unroll 1
        for (int n = 0; n < 6; n++) {
          const int kb = kb4(n);
          if (n == G4GATE) mbar_wait(BAR(RD + 3), L);
          if (n < 3) mbar_wait(BAR(E3 + n), 1);
          else if (n == 4) mbar_wait(BAR(E3 + 3), 1);
          g4w(n, n, kb);
        }
        p = 0; par = L ? 0x3c : 0;
#pragma unroll 1
        for (int n = 6; n < 56; n++) {
          const int kb = kb4(n);
          if (n + PD4 < 56) pf4(n + PD4);
          mbar_wait(BAR(E4 + p), (par >> p) & 1); par ^= 1u << p;
          g4w(n, p, kb);
          if (++p == 6) p = 0;
        }
        if (L == 0)
#pragma unroll 1
          for (int u = 0; u < PD1; u++) pf1(1, u);
      }
    } else if (wu == 9) {
      uint32_t inv = 0;
#pragma unroll 1
      for (int L = 0; L < 2; L++) {
        uint32_t ready = 0;
#pragma unroll 1
        for (int u = 4; u < 32; u++) {
          const int p = u & 3, v = v1(L, u), nn = v & 15, kb = (L || v >= 16) ? kb1(nn) : nn;
          if (L == 0 && (u == XLD || u == XLD + XST) && elect_one()) {
            const int h = u != XLD;
            mbar_expect(BAR(XF + h), 16384);
            tma2d(sb + OFF_X + h * 16384, &P.x0, BAR(XF + h), 128 * j + 64 * h, 128 * i);
          }
          if (nn < 2) continue;
          if (L && u < 12) mbar_wait(BAR(F1 + p), u >> 3);
          if (u >= 4 + 4 * L) mbar_wait(BAR(E1 + p), ((u >> 2) - 1) & 1);
          if (L) {
            flag_wait(gFlag[0][0][i], inv, 1u << kb, ready);
            if (elect_one()) bulk_ld(sb + slot1(p), gXB + (i * 16 + kb) * 16384, 16384, BAR(F1 + p));
          } else if (elect_one()) tma2d(sb + slot1(p), &P.x0, BAR(F1 + p), kb * 64, 128 * i);
        }
        ready = 0;
        if (L == 0) inv = (__shfl_sync(0xffffffffu, load_tag(), 0) & 1) - 1;
        int p = 0; uint32_t par = L ? 0x1e : 0;
#pragma unroll 1
        for (int n = 0; n < 16; n++) {
          const int hp = kb2(n);
          if (n == 8) { par ^= 8; p = 4; continue; }
          if (n >= 5) { mbar_wait(BAR(E2 + p), (par >> p) & 1); par ^= 1u << p; }
          else if (n < 4) mbar_wait(BAR(E1 + n), 1);
          flag_wait(gFlag[L][1][i], inv, 1u << hp, ready);
          if (n == 9) ST(4);
          if (elect_one()) bulk_ld(sb + slot2(p), gOB + (i * 16 + hp) * 16384, 16384, BAR(F2 + p));
          if (++p == 5) p = 0;
        }
        ready = 0;
        mbar_wait(BAR(E2 + 0), 1);
#pragma unroll 1
        for (int n = 2; n < 32; n++) {
          const int p = n & 3, kb = kb3(n);
          if (n > 3) mbar_wait(BAR(E3 + p), ((n >> 2) - 1) & 1);
          flag_wait(gFlag[L][2][j], inv, 1u << kb, ready);
          if (n == 2) ST(12);
          if (elect_one()) {
            const uint8_t* src = gHB + (j * 32 + kb) * 16384;
            if (n != 16 && n != 31) bulk_ld_mc(sb + slot3(p) + r * 8192, src + r * 8192, 8192, BAR(F3 + p));
            else bulk_ld(sb + slot3(p), src, 16384, BAR(F3 + p));
          }
        }
        ready = 0; p = 1; par = L ? 0x3c : 0;
#pragma unroll 1
        for (int t = 0; t < 8; t++) {
          const int mm = (m + t + 1) & 7;
          if (t < 3) mbar_wait(BAR(E3 + 1 + t), 1);
          if (t >= 5) { mbar_wait(BAR(E4 + p), (par >> p) & 1); par ^= 1u << p; }
          flag_wait(gFlag[L][6][j], inv, 3u << (2 * mm), ready);
          if (t == 0) ST(20);
          if (elect_one()) bulk_ld_mc(sb + slot4(p) + 16384 + r * 8192, gUB + (j * 56 + 48 + mm) * 16384 + r * 8192, 8192, BAR(F4 + p));
          if (++p == 6) p = 0;
        }
#pragma unroll 1
        for (int c = 0; c < 3; c++) {
          ready = 0;
#pragma unroll 1
          for (int t = 0; t < 15; t++) {
            const int ii = t < 14 ? (2 * m + 2 + t) & 15 : i ^ 1;
            if (c == 0 && (t == 0 || t == 7)) { par ^= 1u << p; if (++p == 6) p = 0; }
            mbar_wait(BAR(E4 + p), (par >> p) & 1); par ^= 1u << p;
            flag_wait(gFlag[L][3 + c][j], inv, 1u << ii, ready);
            if (elect_one()) {
              const uint8_t* src = gUB + (j * 56 + 16 * c + ii) * 16384;
              if (t < 14) bulk_ld_mc(sb + slot4(p) + 16384 + r * 8192, src + r * 8192, 8192, BAR(F4 + p));
              else bulk_ld(sb + slot4(p) + 16384, src, 16384, BAR(F4 + p));
            }
            if (++p == 6) p = 0;
          }
        }
      }
    } else {
      const int h = wu - 10, i0 = i, j0 = j;
      {
      const uint32_t tag = load_tag();
      int lane = tid & 31, i = i0, j = j0;
#define FRESH asm volatile("" : "+r"(lane), "+r"(i), "+r"(j))
      auto signal = [&](int k) { if (lane == 0) mbar_arrive(BAR(k)); };
      auto publish = [&](uint32_t* f, int bit) { if (lane == 0) flag_set(f, 1u << bit); __syncwarp(); };
#pragma unroll 1
      for (int c = 32 * h + lane; c < 288; c += 64)
        sts16(sb + OFF_B1 + 2 * c, c >= 224 ? 0u : pack2(0.5f * __bfloat162float(P.b1[c < 192 ? 64 * (7 * m + 4 * r) + c : 64 * (7 * m + 3) + 32 * r + c - 192]), 0.f));
      if (h == 0) sts32f(sb + OFF_CS + 768 + 4 * lane, 0.f);
#pragma unroll 1
      for (int L = 0; L < 2; L++) {
        FRESH;
        if (L == 0) {
          mbar_wait(BAR(CSJ), 0);
          float c0 = 0.f, c1 = 0.f, c2 = 0.f;
          const uint32_t a = sb + OFF_STG + (32 * h + lane) * 4;
#pragma unroll 4
          for (int k = 0; k < 32; k++) { c0 += lds32f(a + k * 784); c1 += lds32f(a + k * 784 + 256); c2 += lds32f(a + k * 784 + 512); }
          ll_st3(&gCS[j][i][32 * h + lane], __float_as_uint(c0), __float_as_uint(c1), __float_as_uint(c2), tag);
          __nanosleep(500);
        }
        FRESH;
        if (L == 0) {
#pragma unroll 1
          for (int ab = 0; ab < 2; ab++) {
            float c0 = 0.f, c1 = 0.f, c2 = 0.f;
#pragma unroll 1
            for (int b4 = 0; b4 < 8; b4 += 4) {
              uint32_t a[4], b[4], c[4], n = 0, bad;
              do {
                bad = 0;
#pragma unroll
                for (int e = 0; e < 4; e++) bad |= ll_ld3(&gCS[j][2 * (b4 + e) + ab][32 * h + lane], a[e], b[e], c[e], tag);
              } while (bad && ++n < SPIN_MAX);
#pragma unroll
              for (int e = 0; e < 4; e++) { c0 += __uint_as_float(a[e]); c1 += __uint_as_float(b[e]); c2 += __uint_as_float(c[e]); }
            }
            const uint32_t a = sb + OFF_CS + ab * 768 + (4 * h + (lane >> 3)) * 32 + (lane & 7) * 2;
            const uint32_t h0 = pack2(c0, 0.f), h1 = pack2(c1, 0.f), h2 = pack2(c2, 0.f);
            sts16(a, h0); sts16(a + 256, h1); sts16(a + 512, h2);
            sts16(a + 16, pack2(c0 - bf_lo(h0), 0.f)); sts16(a + 272, pack2(c1 - bf_lo(h1), 0.f)); sts16(a + 528, pack2(c2 - bf_lo(h2), 0.f));
            fence_async_smem();
            __syncwarp();
            if (ab == 0) signal(STAT);
          }
        }
#pragma unroll 1
        for (int ab = 0; ab < 2; ab++) {
          FRESH;
          uint32_t v[18], tg[6];
          const uint32_t xs = sb + OFF_STG + h * 16384 + lane * 8;
          uint4* hp = &gHalo[L][i][j][6 * h][lane];
#pragma unroll
          for (int c = 0; c < 6; c++) { tg[c] = (2 * tag + ab) * 8 + c; asm volatile("" : "+r"(tg[c])); }
          asm volatile("" : "+l"(hp));
          mbar_wait(BAR(FOLD + ab), L);
          if (ab && h == 0) ST(6);
          if (i < 15) {
            halo_send(hp, xs, tg);
          }
          if (ab && h == 0) ST(26);
          if (i > 0) {
            if (!ab) __nanosleep(HALO_A_NS);
            uint32_t n = 0, bad;
            do {
              bad = 0;
#pragma unroll
              for (int c = 0; c < 6; c++) bad |= ll_ld3(hp + c * 32 - 8 * 12 * 32, v[3 * c], v[3 * c + 1], v[3 * c + 2], (2 * tag + ab) * 8);
              if (ab && h == 0 && n == 0) ST(28);
            } while (bad > 7 && ++n < SPIN_MAX);
            if (ab && h == 0) ST(27);
          } else {
#pragma unroll
            for (int c = 0; c < 18; c++) v[c] = 0u;
          }
#pragma unroll
          for (int c = 0; c < 6; c++) sts64f(xs + c * 256, __uint_as_float(v[3 * c]), __uint_as_float(v[3 * c + 1]));
          sts64f(xs + 1536, __uint_as_float(v[2]), __uint_as_float(v[5]));
          sts64f(xs + 1792, __uint_as_float(v[8]), __uint_as_float(v[11]));
          __syncwarp();
          signal(HALO + ab);
          if (ab && h == 0) ST(7);
          FRESH;
          if (ab == 0 && lane == 0) asm volatile("st.relaxed.gpu.global.u32 [%0], %1;" ::"l"(&gAck[L][i][j][h][0]), "r"(tag) : "memory");
          uint8_t* dst = gOB + (i * 16 + 2 * j + ab) * 16384;
          uint32_t* flag = gFlag[L][1][i];
          asm volatile("" : "+l"(dst), "+l"(flag));
          mbar_wait(BAR(JOB + ab), L);
          if (h == 0) {
            if (ab) ST(1);
            if (lane == 0) { bulk_st(dst, sb + OFF_STG, 16384); bulk_commit(); bulk_wait0(); }
            signal(STD + ab);
            if (ab) ST(2);
            publish(flag, 2 * j + ab);
            if (ab) ST(3);
          } else if (ab == 0) {
            if (i < 15 && lane < 2) {
              uint32_t t, n = 0;
              do { asm volatile("ld.relaxed.gpu.global.u32 %0, [%1];" : "=r"(t) : "l"(&gAck[L][i + 1][j][lane][0]) : "memory"); } while (t != tag && ++n < SPIN_MAX);
            }
            __syncwarp();
            signal(STD);
          }
        }
#pragma unroll 1
        for (int k = 0; k < 4 - L; k++) {
          FRESH;
          const int job = 2 * k + h;
          uint8_t* dst = k == 0 ? gHB + (j * 32 + 2 * i + 1) * 16384 : k == 3 ? gXB + (i * 16 + 2 * j + 1) * 16384 : gUB + (j * 56 + 16 * (job - 3) + i) * 16384;
          uint32_t* flag = k == 3 ? gFlag[0][0][i] : gFlag[L][(0x543622 >> (4 * job)) & 15][j];
          uint32_t bit = 1u << (k == 0 ? 2 * i + h : k == 3 ? 2 * j + h : i);
          asm volatile("" : "+l"(dst), "+l"(flag), "+r"(bit));
          mbar_wait(BAR(JOB + ((0x98654732 >> (4 * job)) & 15)), L);
          if (job < 3 && h == 0) ST(job ? 17 : 9);
          if ((0xba >> job) & 1) {
            if (job == 1) mbar_wait(BAR(RD + 4), L);
            if (job == 3) {
              __nanosleep(U0D);
              if (lane == 0) { bulk_st(dst, sb + OFF_X, 16384); bulk_commit(); bulk_wait0(); }
            } else warp_store(dst + lane * 16, sb + lane * 16 + OFF_X + (job == 5 ? 0 : 16384), 16384, job == 1 ? H1D : job == 7 ? X1D : 0, job == 7 ? 0 : PACE);
            if (job != 7) signal(RD + ((0x112000 >> (4 * job)) & 15));
          }
          if (lane == 0) flag_set(flag, bit);
          __syncwarp();
          if (job < 3 && h == 0) { signal(RD + 4 - k); ST(job ? 19 : 11); }
        }
      }
      if (blockIdx.x == 0 && h == 0 && lane == 0) asm volatile("st.relaxed.gpu.global.u32 [%0], %1;" ::"l"(&gEpoch), "r"(tag) : "memory");
      }
    }
    __syncwarp();
    cluster_bar();
  } else {
    reg_alloc<232>();
    asm volatile("barrier.cluster.wait;" ::: "memory");
    const uint32_t rbars = mapa(bars, tid & 1);
    const bool relp = (tid & 127) < 2;
    const uint32_t sd = (sb & 0x3FFFF) >> 4, sda = sd + wg * 512;
    uint32_t tag;
    asm volatile("ld.relaxed.gpu.global.u32 %0, [%1];" : "=r"(tag) : "l"(&gEpoch + (fresh_tid() >> 10)) : "memory");
    auto release = [&](int k) { if (relp) mbar_arrive_cl(rbars + 8 * k); };
    auto signal = [&](int k) { __syncwarp(); if ((fresh_tid() & 31) == 0) mbar_arrive(BAR(k)); };
#define GEOM const int t7 = fresh_tid() & 127, lane = t7 & 31, w = t7 >> 5, g = lane >> 2, q = lane & 3, \
                       lr = lane & 15, lt = lane >> 4, l7 = lane & 7; (void)w; (void)g; (void)q; (void)lr; (void)lt; (void)l7

#pragma unroll 1
    for (int L = 0; L < 2; L++) {
      float acca[96], accb[96], xa[64], acc3[112];
      float nmean0, nmean1, rstd0, rstd1;
      uint16_t b2a, b2b;
      uint2 *e2p, *e2s; uint8_t* e2g; uint32_t e2h;
      uint32_t Q[2][8], K[2][8], V[16];
      auto g1_issue = [&](float (&acc)[96], uint32_t a, uint32_t st, auto first) {
        const uint32_t da = sda + (a >> 4), db = sd + (st >> 4);
        wg_fence();
        static_for<0, 4>([&](auto kk) {
          constexpr uint32_t ia = DI(kk.value * 32, 16), ib = DI(16384 + (kk.value >> 1) * 12288 + (kk.value & 1) * 2048, 4096);
          if constexpr (first.value && kk.value == 0) wgmma_192z<0, 1, ia, ib>(acc, da, db); else wgmma_192<0, 1, ia, ib>(acc, da, db);
        });
        wg_commit();
      };
      auto g1_step = [&](float (&acc)[96], int u, bool rel, bool lead = false) {
        const int p = u & 3;
        mbar_wait(BAR(F1 + p), (u >> 2) & 1);
        KB(u);
        g1_issue(acc, slot1(p), slot1(p), False{});
        if (lead) nb_arrive<NB_LEAD>(256);
        wg_wait<1>();
        if (rel) release(E1 + ((u - 1) & 3));
      };
      auto g1_loop = [&](float (&acc)[96], int u0, int u1, int urel) {
        int u = u0;
#pragma unroll 1
        do { g1_step(acc, u, u > urel); } while (++u < u1);
      };
      auto load_x = [&]() {
        GEOM;
#pragma unroll
        for (int t = 0; t < 16; t += 2) {
          uint32_t v0, v1, v2, v3;
          ldsm4(sb + OFF_X + (t >> 3) * 16384 + (16 * wu + lr) * 128 + ((((t & 7) + lt) ^ l7) << 4), v0, v1, v2, v3);
          xa[4 * t + 0] = bf_lo(v0); xa[4 * t + 1] = bf_hi(v0); xa[4 * t + 2] = bf_lo(v1); xa[4 * t + 3] = bf_hi(v1);
          xa[4 * t + 4] = bf_lo(v2); xa[4 * t + 5] = bf_hi(v2); xa[4 * t + 6] = bf_lo(v3); xa[4 * t + 7] = bf_hi(v3);
        }
      };
      auto stat_base = [&]() { return &gST[0][0][0][0][0] + ((L * 16 + opq(i)) * 8 + wu) * 128; };
      auto stat_slot = [&]() { const int lane = fresh_tid() & 31; return stat_base() + 16 * j + 2 * (lane >> 2) + (lane & 1); };
      auto stat_publish = [&](uint2* sp, float s0, float q0, float s2, float q2, uint32_t tg) {
        const int q = fresh_tid() & 3;
        const bool h1 = q & 1;
        float sm = (h1 ? s2 : s0) + __shfl_xor_sync(0xffffffffu, h1 ? s0 : s2, 1);
        float sq = (h1 ? q2 : q0) + __shfl_xor_sync(0xffffffffu, h1 ? q0 : q2, 1);
        sm += __shfl_xor_sync(0xffffffffu, sm, 2); sq += __shfl_xor_sync(0xffffffffu, sq, 2);
        stat_st(sp, sm, sq, tg, q < 2);
        return sm;
      };
      auto g1_stats = [&](int u0) {
        GEOM;
        const uint32_t xr = sb + OFF_X + (16 * wu + lr) * 128;
        float s0 = 0.f, q0 = 0.f, s2 = 0.f, q2 = 0.f;
        uint32_t v[8] = {0u, 0u, 0u, 0u, 0u, 0u, 0u, 0u};
#pragma unroll 1
        for (int k = 0; k < 5; k++) {
#pragma unroll
          for (int e = 0; e < 8; e += 2) {
            const float a = bf_lo(v[e]), b = bf_hi(v[e]), c = bf_lo(v[e + 1]), d = bf_hi(v[e + 1]);
            s0 += a + b; q0 = fmaf(a, a, fmaf(b, b, q0)); s2 += c + d; q2 = fmaf(c, c, fmaf(d, d, q2));
          }
          if (k == 4) break;
          const uint32_t o = ((2 * k + lt) ^ l7) << 4;
          ldsm4(xr + o, v[0], v[1], v[2], v[3]);
          ldsm4(xr + o + 16384, v[4], v[5], v[6], v[7]);
          g1_step(acca, u0 + k, true);
        }
        stat_publish(stat_slot(), s0, q0, s2, q2, 2 * (tag + 1));
      };
      uint32_t sv0[4], sv1[4];
      auto stat_src = [&]() { return stat_base() + 2 * (fresh_tid() & 31); };
      auto stat_fetch = [&](const uint2* sp) { stat_ld2(sp, sv0); stat_ld2(sp + 64, sv1); };
      auto stat_await = [&](auto src, uint32_t tg) {
#pragma unroll 1
        for (uint32_t n = 0; (((sv0[0] ^ tg) | (sv0[2] ^ tg) | (sv1[0] ^ tg) | (sv1[2] ^ tg)) & 15u) && n < SPIN_MAX; n++) stat_fetch(src());
        __syncwarp();
      };
      auto ln_stats = [&]() {
        GEOM;
        stat_await(stat_src, 2 * (tag + 1));
        float mean0, var0, mean1, var1;
        stat_combine(sv0[0], sv0[1], sv1[0], sv1[1], untag(__shfl_sync(0xffffffffu, sv0[0], l7)), mean0, var0);
        stat_combine(sv0[2], sv0[3], sv1[2], sv1[3], untag(__shfl_sync(0xffffffffu, sv0[2], l7)), mean1, var1);
        nmean0 = -__shfl_sync(0xffffffffu, mean0, g); rstd0 = rsq(__shfl_sync(0xffffffffu, var0, g) + 1e-5f);
        nmean1 = -__shfl_sync(0xffffffffu, mean1, g); rstd1 = rsq(__shfl_sync(0xffffffffu, var1, g) + 1e-5f);
      };
      auto center = [&](float (&acc)[96], int ab) {
        const bool q0 = (fresh_tid() & 3) == 0;
        const uint32_t h0 = pack2(nmean0, nmean0), h1 = pack2(nmean1, nmean1);
        const float l0 = nmean0 - bf_lo(h0), l1 = nmean1 - bf_lo(h1);
        const uint32_t a0 = q0 ? h0 : 0u, a1 = q0 ? h1 : 0u, a2 = q0 ? pack2(l0, l0) : 0u, a3 = q0 ? pack2(l1, l1) : 0u;
        wg_fence();
        wgmma_rs_192(acc, a0, a1, a2, a3, mkdesc_vec(sb + OFF_CS + ab * 768, 32));
      };
      auto frag = [&](float (&acc)[96], int t, uint32_t& p0, uint32_t& p1) {
        if (t >= 8) { p0 = pack2(acc[4 * t] * rstd0, acc[4 * t + 1] * rstd0); p1 = pack2(acc[4 * t + 2] * rstd1, acc[4 * t + 3] * rstd1); }
        else { p0 = pack2(acc[4 * t], acc[4 * t + 1]); p1 = pack2(acc[4 * t + 2], acc[4 * t + 3]); }
      };
      auto fold_v = [&](float (&acc)[96], int t0, int t1) {
        GEOM;
        const uint32_t a = sb + OFF_STG + 16384 + ((wu + 1) & 7) * 2048 + lr * 128;
#pragma unroll
        for (int t = t0; t < t1; t += 2) {
          uint32_t p0, p1, p2, p3;
          frag(acc, 16 + t, p0, p1); frag(acc, 17 + t, p2, p3);
          stsm4(a + (((t + lt) ^ l7) << 4), p0, p1, p2, p3);
        }
        __syncwarp();
#pragma unroll
        for (int t = t0; t < t1; t += 2) ldsm4t(a + (((t + lt) ^ l7) << 4), V[2 * t], V[2 * t + 1], V[2 * t + 2], V[2 * t + 3]);
      };
      auto fold_k = [&](float (&acc)[96], int ab, int h0, int h1) {
        GEOM;
        const uint32_t a = sb + OFF_STG + ((wu + 1) & 7) * 2048 + lane * 16;
#pragma unroll
        for (int hh = h0; hh < h1; hh++) {
#pragma unroll
          for (int t = 4 * hh; t < 4 * hh + 4; t++) frag(acc, 8 + t, K[0][t], K[1][t]);
#pragma unroll
          for (int o = 0; o < 2; o++) sts128(a + (2 * o + hh) * 512, K[o][4 * hh], K[o][4 * hh + 1], K[o][4 * hh + 2], K[o][4 * hh + 3]);
        }
        if (h1 == 2 && wu == 7) signal(FOLD + ab);
      };
      auto fold_q = [&](float (&acc)[96]) {
#pragma unroll
        for (int t = 0; t < 8; t++) frag(acc, t, Q[0][t], Q[1][t]);
      };
      auto attend = [&](int ab, auto drain, auto resume) {
        GEOM;
        nb_sync<NB_BOTH>(256);
        const uint32_t xa_ = sb + OFF_STG + wu * 2048 + lane * 16;
        if (wu == 0) mbar_wait(BAR(HALO + ab), L);
        uint32_t KH[2][8], VH[16];
#pragma unroll
        for (int c = 0; c < 4; c++) {
          lds128(xa_ + c * 512, KH[c >> 1][4 * (c & 1)], KH[c >> 1][4 * (c & 1) + 1], KH[c >> 1][4 * (c & 1) + 2], KH[c >> 1][4 * (c & 1) + 3]);
          ldsm4t(sb + OFF_STG + 16384 + wu * 2048 + lr * 128 + (((2 * c + lt) ^ l7) << 4), VH[4 * c], VH[4 * c + 1], VH[4 * c + 2], VH[4 * c + 3]);
        }
        TS2(11 + ab + 32 * L);
        const bool e = g & 1, zneg = (g >> 1) < q, first = (i == 0) && (wu == 0);
        const float sc0 = rstd0 * (0.17677669530f * 1.4426950409f), sc1 = rstd1 * (0.17677669530f * 1.4426950409f);
        float mk0 = first ? __fdividef(-1.0e9f * 1.4426950409f, sc0) : 0.f, mk1 = first ? __fdividef(-1.0e9f * 1.4426950409f, sc1) : 0.f;
        const uint32_t sa = e ? 0x1044u : 0x4410u, sbb = e ? 0x3244u : 0x4432u;
        uint32_t sel[3] = {zneg ? sbb : 0x4444u, sa, zneg ? 0x4444u : sbb};
        uint32_t oa = sb + OFF_STG + (16 * wu + lr) * 128 + ((lt ^ l7) << 4);
        asm volatile("" : "+r"(sel[0]), "+r"(sel[1]), "+r"(sel[2]), "+r"(oa), "+f"(mk0), "+f"(mk1));
        drain();
        uint32_t pr[2][6];
        float l[2][2];
#pragma unroll
        for (int hh = 0; hh < 2; hh++)
          attn_probs(&Q[0][4 * hh], &Q[1][4 * hh], &KH[0][4 * hh], &KH[1][4 * hh], &K[0][4 * hh], &K[1][4 * hh], sc0, sc1, mk0, mk1, e, zneg, sel, pr[hh], l[hh]);
        float o[2][4][4];
#pragma unroll
        for (int hh = 0; hh < 2; hh++) attn_pv(pr[hh], &VH[8 * hh], &V[8 * hh], o[hh]);
#pragma unroll
        for (int hh = 0; hh < 2; hh++) {
          float l0 = l[hh][0], l1 = l[hh][1];
          l0 += __shfl_xor_sync(0xffffffffu, l0, 1); l1 += __shfl_xor_sync(0xffffffffu, l1, 1);
          l0 += __shfl_xor_sync(0xffffffffu, l0, 2); l1 += __shfl_xor_sync(0xffffffffu, l1, 2);
          asm("rcp.approx.ftz.f32 %0, %0;" : "+f"(l0)); asm("rcp.approx.ftz.f32 %0, %0;" : "+f"(l1));
#pragma unroll
          for (int dt = 0; dt < 4; dt += 2)
            stsm4(oa ^ ((4 * hh + dt) << 4),
                  pack2(o[hh][dt][0] * l0, o[hh][dt][1] * l0), pack2(o[hh][dt][2] * l1, o[hh][dt][3] * l1),
                  pack2(o[hh][dt + 1][0] * l0, o[hh][dt + 1][1] * l0), pack2(o[hh][dt + 1][2] * l1, o[hh][dt + 1][3] * l1));
        }
        fence_async_smem();
        signal(JOB + ab);
        nb_sync<NB_BOTH>(256);
        resume();
      };

      TS(1 + 32 * L);
      if (L == 0 && wu == 0) S5(7);
      mbar_wait(BAR(F1), 0); if (L == 0 && wu == 0) S5(8); KB(0);    g1_issue(acca, L ? OFF_X : slot1(0), slot1(0), True{});
      mbar_wait(BAR(F1 + 1), 0); KB(1); g1_issue(acca, L ? OFF_X + 16384 : slot1(1), slot1(1), False{});
      wg_wait<1>(); release(E1 + 0);
      if (L == 0) {
        GEOM;
        const bf16* wp = P.wqkv_p + ((128 * opq(m) + 16 * wg + (t7 >> 3)) * 3072 + 128 * opq(j) + 64 * r + l7 * 8);
        const uint32_t ca = sb + OFF_STG + (16 * wg + (t7 >> 3)) * 784 + l7 * 32;
#pragma unroll 1
        for (int p = 0; p < 3; p++) {
          uint4 wv[4];
#pragma unroll
          for (int k = 0; k < 4; k++)
            asm volatile("ld.global.nc.v4.u32 {%0, %1, %2, %3}, [%4];" : "=r"(wv[k].x), "=r"(wv[k].y), "=r"(wv[k].z), "=r"(wv[k].w)
                         : "l"(wp + k * 32 * 3072 + p * 1024));
          g1_loop(acca, 2 + 3 * p, p < 2 ? 5 + 3 * p : 10, 0);
          float cs[8];
#pragma unroll
          for (int k = 0; k < 4; k++) {
            const uint4 v = wv[k];
            const float t[8] = {bf_lo(v.x), bf_hi(v.x), bf_lo(v.y), bf_hi(v.y), bf_lo(v.z), bf_hi(v.z), bf_lo(v.w), bf_hi(v.w)};
#pragma unroll
            for (int e = 0; e < 8; e++) cs[e] = k ? cs[e] + t[e] : t[e];
          }
          sts128(ca + p * 256, __float_as_uint(cs[0]), __float_as_uint(cs[1]), __float_as_uint(cs[2]), __float_as_uint(cs[3]));
          sts128(ca + p * 256 + 16, __float_as_uint(cs[4]), __float_as_uint(cs[5]), __float_as_uint(cs[6]), __float_as_uint(cs[7]));
        }
        signal(CSJ);
        mbar_wait(BAR(XF), 0); mbar_wait(BAR(XF + 1), 0);
      }
      {
        const int u0 = L ? 2 : 10;
        mbar_wait(BAR(F1 + 2), 0); KB(u0); g1_issue(accb, OFF_X, slot1(2), True{});
        wg_wait<1>(); release(E1 + 1);
        mbar_wait(BAR(F1 + 3), 0); KB(u0 + 1); g1_issue(accb, OFF_X + 16384, slot1(3), False{});
        wg_wait<1>(); release(E1 + 2);
        g1_stats(u0 + 2);
        g1_loop(acca, u0 + 6, 18, 0);
      }
      stat_fetch(stat_src());
      const int fa = FA + (wg ? 0 : FO);
      g1_loop(accb, 18, fa, 0);
      ln_stats();
      if (L == 0) mbar_wait(BAR(STAT), 0);
      center(acca, 0); wg_commit();
      wg_wait<0>(); release(E1 + ((fa - 1) & 3));
      fence_regs(acca);
      TS(2 + 32 * L);
      fold_v(acca, 0, 8); fold_k(acca, 0, 0, 2); fold_q(acca);
      sched_fence(P.zero);
      g1_loop(accb, fa, ATT, fa);
      attend(0, [&]() { wg_wait<0>(); release(E1 + ((ATT - 1) & 3)); mbar_wait(BAR(F1 + (ATT & 3)), (ATT >> 2) & 1); },
             [&]() { KB(ATT); g1_issue(accb, slot1(ATT & 3), slot1(ATT & 3), False{});
                     mbar_wait(BAR(F1 + ((ATT + 1) & 3)), ((ATT + 1) >> 2) & 1);
                     KB(ATT + 1); g1_issue(accb, slot1((ATT + 1) & 3), slot1((ATT + 1) & 3), False{}); });
      wg_wait<1>(); release(E1 + (ATT & 3));
      TS(3 + 32 * L);
      load_x();
      fence_regs(xa);
      center(accb, 1);
#pragma unroll 1
      for (int u = ATT + 2; u < 32; u++) {
        const bool hold = u == 32 - LEAD1 && wg == 0;
        if (hold) { wg_wait<0>(); release(E1 + ((31 - LEAD1) & 3)); nb_sync<NB_LEAD>(256); }
        g1_step(accb, u, !hold, u == 31 && wg == 1);
      }
      mbar_wait(BAR(STD), L);
      wg_wait<0>(); release(E1 + 3);
      fence_regs(accb);
      TS(4 + 32 * L);
      if (wu == 7) ST(0);
      fold_v(accb, 0, 8); fold_k(accb, 1, 0, 2);
      fold_q(accb);
      TS2(29 + 32 * L);
      {
        auto g2_issue = [&](int p, bool own) {
          const uint32_t st = slot2(p);
          const uint32_t da = sda + ((own ? OFF_STG : st) >> 4), db = sd + (st >> 4);
          wg_fence();
          static_for<0, 4>([&](auto kk) { wgmma_128<0, 1, DI(kk.value * 32, 16), DI(16384 + kk.value * 2048, 8192)>(xa, da, db); });
          wg_commit();
        };
        uint32_t par = L ? 0x1e : 0;
        int p = 0, pp = 0;
        auto g2_loop = [&](int n0, int n1, int nrel) {
#pragma unroll 1
          for (int n = n0; n < n1; n++) {
            mbar_wait(BAR(F2 + p), (par >> p) & 1);
            KB(32 + n);
            if (n == 9 && wu == 0) ST(5);
            par ^= 1u << p;
            g2_issue(p, n == 8);
            if (n1 == 16 && n == 15 && wg == 0) nb_arrive<NB_LEAD>(256);
            wg_wait<1>();
            if (n > nrel) release(E2 + pp);
            pp = p; if (++p == 5) p = 0;
          }
        };
        g2_loop(0, COVER, 0);
        attend(1, [&]() { wg_wait<0>(); release(E2 + COVER - 1); mbar_wait(BAR(F2 + COVER), (par >> COVER) & 1); },
               [&]() { KB(32 + COVER); g2_issue(COVER, false);
                       mbar_wait(BAR(F2 + COVER + 1), (par >> (COVER + 1)) & 1);
                       KB(33 + COVER); g2_issue(COVER + 1, false); });
        wg_wait<1>(); release(E2 + COVER);
        par ^= 3u << COVER; pp = COVER + 1; p = (COVER + 2) % 5;
        TS(30 + 32 * L);
        {
          const bf16* bp = P.b2 + (128 * opq(i) + 16 * wu + ((fresh_tid() & 31) >> 2));
          asm volatile("ld.global.nc.u16 %0, [%1];" : "=h"(b2a) : "l"(bp));
          asm volatile("ld.global.nc.u16 %0, [%1];" : "=h"(b2b) : "l"(bp + 8));
        }
        TS2(14 + 32 * L);
        {
          GEOM;
          e2p = stat_slot(); e2s = stat_src();
          e2g = gHB + (opq(j) * 32 + 2 * i) * 16384 + w * 2048 + lane * 16;
          e2h = sb + OFF_X + wg * 16384 + (16 * w + lr) * 128 + ((lt ^ l7) << 4);
          asm volatile("" : "+l"(e2p), "+l"(e2s), "+l"(e2g), "+r"(e2h));
        }
        g2_loop(COVER + 2, 16 - LEAD2, 0);
        if (wg == 1) { wg_wait<0>(); release(E2 + pp); nb_sync<NB_LEAD>(256); }
        g2_loop(16 - LEAD2, 16, wg == 1 ? 16 - LEAD2 : 0);
        wg_wait<0>();
        release(E2 + 0);
        fence_regs(xa);
      }
      TS(5 + 32 * L);
      if (wu == 0) ST(8);
      {
        GEOM;
        const uint32_t tg = 2 * (tag + 1) + 1;
        float s0 = 0.f, s1 = 0.f, s2 = 0.f, s3 = 0.f, q0 = 0.f, q1 = 0.f, q2 = 0.f, q3 = 0.f;
#pragma unroll
        for (int t = 0; t < 16; t++) {
          s0 += xa[4 * t]; s1 += xa[4 * t + 1]; s2 += xa[4 * t + 2]; s3 += xa[4 * t + 3];
          q0 = fmaf(xa[4 * t], xa[4 * t], q0); q1 = fmaf(xa[4 * t + 1], xa[4 * t + 1], q1);
          q2 = fmaf(xa[4 * t + 2], xa[4 * t + 2], q2); q3 = fmaf(xa[4 * t + 3], xa[4 * t + 3], q3);
        }
        const float sm = stat_publish(e2p, s0 + s1, q0 + q1, s2 + s3, q2 + q3, tg);
        const uint32_t t0 = clock32();
        TS2(13 + 32 * L);
        const float pv0 = __shfl_sync(0xffffffffu, sm, 4 * l7) * (1.f / 128), pv1 = __shfl_sync(0xffffffffu, sm, 4 * l7 + 1) * (1.f / 128);
        while (clock32() - t0 < STAT_CLK) {}
        stat_fetch(e2s);
        wg_fence();
        wgmma_rs_224z(acc3, q == 0 ? 0x3f80u : 0u, q == 0 ? 0x3f80u : 0u, 0u, 0u, mkdesc_vec(sb + OFF_B1, 16));
        wg_commit();
        stat_await([&]() { return e2s; }, tg);
        float r0, m0, r1, m1;
        {
          float mean0, var0, mean1, var1;
          stat_combine(sv0[0], sv0[1], sv1[0], sv1[1], pv0, mean0, var0); stat_combine(sv0[2], sv0[3], sv1[2], sv1[3], pv1, mean1, var1);
          mean0 = __shfl_sync(0xffffffffu, mean0, g); var0 = __shfl_sync(0xffffffffu, var0, g);
          mean1 = __shfl_sync(0xffffffffu, mean1, g); var1 = __shfl_sync(0xffffffffu, var1, g);
          r0 = 0.5f * rsq(fmaf(var0 + 1e-5f, 1e-5f, var0)); r1 = 0.5f * rsq(fmaf(var1 + 1e-5f, 1e-5f, var1));
          m0 = -mean0 * r0; m1 = -mean1 * r1;
        }
        TS2(15 + 32 * L);
#pragma unroll
        for (int t = 0; t < 16; t += 2) {
          stsm4((e2h ^ ((t & 7) << 4)) + (t >> 3) * 8192,
                pack2(fmaf(xa[4 * t], r0, m0), fmaf(xa[4 * t + 1], r0, m0)), pack2(fmaf(xa[4 * t + 2], r1, m1), fmaf(xa[4 * t + 3], r1, m1)),
                pack2(fmaf(xa[4 * t + 4], r0, m0), fmaf(xa[4 * t + 5], r0, m0)), pack2(fmaf(xa[4 * t + 6], r1, m1), fmaf(xa[4 * t + 7], r1, m1)));
          if ((t & 7) == 6 && wg == 0) {
            __syncwarp();
            copy_out<4>(e2g + (t >> 3) * 8192, sb + OFF_X + (t >> 3) * 8192 + w * 2048 + lane * 16, 512);
          }
        }
        signal(JOB + 2 + wg);
        fence_async_smem();
        mbar_wait(BAR(F3 + 0), 0);
        nb_sync<NB_BOTH>(256);
      }
      TS(6 + 32 * L);
      auto g3_issue = [&](uint32_t a, int p) {
        const uint32_t da = sda + (a >> 4), db = sd + (slot3(p) >> 4);
        wg_fence();
        static_for<0, 4>([&](auto kk) { wgmma_224<1, 1, DI(kk.value * 2048, 8192), DI(16384 + kk.value * 2048, 8192)>(acc3, da, db); });
        wg_commit();
      };
      KB(48); g3_issue(OFF_X, 0);
      mbar_wait(BAR(F3 + 1), 0); KB(49); g3_issue(OFF_X + 16384, 1);
      sched_fence(P.zero);
      {
        const float c0 = __uint_as_float((uint32_t)b2a << 16), c1 = __uint_as_float((uint32_t)b2b << 16);
#pragma unroll
        for (int t = 0; t < 16; t++) { xa[4 * t] += c0; xa[4 * t + 1] += c0; xa[4 * t + 2] += c1; xa[4 * t + 3] += c1; }
        fence_regs(xa);
      }
      wg_wait<1>(); release(E3 + 0);
      auto g3_loop = [&](int n0, int n1, int nrel) {
#pragma unroll 1
        for (int n = n0; n < n1; n++) {
          const int p = n & 3;
          mbar_wait(BAR(F3 + p), (n >> 2) & 1);
          KB(48 + n);
          if (n == 3 && wu == 0) ST(13);
          if (n == 2 && wu == 0) ST(14);
          g3_issue(slot3(p), p);
          wg_wait<1>();
          if (n > nrel) release(E3 + ((n - 1) & 3));
        }
      };
      g3_loop(2, 29, 0);
      uint32_t ua;
      uint8_t* ug;
      {
        GEOM;
        ua = sb + OFF_X + wg * 8192 + (8 * lt + l7) * 128 + (((2 * w + ((lane >> 3) & 1)) ^ l7) << 4);
        ug = gUB + (opq(j) * 56 + 48 + m) * 16384 + r * 4096 + wg * 8192 + (lane >> 1) * 128 + (((2 * w + (lane & 1)) ^ ((lane >> 1) & 7)) << 4);
      }
      auto gelu8 = [&](int c, int k) {
        const int o = 32 * c + 8 * k;
        stsm4t(ua + (c & 1) * 16384 + k * 2048,
               pack2(gelu_half(acc3[o]), gelu_half(acc3[o + 1])), pack2(gelu_half(acc3[o + 2]), gelu_half(acc3[o + 3])),
               pack2(gelu_half(acc3[o + 4]), gelu_half(acc3[o + 5])), pack2(gelu_half(acc3[o + 6]), gelu_half(acc3[o + 7])));
      };
      {
        auto part = [&](auto p, auto half) {
          static_for<0, 4>([&](auto kk) {
            constexpr uint32_t o = slot3(p.value) + kk.value * 2048;
            if constexpr (half.value) wgmma_32<1, 1, DI(o, 8192), DI(o + 40960, 8192), 96>(acc3, sda, sd);
            else wgmma_192<1, 1, DI(o, 8192), DI(o + 16384, 8192), 0>(acc3, sda, sd);
          });
        };
        mbar_wait(BAR(RD), L);
        mbar_wait(BAR(F3 + 1), 1); mbar_wait(BAR(F3 + 2), 1);
        wg_wait<0>(); release(E3 + 0);
#pragma unroll
        for (int k = 0; k < 112; k++) { float t; asm volatile("mov.b32 %0, %1;" : "=f"(t) : "f"(acc3[k]) : "memory"); acc3[k] = t; }
        sched_fence(P.zero);
        KB(77);
        wg_fence(); part(Int<1>{}, True{}); part(Int<2>{}, True{});
        mbar_wait(BAR(F3 + 3), 1); wg_fence(); part(Int<3>{}, True{}); wg_commit();
        part(Int<1>{}, False{}); wg_commit();
        wg_wait<1>();
#pragma unroll
        for (int k = 96; k < 112; k++) asm volatile("" : "+f"(acc3[k])::"memory");
        gelu8(3, 0); gelu8(3, 1);
        __syncwarp();
        copy_out<2>(ug, sb + OFF_X + 16384 + (uint32_t)((ug - gUB) & 0x2fff), 2048);
        signal(JOB + 7);
        sched_fence(P.zero);
        KB(78);
        wg_fence(); part(Int<2>{}, False{}); wg_commit();
        wg_wait<1>(); release(E3 + 1);
        KB(79);
        part(Int<3>{}, False{}); wg_commit();
        wg_wait<1>(); release(E3 + 2);
        wg_wait<0>(); release(E3 + 3);
      }
      fence_regs(acc3);
      TS(7 + 32 * L);
      if (wu == 0) ST(16);
      auto g4_issue = [&](int p, uint32_t b) {
        const uint32_t da = sda + (slot4(p) >> 4), db = sd + (b >> 4);
        wg_fence();
        static_for<0, 4>([&](auto kk) { wgmma_128<1, 1, DI(kk.value * 2048, 8192), DI(kk.value * 2048, 8192)>(xa, da, db); });
        wg_commit();
      };
#pragma unroll
      for (int k = 0; k < 4; k++) gelu8(0, k);
      fence_async_smem();
      signal(JOB + 4);
      nb_sync<NB_BOTH>(256);
      TS(8 + 32 * L);
      static_for<0, 18>([&](auto nn) {
        constexpr int n = nn.value, p = n % 6;
        if (n == 9 || n == 17) mbar_wait(BAR(JOB + 4 + (n >> 3)), L);
        mbar_wait(BAR(F4 + p), (n / 6 + (p >= 2 ? L : 0)) & 1);
        KB(80 + n);
        if (n == 1 && wu == 0) ST(21);
        if (n == 0 && wu == 0) ST(22);
        wg_fence();
        static_for<0, 4>([&](auto kk) {
          wgmma_128<1, 1, DI(slot4(p) + kk.value * 2048, 8192), DI((n == 9 ? OFF_X + 16384 : n % 17 ? slot4(p) + 16384 : OFF_X) + kk.value * 2048, 8192)>(xa, sda, sd);
        });
        wg_commit();
        if (n) { wg_wait<1>(); release(E4 + (n + 5) % 6); }
        if (n == 8) mbar_wait(BAR(RD + 2), L);
        else if (n < 16 && !(n & 1)) sched_fence(P.zero);
        if constexpr (n < 16 && !(n & 1)) gelu8(1 + (n >> 3), (n >> 1) & 3);
        if ((n & 7) == 7) { fence_async_smem(); signal(JOB + 5 + (n >> 3)); }
      });
      {
        int p = 0, pp = 5;
        uint32_t par = L ? 0x03 : 0x3f;
        auto g4_loop = [&](int n0, int n1, int nrel) {
#pragma unroll 1
          for (int n = n0; n < n1; n++) {
            mbar_wait(BAR(F4 + p), (par >> p) & 1);
            KB(80 + n);
            par ^= 1u << p;
            g4_issue(p, slot4(p) + 16384);
            if (n1 == 56 && n == 55 && wg == 0) nb_arrive<NB_LEAD>(256);
            wg_wait<1>();
            if (n > nrel) release(E4 + pp);
            pp = p; if (++p == 6) p = 0;
          }
        };
        g4_loop(18, 56 - LEAD4, 0);
        if (wg == 1) { wg_wait<0>(); release(E4 + pp); nb_sync<NB_LEAD>(256); }
        g4_loop(56 - LEAD4, 56, wg == 1 ? 56 - LEAD4 : 0);
      }
      mbar_wait(BAR(RD + 1), L);
      wg_wait<0>();
      release(E4 + 1);
      fence_regs(xa);
      TS(9 + 32 * L);
      {
        GEOM;
#pragma unroll
        for (int t = 0; t < 16; t += 2) {
          stsm4(sb + OFF_X + (t >> 3) * 16384 + (16 * wu + lr) * 128 + ((((t & 7) + lt) ^ l7) << 4),
                pack2(xa[4 * t], xa[4 * t + 1]), pack2(xa[4 * t + 2], xa[4 * t + 3]),
                pack2(xa[4 * t + 4], xa[4 * t + 5]), pack2(xa[4 * t + 6], xa[4 * t + 7]));
          if (t == 6 && L == 0) {
            __syncwarp();
            const int o = wu * 2048 + lane * 16;
            copy_out<4>(gXB + (opq(i) * 16 + 2 * j) * 16384 + o, sb + OFF_X + o, 512);
            signal(JOB + 8);
          }
        }
        fence_async_smem();
        if (L == 0) signal(JOB + 9);
        else {
          __syncwarp();
          if (elect_one()) {
            tma2d_store(&P.out, sb + OFF_X + wu * 2048, 128 * j, 128 * i + 16 * wu);
            tma2d_store(&P.out, sb + OFF_X + 16384 + wu * 2048, 128 * j + 64, 128 * i + 16 * wu);
            bulk_commit(); bulk_wait0();
          }
          __syncwarp();
        }
        nb_sync<NB_BOTH>(256);
      }
      TS(10 + 32 * L);
      KB(136);
    }
    cluster_bar();
    TS(32);
  }
}

typedef CUresult (*EncodeFn)(CUtensorMap*, CUtensorMapDataType, cuuint32_t, void*, const cuuint64_t*, const cuuint64_t*, const cuuint32_t*,
                             const cuuint32_t*, CUtensorMapInterleave, CUtensorMapSwizzle, CUtensorMapL2promotion, CUtensorMapFloatOOBfill);

void make_map(EncodeFn enc, CUtensorMap* mp, const void* base, int rank, cuuint64_t d0, cuuint64_t d1, cuuint64_t d2, cuuint64_t s1, cuuint64_t s2,
              cuuint32_t b0, cuuint32_t b1, cuuint32_t b2) {
  cuuint64_t dims[3] = {d0, d1, d2}, strides[2] = {s1, s2};
  cuuint32_t box[3] = {b0, b1, b2}, es[3] = {1, 1, 1};
  CUresult res = enc(mp, CU_TENSOR_MAP_DATA_TYPE_BFLOAT16, rank, const_cast<void*>(base), dims, strides, box, es, CU_TENSOR_MAP_INTERLEAVE_NONE,
                     CU_TENSOR_MAP_SWIZZLE_128B, CU_TENSOR_MAP_L2_PROMOTION_L2_128B, CU_TENSOR_MAP_FLOAT_OOB_FILL_NONE);
  (void)res;
}

}

extern "C" void kernel_launch(void* const* d_in, const int* in_sizes, int n_in, void* d_out, int out_size) {
  (void)in_sizes; (void)n_in; (void)out_size;
  static EncodeFn enc = nullptr;
  if (!enc) {
    void* fn = nullptr;
    cudaDriverEntryPointQueryResult qr;
    cudaGetDriverEntryPoint("cuTensorMapEncodeTiled", &fn, cudaEnableDefault, &qr);
    enc = (EncodeFn)fn;
    cudaFuncSetAttribute(fused_kernel, cudaFuncAttributeMaxDynamicSharedMemorySize, SMEM_BYTES);
  }
  Params P;
  make_map(enc, &P.x0, d_in[0], 2, D_, S_, 1, D_ * 2, 0, 64, 128, 1);
  make_map(enc, &P.wqkv, d_in[1], 3, D_, D_, 3, 3 * D_ * 2, D_ * 2, 64, 32, 3);
  make_map(enc, &P.wo, d_in[2], 2, D_, D_, 1, D_ * 2, 0, 64, 64, 1);
  make_map(enc, &P.w1, d_in[4], 3, 64, S_, F_ / 64, F_ * 2, 128, 64, 64, 3);
  make_map(enc, &P.w1h, d_in[4], 3, 32, S_, F_ / 32, F_ * 2, 64, 64, 64, 1);
  make_map(enc, &P.w2, d_in[6], 3, 64, F_, S_ / 64, S_ * 2, 128, 64, 64, 2);
  make_map(enc, &P.out, d_out, 2, D_, S_, 1, D_ * 2, 0, 64, 16, 1);
  P.wqkv_p = (const bf16*)d_in[1];
  P.wo_p = (const bf16*)d_in[2];
  P.w1_p = (const bf16*)d_in[4];
  P.w2_p = (const bf16*)d_in[6];
  P.b1 = (const bf16*)d_in[5];
  P.b2 = (const bf16*)d_in[7];
  P.zero = 0;
  fused_kernel<<<128, 384, SMEM_BYTES>>>(P);
}
```

```cpp
#include <cuda_runtime.h>
#include <cuda_bf16.h>
#include <cuda.h>
#include <stdint.h>

namespace {

typedef __nv_bfloat16 bf16;
constexpr int S_ = 2048, D_ = 1024, F_ = 3584;

constexpr uint32_t OFF_STG  = 163840;
constexpr uint32_t OFF_X    = 196608;
constexpr uint32_t OFF_BAR  = 229376;
constexpr uint32_t OFF_CS   = OFF_BAR + 512;
constexpr uint32_t OFF_B1   = OFF_CS + 1536;
constexpr uint32_t SMEM_BYTES = OFF_B1 + 896 + 128;
constexpr int F1 = 0, E1 = 4, F2 = 8, E2 = 13, F3 = 18, E3 = 22, F4 = 26, E4 = 32;
constexpr int JOB = 38;
constexpr int RD = 48;
constexpr int XF = 54, STD = 56, STAT = 58, FOLD = 59, CSJ = 61, HALO = 62;
constexpr int NB_BOTH = 1, NB_HELP = 2, NB_INIT = 3, NB_LEAD = 4;

__host__ __device__ constexpr uint32_t slot1(int p) { return p * 40960; }
__host__ __device__ constexpr uint32_t slot2(int p) { return p * 32768; }
__host__ __device__ constexpr uint32_t slot3(int p) { return ((p + 2) & 3) * 49152; }
__host__ __device__ constexpr uint32_t slot4(int p) { return (p < 2 ? p + 4 : p - 2) * 32768; }

__device__ __align__(1024) uint8_t gXB[16 * 16 * 16384];
__device__ __align__(1024) uint8_t gOB[16 * 16 * 16384];
__device__ __align__(1024) uint8_t gHB[8 * 32 * 16384];
__device__ __align__(1024) uint8_t gUB[8 * 56 * 16384];
__device__ __align__(1024) uint2   gST[2][16][8][8][16];
__device__ __align__(1024) uint4   gHalo[2][16][8][12][32];
__device__ __align__(1024) uint32_t gAck[2][16][8][2][8];
__device__ __align__(1024) uint4   gCS[8][16][64];
__device__ __align__(1024) uint32_t gFlag[2][7][16][32];
__device__ uint32_t gEpoch;
#define TS(k)
#define TS2(k)

#define S5(k)
#define KB(k)
#define ST(k)
struct Params {
  CUtensorMap x0, wqkv, wo, w1, w1h, w2, out;
  const bf16 *wqkv_p, *wo_p, *w1_p, *w2_p, *b1, *b2;
  uint32_t zero;
};

template <int TA, int TB, uint32_t IA, uint32_t IB, int O = 0, int LEN> __device__ __forceinline__ void wgmma_32(float (&d)[LEN], uint32_t da, uint32_t db) {
  asm volatile("{\n.reg .b64 da, db;\n.reg .b32 la, lb;\nadd.u32 la, %16, %20;\nadd.u32 lb, %17, %21;\nmov.b64 da, {la, 0x40000040};\nmov.b64 db, {lb, 0x40000040};\n"
  "wgmma.mma_async.sync.aligned.m64n32k16.f32.bf16.bf16 {"
  "%0, %1, %2, %3, %4, %5, %6, %7, %8, %9, %10, %11, %12, %13, %14, %15"
  "}, da, db, 1, 1, 1, %18, %19;\n}\n"
  : "+f"(d[O + 0]), "+f"(d[O + 1]), "+f"(d[O + 2]), "+f"(d[O + 3]), "+f"(d[O + 4]), "+f"(d[O + 5]), "+f"(d[O + 6]), "+f"(d[O + 7]),
    "+f"(d[O + 8]), "+f"(d[O + 9]), "+f"(d[O + 10]), "+f"(d[O + 11]), "+f"(d[O + 12]), "+f"(d[O + 13]), "+f"(d[O + 14]), "+f"(d[O + 15])
  : "r"(da), "r"(db), "n"(TA), "n"(TB), "n"(IA), "n"(IB));
}
template <int TA, int TB, uint32_t IA, uint32_t IB, int O = 0, int LEN> __device__ __forceinline__ void wgmma_128(float (&d)[LEN], uint32_t da, uint32_t db) {
  asm volatile("{\n.reg .b64 da, db;\n.reg .b32 la, lb;\nadd.u32 la, %64, %68;\nadd.u32 lb, %65, %69;\nmov.b64 da, {la, 0x40000040};\nmov.b64 db, {lb, 0x40000040};\n"
  "wgmma.mma_async.sync.aligned.m64n128k16.f32.bf16.bf16 {"
  "%0, %1, %2, %3, %4, %5, %6, %7, %8, %9, %10, %11, %12, %13, %14, %15, "
  "%16, %17, %18, %19, %20, %21, %22, %23, %24, %25, %26, %27, %28, %29, %30, %31, "
  "%32, %33, %34, %35, %36, %37, %38, %39, %40, %41, %42, %43, %44, %45, %46, %47, "
  "%48, %49, %50, %51, %52, %53, %54, %55, %56, %57, %58, %59, %60, %61, %62, %63"
  "}, da, db, 1, 1, 1, %66, %67;\n}\n"
  : "+f"(d[O + 0]), "+f"(d[O + 1]), "+f"(d[O + 2]), "+f"(d[O + 3]), "+f"(d[O + 4]), "+f"(d[O + 5]), "+f"(d[O + 6]), "+f"(d[O + 7]),
    "+f"(d[O + 8]), "+f"(d[O + 9]), "+f"(d[O + 10]), "+f"(d[O + 11]), "+f"(d[O + 12]), "+f"(d[O + 13]), "+f"(d[O + 14]), "+f"(d[O + 15]),
    "+f"(d[O + 16]), "+f"(d[O + 17]), "+f"(d[O + 18]), "+f"(d[O + 19]), "+f"(d[O + 20]), "+f"(d[O + 21]), "+f"(d[O + 22]), "+f"(d[O + 23]),
    "+f"(d[O + 24]), "+f"(d[O + 25]), "+f"(d[O + 26]), "+f"(d[O + 27]), "+f"(d[O + 28]), "+f"(d[O + 29]), "+f"(d[O + 30]), "+f"(d[O + 31]),
    "+f"(d[O + 32]), "+f"(d[O + 33]), "+f"(d[O + 34]), "+f"(d[O + 35]), "+f"(d[O + 36]), "+f"(d[O + 37]), "+f"(d[O + 38]), "+f"(d[O + 39]),
    "+f"(d[O + 40]), "+f"(d[O + 41]), "+f"(d[O + 42]), "+f"(d[O + 43]), "+f"(d[O + 44]), "+f"(d[O + 45]), "+f"(d[O + 46]), "+f"(d[O + 47]),
    "+f"(d[O + 48]), "+f"(d[O + 49]), "+f"(d[O + 50]), "+f"(d[O + 51]), "+f"(d[O + 52]), "+f"(d[O + 53]), "+f"(d[O + 54]), "+f"(d[O + 55]),
    "+f"(d[O + 56]), "+f"(d[O + 57]), "+f"(d[O + 58]), "+f"(d[O + 59]), "+f"(d[O + 60]), "+f"(d[O + 61]), "+f"(d[O + 62]), "+f"(d[O + 63])
  : "r"(da), "r"(db), "n"(TA), "n"(TB), "n"(IA), "n"(IB));
}
template <int TA, int TB, uint32_t IA, uint32_t IB, int O = 0, int LEN> __device__ __forceinline__ void wgmma_192(float (&d)[LEN], uint32_t da, uint32_t db) {
  asm volatile("{\n.reg .b64 da, db;\n.reg .b32 la, lb;\nadd.u32 la, %96, %100;\nadd.u32 lb, %97, %101;\nmov.b64 da, {la, 0x40000040};\nmov.b64 db, {lb, 0x40000040};\n"
  "wgmma.mma_async.sync.aligned.m64n192k16.f32.bf16.bf16 {"
  "%0, %1, %2, %3, %4, %5, %6, %7, %8, %9, %10, %11, %12, %13, %14, %15, "
  "%16, %17, %18, %19, %20, %21, %22, %23, %24, %25, %26, %27, %28, %29, %30, %31, "
  "%32, %33, %34, %35, %36, %37, %38, %39, %40, %41, %42, %43, %44, %45, %46, %47, "
  "%48, %49, %50, %51, %52, %53, %54, %55, %56, %57, %58, %59, %60, %61, %62, %63, "
  "%64, %65, %66, %67, %68, %69, %70, %71, %72, %73, %74, %75, %76, %77, %78, %79, "
  "%80, %81, %82, %83, %84, %85, %86, %87, %88, %89, %90, %91, %92, %93, %94, %95"
  "}, da, db, 1, 1, 1, %98, %99;\n}\n"
  : "+f"(d[O + 0]), "+f"(d[O + 1]), "+f"(d[O + 2]), "+f"(d[O + 3]), "+f"(d[O + 4]), "+f"(d[O + 5]), "+f"(d[O + 6]), "+f"(d[O + 7]),
    "+f"(d[O + 8]), "+f"(d[O + 9]), "+f"(d[O + 10]), "+f"(d[O + 11]), "+f"(d[O + 12]), "+f"(d[O + 13]), "+f"(d[O + 14]), "+f"(d[O + 15]),
    "+f"(d[O + 16]), "+f"(d[O + 17]), "+f"(d[O + 18]), "+f"(d[O + 19]), "+f"(d[O + 20]), "+f"(d[O + 21]), "+f"(d[O + 22]), "+f"(d[O + 23]),
    "+f"(d[O + 24]), "+f"(d[O + 25]), "+f"(d[O + 26]), "+f"(d[O + 27]), "+f"(d[O + 28]), "+f"(d[O + 29]), "+f"(d[O + 30]), "+f"(d[O + 31]),
    "+f"(d[O + 32]), "+f"(d[O + 33]), "+f"(d[O + 34]), "+f"(d[O + 35]), "+f"(d[O + 36]), "+f"(d[O + 37]), "+f"(d[O + 38]), "+f"(d[O + 39]),
    "+f"(d[O + 40]), "+f"(d[O + 41]), "+f"(d[O + 42]), "+f"(d[O + 43]), "+f"(d[O + 44]), "+f"(d[O + 45]), "+f"(d[O + 46]), "+f"(d[O + 47]),
    "+f"(d[O + 48]), "+f"(d[O + 49]), "+f"(d[O + 50]), "+f"(d[O + 51]), "+f"(d[O + 52]), "+f"(d[O + 53]), "+f"(d[O + 54]), "+f"(d[O + 55]),
    "+f"(d[O + 56]), "+f"(d[O + 57]), "+f"(d[O + 58]), "+f"(d[O + 59]), "+f"(d[O + 60]), "+f"(d[O + 61]), "+f"(d[O + 62]), "+f"(d[O + 63]),
    "+f"(d[O + 64]), "+f"(d[O + 65]), "+f"(d[O + 66]), "+f"(d[O + 67]), "+f"(d[O + 68]), "+f"(d[O + 69]), "+f"(d[O + 70]), "+f"(d[O + 71]),
    "+f"(d[O + 72]), "+f"(d[O + 73]), "+f"(d[O + 74]), "+f"(d[O + 75]), "+f"(d[O + 76]), "+f"(d[O + 77]), "+f"(d[O + 78]), "+f"(d[O + 79]),
    "+f"(d[O + 80]), "+f"(d[O + 81]), "+f"(d[O + 82]), "+f"(d[O + 83]), "+f"(d[O + 84]), "+f"(d[O + 85]), "+f"(d[O + 86]), "+f"(d[O + 87]),
    "+f"(d[O + 88]), "+f"(d[O + 89]), "+f"(d[O + 90]), "+f"(d[O + 91]), "+f"(d[O + 92]), "+f"(d[O + 93]), "+f"(d[O + 94]), "+f"(d[O + 95])
  : "r"(da), "r"(db), "n"(TA), "n"(TB), "n"(IA), "n"(IB));
}
template <int TA, int TB, uint32_t IA, uint32_t IB, int O = 0, int LEN> __device__ __forceinline__ void wgmma_192z(float (&d)[LEN], uint32_t da, uint32_t db) {
  asm volatile("{\n.reg .b64 da, db;\n.reg .b32 la, lb;\nadd.u32 la, %96, %100;\nadd.u32 lb, %97, %101;\nmov.b64 da, {la, 0x40000040};\nmov.b64 db, {lb, 0x40000040};\n"
  "wgmma.mma_async.sync.aligned.m64n192k16.f32.bf16.bf16 {"
  "%0, %1, %2, %3, %4, %5, %6, %7, %8, %9, %10, %11, %12, %13, %14, %15, "
  "%16, %17, %18, %19, %20, %21, %22, %23, %24, %25, %26, %27, %28, %29, %30, %31, "
  "%32, %33, %34, %35, %36, %37, %38, %39, %40, %41, %42, %43, %44, %45, %46, %47, "
  "%48, %49, %50, %51, %52, %53, %54, %55, %56, %57, %58, %59, %60, %61, %62, %63, "
  "%64, %65, %66, %67, %68, %69, %70, %71, %72, %73, %74, %75, %76, %77, %78, %79, "
  "%80, %81, %82, %83, %84, %85, %86, %87, %88, %89, %90, %91, %92, %93, %94, %95"
  "}, da, db, 0, 1, 1, %98, %99;\n}\n"
  : "=f"(d[O + 0]), "=f"(d[O + 1]), "=f"(d[O + 2]), "=f"(d[O + 3]), "=f"(d[O + 4]), "=f"(d[O + 5]), "=f"(d[O + 6]), "=f"(d[O + 7]),
    "=f"(d[O + 8]), "=f"(d[O + 9]), "=f"(d[O + 10]), "=f"(d[O + 11]), "=f"(d[O + 12]), "=f"(d[O + 13]), "=f"(d[O + 14]), "=f"(d[O + 15]),
    "=f"(d[O + 16]), "=f"(d[O + 17]), "=f"(d[O + 18]), "=f"(d[O + 19]), "=f"(d[O + 20]), "=f"(d[O + 21]), "=f"(d[O + 22]), "=f"(d[O + 23]),
    "=f"(d[O + 24]), "=f"(d[O + 25]), "=f"(d[O + 26]), "=f"(d[O + 27]), "=f"(d[O + 28]), "=f"(d[O + 29]), "=f"(d[O + 30]), "=f"(d[O + 31]),
    "=f"(d[O + 32]), "=f"(d[O + 33]), "=f"(d[O + 34]), "=f"(d[O + 35]), "=f"(d[O + 36]), "=f"(d[O + 37]), "=f"(d[O + 38]), "=f"(d[O + 39]),
    "=f"(d[O + 40]), "=f"(d[O + 41]), "=f"(d[O + 42]), "=f"(d[O + 43]), "=f"(d[O + 44]), "=f"(d[O + 45]), "=f"(d[O + 46]), "=f"(d[O + 47]),
    "=f"(d[O + 48]), "=f"(d[O + 49]), "=f"(d[O + 50]), "=f"(d[O + 51]), "=f"(d[O + 52]), "=f"(d[O + 53]), "=f"(d[O + 54]), "=f"(d[O + 55]),
    "=f"(d[O + 56]), "=f"(d[O + 57]), "=f"(d[O + 58]), "=f"(d[O + 59]), "=f"(d[O + 60]), "=f"(d[O + 61]), "=f"(d[O + 62]), "=f"(d[O + 63]),
    "=f"(d[O + 64]), "=f"(d[O + 65]), "=f"(d[O + 66]), "=f"(d[O + 67]), "=f"(d[O + 68]), "=f"(d[O + 69]), "=f"(d[O + 70]), "=f"(d[O + 71]),
    "=f"(d[O + 72]), "=f"(d[O + 73]), "=f"(d[O + 74]), "=f"(d[O + 75]), "=f"(d[O + 76]), "=f"(d[O + 77]), "=f"(d[O + 78]), "=f"(d[O + 79]),
    "=f"(d[O + 80]), "=f"(d[O + 81]), "=f"(d[O + 82]), "=f"(d[O + 83]), "=f"(d[O + 84]), "=f"(d[O + 85]), "=f"(d[O + 86]), "=f"(d[O + 87]),
    "=f"(d[O + 88]), "=f"(d[O + 89]), "=f"(d[O + 90]), "=f"(d[O + 91]), "=f"(d[O + 92]), "=f"(d[O + 93]), "=f"(d[O + 94]), "=f"(d[O + 95])
  : "r"(da), "r"(db), "n"(TA), "n"(TB), "n"(IA), "n"(IB));
}
template <int TA, int TB, uint32_t IA, uint32_t IB, int O = 0, int LEN> __device__ __forceinline__ void wgmma_224(float (&d)[LEN], uint32_t da, uint32_t db) {
  asm volatile("{\n.reg .b64 da, db;\n.reg .b32 la, lb;\nadd.u32 la, %112, %116;\nadd.u32 lb, %113, %117;\nmov.b64 da, {la, 0x40000040};\nmov.b64 db, {lb, 0x40000040};\n"
  "wgmma.mma_async.sync.aligned.m64n224k16.f32.bf16.bf16 {"
  "%0, %1, %2, %3, %4, %5, %6, %7, %8, %9, %10, %11, %12, %13, %14, %15, "
  "%16, %17, %18, %19, %20, %21, %22, %23, %24, %25, %26, %27, %28, %29, %30, %31, "
  "%32, %33, %34, %35, %36, %37, %38, %39, %40, %41, %42, %43, %44, %45, %46, %47, "
  "%48, %49, %50, %51, %52, %53, %54, %55, %56, %57, %58, %59, %60, %61, %62, %63, "
  "%64, %65, %66, %67, %68, %69, %70, %71, %72, %73, %74, %75, %76, %77, %78, %79, "
  "%80, %81, %82, %83, %84, %85, %86, %87, %88, %89, %90, %91, %92, %93, %94, %95, "
  "%96, %97, %98, %99, %100, %101, %102, %103, %104, %105, %106, %107, %108, %109, %110, %111"
  "}, da, db, 1, 1, 1, %114, %115;\n}\n"
  : "+f"(d[O + 0]), "+f"(d[O + 1]), "+f"(d[O + 2]), "+f"(d[O + 3]), "+f"(d[O + 4]), "+f"(d[O + 5]), "+f"(d[O + 6]), "+f"(d[O + 7]),
    "+f"(d[O + 8]), "+f"(d[O + 9]), "+f"(d[O + 10]), "+f"(d[O + 11]), "+f"(d[O + 12]), "+f"(d[O + 13]), "+f"(d[O + 14]), "+f"(d[O + 15]),
    "+f"(d[O + 16]), "+f"(d[O + 17]), "+f"(d[O + 18]), "+f"(d[O + 19]), "+f"(d[O + 20]), "+f"(d[O + 21]), "+f"(d[O + 22]), "+f"(d[O + 23]),
    "+f"(d[O + 24]), "+f"(d[O + 25]), "+f"(d[O + 26]), "+f"(d[O + 27]), "+f"(d[O + 28]), "+f"(d[O + 29]), "+f"(d[O + 30]), "+f"(d[O + 31]),
    "+f"(d[O + 32]), "+f"(d[O + 33]), "+f"(d[O + 34]), "+f"(d[O + 35]), "+f"(d[O + 36]), "+f"(d[O + 37]), "+f"(d[O + 38]), "+f"(d[O + 39]),
    "+f"(d[O + 40]), "+f"(d[O + 41]), "+f"(d[O + 42]), "+f"(d[O + 43]), "+f"(d[O + 44]), "+f"(d[O + 45]), "+f"(d[O + 46]), "+f"(d[O + 47]),
    "+f"(d[O + 48]), "+f"(d[O + 49]), "+f"(d[O + 50]), "+f"(d[O + 51]), "+f"(d[O + 52]), "+f"(d[O + 53]), "+f"(d[O + 54]), "+f"(d[O + 55]),
    "+f"(d[O + 56]), "+f"(d[O + 57]), "+f"(d[O + 58]), "+f"(d[O + 59]), "+f"(d[O + 60]), "+f"(d[O + 61]), "+f"(d[O + 62]), "+f"(d[O + 63]),
    "+f"(d[O + 64]), "+f"(d[O + 65]), "+f"(d[O + 66]), "+f"(d[O + 67]), "+f"(d[O + 68]), "+f"(d[O + 69]), "+f"(d[O + 70]), "+f"(d[O + 71]),
    "+f"(d[O + 72]), "+f"(d[O + 73]), "+f"(d[O + 74]), "+f"(d[O + 75]), "+f"(d[O + 76]), "+f"(d[O + 77]), "+f"(d[O + 78]), "+f"(d[O + 79]),
    "+f"(d[O + 80]), "+f"(d[O + 81]), "+f"(d[O + 82]), "+f"(d[O + 83]), "+f"(d[O + 84]), "+f"(d[O + 85]), "+f"(d[O + 86]), "+f"(d[O + 87]),
    "+f"(d[O + 88]), "+f"(d[O + 89]), "+f"(d[O + 90]), "+f"(d[O + 91]), "+f"(d[O + 92]), "+f"(d[O + 93]), "+f"(d[O + 94]), "+f"(d[O + 95]),
    "+f"(d[O + 96]), "+f"(d[O + 97]), "+f"(d[O + 98]), "+f"(d[O + 99]), "+f"(d[O + 100]), "+f"(d[O + 101]), "+f"(d[O + 102]), "+f"(d[O + 103]),
    "+f"(d[O + 104]), "+f"(d[O + 105]), "+f"(d[O + 106]), "+f"(d[O + 107]), "+f"(d[O + 108]), "+f"(d[O + 109]), "+f"(d[O + 110]), "+f"(d[O + 111])
  : "r"(da), "r"(db), "n"(TA), "n"(TB), "n"(IA), "n"(IB));
}
__device__ __forceinline__ void wgmma_rs_192(float (&d)[96], uint32_t a0, uint32_t a1, uint32_t a2, uint32_t a3, uint64_t db) {
  asm volatile("wgmma.mma_async.sync.aligned.m64n192k16.f32.bf16.bf16 {"
  "%0, %1, %2, %3, %4, %5, %6, %7, %8, %9, %10, %11, %12, %13, %14, %15, "
  "%16, %17, %18, %19, %20, %21, %22, %23, %24, %25, %26, %27, %28, %29, %30, %31, "
  "%32, %33, %34, %35, %36, %37, %38, %39, %40, %41, %42, %43, %44, %45, %46, %47, "
  "%48, %49, %50, %51, %52, %53, %54, %55, %56, %57, %58, %59, %60, %61, %62, %63, "
  "%64, %65, %66, %67, %68, %69, %70, %71, %72, %73, %74, %75, %76, %77, %78, %79, "
  "%80, %81, %82, %83, %84, %85, %86, %87, %88, %89, %90, %91, %92, %93, %94, %95"
  "}, {%96, %97, %98, %99}, %100, 1, 1, 1, 1;\n"
  : "+f"(d[0]), "+f"(d[1]), "+f"(d[2]), "+f"(d[3]), "+f"(d[4]), "+f"(d[5]), "+f"(d[6]), "+f"(d[7]),
    "+f"(d[8]), "+f"(d[9]), "+f"(d[10]), "+f"(d[11]), "+f"(d[12]), "+f"(d[13]), "+f"(d[14]), "+f"(d[15]),
    "+f"(d[16]), "+f"(d[17]), "+f"(d[18]), "+f"(d[19]), "+f"(d[20]), "+f"(d[21]), "+f"(d[22]), "+f"(d[23]),
    "+f"(d[24]), "+f"(d[25]), "+f"(d[26]), "+f"(d[27]), "+f"(d[28]), "+f"(d[29]), "+f"(d[30]), "+f"(d[31]),
    "+f"(d[32]), "+f"(d[33]), "+f"(d[34]), "+f"(d[35]), "+f"(d[36]), "+f"(d[37]), "+f"(d[38]), "+f"(d[39]),
    "+f"(d[40]), "+f"(d[41]), "+f"(d[42]), "+f"(d[43]), "+f"(d[44]), "+f"(d[45]), "+f"(d[46]), "+f"(d[47]),
    "+f"(d[48]), "+f"(d[49]), "+f"(d[50]), "+f"(d[51]), "+f"(d[52]), "+f"(d[53]), "+f"(d[54]), "+f"(d[55]),
    "+f"(d[56]), "+f"(d[57]), "+f"(d[58]), "+f"(d[59]), "+f"(d[60]), "+f"(d[61]), "+f"(d[62]), "+f"(d[63]),
    "+f"(d[64]), "+f"(d[65]), "+f"(d[66]), "+f"(d[67]), "+f"(d[68]), "+f"(d[69]), "+f"(d[70]), "+f"(d[71]),
    "+f"(d[72]), "+f"(d[73]), "+f"(d[74]), "+f"(d[75]), "+f"(d[76]), "+f"(d[77]), "+f"(d[78]), "+f"(d[79]),
    "+f"(d[80]), "+f"(d[81]), "+f"(d[82]), "+f"(d[83]), "+f"(d[84]), "+f"(d[85]), "+f"(d[86]), "+f"(d[87]),
    "+f"(d[88]), "+f"(d[89]), "+f"(d[90]), "+f"(d[91]), "+f"(d[92]), "+f"(d[93]), "+f"(d[94]), "+f"(d[95])
  : "r"(a0), "r"(a1), "r"(a2), "r"(a3), "l"(db));
}
__device__ __forceinline__ void wgmma_rs_224z(float (&d)[112], uint32_t a0, uint32_t a1, uint32_t a2, uint32_t a3, uint64_t db) {
  asm volatile("wgmma.mma_async.sync.aligned.m64n224k16.f32.bf16.bf16 {"
  "%0, %1, %2, %3, %4, %5, %6, %7, %8, %9, %10, %11, %12, %13, %14, %15, "
  "%16, %17, %18, %19, %20, %21, %22, %23, %24, %25, %26, %27, %28, %29, %30, %31, "
  "%32, %33, %34, %35, %36, %37, %38, %39, %40, %41, %42, %43, %44, %45, %46, %47, "
  "%48, %49, %50, %51, %52, %53, %54, %55, %56, %57, %58, %59, %60, %61, %62, %63, "
  "%64, %65, %66, %67, %68, %69, %70, %71, %72, %73, %74, %75, %76, %77, %78, %79, "
  "%80, %81, %82, %83, %84, %85, %86, %87, %88, %89, %90, %91, %92, %93, %94, %95, "
  "%96, %97, %98, %99, %100, %101, %102, %103, %104, %105, %106, %107, %108, %109, %110, %111"
  "}, {%112, %113, %114, %115}, %116, 0, 1, 1, 1;\n"
  : "=f"(d[0]), "=f"(d[1]), "=f"(d[2]), "=f"(d[3]), "=f"(d[4]), "=f"(d[5]), "=f"(d[6]), "=f"(d[7]),
    "=f"(d[8]), "=f"(d[9]), "=f"(d[10]), "=f"(d[11]), "=f"(d[12]), "=f"(d[13]), "=f"(d[14]), "=f"(d[15]),
    "=f"(d[16]), "=f"(d[17]), "=f"(d[18]), "=f"(d[19]), "=f"(d[20]), "=f"(d[21]), "=f"(d[22]), "=f"(d[23]),
    "=f"(d[24]), "=f"(d[25]), "=f"(d[26]), "=f"(d[27]), "=f"(d[28]), "=f"(d[29]), "=f"(d[30]), "=f"(d[31]),
    "=f"(d[32]), "=f"(d[33]), "=f"(d[34]), "=f"(d[35]), "=f"(d[36]), "=f"(d[37]), "=f"(d[38]), "=f"(d[39]),
    "=f"(d[40]), "=f"(d[41]), "=f"(d[42]), "=f"(d[43]), "=f"(d[44]), "=f"(d[45]), "=f"(d[46]), "=f"(d[47]),
    "=f"(d[48]), "=f"(d[49]), "=f"(d[50]), "=f"(d[51]), "=f"(d[52]), "=f"(d[53]), "=f"(d[54]), "=f"(d[55]),
    "=f"(d[56]), "=f"(d[57]), "=f"(d[58]), "=f"(d[59]), "=f"(d[60]), "=f"(d[61]), "=f"(d[62]), "=f"(d[63]),
    "=f"(d[64]), "=f"(d[65]), "=f"(d[66]), "=f"(d[67]), "=f"(d[68]), "=f"(d[69]), "=f"(d[70]), "=f"(d[71]),
    "=f"(d[72]), "=f"(d[73]), "=f"(d[74]), "=f"(d[75]), "=f"(d[76]), "=f"(d[77]), "=f"(d[78]), "=f"(d[79]),
    "=f"(d[80]), "=f"(d[81]), "=f"(d[82]), "=f"(d[83]), "=f"(d[84]), "=f"(d[85]), "=f"(d[86]), "=f"(d[87]),
    "=f"(d[88]), "=f"(d[89]), "=f"(d[90]), "=f"(d[91]), "=f"(d[92]), "=f"(d[93]), "=f"(d[94]), "=f"(d[95]),
    "=f"(d[96]), "=f"(d[97]), "=f"(d[98]), "=f"(d[99]), "=f"(d[100]), "=f"(d[101]), "=f"(d[102]), "=f"(d[103]),
    "=f"(d[104]), "=f"(d[105]), "=f"(d[106]), "=f"(d[107]), "=f"(d[108]), "=f"(d[109]), "=f"(d[110]), "=f"(d[111])
  : "r"(a0), "r"(a1), "r"(a2), "r"(a3), "l"(db));
}

__device__ __forceinline__ uint32_t smem_u32(const void* p) { return (uint32_t)__cvta_generic_to_shared(p); }
__device__ __forceinline__ void mbar_init(uint32_t bar, uint32_t cnt) { asm volatile("mbarrier.init.shared::cta.b64 [%0], %1;" ::"r"(bar), "r"(cnt) : "memory"); }
__device__ __forceinline__ void mbar_expect(uint32_t bar, uint32_t bytes) { asm volatile("mbarrier.arrive.expect_tx.shared::cta.b64 _, [%0], %1;" ::"r"(bar), "r"(bytes) : "memory"); }
__device__ __forceinline__ void mbar_arrive(uint32_t bar) { asm volatile("mbarrier.arrive.shared::cta.b64 _, [%0];" ::"r"(bar) : "memory"); }
__device__ __forceinline__ void mbar_arrive_cl(uint32_t cbar) { asm volatile("mbarrier.arrive.shared::cluster.b64 _, [%0];" ::"r"(cbar) : "memory"); }
__device__ __forceinline__ uint32_t mapa(uint32_t a, uint32_t cta) { uint32_t r; asm("mapa.shared::cluster.u32 %0, %1, %2;" : "=r"(r) : "r"(a), "r"(cta)); return r; }
__device__ __forceinline__ void mbar_wait(uint32_t bar, uint32_t parity) {
  asm volatile("{\n.reg .pred p;\n.reg .u32 n;\nmov.u32 n, 0;\n"
    "LAB_WAIT:\n"
    "mbarrier.try_wait.parity.shared::cta.b64 p, [%0], %1;\n"
    "@p bra LAB_DONE;\n"
    "add.u32 n, n, 1;\n"
    "setp.lt.u32 p, n, 2000000;\n"
    "@p bra LAB_WAIT;\n"
    "trap;\n"
    "LAB_DONE:\n}\n" ::"r"(bar), "r"(parity) : "memory");
}
constexpr uint32_t SPIN_MAX = 2000000;
__device__ __forceinline__ void tma2d(uint32_t dst, const CUtensorMap* m, uint32_t bar, int c0, int c1) {
  asm volatile("cp.async.bulk.tensor.2d.shared::cluster.global.mbarrier::complete_tx::bytes [%0], [%1, {%3, %4}], [%2];"
    ::"r"(dst), "l"(m), "r"(bar), "r"(c0), "r"(c1) : "memory");
}
__device__ __forceinline__ void tma2d_mc(uint32_t dst, const CUtensorMap* m, uint32_t bar, int c0, int c1) {
  asm volatile("cp.async.bulk.tensor.2d.shared::cluster.global.mbarrier::complete_tx::bytes.multicast::cluster [%0], [%1, {%3, %4}], [%2], %5;"
    ::"r"(dst), "l"(m), "r"(bar), "r"(c0), "r"(c1), "h"((uint16_t)3) : "memory");
}
__device__ __forceinline__ void tma3d(uint32_t dst, const CUtensorMap* m, uint32_t bar, int c0, int c1, int c2) {
  asm volatile("cp.async.bulk.tensor.3d.shared::cluster.global.mbarrier::complete_tx::bytes [%0], [%1, {%3, %4, %5}], [%2];"
    ::"r"(dst), "l"(m), "r"(bar), "r"(c0), "r"(c1), "r"(c2) : "memory");
}
__device__ __forceinline__ void tma3d_mc(uint32_t dst, const CUtensorMap* m, uint32_t bar, int c0, int c1, int c2) {
  asm volatile("cp.async.bulk.tensor.3d.shared::cluster.global.mbarrier::complete_tx::bytes.multicast::cluster [%0], [%1, {%3, %4, %5}], [%2], %6;"
    ::"r"(dst), "l"(m), "r"(bar), "r"(c0), "r"(c1), "r"(c2), "h"((uint16_t)3) : "memory");
}
__device__ __forceinline__ void tma2d_store(const CUtensorMap* m, uint32_t src, int c0, int c1) {
  asm volatile("cp.async.bulk.tensor.2d.global.shared::cta.bulk_group [%0, {%2, %3}], [%1];" ::"l"(m), "r"(src), "r"(c0), "r"(c1) : "memory");
}
__device__ __forceinline__ void bulk_ld(uint32_t dst, const void* src, uint32_t bytes, uint32_t bar) {
  asm volatile("cp.async.bulk.shared::cluster.global.mbarrier::complete_tx::bytes [%0], [%1], %2, [%3];" ::"r"(dst), "l"(src), "r"(bytes), "r"(bar) : "memory");
}
__device__ __forceinline__ void bulk_ld_mc(uint32_t dst, const void* src, uint32_t bytes, uint32_t bar) {
  asm volatile("cp.async.bulk.shared::cluster.global.mbarrier::complete_tx::bytes.multicast::cluster [%0], [%1], %2, [%3], %4;"
    ::"r"(dst), "l"(src), "r"(bytes), "r"(bar), "h"((uint16_t)3) : "memory");
}
__device__ __forceinline__ void bulk_st(void* dst, uint32_t src, uint32_t bytes) {
  asm volatile("cp.async.bulk.global.shared::cta.bulk_group [%0], [%1], %2;" ::"l"(dst), "r"(src), "r"(bytes) : "memory");
}
__device__ __forceinline__ void bulk_commit() { asm volatile("cp.async.bulk.commit_group;" ::: "memory"); }
__device__ __forceinline__ void bulk_wait0() { asm volatile("cp.async.bulk.wait_group 0;" ::: "memory"); }
__device__ __forceinline__ void fence_async_smem() { asm volatile("fence.proxy.async.shared::cta;" ::: "memory"); }
__device__ __forceinline__ void wg_fence() { asm volatile("wgmma.fence.sync.aligned;" ::: "memory"); }
__device__ __forceinline__ void wg_commit() { asm volatile("wgmma.commit_group.sync.aligned;" ::: "memory"); }
template <int N> __device__ __forceinline__ void wg_wait() { asm volatile("wgmma.wait_group.sync.aligned %0;" ::"n"(N) : "memory"); }
template <int R> __device__ __forceinline__ void reg_alloc() { asm volatile("setmaxnreg.inc.sync.aligned.u32 %0;" ::"n"(R)); }
template <int R> __device__ __forceinline__ void reg_dealloc() { asm volatile("setmaxnreg.dec.sync.aligned.u32 %0;" ::"n"(R)); }
__device__ __forceinline__ void cluster_bar() { asm volatile("barrier.cluster.arrive.relaxed;\nbarrier.cluster.wait;" ::: "memory"); }
template <int ID> __device__ __forceinline__ void nb_sync(int n) { asm volatile("barrier.sync %0, %1;" ::"n"(ID), "r"(n) : "memory"); }
template <int ID> __device__ __forceinline__ void nb_arrive(int n) { asm volatile("barrier.arrive %0, %1;" ::"n"(ID), "r"(n) : "memory"); }
__device__ __forceinline__ int fresh_tid() { int t; asm volatile("mov.u32 %0, %%tid.x;" : "=r"(t)); return t; }
__device__ __forceinline__ void sched_fence(uint32_t z) { asm volatile("{\n.reg .pred p;\nsetp.ne.u32 p, %0, 0;\nLAB_S:\n@p nanosleep.u32 0;\n@p bra LAB_S;\n}\n" ::"r"(z) : "memory"); }
__device__ __forceinline__ float rsq(float x) { float y; asm("rsqrt.approx.ftz.f32 %0, %1;" : "=f"(y) : "f"(x)); return y; }
__device__ __forceinline__ int opq(int v) { asm volatile("" : "+r"(v)); return v; }
template <int V> struct Int { static constexpr int value = V; };
struct True { static constexpr bool value = true; };
struct False { static constexpr bool value = false; };
template <int N> __device__ __forceinline__ void fence_regs(float (&d)[N]) {
#pragma unroll
  for (int i = 0; i < N; i++) asm volatile("" : "+f"(d[i])::"memory");
}
__host__ __device__ constexpr uint32_t DI(uint32_t off, uint32_t lbo) { return (off >> 4) + ((lbo >> 4) << 16); }
template <int K, int N, class F> __device__ __forceinline__ void static_for(F f) { if constexpr (K < N) { f(Int<K>{}); static_for<K + 1, N>(f); } }
__device__ __forceinline__ uint64_t mkdesc_vec(uint32_t addr, uint32_t sbo) { return (uint64_t)((addr & 0x3FFFF) >> 4) | ((uint64_t)(sbo >> 4) << 32); }
__device__ __forceinline__ void sts16(uint32_t a, uint32_t v) { asm volatile("st.shared.u16 [%0], %1;" ::"r"(a), "h"((uint16_t)v) : "memory"); }
__device__ __forceinline__ uint32_t pack2(float lo, float hi) { uint32_t r; asm("cvt.rn.bf16x2.f32 %0, %1, %2;" : "=r"(r) : "f"(hi), "f"(lo)); return r; }
__device__ __forceinline__ float bf_lo(uint32_t v) { return __uint_as_float(v << 16); }
__device__ __forceinline__ float bf_hi(uint32_t v) { return __uint_as_float(v & 0xffff0000u); }
__device__ __forceinline__ void stsm4(uint32_t a, uint32_t r0, uint32_t r1, uint32_t r2, uint32_t r3) {
  asm volatile("stmatrix.sync.aligned.m8n8.x4.shared.b16 [%0], {%1, %2, %3, %4};" ::"r"(a), "r"(r0), "r"(r1), "r"(r2), "r"(r3) : "memory");
}
__device__ __forceinline__ void stsm4t(uint32_t a, uint32_t r0, uint32_t r1, uint32_t r2, uint32_t r3) {
  asm volatile("stmatrix.sync.aligned.m8n8.x4.trans.shared.b16 [%0], {%1, %2, %3, %4};" ::"r"(a), "r"(r0), "r"(r1), "r"(r2), "r"(r3) : "memory");
}
__device__ __forceinline__ void ldsm4(uint32_t a, uint32_t& r0, uint32_t& r1, uint32_t& r2, uint32_t& r3) {
  asm volatile("ldmatrix.sync.aligned.m8n8.x4.shared.b16 {%0, %1, %2, %3}, [%4];" : "=r"(r0), "=r"(r1), "=r"(r2), "=r"(r3) : "r"(a) : "memory");
}
__device__ __forceinline__ void ldsm4t(uint32_t a, uint32_t& r0, uint32_t& r1, uint32_t& r2, uint32_t& r3) {
  asm volatile("ldmatrix.sync.aligned.m8n8.x4.trans.shared.b16 {%0, %1, %2, %3}, [%4];" : "=r"(r0), "=r"(r1), "=r"(r2), "=r"(r3) : "r"(a) : "memory");
}
__device__ __forceinline__ void mma16816(float (&c)[4], uint32_t a0, uint32_t a1, uint32_t a2, uint32_t a3, uint32_t b0, uint32_t b1) {
  asm volatile("mma.sync.aligned.m16n8k16.row.col.f32.bf16.bf16.f32 {%0, %1, %2, %3}, {%4, %5, %6, %7}, {%8, %9}, {%10, %11, %12, %13};"
    : "=f"(c[0]), "=f"(c[1]), "=f"(c[2]), "=f"(c[3]) : "r"(a0), "r"(a1), "r"(a2), "r"(a3), "r"(b0), "r"(b1), "f"(c[0]), "f"(c[1]), "f"(c[2]), "f"(c[3]));
}
__device__ __forceinline__ void sts128(uint32_t a, uint32_t r0, uint32_t r1, uint32_t r2, uint32_t r3) {
  asm volatile("st.shared.v4.b32 [%0], {%1, %2, %3, %4};" ::"r"(a), "r"(r0), "r"(r1), "r"(r2), "r"(r3) : "memory");
}
__device__ __forceinline__ void lds128(uint32_t a, uint32_t& r0, uint32_t& r1, uint32_t& r2, uint32_t& r3) {
  asm volatile("ld.shared.v4.b32 {%0, %1, %2, %3}, [%4];" : "=r"(r0), "=r"(r1), "=r"(r2), "=r"(r3) : "r"(a) : "memory");
}
__device__ __forceinline__ float2 lds64f(uint32_t a) { float2 v; asm volatile("ld.shared.v2.f32 {%0, %1}, [%2];" : "=f"(v.x), "=f"(v.y) : "r"(a) : "memory"); return v; }
__device__ __forceinline__ float4 lds128f(uint32_t a) { float4 v; asm volatile("ld.shared.v4.f32 {%0, %1, %2, %3}, [%4];" : "=f"(v.x), "=f"(v.y), "=f"(v.z), "=f"(v.w) : "r"(a) : "memory"); return v; }
__device__ __forceinline__ void sts64f(uint32_t a, float x, float y) { asm volatile("st.shared.v2.f32 [%0], {%1, %2};" ::"r"(a), "f"(x), "f"(y) : "memory"); }
__device__ __forceinline__ float lds32f(uint32_t a) { float v; asm volatile("ld.shared.f32 %0, [%1];" : "=f"(v) : "r"(a) : "memory"); return v; }
__device__ __forceinline__ void sts32f(uint32_t a, float x) { asm volatile("st.shared.f32 [%0], %1;" ::"r"(a), "f"(x) : "memory"); }
__device__ __forceinline__ void stat_st(uint2* p, float sum, float sq, uint32_t tag, bool on) {
  const float mean = sum * (1.f / 128), m2 = fmaxf(fmaf(-mean, sum, sq), 0.f);
  const uint32_t a = ((__float_as_uint(mean) + 8u) & ~15u) | (tag & 15u), b = ((__float_as_uint(m2) + 8u) & ~15u) | (tag & 15u);
  asm volatile("{\n.reg .b64 x;\n.reg .pred p;\nsetp.ne.u32 p, %3, 0;\nmov.b64 x, {%1, %2};\n@p st.relaxed.gpu.global.b64 [%0], x;\n}\n" ::"l"(p), "r"(a), "r"(b), "r"((uint32_t)on) : "memory");
}
__device__ __forceinline__ void stat_ld2(const uint2* p, uint32_t (&v)[4]) {
  asm volatile("{\n.reg .b64 x, y;\nld.relaxed.gpu.global.v2.b64 {x, y}, [%4];\nmov.b64 {%0, %1}, x;\nmov.b64 {%2, %3}, y;\n}\n"
    : "=r"(v[0]), "=r"(v[1]), "=r"(v[2]), "=r"(v[3]) : "l"(p) : "memory");
}
__device__ __forceinline__ float untag(uint32_t v) { return __uint_as_float(v & ~15u); }
__device__ __forceinline__ void ll_st3(uint4* p, uint32_t a, uint32_t b, uint32_t c, uint32_t tag) {
  asm volatile("{\n.reg .b64 x, y;\n.reg .b128 z;\nmov.b64 x, {%1, %2};\nmov.b64 y, {%3, %4};\nmov.b128 z, {x, y};\nst.relaxed.gpu.global.b128 [%0], z;\n}\n"
    ::"l"(p), "r"(a), "r"(b), "r"(c), "r"(tag) : "memory");
}
__device__ __forceinline__ uint32_t ll_ld3(const uint4* p, uint32_t& a, uint32_t& b, uint32_t& c, uint32_t tag) {
  uint32_t t;
  asm volatile("{\n.reg .b64 x, y;\n.reg .b128 z;\nld.relaxed.gpu.global.b128 z, [%4];\nmov.b128 {x, y}, z;\nmov.b64 {%0, %1}, x;\nmov.b64 {%2, %3}, y;\n}\n"
    : "=r"(a), "=r"(b), "=r"(c), "=r"(t) : "l"(p) : "memory");
  return t ^ tag;
}
__device__ __forceinline__ void halo_send(uint4* p, uint32_t a, const uint32_t (&tg)[6]) {
  asm volatile("{\n.reg .b64 x<6>, y<6>, w<2>;\n.reg .b32 c<4>;\n.reg .b128 z<6>;\n"
    "ld.shared.b64 w0, [%1+1536];\nld.shared.b64 w1, [%1+1792];\n"
    "ld.shared.b64 x0, [%1];\nld.shared.b64 x1, [%1+256];\nld.shared.b64 x2, [%1+512];\n"
    "ld.shared.b64 x3, [%1+768];\nld.shared.b64 x4, [%1+1024];\nld.shared.b64 x5, [%1+1280];\n"
    "mov.b64 {c0, c1}, w0;\nmov.b64 {c2, c3}, w1;\n"
    "mov.b64 y0, {c0, %2};\nmov.b64 y1, {c1, %3};\nmov.b64 y2, {c2, %4};\nmov.b64 y3, {c3, %5};\nmov.b64 y4, {%6, %6};\nmov.b64 y5, {%7, %7};\n"
    "mov.b128 z0, {x0, y0};\nmov.b128 z1, {x1, y1};\nmov.b128 z2, {x2, y2};\nmov.b128 z3, {x3, y3};\nmov.b128 z4, {x4, y4};\nmov.b128 z5, {x5, y5};\n"
    "st.relaxed.gpu.global.b128 [%0], z0;\nst.relaxed.gpu.global.b128 [%0+512], z1;\nst.relaxed.gpu.global.b128 [%0+1024], z2;\n"
    "st.relaxed.gpu.global.b128 [%0+1536], z3;\nst.relaxed.gpu.global.b128 [%0+2048], z4;\nst.relaxed.gpu.global.b128 [%0+2560], z5;\n}\n"
    ::"l"(p), "r"(a), "r"(tg[0]), "r"(tg[1]), "r"(tg[2]), "r"(tg[3]), "r"(tg[4]), "r"(tg[5]) : "memory");
}
template <int N> __device__ __forceinline__ void copy_out(uint8_t* dst, uint32_t src, int stride) {
  uint4 v[N];
#pragma unroll
  for (int k = 0; k < N; k++) lds128(src + k * stride, v[k].x, v[k].y, v[k].z, v[k].w);
#pragma unroll
  for (int k = 0; k < N; k++) asm volatile("st.global.v4.b32 [%0], {%1, %2, %3, %4};" ::"l"(dst + k * stride), "r"(v[k].x), "r"(v[k].y), "r"(v[k].z), "r"(v[k].w) : "memory");
}
__device__ __forceinline__ void warp_store(uint8_t* dst, uint32_t src, int bytes, uint32_t delay, uint32_t pace) {
  __nanosleep(delay);
#pragma unroll 1
  for (int o = 0; o < bytes; o += 2048) {
    if (pace) __nanosleep(pace);
    uint4 v[4];
#pragma unroll
    for (int k = 0; k < 4; k++) lds128(src + o + k * 512, v[k].x, v[k].y, v[k].z, v[k].w);
#pragma unroll
    for (int k = 0; k < 4; k++) asm volatile("st.global.v4.b32 [%0], {%1, %2, %3, %4};" ::"l"(dst + o + k * 512), "r"(v[k].x), "r"(v[k].y), "r"(v[k].z), "r"(v[k].w) : "memory");
  }
  __syncwarp();
}
__device__ __forceinline__ uint32_t clock32() { uint32_t t; asm volatile("mov.u32 %0, %%clock;" : "=r"(t)); return t; }
__device__ __forceinline__ void flag_set(uint32_t* p, uint32_t bit) { asm volatile("red.release.gpu.global.xor.b32 [%0], %1;" ::"l"(p), "r"(bit) : "memory"); }
__device__ __forceinline__ void flag_wait(const uint32_t* p, uint32_t inv, uint32_t need, uint32_t& ready) {
  if ((ready & need) == need) return;
  uint32_t n = 0;
  do {
    asm volatile("ld.relaxed.gpu.global.b32 %0, [%1];" : "=r"(ready) : "l"(p) : "memory");
    ready = __shfl_sync(0xffffffffu, ready, 0) ^ inv;
  } while ((ready & need) != need && ++n < SPIN_MAX);
  asm volatile("fence.acquire.gpu;\nfence.proxy.async.global;" ::: "memory");
}
__device__ __forceinline__ bool elect_one() {
  uint32_t p;
  asm volatile("{\n.reg .pred P;\nelect.sync _|P, 0xffffffff;\nselp.u32 %0, 1, 0, P;\n}\n" : "=r"(p));
  return p;
}
__device__ __forceinline__ float gelu_half(float hx) {
  const float y = hx * fmaf(hx * hx, 8.f * 0.0356774081f, 2.f * 0.7978845608f);
  float th;
  asm("tanh.approx.f32 %0, %1;" : "=f"(th) : "f"(y));
  return fmaf(hx, th, hx);
}
__device__ __forceinline__ float ex2(float x) { float y; asm("ex2.approx.ftz.f32 %0, %1;" : "=f"(y) : "f"(x)); return y; }

__device__ __forceinline__ void stat_combine(uint32_t am, uint32_t aq, uint32_t bm, uint32_t bq, float pv, float& mean, float& var) {
  const float d0 = untag(am) - pv, d1 = untag(bm) - pv;
  float s = d0 + d1, q = fmaf(fmaf(d0, d0, d1 * d1), 128.f, untag(aq) + untag(bq));
  s += __shfl_xor_sync(0xffffffffu, s, 8); q += __shfl_xor_sync(0xffffffffu, q, 8);
  s += __shfl_xor_sync(0xffffffffu, s, 16); q += __shfl_xor_sync(0xffffffffu, q, 16);
  s *= 0.125f;
  mean = pv + s;
  var = fmaxf(fmaf(-s, s, q * (1.f / D_)), 0.f);
}

__device__ __forceinline__ void attn_probs(const uint32_t* q0, const uint32_t* q1,
                                           const uint32_t* k0, const uint32_t* k1, const uint32_t* k2, const uint32_t* k3,
                                           float sc0, float sc1, float mk0, float mk1, bool e, bool zneg, const uint32_t (&sel)[3],
                                           uint32_t (&pr)[6], float (&l)[2]) {
  float s[4][4];
#pragma unroll
  for (int n = 0; n < 4; n++) {
    const uint32_t* k = n == 0 ? k0 : n == 1 ? k1 : n == 2 ? k2 : k3;
    s[n][0] = s[n][1] = n < 2 ? mk0 : 0.f; s[n][2] = s[n][3] = n < 2 ? mk1 : 0.f;
    mma16816(s[n], q0[0], q1[0], q0[1], q1[1], k[0], k[1]);
    mma16816(s[n], q0[2], q1[2], q0[3], q1[3], k[2], k[3]);
  }
  float a0 = e ? s[1][1] : s[1][0];
  float b0 = zneg ? (e ? s[0][1] : s[0][0]) : (e ? s[2][1] : s[2][0]);
  float a1 = e ? s[2][3] : s[2][2];
  float b1 = zneg ? (e ? s[1][3] : s[1][2]) : (e ? s[3][3] : s[3][2]);
  float m0 = fmaxf(a0, b0), m1 = fmaxf(a1, b1);
  m0 = fmaxf(m0, __shfl_xor_sync(0xffffffffu, m0, 1)); m1 = fmaxf(m1, __shfl_xor_sync(0xffffffffu, m1, 1));
  m0 = fmaxf(m0, __shfl_xor_sync(0xffffffffu, m0, 2)); m1 = fmaxf(m1, __shfl_xor_sync(0xffffffffu, m1, 2));
  a0 = ex2((a0 - m0) * sc0); b0 = ex2((b0 - m0) * sc0); a1 = ex2((a1 - m1) * sc1); b1 = ex2((b1 - m1) * sc1);
  l[0] = a0 + b0; l[1] = a1 + b1;
  const uint32_t p0 = pack2(a0, b0), p1 = pack2(a1, b1);
#pragma unroll
  for (int k = 0; k < 3; k++) { pr[k] = __byte_perm(p0, 0u, sel[k]); pr[3 + k] = __byte_perm(p1, 0u, sel[k]); }
}
__device__ __forceinline__ void attn_pv(const uint32_t (&pr)[6], const uint32_t* vh, const uint32_t* v, float (&o)[4][4]) {
#pragma unroll
  for (int dt = 0; dt < 4; dt++) {
    o[dt][0] = o[dt][1] = o[dt][2] = o[dt][3] = 0.f;
    mma16816(o[dt], pr[0], 0u, pr[1], pr[3], vh[2 * dt], vh[2 * dt + 1]);
    mma16816(o[dt], pr[2], pr[4], 0u, pr[5], v[2 * dt], v[2 * dt + 1]);
  }
}

#define ATT 25
#define COVER 2
#define HALO_A_NS 300
#define H1D 900
#define FO 2
#define G4GATE 1
#define PFM 7
#define PD1 3
#define PD2 5
#define PD3 3
#define PD4 5
#define FR 1
#define XG 1
#define U0D 300
#define X1D 1200
#define PACE 150
#define LEAD1 3
#define LEAD2 3
#define XLD 7
#define XST 2
#define FA 20
#define LEAD4 4
#define STAT_CLK 150
__global__ void __cluster_dims__(2, 1, 1) __launch_bounds__(384, 1) fused_kernel(const __grid_constant__ Params P) {
  extern __shared__ __align__(1024) uint8_t smem_raw[];
  const uint32_t sb = smem_u32(smem_raw);
  const uint32_t bars = sb + OFF_BAR;
  const int tid = threadIdx.x;
  if (tid == 256) S5(0);
  const int wu = __shfl_sync(0xffffffffu, tid >> 5, 0), wg = wu >> 2;
  const int r = blockIdx.x & 1, cl = blockIdx.x >> 1;
  int grp, slt;
  if (cl < 4) { grp = 0; slt = 4 + cl; }
  else if (cl < 36) { grp = (cl - 4) & 7; slt = (cl - 4) >> 3; }
  else { grp = 1 + (cl - 36) % 7; slt = 4 + (cl - 36) / 7; }
#define MAP 0
  const int m = grp, j = slt;
  const int i = 2 * m + r;
  auto BAR = [&](int k) { return bars + 8 * k; };

  auto kb1 = [&](int n) { const int h = n >= 9, t = n - 2 - 7 * h; return n < 2 ? 2 * j + n : 2 * (t + (t >= j)) + h; };
  auto first_round = [&](int u0, int u1) {
#pragma unroll 1
    for (int u = u0; u < u1; u++) {
      S5(3 + u);
      mbar_expect(BAR(F1 + u), 40960);
      tma2d(sb + slot1(u), &P.x0, BAR(F1 + u), u * 64, 128 * i);
      tma3d(sb + slot1(u) + 16384, &P.wqkv, BAR(F1 + u), 128 * j, u * 64, 0);
      tma3d(sb + slot1(u) + 28672, &P.wqkv, BAR(F1 + u), 128 * j, u * 64 + 32, 0);
    }
  };
  if (wu == 9) {
    if (elect_one()) asm volatile("prefetch.tensormap [%0];" ::"l"(&P.wqkv) : "memory");
    __syncwarp();
  } else if (wu == 8) {
    if (elect_one()) {
      S5(1);
#pragma unroll
      for (int k = 0; k < 4; k++) mbar_init(BAR(F1 + k), 1);
      asm volatile("fence.mbarrier_init.release.cluster;" ::: "memory");
      fence_async_smem();
      first_round(0, FR);
    }
    __syncwarp();
  } else if (wu == 0) {
    if (elect_one()) {
#pragma unroll
      for (int k = E1; k < 64; k++) {
        int cnt = 1;
        if (k < F2 || (k >= E2 && k < F3) || (k >= E3 && k < F4) || (k >= E4 && k < JOB) || k == JOB + 2 || k == JOB + 3) cnt = 4;
        else if ((k >= JOB && k < RD) || k == CSJ) cnt = 8;
        else if (k == RD + 1 || k == STD || k == STAT || k >= HALO) cnt = 2;
        mbar_init(BAR(k), cnt);
      }
      asm volatile("fence.mbarrier_init.release.cluster;" ::: "memory");
      fence_async_smem();
    }
    __syncwarp();
  }
  auto load_tag = [&]() { uint32_t t; asm volatile("ld.relaxed.gpu.global.u32 %0, [%1];" : "=r"(t) : "l"(&gEpoch) : "memory"); return t + 1; };
  TS(0);
  if (wu == 8) nb_arrive<NB_INIT>(384); else nb_sync<NB_INIT>(384);
  asm volatile("barrier.cluster.arrive.relaxed;" ::: "memory");

  if (wg == 2) {
    if (tid == 256) S5(2);
    reg_dealloc<40>();
    if (wu == 8) {
      if (elect_one()) first_round(FR, 4);
      __syncwarp();
    }
    asm volatile("barrier.cluster.wait;" ::: "memory");
    auto kb3 = [&](int n) { const int h = n >= 17, t = n - 2 - 15 * h; return n < 2 ? 2 * i + n : t == 14 ? 2 * (i ^ 1) + h : 2 * ((2 * m + 2 + t) & 15) + h; };
    auto v1 = [&](int L, int u) { const int u0 = L ? 2 : 10; return (u >= u0 && u < 18) ? (u < u0 + 2 ? u - u0 + 16 : u - 2) : u; };
    auto kb2 = [&](int n) { return n < 8 ? 2 * n : n == 8 ? 2 * j + 1 : 2 * (n - 9 + (n - 9 >= j)) + 1; };
    if (wu == 8) {
      const int lane = tid & 31;
      auto pf = [&](const bf16* p, bool on) { if (on) asm volatile("prefetch.global.L2 [%0];" ::"l"(p)); };

      auto k1 = [&](int L, int v) { return (L || v >= 16) ? kb1(v & 15) : v; };
      auto kb4f = [&](int n) {
        const bool own = n == 0 || n == 9 || n == 17;
        const int q = n - 10 - (n > 17), c = own ? n >> 3 : q / 15, t = q - 15 * c;
        const int ii = own ? i : t < 14 ? (2 * m + 2 + t) & 15 : i ^ 1;
        return (n >= 1 && n <= 8) ? 7 * ((m + n) & 7) + 3 : ((7 * ii + 1) >> 1) + c;
      };
      const uint32_t tab4 = kb4f(lane) | (kb4f(lane + 32) << 16);
      auto kb4 = [&](int n) { return (int)((__shfl_sync(0xffffffffu, tab4, n) >> ((n >> 1) & 16)) & 63); };
      const bf16* const q1 = P.wqkv_p + (4 * i + (lane & 3)) * 3072 + (lane >> 2) * 1024 + 128 * j;
      const bf16* const q2 = P.wo_p + (4 * i + (lane & 3)) * 1024 + (lane >> 2) * 64 + 128 * j;
      const bf16* const q3 = P.w1_p + (8 * j + (lane >> 2)) * 3584 + 64 * (7 * m + ((lane & 3) == 3 ? 3 : 4 * r + (lane & 3)));
      const bf16* const q4 = P.w2_p + (8 * j + (lane >> 1)) * 2048 + 128 * i + 64 * (lane & 1);
      auto pf1 = [&](int L, int u) { const int v = v1(L, u); pf(q1 + k1(L, v) * (64 * 3072) + 64 * (v >> 4), (PFM & 1) && lane < 12); };
      auto pf2 = [&](int n) { pf(q2 + kb2(n) * (64 * 1024), (PFM & 2) && lane < 8); };
      auto pf3 = [&](int n) { pf(q3 + kb3(n) * (64 * 3584), PFM & 4); };
      auto pf4 = [&](int n) { pf(q4 + kb4(n) * (64 * 2048), (PFM & 8) && lane < 16); };
#pragma unroll 1
      for (int u = 4; u < 4 + PD1; u++) pf1(0, u);
#pragma unroll 1
      for (int L = 0; L < 2; L++) {
#pragma unroll 1
        for (int u = L ? 0 : 4; u < 32; u++) {
          const int v = v1(L, u), p = u & 3;
          int c0 = 128 * j + 64 * (v >> 4), c1 = k1(L, v) * 64 + 32 * r; uint32_t dst = sb + slot1(p) + 16384 + r * 12288;
          asm volatile("" : "+r"(c0), "+r"(c1), "+r"(dst));
          if (XG && L && u == 4) mbar_wait(BAR(RD + 5), 0);
          if (u >= 4) mbar_wait(BAR(E1 + p), ((u >> 2) - 1) & 1);
          else mbar_wait(BAR(E4 + (u == 3 ? 0 : u + 3)), u == 3);
          if (elect_one()) {
            mbar_expect(BAR(F1 + p), (v & 15) < 2 ? 24576 : 40960);
            tma3d_mc(dst, &P.wqkv, BAR(F1 + p), c0, c1, 0);
          }
          if (u + PD1 < 32) pf1(L, u + PD1);
          if (u + PD2 >= 32) pf2(u + PD2 - 32);
        }
        int p = 0; uint32_t par = L ? 0x1e : 0;
#pragma unroll 1
        for (int n = 0; n < 16; n++) {
          int c1 = kb2(n) * 64;
          asm volatile("" : "+r"(c1));
          if (n >= 5) { mbar_wait(BAR(E2 + p), (par >> p) & 1); par ^= 1u << p; }
          else if (n < 4) mbar_wait(BAR(E1 + n), 1);
          if (elect_one()) {
            mbar_expect(BAR(F2 + p), n == 8 ? 16384 : 32768);
            tma2d_mc(sb + slot2(p) + 16384 + r * 8192, &P.wo, BAR(F2 + p), 128 * j + 64 * r, c1);
          }
          if (++p == 5) p = 0;
          if (n + PD2 < 16) pf2(n + PD2);
          if (n + PD3 + 4 >= 16) pf3(n + PD3 + 4 - 16);
        }
#pragma unroll 1
        for (int u = 0; u < 32; u++) {
          const int n = u < 4 ? (0x2031 >> (4 * u)) & 3 : u, p = n & 3;
          int kb = kb3(n);
          asm volatile("" : "+r"(kb));
          if (n == 4) mbar_wait(BAR(RD + 4), L);
          if (n >= 4) mbar_wait(BAR(E3 + p), ((n >> 2) - 1) & 1);
          else if (n == 1) mbar_wait(BAR(STD + 1), L);
          else if (n == 3) mbar_wait(BAR(E2 + 2), L);
          else if (n == 0) mbar_wait(BAR(E2 + 4), L);
          else mbar_wait(BAR(E2 + 0), 1);
          if (elect_one()) {
            mbar_expect(BAR(F3 + p), n < 2 ? 32768 : 49152);
            tma3d(sb + slot3(p) + 16384, &P.w1, BAR(F3 + p), 0, kb * 64, 7 * m + 4 * r);
            tma3d(sb + slot3(p) + 40960, &P.w1h, BAR(F3 + p), 0, kb * 64, 14 * m + 6 + r);
          }
          if (u >= 4 && u + PD3 < 32) pf3(u + PD3);
          if (u + PD4 + 6 >= 32) pf4(u + PD4 + 6 - 32);
        }
        auto g4w = [&](int n, int p, int kb) {
          if (elect_one()) {
            mbar_expect(BAR(F4 + p), (n == 0 || n == 9 || n == 17) ? 16384 : 32768);
            tma3d(sb + slot4(p), &P.w2, BAR(F4 + p), 0, kb * 64, 2 * i);
          }
        };
#pragma unroll 1
        for (int n = 0; n < 6; n++) {
          const int kb = kb4(n);
          if (n == G4GATE) mbar_wait(BAR(RD + 3), L);
          if (n < 3) mbar_wait(BAR(E3 + n), 1);
          else if (n == 4) mbar_wait(BAR(E3 + 3), 1);
          g4w(n, n, kb);
        }
        p = 0; par = L ? 0x3c : 0;
#pragma unroll 1
        for (int n = 6; n < 56; n++) {
          const int kb = kb4(n);
          if (n + PD4 < 56) pf4(n + PD4);
          mbar_wait(BAR(E4 + p), (par >> p) & 1); par ^= 1u << p;
          g4w(n, p, kb);
          if (++p == 6) p = 0;
        }
        if (L == 0)
#pragma unroll 1
          for (int u = 0; u < PD1; u++) pf1(1, u);
      }
    } else if (wu == 9) {
      uint32_t inv = 0;
#define ADDR(d, s) uint32_t dst = (d); const uint8_t* src = (s); asm volatile("" : "+r"(dst), "+l"(src))
#pragma unroll 1
      for (int L = 0; L < 2; L++) {
        uint32_t ready = 0;
#pragma unroll 1
        for (int u = 4; u < 32; u++) {
          const int p = u & 3, v = v1(L, u), nn = v & 15, kb = (L || v >= 16) ? kb1(nn) : nn;
          if (L == 0 && (u == XLD || u == XLD + XST) && elect_one()) {
            const int h = u != XLD;
            mbar_expect(BAR(XF + h), 16384);
            tma2d(sb + OFF_X + h * 16384, &P.x0, BAR(XF + h), 128 * j + 64 * h, 128 * i);
          }
          if (nn < 2) continue;
          ADDR(sb + slot1(p), gXB + (i * 16 + kb) * 16384);
          if (L && u < 12) mbar_wait(BAR(F1 + p), u >> 3);
          if (u >= 4 + 4 * L) mbar_wait(BAR(E1 + p), ((u >> 2) - 1) & 1);
          if (L) {
            flag_wait(gFlag[0][0][i], inv, 1u << kb, ready);
            if (elect_one()) bulk_ld(dst, src, 16384, BAR(F1 + p));
          } else if (elect_one()) tma2d(sb + slot1(p), &P.x0, BAR(F1 + p), kb * 64, 128 * i);
        }
        ready = 0;
        if (L == 0) inv = (__shfl_sync(0xffffffffu, load_tag(), 0) & 1) - 1;
        int p = 0; uint32_t par = L ? 0x1e : 0;
#pragma unroll 1
        for (int n = 0; n < 16; n++) {
          const int hp = kb2(n);
          if (n == 8) { par ^= 8; p = 4; continue; }
          ADDR(sb + slot2(p), gOB + (i * 16 + hp) * 16384);
          if (n >= 5) { mbar_wait(BAR(E2 + p), (par >> p) & 1); par ^= 1u << p; }
          else if (n < 4) mbar_wait(BAR(E1 + n), 1);
          flag_wait(gFlag[L][1][i], inv, 1u << hp, ready);
          if (n == 9) ST(4);
          if (elect_one()) bulk_ld(dst, src, 16384, BAR(F2 + p));
          if (++p == 5) p = 0;
        }
        ready = 0;
        mbar_wait(BAR(E2 + 0), 1);
#pragma unroll 1
        for (int n = 2; n < 32; n++) {
          const int p = n & 3, kb = kb3(n);
          const int o = (n != 16 && n != 31) ? r * 8192 : 0;
          ADDR(sb + slot3(p) + o, gHB + (j * 32 + kb) * 16384 + o);
          if (n > 3) mbar_wait(BAR(E3 + p), ((n >> 2) - 1) & 1);
          flag_wait(gFlag[L][2][j], inv, 1u << kb, ready);
          if (n == 2) ST(12);
          if (elect_one()) {
            if (n != 16 && n != 31) bulk_ld_mc(dst, src, 8192, BAR(F3 + p));
            else bulk_ld(dst, src, 16384, BAR(F3 + p));
          }
        }
        ready = 0; p = 1; par = L ? 0x3c : 0;
#pragma unroll 1
        for (int t = 0; t < 8; t++) {
          const int mm = (m + t + 1) & 7;
          ADDR(sb + slot4(p) + 16384 + r * 8192, gUB + (j * 56 + 48 + mm) * 16384 + r * 8192);
          if (t < 3) mbar_wait(BAR(E3 + 1 + t), 1);
          if (t >= 5) { mbar_wait(BAR(E4 + p), (par >> p) & 1); par ^= 1u << p; }
          flag_wait(gFlag[L][6][j], inv, 3u << (2 * mm), ready);
          if (t == 0) ST(20);
          if (elect_one()) bulk_ld_mc(dst, src, 8192, BAR(F4 + p));
          if (++p == 6) p = 0;
        }
#pragma unroll 1
        for (int c = 0; c < 3; c++) {
          ready = 0;
#pragma unroll 1
          for (int t = 0; t < 15; t++) {
            const int ii = t < 14 ? (2 * m + 2 + t) & 15 : i ^ 1;
            if (c == 0 && (t == 0 || t == 7)) { par ^= 1u << p; if (++p == 6) p = 0; }
            const int o = t < 14 ? r * 8192 : 0;
            ADDR(sb + slot4(p) + 16384 + o, gUB + (j * 56 + 16 * c + ii) * 16384 + o);
            mbar_wait(BAR(E4 + p), (par >> p) & 1); par ^= 1u << p;
            flag_wait(gFlag[L][3 + c][j], inv, 1u << ii, ready);
            if (elect_one()) {
              if (t < 14) bulk_ld_mc(dst, src, 8192, BAR(F4 + p));
              else bulk_ld(dst, src, 16384, BAR(F4 + p));
            }
            if (++p == 6) p = 0;
          }
        }
      }
    } else {
      const int h = wu - 10, i0 = i, j0 = j;
      {
      const uint32_t tag = load_tag();
      int lane = tid & 31, i = i0, j = j0;
#define FRESH asm volatile("" : "+r"(lane), "+r"(i), "+r"(j))
      auto signal = [&](int k) { if (lane == 0) mbar_arrive(BAR(k)); };
      auto publish = [&](uint32_t* f, int bit) { if (lane == 0) flag_set(f, 1u << bit); __syncwarp(); };
#pragma unroll 1
      for (int c = 32 * h + lane; c < 288; c += 64)
        sts16(sb + OFF_B1 + 2 * c, c >= 224 ? 0u : pack2(0.5f * __bfloat162float(P.b1[c < 192 ? 64 * (7 * m + 4 * r) + c : 64 * (7 * m + 3) + 32 * r + c - 192]), 0.f));
      if (h == 0) sts32f(sb + OFF_CS + 768 + 4 * lane, 0.f);
#pragma unroll 1
      for (int L = 0; L < 2; L++) {
        FRESH;
        if (L == 0) {
          mbar_wait(BAR(CSJ), 0);
          float c0 = 0.f, c1 = 0.f, c2 = 0.f;
          const uint32_t a = sb + OFF_STG + (32 * h + lane) * 4;
#pragma unroll 4
          for (int k = 0; k < 32; k++) { c0 += lds32f(a + k * 784); c1 += lds32f(a + k * 784 + 256); c2 += lds32f(a + k * 784 + 512); }
          ll_st3(&gCS[j][i][32 * h + lane], __float_as_uint(c0), __float_as_uint(c1), __float_as_uint(c2), tag);
          __nanosleep(500);
        }
        FRESH;
        if (L == 0) {
#pragma unroll 1
          for (int ab = 0; ab < 2; ab++) {
            float c0 = 0.f, c1 = 0.f, c2 = 0.f;
#pragma unroll 1
            for (int b4 = 0; b4 < 8; b4 += 4) {
              uint32_t a[4], b[4], c[4], n = 0, bad;
              do {
                bad = 0;
#pragma unroll
                for (int e = 0; e < 4; e++) bad |= ll_ld3(&gCS[j][2 * (b4 + e) + ab][32 * h + lane], a[e], b[e], c[e], tag);
              } while (bad && ++n < SPIN_MAX);
#pragma unroll
              for (int e = 0; e < 4; e++) { c0 += __uint_as_float(a[e]); c1 += __uint_as_float(b[e]); c2 += __uint_as_float(c[e]); }
            }
            const uint32_t a = sb + OFF_CS + ab * 768 + (4 * h + (lane >> 3)) * 32 + (lane & 7) * 2;
            const uint32_t h0 = pack2(c0, 0.f), h1 = pack2(c1, 0.f), h2 = pack2(c2, 0.f);
            sts16(a, h0); sts16(a + 256, h1); sts16(a + 512, h2);
            sts16(a + 16, pack2(c0 - bf_lo(h0), 0.f)); sts16(a + 272, pack2(c1 - bf_lo(h1), 0.f)); sts16(a + 528, pack2(c2 - bf_lo(h2), 0.f));
            fence_async_smem();
            __syncwarp();
            if (ab == 0) signal(STAT);
          }
        }
#pragma unroll 1
        for (int ab = 0; ab < 2; ab++) {
          FRESH;
          uint32_t v[18], tg[6];
          const uint32_t xs = sb + OFF_STG + h * 16384 + lane * 8;
          uint4* hp = &gHalo[L][i][j][6 * h][lane];
#pragma unroll
          for (int c = 0; c < 6; c++) { tg[c] = (2 * tag + ab) * 8 + c; asm volatile("" : "+r"(tg[c])); }
          asm volatile("" : "+l"(hp));
          mbar_wait(BAR(FOLD + ab), L);
          if (ab && h == 0) ST(6);
          if (i < 15) {
            halo_send(hp, xs, tg);
          }
          if (ab && h == 0) ST(26);
          if (i > 0) {
            if (!ab) __nanosleep(HALO_A_NS);
            uint32_t n = 0, bad;
            do {
              bad = 0;
#pragma unroll
              for (int c = 0; c < 6; c++) bad |= ll_ld3(hp + c * 32 - 8 * 12 * 32, v[3 * c], v[3 * c + 1], v[3 * c + 2], (2 * tag + ab) * 8);
              if (ab && h == 0 && n == 0) ST(28);
            } while (bad > 7 && ++n < SPIN_MAX);
            if (ab && h == 0) ST(27);
          } else {
#pragma unroll
            for (int c = 0; c < 18; c++) v[c] = 0u;
          }
#pragma unroll
          for (int c = 0; c < 6; c++) sts64f(xs + c * 256, __uint_as_float(v[3 * c]), __uint_as_float(v[3 * c + 1]));
          sts64f(xs + 1536, __uint_as_float(v[2]), __uint_as_float(v[5]));
          sts64f(xs + 1792, __uint_as_float(v[8]), __uint_as_float(v[11]));
          __syncwarp();
          signal(HALO + ab);
          if (ab && h == 0) ST(7);
          FRESH;
          if (ab == 0 && lane == 0) asm volatile("st.relaxed.gpu.global.u32 [%0], %1;" ::"l"(&gAck[L][i][j][h][0]), "r"(tag) : "memory");
          uint8_t* dst = gOB + (i * 16 + 2 * j + ab) * 16384;
          uint32_t* flag = gFlag[L][1][i];
          asm volatile("" : "+l"(dst), "+l"(flag));
          mbar_wait(BAR(JOB + ab), L);
          if (h == 0) {
            if (ab) ST(1);
            if (lane == 0) { bulk_st(dst, sb + OFF_STG, 16384); bulk_commit(); bulk_wait0(); }
            signal(STD + ab);
            if (ab) ST(2);
            publish(flag, 2 * j + ab);
            if (ab) ST(3);
          } else if (ab == 0) {
            if (i < 15 && lane < 2) {
              uint32_t t, n = 0;
              do { asm volatile("ld.relaxed.gpu.global.u32 %0, [%1];" : "=r"(t) : "l"(&gAck[L][i + 1][j][lane][0]) : "memory"); } while (t != tag && ++n < SPIN_MAX);
            }
            __syncwarp();
            signal(STD);
          }
        }
#pragma unroll 1
        for (int k = 0; k < 4 - L; k++) {
          FRESH;
          const int job = 2 * k + h;
          uint8_t* dst = k == 0 ? gHB + (j * 32 + 2 * i + 1) * 16384 : k == 3 ? gXB + (i * 16 + 2 * j + 1) * 16384 : gUB + (j * 56 + 16 * (job - 3) + i) * 16384;
          uint32_t* flag = k == 3 ? gFlag[0][0][i] : gFlag[L][(0x543622 >> (4 * job)) & 15][j];
          uint32_t bit = 1u << (k == 0 ? 2 * i + h : k == 3 ? 2 * j + h : i);
          asm volatile("" : "+l"(dst), "+l"(flag), "+r"(bit));
          mbar_wait(BAR(JOB + ((0x98654732 >> (4 * job)) & 15)), L);
          if (job < 3 && h == 0) ST(job ? 17 : 9);
          if ((0xba >> job) & 1) {
            if (job == 1) mbar_wait(BAR(RD + 4), L);
            if (job == 3) {
              __nanosleep(U0D);
              if (lane == 0) { bulk_st(dst, sb + OFF_X, 16384); bulk_commit(); bulk_wait0(); }
            } else warp_store(dst + lane * 16, sb + lane * 16 + OFF_X + (job == 5 ? 0 : 16384), 16384, job == 1 ? H1D : job == 7 ? X1D : 0, job == 7 ? 0 : PACE);
            if (job != 7) signal(RD + ((0x112000 >> (4 * job)) & 15));
          }
          if (lane == 0) flag_set(flag, bit);
          __syncwarp();
          if (h == 0 && k != 2) { signal(RD + (k == 3 ? 5 : 4 - k)); if (k < 2) ST(job ? 19 : 11); }
        }
      }
      if (blockIdx.x == 0 && h == 0 && lane == 0) asm volatile("st.relaxed.gpu.global.u32 [%0], %1;" ::"l"(&gEpoch), "r"(tag) : "memory");
      }
    }
    __syncwarp();
    cluster_bar();
  } else {
    reg_alloc<232>();
    asm volatile("barrier.cluster.wait;" ::: "memory");
    const uint32_t rbars = mapa(bars, tid & 1);
    const bool relp = (tid & 127) < 2;
    const uint32_t sd = (sb & 0x3FFFF) >> 4, sda = sd + wg * 512;
    uint32_t tag;
    asm volatile("ld.relaxed.gpu.global.u32 %0, [%1];" : "=r"(tag) : "l"(&gEpoch + (fresh_tid() >> 10)) : "memory");
    auto release = [&](int k) { if (relp) mbar_arrive_cl(rbars + 8 * k); };
    auto signal = [&](int k) { __syncwarp(); if ((fresh_tid() & 31) == 0) mbar_arrive(BAR(k)); };
#define GEOM const int t7 = fresh_tid() & 127, lane = t7 & 31, w = t7 >> 5, g = lane >> 2, q = lane & 3, \
                       lr = lane & 15, lt = lane >> 4, l7 = lane & 7; (void)w; (void)g; (void)q; (void)lr; (void)lt; (void)l7

#pragma unroll 1
    for (int L = 0; L < 2; L++) {
      float acca[96], accb[96], xa[64], acc3[112];
      float nmean0, nmean1, rstd0, rstd1;
      uint16_t b2a, b2b;
      uint2 *e2p, *e2s; uint8_t* e2g; uint32_t e2h;
      uint32_t Q[2][8], K[2][8], V[16];
      auto g1_issue = [&](float (&acc)[96], uint32_t a, uint32_t st, auto first) {
        const uint32_t da = sda + (a >> 4), db = sd + (st >> 4);
        wg_fence();
        static_for<0, 4>([&](auto kk) {
          constexpr uint32_t ia = DI(kk.value * 32, 16), ib = DI(16384 + (kk.value >> 1) * 12288 + (kk.value & 1) * 2048, 4096);
          if constexpr (first.value && kk.value == 0) wgmma_192z<0, 1, ia, ib>(acc, da, db); else wgmma_192<0, 1, ia, ib>(acc, da, db);
        });
        wg_commit();
      };
      auto g1_step = [&](float (&acc)[96], int u, bool rel, bool lead = false) {
        const int p = u & 3;
        mbar_wait(BAR(F1 + p), (u >> 2) & 1);
        KB(u);
        g1_issue(acc, slot1(p), slot1(p), False{});
        if (lead) nb_arrive<NB_LEAD>(256);
        wg_wait<1>();
        if (rel) release(E1 + ((u - 1) & 3));
      };
      auto g1_loop = [&](float (&acc)[96], int u0, int u1, int urel) {
        int u = u0;
#pragma unroll 1
        do { g1_step(acc, u, u > urel); } while (++u < u1);
      };
      auto load_x = [&]() {
        GEOM;
#pragma unroll
        for (int t = 0; t < 16; t += 2) {
          uint32_t v0, v1, v2, v3;
          ldsm4(sb + OFF_X + (t >> 3) * 16384 + (16 * wu + lr) * 128 + ((((t & 7) + lt) ^ l7) << 4), v0, v1, v2, v3);
          xa[4 * t + 0] = bf_lo(v0); xa[4 * t + 1] = bf_hi(v0); xa[4 * t + 2] = bf_lo(v1); xa[4 * t + 3] = bf_hi(v1);
          xa[4 * t + 4] = bf_lo(v2); xa[4 * t + 5] = bf_hi(v2); xa[4 * t + 6] = bf_lo(v3); xa[4 * t + 7] = bf_hi(v3);
        }
      };
      auto stat_base = [&]() { return &gST[0][0][0][0][0] + ((L * 16 + opq(i)) * 8 + wu) * 128; };
      auto stat_slot = [&]() { const int lane = fresh_tid() & 31; return stat_base() + 16 * j + 2 * (lane >> 2) + (lane & 1); };
      auto stat_publish = [&](uint2* sp, float s0, float q0, float s2, float q2, uint32_t tg) {
        const int q = fresh_tid() & 3;
        const bool h1 = q & 1;
        float sm = (h1 ? s2 : s0) + __shfl_xor_sync(0xffffffffu, h1 ? s0 : s2, 1);
        float sq = (h1 ? q2 : q0) + __shfl_xor_sync(0xffffffffu, h1 ? q0 : q2, 1);
        sm += __shfl_xor_sync(0xffffffffu, sm, 2); sq += __shfl_xor_sync(0xffffffffu, sq, 2);
        stat_st(sp, sm, sq, tg, q < 2);
        return sm;
      };
      auto g1_stats = [&](int u0) {
        GEOM;
        const uint32_t xr = sb + OFF_X + (16 * wu + lr) * 128;
        float s0 = 0.f, q0 = 0.f, s2 = 0.f, q2 = 0.f;
        uint32_t v[8] = {0u, 0u, 0u, 0u, 0u, 0u, 0u, 0u};
#pragma unroll 1
        for (int k = 0; k < 5; k++) {
#pragma unroll
          for (int e = 0; e < 8; e += 2) {
            const float a = bf_lo(v[e]), b = bf_hi(v[e]), c = bf_lo(v[e + 1]), d = bf_hi(v[e + 1]);
            s0 += a + b; q0 = fmaf(a, a, fmaf(b, b, q0)); s2 += c + d; q2 = fmaf(c, c, fmaf(d, d, q2));
          }
          if (k == 4) break;
          const uint32_t o = ((2 * k + lt) ^ l7) << 4;
          ldsm4(xr + o, v[0], v[1], v[2], v[3]);
          ldsm4(xr + o + 16384, v[4], v[5], v[6], v[7]);
          g1_step(acca, u0 + k, true);
        }
        stat_publish(stat_slot(), s0, q0, s2, q2, 2 * (tag + 1));
      };
      uint32_t sv0[4], sv1[4];
      auto stat_src = [&]() { return stat_base() + 2 * (fresh_tid() & 31); };
      auto stat_fetch = [&](const uint2* sp) { stat_ld2(sp, sv0); stat_ld2(sp + 64, sv1); };
      auto stat_await = [&](auto src, uint32_t tg) {
#pragma unroll 1
        for (uint32_t n = 0; (((sv0[0] ^ tg) | (sv0[2] ^ tg) | (sv1[0] ^ tg) | (sv1[2] ^ tg)) & 15u) && n < SPIN_MAX; n++) stat_fetch(src());
        __syncwarp();
      };
      auto ln_stats = [&]() {
        GEOM;
        stat_await(stat_src, 2 * (tag + 1));
        float mean0, var0, mean1, var1;
        stat_combine(sv0[0], sv0[1], sv1[0], sv1[1], untag(__shfl_sync(0xffffffffu, sv0[0], l7)), mean0, var0);
        stat_combine(sv0[2], sv0[3], sv1[2], sv1[3], untag(__shfl_sync(0xffffffffu, sv0[2], l7)), mean1, var1);
        nmean0 = -__shfl_sync(0xffffffffu, mean0, g); rstd0 = rsq(__shfl_sync(0xffffffffu, var0, g) + 1e-5f);
        nmean1 = -__shfl_sync(0xffffffffu, mean1, g); rstd1 = rsq(__shfl_sync(0xffffffffu, var1, g) + 1e-5f);
      };
      auto center = [&](float (&acc)[96], int ab) {
        const bool q0 = (fresh_tid() & 3) == 0;
        const uint32_t h0 = pack2(nmean0, nmean0), h1 = pack2(nmean1, nmean1);
        const float l0 = nmean0 - bf_lo(h0), l1 = nmean1 - bf_lo(h1);
        const uint32_t a0 = q0 ? h0 : 0u, a1 = q0 ? h1 : 0u, a2 = q0 ? pack2(l0, l0) : 0u, a3 = q0 ? pack2(l1, l1) : 0u;
        wg_fence();
        wgmma_rs_192(acc, a0, a1, a2, a3, mkdesc_vec(sb + OFF_CS + ab * 768, 32));
      };
      auto frag = [&](float (&acc)[96], int t, uint32_t& p0, uint32_t& p1) {
        if (t >= 8) { p0 = pack2(acc[4 * t] * rstd0, acc[4 * t + 1] * rstd0); p1 = pack2(acc[4 * t + 2] * rstd1, acc[4 * t + 3] * rstd1); }
        else { p0 = pack2(acc[4 * t], acc[4 * t + 1]); p1 = pack2(acc[4 * t + 2], acc[4 * t + 3]); }
      };
      auto fold_v = [&](float (&acc)[96], int t0, int t1) {
        GEOM;
        const uint32_t a = sb + OFF_STG + 16384 + ((wu + 1) & 7) * 2048 + lr * 128;
#pragma unroll
        for (int t = t0; t < t1; t += 2) {
          uint32_t p0, p1, p2, p3;
          frag(acc, 16 + t, p0, p1); frag(acc, 17 + t, p2, p3);
          stsm4(a + (((t + lt) ^ l7) << 4), p0, p1, p2, p3);
        }
        __syncwarp();
#pragma unroll
        for (int t = t0; t < t1; t += 2) ldsm4t(a + (((t + lt) ^ l7) << 4), V[2 * t], V[2 * t + 1], V[2 * t + 2], V[2 * t + 3]);
      };
      auto fold_k = [&](float (&acc)[96], int ab, int h0, int h1) {
        GEOM;
        const uint32_t a = sb + OFF_STG + ((wu + 1) & 7) * 2048 + lane * 16;
#pragma unroll
        for (int hh = h0; hh < h1; hh++) {
#pragma unroll
          for (int t = 4 * hh; t < 4 * hh + 4; t++) frag(acc, 8 + t, K[0][t], K[1][t]);
#pragma unroll
          for (int o = 0; o < 2; o++) sts128(a + (2 * o + hh) * 512, K[o][4 * hh], K[o][4 * hh + 1], K[o][4 * hh + 2], K[o][4 * hh + 3]);
        }
        if (h1 == 2 && wu == 7) signal(FOLD + ab);
      };
      auto fold_q = [&](float (&acc)[96]) {
#pragma unroll
        for (int t = 0; t < 8; t++) frag(acc, t, Q[0][t], Q[1][t]);
      };
      auto attend = [&](int ab, auto drain, auto resume) {
        GEOM;
        nb_sync<NB_BOTH>(256);
        const uint32_t xa_ = sb + OFF_STG + wu * 2048 + lane * 16;
        if (wu == 0) mbar_wait(BAR(HALO + ab), L);
        uint32_t KH[2][8], VH[16];
#pragma unroll
        for (int c = 0; c < 4; c++) {
          lds128(xa_ + c * 512, KH[c >> 1][4 * (c & 1)], KH[c >> 1][4 * (c & 1) + 1], KH[c >> 1][4 * (c & 1) + 2], KH[c >> 1][4 * (c & 1) + 3]);
          ldsm4t(sb + OFF_STG + 16384 + wu * 2048 + lr * 128 + (((2 * c + lt) ^ l7) << 4), VH[4 * c], VH[4 * c + 1], VH[4 * c + 2], VH[4 * c + 3]);
        }
        TS2(11 + ab + 32 * L);
        const bool e = g & 1, zneg = (g >> 1) < q, first = (i == 0) && (wu == 0);
        const float sc0 = rstd0 * (0.17677669530f * 1.4426950409f), sc1 = rstd1 * (0.17677669530f * 1.4426950409f);
        float mk0 = first ? __fdividef(-1.0e9f * 1.4426950409f, sc0) : 0.f, mk1 = first ? __fdividef(-1.0e9f * 1.4426950409f, sc1) : 0.f;
        const uint32_t sa = e ? 0x1044u : 0x4410u, sbb = e ? 0x3244u : 0x4432u;
        uint32_t sel[3] = {zneg ? sbb : 0x4444u, sa, zneg ? 0x4444u : sbb};
        uint32_t oa = sb + OFF_STG + (16 * wu + lr) * 128 + ((lt ^ l7) << 4);
        asm volatile("" : "+r"(sel[0]), "+r"(sel[1]), "+r"(sel[2]), "+r"(oa), "+f"(mk0), "+f"(mk1));
        drain();
        uint32_t pr[2][6];
        float l[2][2];
#pragma unroll
        for (int hh = 0; hh < 2; hh++)
          attn_probs(&Q[0][4 * hh], &Q[1][4 * hh], &KH[0][4 * hh], &KH[1][4 * hh], &K[0][4 * hh], &K[1][4 * hh], sc0, sc1, mk0, mk1, e, zneg, sel, pr[hh], l[hh]);
        float o[2][4][4];
#pragma unroll
        for (int hh = 0; hh < 2; hh++) attn_pv(pr[hh], &VH[8 * hh], &V[8 * hh], o[hh]);
#pragma unroll
        for (int hh = 0; hh < 2; hh++) {
          float l0 = l[hh][0], l1 = l[hh][1];
          l0 += __shfl_xor_sync(0xffffffffu, l0, 1); l1 += __shfl_xor_sync(0xffffffffu, l1, 1);
          l0 += __shfl_xor_sync(0xffffffffu, l0, 2); l1 += __shfl_xor_sync(0xffffffffu, l1, 2);
          asm("rcp.approx.ftz.f32 %0, %0;" : "+f"(l0)); asm("rcp.approx.ftz.f32 %0, %0;" : "+f"(l1));
#pragma unroll
          for (int dt = 0; dt < 4; dt += 2)
            stsm4(oa ^ ((4 * hh + dt) << 4),
                  pack2(o[hh][dt][0] * l0, o[hh][dt][1] * l0), pack2(o[hh][dt][2] * l1, o[hh][dt][3] * l1),
                  pack2(o[hh][dt + 1][0] * l0, o[hh][dt + 1][1] * l0), pack2(o[hh][dt + 1][2] * l1, o[hh][dt + 1][3] * l1));
        }
        fence_async_smem();
        signal(JOB + ab);
        nb_sync<NB_BOTH>(256);
        resume();
      };

      TS(1 + 32 * L);
      if (L == 0 && wu == 0) S5(7);
      mbar_wait(BAR(F1), 0); if (L == 0 && wu == 0) S5(8); KB(0);    g1_issue(acca, L ? OFF_X : slot1(0), slot1(0), True{});
      mbar_wait(BAR(F1 + 1), 0); KB(1); g1_issue(acca, L ? OFF_X + 16384 : slot1(1), slot1(1), False{});
      wg_wait<1>(); release(E1 + 0);
      if (L == 0) {
        GEOM;
        const bf16* wp = P.wqkv_p + ((128 * opq(m) + 16 * wg + (t7 >> 3)) * 3072 + 128 * opq(j) + 64 * r + l7 * 8);
        const uint32_t ca = sb + OFF_STG + (16 * wg + (t7 >> 3)) * 784 + l7 * 32;
#pragma unroll 1
        for (int p = 0; p < 3; p++) {
          uint4 wv[4];
#pragma unroll
          for (int k = 0; k < 4; k++)
            asm volatile("ld.global.nc.v4.u32 {%0, %1, %2, %3}, [%4];" : "=r"(wv[k].x), "=r"(wv[k].y), "=r"(wv[k].z), "=r"(wv[k].w)
                         : "l"(wp + k * 32 * 3072 + p * 1024));
          g1_loop(acca, 2 + 3 * p, p < 2 ? 5 + 3 * p : 10, 0);
          float cs[8];
#pragma unroll
          for (int k = 0; k < 4; k++) {
            const uint4 v = wv[k];
            const float t[8] = {bf_lo(v.x), bf_hi(v.x), bf_lo(v.y), bf_hi(v.y), bf_lo(v.z), bf_hi(v.z), bf_lo(v.w), bf_hi(v.w)};
#pragma unroll
            for (int e = 0; e < 8; e++) cs[e] = k ? cs[e] + t[e] : t[e];
          }
          sts128(ca + p * 256, __float_as_uint(cs[0]), __float_as_uint(cs[1]), __float_as_uint(cs[2]), __float_as_uint(cs[3]));
          sts128(ca + p * 256 + 16, __float_as_uint(cs[4]), __float_as_uint(cs[5]), __float_as_uint(cs[6]), __float_as_uint(cs[7]));
        }
        signal(CSJ);
        mbar_wait(BAR(XF), 0); mbar_wait(BAR(XF + 1), 0);
      }
      {
        const int u0 = L ? 2 : 10;
        mbar_wait(BAR(F1 + 2), 0); KB(u0); g1_issue(accb, OFF_X, slot1(2), True{});
        wg_wait<1>(); release(E1 + 1);
        mbar_wait(BAR(F1 + 3), 0); KB(u0 + 1); g1_issue(accb, OFF_X + 16384, slot1(3), False{});
        wg_wait<1>(); release(E1 + 2);
        g1_stats(u0 + 2);
        g1_loop(acca, u0 + 6, 18, 0);
      }
      stat_fetch(stat_src());
      const int fa = FA + (wg ? 0 : FO);
      g1_loop(accb, 18, fa, 0);
      ln_stats();
      if (L == 0) mbar_wait(BAR(STAT), 0);
      center(acca, 0); wg_commit();
      wg_wait<0>(); release(E1 + ((fa - 1) & 3));
      fence_regs(acca);
      TS(2 + 32 * L);
      fold_v(acca, 0, 8); fold_k(acca, 0, 0, 2); fold_q(acca);
      sched_fence(P.zero);
      g1_loop(accb, fa, ATT, fa);
      attend(0, [&]() { wg_wait<0>(); release(E1 + ((ATT - 1) & 3)); mbar_wait(BAR(F1 + (ATT & 3)), (ATT >> 2) & 1); },
             [&]() { KB(ATT); g1_issue(accb, slot1(ATT & 3), slot1(ATT & 3), False{});
                     mbar_wait(BAR(F1 + ((ATT + 1) & 3)), ((ATT + 1) >> 2) & 1);
                     KB(ATT + 1); g1_issue(accb, slot1((ATT + 1) & 3), slot1((ATT + 1) & 3), False{}); });
      wg_wait<1>(); release(E1 + (ATT & 3));
      TS(3 + 32 * L);
      load_x();
      fence_regs(xa);
      center(accb, 1);
#pragma unroll 1
      for (int u = ATT + 2; u < 32; u++) {
        const bool hold = u == 32 - LEAD1 && wg == 0;
        if (hold) { wg_wait<0>(); release(E1 + ((31 - LEAD1) & 3)); nb_sync<NB_LEAD>(256); }
        g1_step(accb, u, !hold, u == 31 && wg == 1);
      }
      mbar_wait(BAR(STD), L);
      wg_wait<0>(); release(E1 + 3);
      fence_regs(accb);
      TS(4 + 32 * L);
      if (wu == 7) ST(0);
      fold_v(accb, 0, 8); fold_k(accb, 1, 0, 2);
      fold_q(accb);
      TS2(29 + 32 * L);
      {
        auto g2_issue = [&](int p, bool own) {
          const uint32_t st = slot2(p);
          const uint32_t da = sda + ((own ? OFF_STG : st) >> 4), db = sd + (st >> 4);
          wg_fence();
          static_for<0, 4>([&](auto kk) { wgmma_128<0, 1, DI(kk.value * 32, 16), DI(16384 + kk.value * 2048, 8192)>(xa, da, db); });
          wg_commit();
        };
        uint32_t par = L ? 0x1e : 0;
        int p = 0, pp = 0;
        auto g2_loop = [&](int n0, int n1, int nrel) {
#pragma unroll 1
          for (int n = n0; n < n1; n++) {
            mbar_wait(BAR(F2 + p), (par >> p) & 1);
            KB(32 + n);
            if (n == 9 && wu == 0) ST(5);
            par ^= 1u << p;
            g2_issue(p, n == 8);
            if (n1 == 16 && n == 15 && wg == 0) nb_arrive<NB_LEAD>(256);
            wg_wait<1>();
            if (n > nrel) release(E2 + pp);
            pp = p; if (++p == 5) p = 0;
          }
        };
        g2_loop(0, COVER, 0);
        attend(1, [&]() { wg_wait<0>(); release(E2 + COVER - 1); mbar_wait(BAR(F2 + COVER), (par >> COVER) & 1); },
               [&]() { KB(32 + COVER); g2_issue(COVER, false);
                       mbar_wait(BAR(F2 + COVER + 1), (par >> (COVER + 1)) & 1);
                       KB(33 + COVER); g2_issue(COVER + 1, false); });
        wg_wait<1>(); release(E2 + COVER);
        par ^= 3u << COVER; pp = COVER + 1; p = (COVER + 2) % 5;
        TS(30 + 32 * L);
        {
          const bf16* bp = P.b2 + (128 * opq(i) + 16 * wu + ((fresh_tid() & 31) >> 2));
          asm volatile("ld.global.nc.u16 %0, [%1];" : "=h"(b2a) : "l"(bp));
          asm volatile("ld.global.nc.u16 %0, [%1];" : "=h"(b2b) : "l"(bp + 8));
        }
        TS2(14 + 32 * L);
        {
          GEOM;
          e2p = stat_slot(); e2s = stat_src();
          e2g = gHB + (opq(j) * 32 + 2 * i) * 16384 + w * 2048 + lane * 16;
          e2h = sb + OFF_X + wg * 16384 + (16 * w + lr) * 128 + ((lt ^ l7) << 4);
          asm volatile("" : "+l"(e2p), "+l"(e2s), "+l"(e2g), "+r"(e2h));
        }
        g2_loop(COVER + 2, 16 - LEAD2, 0);
        if (wg == 1) { wg_wait<0>(); release(E2 + pp); nb_sync<NB_LEAD>(256); }
        g2_loop(16 - LEAD2, 16, wg == 1 ? 16 - LEAD2 : 0);
        wg_wait<0>();
        release(E2 + 0);
        fence_regs(xa);
      }
      TS(5 + 32 * L);
      if (wu == 0) ST(8);
      {
        GEOM;
        const uint32_t tg = 2 * (tag + 1) + 1;
        float s0 = 0.f, s1 = 0.f, s2 = 0.f, s3 = 0.f, q0 = 0.f, q1 = 0.f, q2 = 0.f, q3 = 0.f;
#pragma unroll
        for (int t = 0; t < 16; t++) {
          s0 += xa[4 * t]; s1 += xa[4 * t + 1]; s2 += xa[4 * t + 2]; s3 += xa[4 * t + 3];
          q0 = fmaf(xa[4 * t], xa[4 * t], q0); q1 = fmaf(xa[4 * t + 1], xa[4 * t + 1], q1);
          q2 = fmaf(xa[4 * t + 2], xa[4 * t + 2], q2); q3 = fmaf(xa[4 * t + 3], xa[4 * t + 3], q3);
        }
        const float sm = stat_publish(e2p, s0 + s1, q0 + q1, s2 + s3, q2 + q3, tg);
        const uint32_t t0 = clock32();
        TS2(13 + 32 * L);
        const float pv0 = __shfl_sync(0xffffffffu, sm, 4 * l7) * (1.f / 128), pv1 = __shfl_sync(0xffffffffu, sm, 4 * l7 + 1) * (1.f / 128);
        while (clock32() - t0 < STAT_CLK) {}
        stat_fetch(e2s);
        wg_fence();
        wgmma_rs_224z(acc3, q == 0 ? 0x3f80u : 0u, q == 0 ? 0x3f80u : 0u, 0u, 0u, mkdesc_vec(sb + OFF_B1, 16));
        wg_commit();
        stat_await([&]() { return e2s; }, tg);
        float r0, m0, r1, m1;
        {
          float mean0, var0, mean1, var1;
          stat_combine(sv0[0], sv0[1], sv1[0], sv1[1], pv0, mean0, var0); stat_combine(sv0[2], sv0[3], sv1[2], sv1[3], pv1, mean1, var1);
          mean0 = __shfl_sync(0xffffffffu, mean0, g); var0 = __shfl_sync(0xffffffffu, var0, g);
          mean1 = __shfl_sync(0xffffffffu, mean1, g); var1 = __shfl_sync(0xffffffffu, var1, g);
          r0 = 0.5f * rsq(fmaf(var0 + 1e-5f, 1e-5f, var0)); r1 = 0.5f * rsq(fmaf(var1 + 1e-5f, 1e-5f, var1));
          m0 = -mean0 * r0; m1 = -mean1 * r1;
        }
        TS2(15 + 32 * L);
#pragma unroll
        for (int t = 0; t < 16; t += 2) {
          stsm4((e2h ^ ((t & 7) << 4)) + (t >> 3) * 8192,
                pack2(fmaf(xa[4 * t], r0, m0), fmaf(xa[4 * t + 1], r0, m0)), pack2(fmaf(xa[4 * t + 2], r1, m1), fmaf(xa[4 * t + 3], r1, m1)),
                pack2(fmaf(xa[4 * t + 4], r0, m0), fmaf(xa[4 * t + 5], r0, m0)), pack2(fmaf(xa[4 * t + 6], r1, m1), fmaf(xa[4 * t + 7], r1, m1)));
          if ((t & 7) == 6 && wg == 0) {
            __syncwarp();
            copy_out<4>(e2g + (t >> 3) * 8192, sb + OFF_X + (t >> 3) * 8192 + w * 2048 + lane * 16, 512);
          }
        }
        signal(JOB + 2 + wg);
        fence_async_smem();
        mbar_wait(BAR(F3 + 0), 0);
        nb_sync<NB_BOTH>(256);
      }
      TS(6 + 32 * L);
      auto g3_issue = [&](uint32_t a, int p) {
        const uint32_t da = sda + (a >> 4), db = sd + (slot3(p) >> 4);
        wg_fence();
        static_for<0, 4>([&](auto kk) { wgmma_224<1, 1, DI(kk.value * 2048, 8192), DI(16384 + kk.value * 2048, 8192)>(acc3, da, db); });
        wg_commit();
      };
      KB(48); g3_issue(OFF_X, 0);
      mbar_wait(BAR(F3 + 1), 0); KB(49); g3_issue(OFF_X + 16384, 1);
      sched_fence(P.zero);
      {
        const float c0 = __uint_as_float((uint32_t)b2a << 16), c1 = __uint_as_float((uint32_t)b2b << 16);
#pragma unroll
        for (int t = 0; t < 16; t++) { xa[4 * t] += c0; xa[4 * t + 1] += c0; xa[4 * t + 2] += c1; xa[4 * t + 3] += c1; }
        fence_regs(xa);
      }
      wg_wait<1>(); release(E3 + 0);
      auto g3_loop = [&](int n0, int n1, int nrel) {
#pragma unroll 1
        for (int n = n0; n < n1; n++) {
          const int p = n & 3;
          mbar_wait(BAR(F3 + p), (n >> 2) & 1);
          KB(48 + n);
          if (n == 3 && wu == 0) ST(13);
          if (n == 2 && wu == 0) ST(14);
          g3_issue(slot3(p), p);
          wg_wait<1>();
          if (n > nrel) release(E3 + ((n - 1) & 3));
        }
      };
      g3_loop(2, 29, 0);
      uint32_t ua;
      uint8_t* ug;
      {
        GEOM;
        ua = sb + OFF_X + wg * 8192 + (8 * lt + l7) * 128 + (((2 * w + ((lane >> 3) & 1)) ^ l7) << 4);
        ug = gUB + (opq(j) * 56 + 48 + m) * 16384 + r * 4096 + wg * 8192 + (lane >> 1) * 128 + (((2 * w + (lane & 1)) ^ ((lane >> 1) & 7)) << 4);
      }
      auto gelu8 = [&](int c, int k) {
        const int o = 32 * c + 8 * k;
        stsm4t(ua + (c & 1) * 16384 + k * 2048,
               pack2(gelu_half(acc3[o]), gelu_half(acc3[o + 1])), pack2(gelu_half(acc3[o + 2]), gelu_half(acc3[o + 3])),
               pack2(gelu_half(acc3[o + 4]), gelu_half(acc3[o + 5])), pack2(gelu_half(acc3[o + 6]), gelu_half(acc3[o + 7])));
      };
      {
        auto part = [&](auto p, auto half) {
          static_for<0, 4>([&](auto kk) {
            constexpr uint32_t o = slot3(p.value) + kk.value * 2048;
            if constexpr (half.value) wgmma_32<1, 1, DI(o, 8192), DI(o + 40960, 8192), 96>(acc3, sda, sd);
            else wgmma_192<1, 1, DI(o, 8192), DI(o + 16384, 8192), 0>(acc3, sda, sd);
          });
        };
        mbar_wait(BAR(RD), L);
        mbar_wait(BAR(F3 + 1), 1); mbar_wait(BAR(F3 + 2), 1);
        wg_wait<0>(); release(E3 + 0);
#pragma unroll
        for (int k = 0; k < 112; k++) { float t; asm volatile("mov.b32 %0, %1;" : "=f"(t) : "f"(acc3[k]) : "memory"); acc3[k] = t; }
        sched_fence(P.zero);
        KB(77);
        wg_fence(); part(Int<1>{}, True{}); part(Int<2>{}, True{});
        mbar_wait(BAR(F3 + 3), 1); wg_fence(); part(Int<3>{}, True{}); wg_commit();
        part(Int<1>{}, False{}); wg_commit();
        wg_wait<1>();
#pragma unroll
        for (int k = 96; k < 112; k++) asm volatile("" : "+f"(acc3[k])::"memory");
        gelu8(3, 0); gelu8(3, 1);
        __syncwarp();
        copy_out<2>(ug, sb + OFF_X + 16384 + (uint32_t)((ug - gUB) & 0x2fff), 2048);
        signal(JOB + 7);
        sched_fence(P.zero);
        KB(78);
        wg_fence(); part(Int<2>{}, False{}); wg_commit();
        wg_wait<1>(); release(E3 + 1);
        KB(79);
        part(Int<3>{}, False{}); wg_commit();
        wg_wait<1>(); release(E3 + 2);
        wg_wait<0>(); release(E3 + 3);
      }
      fence_regs(acc3);
      TS(7 + 32 * L);
      if (wu == 0) ST(16);
      auto g4_issue = [&](int p, uint32_t b) {
        const uint32_t da = sda + (slot4(p) >> 4), db = sd + (b >> 4);
        wg_fence();
        static_for<0, 4>([&](auto kk) { wgmma_128<1, 1, DI(kk.value * 2048, 8192), DI(kk.value * 2048, 8192)>(xa, da, db); });
        wg_commit();
      };
#pragma unroll
      for (int k = 0; k < 4; k++) gelu8(0, k);
      fence_async_smem();
      signal(JOB + 4);
      nb_sync<NB_BOTH>(256);
      TS(8 + 32 * L);
      static_for<0, 18>([&](auto nn) {
        constexpr int n = nn.value, p = n % 6;
        if (n == 9 || n == 17) mbar_wait(BAR(JOB + 4 + (n >> 3)), L);
        mbar_wait(BAR(F4 + p), (n / 6 + (p >= 2 ? L : 0)) & 1);
        KB(80 + n);
        if (n == 1 && wu == 0) ST(21);
        if (n == 0 && wu == 0) ST(22);
        wg_fence();
        static_for<0, 4>([&](auto kk) {
          wgmma_128<1, 1, DI(slot4(p) + kk.value * 2048, 8192), DI((n == 9 ? OFF_X + 16384 : n % 17 ? slot4(p) + 16384 : OFF_X) + kk.value * 2048, 8192)>(xa, sda, sd);
        });
        wg_commit();
        if (n) { wg_wait<1>(); release(E4 + (n + 5) % 6); }
        if (n == 8) mbar_wait(BAR(RD + 2), L);
        else if (n < 16 && !(n & 1)) sched_fence(P.zero);
        if constexpr (n < 16 && !(n & 1)) gelu8(1 + (n >> 3), (n >> 1) & 3);
        if ((n & 7) == 7) { fence_async_smem(); signal(JOB + 5 + (n >> 3)); }
      });
      {
        int p = 0, pp = 5;
        uint32_t par = L ? 0x03 : 0x3f;
        auto g4_loop = [&](int n0, int n1, int nrel) {
#pragma unroll 1
          for (int n = n0; n < n1; n++) {
            mbar_wait(BAR(F4 + p), (par >> p) & 1);
            KB(80 + n);
            par ^= 1u << p;
            g4_issue(p, slot4(p) + 16384);
            if (n1 == 56 && n == 55 && wg == 0) nb_arrive<NB_LEAD>(256);
            wg_wait<1>();
            if (n > nrel) release(E4 + pp);
            pp = p; if (++p == 6) p = 0;
          }
        };
        g4_loop(18, 56 - LEAD4, 0);
        if (wg == 1) { wg_wait<0>(); release(E4 + pp); nb_sync<NB_LEAD>(256); }
        g4_loop(56 - LEAD4, 56, wg == 1 ? 56 - LEAD4 : 0);
      }
      mbar_wait(BAR(RD + 1), L);
      wg_wait<0>();
      release(E4 + 1);
      fence_regs(xa);
      TS(9 + 32 * L);
      {
        GEOM;
#pragma unroll
        for (int t = 0; t < 16; t += 2) {
          stsm4(sb + OFF_X + (t >> 3) * 16384 + (16 * wu + lr) * 128 + ((((t & 7) + lt) ^ l7) << 4),
                pack2(xa[4 * t], xa[4 * t + 1]), pack2(xa[4 * t + 2], xa[4 * t + 3]),
                pack2(xa[4 * t + 4], xa[4 * t + 5]), pack2(xa[4 * t + 6], xa[4 * t + 7]));
          if (t == 6 && L == 0) {
            __syncwarp();
            const int o = wu * 2048 + lane * 16;
            copy_out<4>(gXB + (opq(i) * 16 + 2 * j) * 16384 + o, sb + OFF_X + o, 512);
            signal(JOB + 8);
          }
        }
        fence_async_smem();
        if (L == 0) signal(JOB + 9);
        else {
          __syncwarp();
          if (elect_one()) {
            tma2d_store(&P.out, sb + OFF_X + wu * 2048, 128 * j, 128 * i + 16 * wu);
            tma2d_store(&P.out, sb + OFF_X + 16384 + wu * 2048, 128 * j + 64, 128 * i + 16 * wu);
            bulk_commit(); bulk_wait0();
          }
          __syncwarp();
        }
        nb_sync<NB_BOTH>(256);
      }
      TS(10 + 32 * L);
      KB(136);
    }
    cluster_bar();
    TS(32);
  }
}

typedef CUresult (*EncodeFn)(CUtensorMap*, CUtensorMapDataType, cuuint32_t, void*, const cuuint64_t*, const cuuint64_t*, const cuuint32_t*,
                             const cuuint32_t*, CUtensorMapInterleave, CUtensorMapSwizzle, CUtensorMapL2promotion, CUtensorMapFloatOOBfill);

void make_map(EncodeFn enc, CUtensorMap* mp, const void* base, int rank, cuuint64_t d0, cuuint64_t d1, cuuint64_t d2, cuuint64_t s1, cuuint64_t s2,
              cuuint32_t b0, cuuint32_t b1, cuuint32_t b2) {
  cuuint64_t dims[3] = {d0, d1, d2}, strides[2] = {s1, s2};
  cuuint32_t box[3] = {b0, b1, b2}, es[3] = {1, 1, 1};
  CUresult res = enc(mp, CU_TENSOR_MAP_DATA_TYPE_BFLOAT16, rank, const_cast<void*>(base), dims, strides, box, es, CU_TENSOR_MAP_INTERLEAVE_NONE,
                     CU_TENSOR_MAP_SWIZZLE_128B, CU_TENSOR_MAP_L2_PROMOTION_L2_128B, CU_TENSOR_MAP_FLOAT_OOB_FILL_NONE);
  (void)res;
}

}

extern "C" void kernel_launch(void* const* d_in, const int* in_sizes, int n_in, void* d_out, int out_size) {
  (void)in_sizes; (void)n_in; (void)out_size;
  static EncodeFn enc = nullptr;
  if (!enc) {
    void* fn = nullptr;
    cudaDriverEntryPointQueryResult qr;
    cudaGetDriverEntryPoint("cuTensorMapEncodeTiled", &fn, cudaEnableDefault, &qr);
    enc = (EncodeFn)fn;
    cudaFuncSetAttribute(fused_kernel, cudaFuncAttributeMaxDynamicSharedMemorySize, SMEM_BYTES);
  }
  Params P;
  make_map(enc, &P.x0, d_in[0], 2, D_, S_, 1, D_ * 2, 0, 64, 128, 1);
  make_map(enc, &P.wqkv, d_in[1], 3, D_, D_, 3, 3 * D_ * 2, D_ * 2, 64, 32, 3);
  make_map(enc, &P.wo, d_in[2], 2, D_, D_, 1, D_ * 2, 0, 64, 64, 1);
  make_map(enc, &P.w1, d_in[4], 3, 64, S_, F_ / 64, F_ * 2, 128, 64, 64, 3);
  make_map(enc, &P.w1h, d_in[4], 3, 32, S_, F_ / 32, F_ * 2, 64, 64, 64, 1);
  make_map(enc, &P.w2, d_in[6], 3, 64, F_, S_ / 64, S_ * 2, 128, 64, 64, 2);
  make_map(enc, &P.out, d_out, 2, D_, S_, 1, D_ * 2, 0, 64, 16, 1);
  P.wqkv_p = (const bf16*)d_in[1];
  P.wo_p = (const bf16*)d_in[2];
  P.w1_p = (const bf16*)d_in[4];
  P.w2_p = (const bf16*)d_in[6];
  P.b1 = (const bf16*)d_in[5];
  P.b2 = (const bf16*)d_in[7];
  P.zero = 0;
  fused_kernel<<<128, 384, SMEM_BYTES>>>(P);
}
```

```cpp
#include <cuda_runtime.h>
#include <cuda_bf16.h>
#include <cuda.h>
#include <stdint.h>

namespace {

typedef __nv_bfloat16 bf16;
constexpr int S_ = 2048, D_ = 1024, F_ = 3584;

constexpr uint32_t OFF_STG  = 163840;
constexpr uint32_t OFF_X    = 196608;
constexpr uint32_t OFF_BAR  = 229376;
constexpr uint32_t OFF_CS   = OFF_BAR + 512;
constexpr uint32_t OFF_B1   = OFF_CS + 1536;
constexpr uint32_t SMEM_BYTES = OFF_B1 + 896 + 128;
constexpr int F1 = 0, E1 = 4, F2 = 8, E2 = 13, F3 = 18, E3 = 22, F4 = 26, E4 = 32;
constexpr int JOB = 38;
constexpr int RD = 48;
constexpr int XF = 54, STD = 56, STAT = 58, FOLD = 59, CSJ = 61, HALO = 62;
constexpr int NB_BOTH = 1, NB_HELP = 2, NB_INIT = 3, NB_LEAD = 4;

__host__ __device__ constexpr uint32_t slot1(int p) { return p * 40960; }
__host__ __device__ constexpr uint32_t slot2(int p) { return p * 32768; }
__host__ __device__ constexpr uint32_t slot3(int p) { return ((p + 2) & 3) * 49152; }
__host__ __device__ constexpr uint32_t slot4(int p) { return (p < 2 ? p + 4 : p - 2) * 32768; }

__device__ __align__(1024) uint8_t gXB[16 * 16 * 16384];
__device__ __align__(1024) uint8_t gOB[16 * 16 * 16384];
__device__ __align__(1024) uint8_t gHB[8 * 32 * 16384];
__device__ __align__(1024) uint8_t gUB[8 * 56 * 16384];
__device__ __align__(1024) uint2   gST[2][16][8][8][16];
__device__ __align__(1024) uint4   gHalo[2][16][8][12][32];
__device__ __align__(1024) uint32_t gAck[2][16][8][2][8];
__device__ __align__(1024) uint4   gCS[8][16][64];
__device__ __align__(1024) uint32_t gFlag[2][7][16][32];
__device__ uint32_t gEpoch;
#define TS(k)
#define TS2(k)

#define S5(k)
#define KB(k)
#define ST(k)
struct Params {
  CUtensorMap x0, wqkv, wo, w1, w1h, w2;
  uint8_t* out;
  const bf16 *wqkv_p, *wo_p, *w1_p, *w2_p, *b1, *b2;
  uint32_t zero;
};

template <int TA, int TB, uint32_t IA, uint32_t IB, int O = 0, int LEN> __device__ __forceinline__ void wgmma_32(float (&d)[LEN], uint32_t da, uint32_t db) {
  asm volatile("{\n.reg .b64 da, db;\n.reg .b32 la, lb;\nadd.u32 la, %16, %20;\nadd.u32 lb, %17, %21;\nmov.b64 da, {la, 0x40000040};\nmov.b64 db, {lb, 0x40000040};\n"
  "wgmma.mma_async.sync.aligned.m64n32k16.f32.bf16.bf16 {"
  "%0, %1, %2, %3, %4, %5, %6, %7, %8, %9, %10, %11, %12, %13, %14, %15"
  "}, da, db, 1, 1, 1, %18, %19;\n}\n"
  : "+f"(d[O + 0]), "+f"(d[O + 1]), "+f"(d[O + 2]), "+f"(d[O + 3]), "+f"(d[O + 4]), "+f"(d[O + 5]), "+f"(d[O + 6]), "+f"(d[O + 7]),
    "+f"(d[O + 8]), "+f"(d[O + 9]), "+f"(d[O + 10]), "+f"(d[O + 11]), "+f"(d[O + 12]), "+f"(d[O + 13]), "+f"(d[O + 14]), "+f"(d[O + 15])
  : "r"(da), "r"(db), "n"(TA), "n"(TB), "n"(IA), "n"(IB));
}
template <int TA, int TB, uint32_t IA, uint32_t IB, int O = 0, int LEN> __device__ __forceinline__ void wgmma_128(float (&d)[LEN], uint32_t da, uint32_t db) {
  asm volatile("{\n.reg .b64 da, db;\n.reg .b32 la, lb;\nadd.u32 la, %64, %68;\nadd.u32 lb, %65, %69;\nmov.b64 da, {la, 0x40000040};\nmov.b64 db, {lb, 0x40000040};\n"
  "wgmma.mma_async.sync.aligned.m64n128k16.f32.bf16.bf16 {"
  "%0, %1, %2, %3, %4, %5, %6, %7, %8, %9, %10, %11, %12, %13, %14, %15, "
  "%16, %17, %18, %19, %20, %21, %22, %23, %24, %25, %26, %27, %28, %29, %30, %31, "
  "%32, %33, %34, %35, %36, %37, %38, %39, %40, %41, %42, %43, %44, %45, %46, %47, "
  "%48, %49, %50, %51, %52, %53, %54, %55, %56, %57, %58, %59, %60, %61, %62, %63"
  "}, da, db, 1, 1, 1, %66, %67;\n}\n"
  : "+f"(d[O + 0]), "+f"(d[O + 1]), "+f"(d[O + 2]), "+f"(d[O + 3]), "+f"(d[O + 4]), "+f"(d[O + 5]), "+f"(d[O + 6]), "+f"(d[O + 7]),
    "+f"(d[O + 8]), "+f"(d[O + 9]), "+f"(d[O + 10]), "+f"(d[O + 11]), "+f"(d[O + 12]), "+f"(d[O + 13]), "+f"(d[O + 14]), "+f"(d[O + 15]),
    "+f"(d[O + 16]), "+f"(d[O + 17]), "+f"(d[O + 18]), "+f"(d[O + 19]), "+f"(d[O + 20]), "+f"(d[O + 21]), "+f"(d[O + 22]), "+f"(d[O + 23]),
    "+f"(d[O + 24]), "+f"(d[O + 25]), "+f"(d[O + 26]), "+f"(d[O + 27]), "+f"(d[O + 28]), "+f"(d[O + 29]), "+f"(d[O + 30]), "+f"(d[O + 31]),
    "+f"(d[O + 32]), "+f"(d[O + 33]), "+f"(d[O + 34]), "+f"(d[O + 35]), "+f"(d[O + 36]), "+f"(d[O + 37]), "+f"(d[O + 38]), "+f"(d[O + 39]),
    "+f"(d[O + 40]), "+f"(d[O + 41]), "+f"(d[O + 42]), "+f"(d[O + 43]), "+f"(d[O + 44]), "+f"(d[O + 45]), "+f"(d[O + 46]), "+f"(d[O + 47]),
    "+f"(d[O + 48]), "+f"(d[O + 49]), "+f"(d[O + 50]), "+f"(d[O + 51]), "+f"(d[O + 52]), "+f"(d[O + 53]), "+f"(d[O + 54]), "+f"(d[O + 55]),
    "+f"(d[O + 56]), "+f"(d[O + 57]), "+f"(d[O + 58]), "+f"(d[O + 59]), "+f"(d[O + 60]), "+f"(d[O + 61]), "+f"(d[O + 62]), "+f"(d[O + 63])
  : "r"(da), "r"(db), "n"(TA), "n"(TB), "n"(IA), "n"(IB));
}
template <int TA, int TB, uint32_t IA, uint32_t IB, int O = 0, int LEN> __device__ __forceinline__ void wgmma_192(float (&d)[LEN], uint32_t da, uint32_t db) {
  asm volatile("{\n.reg .b64 da, db;\n.reg .b32 la, lb;\nadd.u32 la, %96, %100;\nadd.u32 lb, %97, %101;\nmov.b64 da, {la, 0x40000040};\nmov.b64 db, {lb, 0x40000040};\n"
  "wgmma.mma_async.sync.aligned.m64n192k16.f32.bf16.bf16 {"
  "%0, %1, %2, %3, %4, %5, %6, %7, %8, %9, %10, %11, %12, %13, %14, %15, "
  "%16, %17, %18, %19, %20, %21, %22, %23, %24, %25, %26, %27, %28, %29, %30, %31, "
  "%32, %33, %34, %35, %36, %37, %38, %39, %40, %41, %42, %43, %44, %45, %46, %47, "
  "%48, %49, %50, %51, %52, %53, %54, %55, %56, %57, %58, %59, %60, %61, %62, %63, "
  "%64, %65, %66, %67, %68, %69, %70, %71, %72, %73, %74, %75, %76, %77, %78, %79, "
  "%80, %81, %82, %83, %84, %85, %86, %87, %88, %89, %90, %91, %92, %93, %94, %95"
  "}, da, db, 1, 1, 1, %98, %99;\n}\n"
  : "+f"(d[O + 0]), "+f"(d[O + 1]), "+f"(d[O + 2]), "+f"(d[O + 3]), "+f"(d[O + 4]), "+f"(d[O + 5]), "+f"(d[O + 6]), "+f"(d[O + 7]),
    "+f"(d[O + 8]), "+f"(d[O + 9]), "+f"(d[O + 10]), "+f"(d[O + 11]), "+f"(d[O + 12]), "+f"(d[O + 13]), "+f"(d[O + 14]), "+f"(d[O + 15]),
    "+f"(d[O + 16]), "+f"(d[O + 17]), "+f"(d[O + 18]), "+f"(d[O + 19]), "+f"(d[O + 20]), "+f"(d[O + 21]), "+f"(d[O + 22]), "+f"(d[O + 23]),
    "+f"(d[O + 24]), "+f"(d[O + 25]), "+f"(d[O + 26]), "+f"(d[O + 27]), "+f"(d[O + 28]), "+f"(d[O + 29]), "+f"(d[O + 30]), "+f"(d[O + 31]),
    "+f"(d[O + 32]), "+f"(d[O + 33]), "+f"(d[O + 34]), "+f"(d[O + 35]), "+f"(d[O + 36]), "+f"(d[O + 37]), "+f"(d[O + 38]), "+f"(d[O + 39]),
    "+f"(d[O + 40]), "+f"(d[O + 41]), "+f"(d[O + 42]), "+f"(d[O + 43]), "+f"(d[O + 44]), "+f"(d[O + 45]), "+f"(d[O + 46]), "+f"(d[O + 47]),
    "+f"(d[O + 48]), "+f"(d[O + 49]), "+f"(d[O + 50]), "+f"(d[O + 51]), "+f"(d[O + 52]), "+f"(d[O + 53]), "+f"(d[O + 54]), "+f"(d[O + 55]),
    "+f"(d[O + 56]), "+f"(d[O + 57]), "+f"(d[O + 58]), "+f"(d[O + 59]), "+f"(d[O + 60]), "+f"(d[O + 61]), "+f"(d[O + 62]), "+f"(d[O + 63]),
    "+f"(d[O + 64]), "+f"(d[O + 65]), "+f"(d[O + 66]), "+f"(d[O + 67]), "+f"(d[O + 68]), "+f"(d[O + 69]), "+f"(d[O + 70]), "+f"(d[O + 71]),
    "+f"(d[O + 72]), "+f"(d[O + 73]), "+f"(d[O + 74]), "+f"(d[O + 75]), "+f"(d[O + 76]), "+f"(d[O + 77]), "+f"(d[O + 78]), "+f"(d[O + 79]),
    "+f"(d[O + 80]), "+f"(d[O + 81]), "+f"(d[O + 82]), "+f"(d[O + 83]), "+f"(d[O + 84]), "+f"(d[O + 85]), "+f"(d[O + 86]), "+f"(d[O + 87]),
    "+f"(d[O + 88]), "+f"(d[O + 89]), "+f"(d[O + 90]), "+f"(d[O + 91]), "+f"(d[O + 92]), "+f"(d[O + 93]), "+f"(d[O + 94]), "+f"(d[O + 95])
  : "r"(da), "r"(db), "n"(TA), "n"(TB), "n"(IA), "n"(IB));
}
template <int TA, int TB, uint32_t IA, uint32_t IB, int O = 0, int LEN> __device__ __forceinline__ void wgmma_192z(float (&d)[LEN], uint32_t da, uint32_t db) {
  asm volatile("{\n.reg .b64 da, db;\n.reg .b32 la, lb;\nadd.u32 la, %96, %100;\nadd.u32 lb, %97, %101;\nmov.b64 da, {la, 0x40000040};\nmov.b64 db, {lb, 0x40000040};\n"
  "wgmma.mma_async.sync.aligned.m64n192k16.f32.bf16.bf16 {"
  "%0, %1, %2, %3, %4, %5, %6, %7, %8, %9, %10, %11, %12, %13, %14, %15, "
  "%16, %17, %18, %19, %20, %21, %22, %23, %24, %25, %26, %27, %28, %29, %30, %31, "
  "%32, %33, %34, %35, %36, %37, %38, %39, %40, %41, %42, %43, %44, %45, %46, %47, "
  "%48, %49, %50, %51, %52, %53, %54, %55, %56, %57, %58, %59, %60, %61, %62, %63, "
  "%64, %65, %66, %67, %68, %69, %70, %71, %72, %73, %74, %75, %76, %77, %78, %79, "
  "%80, %81, %82, %83, %84, %85, %86, %87, %88, %89, %90, %91, %92, %93, %94, %95"
  "}, da, db, 0, 1, 1, %98, %99;\n}\n"
  : "=f"(d[O + 0]), "=f"(d[O + 1]), "=f"(d[O + 2]), "=f"(d[O + 3]), "=f"(d[O + 4]), "=f"(d[O + 5]), "=f"(d[O + 6]), "=f"(d[O + 7]),
    "=f"(d[O + 8]), "=f"(d[O + 9]), "=f"(d[O + 10]), "=f"(d[O + 11]), "=f"(d[O + 12]), "=f"(d[O + 13]), "=f"(d[O + 14]), "=f"(d[O + 15]),
    "=f"(d[O + 16]), "=f"(d[O + 17]), "=f"(d[O + 18]), "=f"(d[O + 19]), "=f"(d[O + 20]), "=f"(d[O + 21]), "=f"(d[O + 22]), "=f"(d[O + 23]),
    "=f"(d[O + 24]), "=f"(d[O + 25]), "=f"(d[O + 26]), "=f"(d[O + 27]), "=f"(d[O + 28]), "=f"(d[O + 29]), "=f"(d[O + 30]), "=f"(d[O + 31]),
    "=f"(d[O + 32]), "=f"(d[O + 33]), "=f"(d[O + 34]), "=f"(d[O + 35]), "=f"(d[O + 36]), "=f"(d[O + 37]), "=f"(d[O + 38]), "=f"(d[O + 39]),
    "=f"(d[O + 40]), "=f"(d[O + 41]), "=f"(d[O + 42]), "=f"(d[O + 43]), "=f"(d[O + 44]), "=f"(d[O + 45]), "=f"(d[O + 46]), "=f"(d[O + 47]),
    "=f"(d[O + 48]), "=f"(d[O + 49]), "=f"(d[O + 50]), "=f"(d[O + 51]), "=f"(d[O + 52]), "=f"(d[O + 53]), "=f"(d[O + 54]), "=f"(d[O + 55]),
    "=f"(d[O + 56]), "=f"(d[O + 57]), "=f"(d[O + 58]), "=f"(d[O + 59]), "=f"(d[O + 60]), "=f"(d[O + 61]), "=f"(d[O + 62]), "=f"(d[O + 63]),
    "=f"(d[O + 64]), "=f"(d[O + 65]), "=f"(d[O + 66]), "=f"(d[O + 67]), "=f"(d[O + 68]), "=f"(d[O + 69]), "=f"(d[O + 70]), "=f"(d[O + 71]),
    "=f"(d[O + 72]), "=f"(d[O + 73]), "=f"(d[O + 74]), "=f"(d[O + 75]), "=f"(d[O + 76]), "=f"(d[O + 77]), "=f"(d[O + 78]), "=f"(d[O + 79]),
    "=f"(d[O + 80]), "=f"(d[O + 81]), "=f"(d[O + 82]), "=f"(d[O + 83]), "=f"(d[O + 84]), "=f"(d[O + 85]), "=f"(d[O + 86]), "=f"(d[O + 87]),
    "=f"(d[O + 88]), "=f"(d[O + 89]), "=f"(d[O + 90]), "=f"(d[O + 91]), "=f"(d[O + 92]), "=f"(d[O + 93]), "=f"(d[O + 94]), "=f"(d[O + 95])
  : "r"(da), "r"(db), "n"(TA), "n"(TB), "n"(IA), "n"(IB));
}
template <int TA, int TB, uint32_t IA, uint32_t IB, int O = 0, int LEN> __device__ __forceinline__ void wgmma_224(float (&d)[LEN], uint32_t da, uint32_t db) {
  asm volatile("{\n.reg .b64 da, db;\n.reg .b32 la, lb;\nadd.u32 la, %112, %116;\nadd.u32 lb, %113, %117;\nmov.b64 da, {la, 0x40000040};\nmov.b64 db, {lb, 0x40000040};\n"
  "wgmma.mma_async.sync.aligned.m64n224k16.f32.bf16.bf16 {"
  "%0, %1, %2, %3, %4, %5, %6, %7, %8, %9, %10, %11, %12, %13, %14, %15, "
  "%16, %17, %18, %19, %20, %21, %22, %23, %24, %25, %26, %27, %28, %29, %30, %31, "
  "%32, %33, %34, %35, %36, %37, %38, %39, %40, %41, %42, %43, %44, %45, %46, %47, "
  "%48, %49, %50, %51, %52, %53, %54, %55, %56, %57, %58, %59, %60, %61, %62, %63, "
  "%64, %65, %66, %67, %68, %69, %70, %71, %72, %73, %74, %75, %76, %77, %78, %79, "
  "%80, %81, %82, %83, %84, %85, %86, %87, %88, %89, %90, %91, %92, %93, %94, %95, "
  "%96, %97, %98, %99, %100, %101, %102, %103, %104, %105, %106, %107, %108, %109, %110, %111"
  "}, da, db, 1, 1, 1, %114, %115;\n}\n"
  : "+f"(d[O + 0]), "+f"(d[O + 1]), "+f"(d[O + 2]), "+f"(d[O + 3]), "+f"(d[O + 4]), "+f"(d[O + 5]), "+f"(d[O + 6]), "+f"(d[O + 7]),
    "+f"(d[O + 8]), "+f"(d[O + 9]), "+f"(d[O + 10]), "+f"(d[O + 11]), "+f"(d[O + 12]), "+f"(d[O + 13]), "+f"(d[O + 14]), "+f"(d[O + 15]),
    "+f"(d[O + 16]), "+f"(d[O + 17]), "+f"(d[O + 18]), "+f"(d[O + 19]), "+f"(d[O + 20]), "+f"(d[O + 21]), "+f"(d[O + 22]), "+f"(d[O + 23]),
    "+f"(d[O + 24]), "+f"(d[O + 25]), "+f"(d[O + 26]), "+f"(d[O + 27]), "+f"(d[O + 28]), "+f"(d[O + 29]), "+f"(d[O + 30]), "+f"(d[O + 31]),
    "+f"(d[O + 32]), "+f"(d[O + 33]), "+f"(d[O + 34]), "+f"(d[O + 35]), "+f"(d[O + 36]), "+f"(d[O + 37]), "+f"(d[O + 38]), "+f"(d[O + 39]),
    "+f"(d[O + 40]), "+f"(d[O + 41]), "+f"(d[O + 42]), "+f"(d[O + 43]), "+f"(d[O + 44]), "+f"(d[O + 45]), "+f"(d[O + 46]), "+f"(d[O + 47]),
    "+f"(d[O + 48]), "+f"(d[O + 49]), "+f"(d[O + 50]), "+f"(d[O + 51]), "+f"(d[O + 52]), "+f"(d[O + 53]), "+f"(d[O + 54]), "+f"(d[O + 55]),
    "+f"(d[O + 56]), "+f"(d[O + 57]), "+f"(d[O + 58]), "+f"(d[O + 59]), "+f"(d[O + 60]), "+f"(d[O + 61]), "+f"(d[O + 62]), "+f"(d[O + 63]),
    "+f"(d[O + 64]), "+f"(d[O + 65]), "+f"(d[O + 66]), "+f"(d[O + 67]), "+f"(d[O + 68]), "+f"(d[O + 69]), "+f"(d[O + 70]), "+f"(d[O + 71]),
    "+f"(d[O + 72]), "+f"(d[O + 73]), "+f"(d[O + 74]), "+f"(d[O + 75]), "+f"(d[O + 76]), "+f"(d[O + 77]), "+f"(d[O + 78]), "+f"(d[O + 79]),
    "+f"(d[O + 80]), "+f"(d[O + 81]), "+f"(d[O + 82]), "+f"(d[O + 83]), "+f"(d[O + 84]), "+f"(d[O + 85]), "+f"(d[O + 86]), "+f"(d[O + 87]),
    "+f"(d[O + 88]), "+f"(d[O + 89]), "+f"(d[O + 90]), "+f"(d[O + 91]), "+f"(d[O + 92]), "+f"(d[O + 93]), "+f"(d[O + 94]), "+f"(d[O + 95]),
    "+f"(d[O + 96]), "+f"(d[O + 97]), "+f"(d[O + 98]), "+f"(d[O + 99]), "+f"(d[O + 100]), "+f"(d[O + 101]), "+f"(d[O + 102]), "+f"(d[O + 103]),
    "+f"(d[O + 104]), "+f"(d[O + 105]), "+f"(d[O + 106]), "+f"(d[O + 107]), "+f"(d[O + 108]), "+f"(d[O + 109]), "+f"(d[O + 110]), "+f"(d[O + 111])
  : "r"(da), "r"(db), "n"(TA), "n"(TB), "n"(IA), "n"(IB));
}
__device__ __forceinline__ void wgmma_rs_192(float (&d)[96], uint32_t a0, uint32_t a1, uint32_t a2, uint32_t a3, uint64_t db) {
  asm volatile("wgmma.mma_async.sync.aligned.m64n192k16.f32.bf16.bf16 {"
  "%0, %1, %2, %3, %4, %5, %6, %7, %8, %9, %10, %11, %12, %13, %14, %15, "
  "%16, %17, %18, %19, %20, %21, %22, %23, %24, %25, %26, %27, %28, %29, %30, %31, "
  "%32, %33, %34, %35, %36, %37, %38, %39, %40, %41, %42, %43, %44, %45, %46, %47, "
  "%48, %49, %50, %51, %52, %53, %54, %55, %56, %57, %58, %59, %60, %61, %62, %63, "
  "%64, %65, %66, %67, %68, %69, %70, %71, %72, %73, %74, %75, %76, %77, %78, %79, "
  "%80, %81, %82, %83, %84, %85, %86, %87, %88, %89, %90, %91, %92, %93, %94, %95"
  "}, {%96, %97, %98, %99}, %100, 1, 1, 1, 1;\n"
  : "+f"(d[0]), "+f"(d[1]), "+f"(d[2]), "+f"(d[3]), "+f"(d[4]), "+f"(d[5]), "+f"(d[6]), "+f"(d[7]),
    "+f"(d[8]), "+f"(d[9]), "+f"(d[10]), "+f"(d[11]), "+f"(d[12]), "+f"(d[13]), "+f"(d[14]), "+f"(d[15]),
    "+f"(d[16]), "+f"(d[17]), "+f"(d[18]), "+f"(d[19]), "+f"(d[20]), "+f"(d[21]), "+f"(d[22]), "+f"(d[23]),
    "+f"(d[24]), "+f"(d[25]), "+f"(d[26]), "+f"(d[27]), "+f"(d[28]), "+f"(d[29]), "+f"(d[30]), "+f"(d[31]),
    "+f"(d[32]), "+f"(d[33]), "+f"(d[34]), "+f"(d[35]), "+f"(d[36]), "+f"(d[37]), "+f"(d[38]), "+f"(d[39]),
    "+f"(d[40]), "+f"(d[41]), "+f"(d[42]), "+f"(d[43]), "+f"(d[44]), "+f"(d[45]), "+f"(d[46]), "+f"(d[47]),
    "+f"(d[48]), "+f"(d[49]), "+f"(d[50]), "+f"(d[51]), "+f"(d[52]), "+f"(d[53]), "+f"(d[54]), "+f"(d[55]),
    "+f"(d[56]), "+f"(d[57]), "+f"(d[58]), "+f"(d[59]), "+f"(d[60]), "+f"(d[61]), "+f"(d[62]), "+f"(d[63]),
    "+f"(d[64]), "+f"(d[65]), "+f"(d[66]), "+f"(d[67]), "+f"(d[68]), "+f"(d[69]), "+f"(d[70]), "+f"(d[71]),
    "+f"(d[72]), "+f"(d[73]), "+f"(d[74]), "+f"(d[75]), "+f"(d[76]), "+f"(d[77]), "+f"(d[78]), "+f"(d[79]),
    "+f"(d[80]), "+f"(d[81]), "+f"(d[82]), "+f"(d[83]), "+f"(d[84]), "+f"(d[85]), "+f"(d[86]), "+f"(d[87]),
    "+f"(d[88]), "+f"(d[89]), "+f"(d[90]), "+f"(d[91]), "+f"(d[92]), "+f"(d[93]), "+f"(d[94]), "+f"(d[95])
  : "r"(a0), "r"(a1), "r"(a2), "r"(a3), "l"(db));
}
__device__ __forceinline__ void wgmma_rs_224z(float (&d)[112], uint32_t a0, uint32_t a1, uint32_t a2, uint32_t a3, uint64_t db) {
  asm volatile("wgmma.mma_async.sync.aligned.m64n224k16.f32.bf16.bf16 {"
  "%0, %1, %2, %3, %4, %5, %6, %7, %8, %9, %10, %11, %12, %13, %14, %15, "
  "%16, %17, %18, %19, %20, %21, %22, %23, %24, %25, %26, %27, %28, %29, %30, %31, "
  "%32, %33, %34, %35, %36, %37, %38, %39, %40, %41, %42, %43, %44, %45, %46, %47, "
  "%48, %49, %50, %51, %52, %53, %54, %55, %56, %57, %58, %59, %60, %61, %62, %63, "
  "%64, %65, %66, %67, %68, %69, %70, %71, %72, %73, %74, %75, %76, %77, %78, %79, "
  "%80, %81, %82, %83, %84, %85, %86, %87, %88, %89, %90, %91, %92, %93, %94, %95, "
  "%96, %97, %98, %99, %100, %101, %102, %103, %104, %105, %106, %107, %108, %109, %110, %111"
  "}, {%112, %113, %114, %115}, %116, 0, 1, 1, 1;\n"
  : "=f"(d[0]), "=f"(d[1]), "=f"(d[2]), "=f"(d[3]), "=f"(d[4]), "=f"(d[5]), "=f"(d[6]), "=f"(d[7]),
    "=f"(d[8]), "=f"(d[9]), "=f"(d[10]), "=f"(d[11]), "=f"(d[12]), "=f"(d[13]), "=f"(d[14]), "=f"(d[15]),
    "=f"(d[16]), "=f"(d[17]), "=f"(d[18]), "=f"(d[19]), "=f"(d[20]), "=f"(d[21]), "=f"(d[22]), "=f"(d[23]),
    "=f"(d[24]), "=f"(d[25]), "=f"(d[26]), "=f"(d[27]), "=f"(d[28]), "=f"(d[29]), "=f"(d[30]), "=f"(d[31]),
    "=f"(d[32]), "=f"(d[33]), "=f"(d[34]), "=f"(d[35]), "=f"(d[36]), "=f"(d[37]), "=f"(d[38]), "=f"(d[39]),
    "=f"(d[40]), "=f"(d[41]), "=f"(d[42]), "=f"(d[43]), "=f"(d[44]), "=f"(d[45]), "=f"(d[46]), "=f"(d[47]),
    "=f"(d[48]), "=f"(d[49]), "=f"(d[50]), "=f"(d[51]), "=f"(d[52]), "=f"(d[53]), "=f"(d[54]), "=f"(d[55]),
    "=f"(d[56]), "=f"(d[57]), "=f"(d[58]), "=f"(d[59]), "=f"(d[60]), "=f"(d[61]), "=f"(d[62]), "=f"(d[63]),
    "=f"(d[64]), "=f"(d[65]), "=f"(d[66]), "=f"(d[67]), "=f"(d[68]), "=f"(d[69]), "=f"(d[70]), "=f"(d[71]),
    "=f"(d[72]), "=f"(d[73]), "=f"(d[74]), "=f"(d[75]), "=f"(d[76]), "=f"(d[77]), "=f"(d[78]), "=f"(d[79]),
    "=f"(d[80]), "=f"(d[81]), "=f"(d[82]), "=f"(d[83]), "=f"(d[84]), "=f"(d[85]), "=f"(d[86]), "=f"(d[87]),
    "=f"(d[88]), "=f"(d[89]), "=f"(d[90]), "=f"(d[91]), "=f"(d[92]), "=f"(d[93]), "=f"(d[94]), "=f"(d[95]),
    "=f"(d[96]), "=f"(d[97]), "=f"(d[98]), "=f"(d[99]), "=f"(d[100]), "=f"(d[101]), "=f"(d[102]), "=f"(d[103]),
    "=f"(d[104]), "=f"(d[105]), "=f"(d[106]), "=f"(d[107]), "=f"(d[108]), "=f"(d[109]), "=f"(d[110]), "=f"(d[111])
  : "r"(a0), "r"(a1), "r"(a2), "r"(a3), "l"(db));
}

__device__ __forceinline__ uint32_t smem_u32(const void* p) { return (uint32_t)__cvta_generic_to_shared(p); }
__device__ __forceinline__ void mbar_init(uint32_t bar, uint32_t cnt) { asm volatile("mbarrier.init.shared::cta.b64 [%0], %1;" ::"r"(bar), "r"(cnt) : "memory"); }
__device__ __forceinline__ void mbar_expect(uint32_t bar, uint32_t bytes) { asm volatile("mbarrier.arrive.expect_tx.shared::cta.b64 _, [%0], %1;" ::"r"(bar), "r"(bytes) : "memory"); }
__device__ __forceinline__ void mbar_arrive(uint32_t bar) { asm volatile("mbarrier.arrive.shared::cta.b64 _, [%0];" ::"r"(bar) : "memory"); }
__device__ __forceinline__ void mbar_arrive_cl(uint32_t cbar) { asm volatile("mbarrier.arrive.shared::cluster.b64 _, [%0];" ::"r"(cbar) : "memory"); }
__device__ __forceinline__ uint32_t mapa(uint32_t a, uint32_t cta) { uint32_t r; asm("mapa.shared::cluster.u32 %0, %1, %2;" : "=r"(r) : "r"(a), "r"(cta)); return r; }
__device__ __forceinline__ void mbar_wait(uint32_t bar, uint32_t parity) {
  asm volatile("{\n.reg .pred p;\n.reg .u32 n;\nmov.u32 n, 0;\n"
    "LAB_WAIT:\n"
    "mbarrier.try_wait.parity.shared::cta.b64 p, [%0], %1;\n"
    "@p bra LAB_DONE;\n"
    "add.u32 n, n, 1;\n"
    "setp.lt.u32 p, n, 2000000;\n"
    "@p bra LAB_WAIT;\n"
    "trap;\n"
    "LAB_DONE:\n}\n" ::"r"(bar), "r"(parity) : "memory");
}
constexpr uint32_t SPIN_MAX = 2000000;
__device__ __forceinline__ void tma2d(uint32_t dst, const CUtensorMap* m, uint32_t bar, int c0, int c1) {
  asm volatile("cp.async.bulk.tensor.2d.shared::cluster.global.mbarrier::complete_tx::bytes [%0], [%1, {%3, %4}], [%2];"
    ::"r"(dst), "l"(m), "r"(bar), "r"(c0), "r"(c1) : "memory");
}
__device__ __forceinline__ void tma2d_mc(uint32_t dst, const CUtensorMap* m, uint32_t bar, int c0, int c1) {
  asm volatile("cp.async.bulk.tensor.2d.shared::cluster.global.mbarrier::complete_tx::bytes.multicast::cluster [%0], [%1, {%3, %4}], [%2], %5;"
    ::"r"(dst), "l"(m), "r"(bar), "r"(c0), "r"(c1), "h"((uint16_t)3) : "memory");
}
__device__ __forceinline__ void tma3d(uint32_t dst, const CUtensorMap* m, uint32_t bar, int c0, int c1, int c2) {
  asm volatile("cp.async.bulk.tensor.3d.shared::cluster.global.mbarrier::complete_tx::bytes [%0], [%1, {%3, %4, %5}], [%2];"
    ::"r"(dst), "l"(m), "r"(bar), "r"(c0), "r"(c1), "r"(c2) : "memory");
}
__device__ __forceinline__ void tma3d_mc(uint32_t dst, const CUtensorMap* m, uint32_t bar, int c0, int c1, int c2) {
  asm volatile("cp.async.bulk.tensor.3d.shared::cluster.global.mbarrier::complete_tx::bytes.multicast::cluster [%0], [%1, {%3, %4, %5}], [%2], %6;"
    ::"r"(dst), "l"(m), "r"(bar), "r"(c0), "r"(c1), "r"(c2), "h"((uint16_t)3) : "memory");
}
__device__ __forceinline__ void bulk_ld(uint32_t dst, const void* src, uint32_t bytes, uint32_t bar) {
  asm volatile("cp.async.bulk.shared::cluster.global.mbarrier::complete_tx::bytes [%0], [%1], %2, [%3];" ::"r"(dst), "l"(src), "r"(bytes), "r"(bar) : "memory");
}
__device__ __forceinline__ void bulk_ld_mc(uint32_t dst, const void* src, uint32_t bytes, uint32_t bar) {
  asm volatile("cp.async.bulk.shared::cluster.global.mbarrier::complete_tx::bytes.multicast::cluster [%0], [%1], %2, [%3], %4;"
    ::"r"(dst), "l"(src), "r"(bytes), "r"(bar), "h"((uint16_t)3) : "memory");
}
__device__ __forceinline__ void bulk_st(void* dst, uint32_t src, uint32_t bytes) {
  asm volatile("cp.async.bulk.global.shared::cta.bulk_group [%0], [%1], %2;" ::"l"(dst), "r"(src), "r"(bytes) : "memory");
}
__device__ __forceinline__ void bulk_commit() { asm volatile("cp.async.bulk.commit_group;" ::: "memory"); }
__device__ __forceinline__ void bulk_wait0() { asm volatile("cp.async.bulk.wait_group 0;" ::: "memory"); }
__device__ __forceinline__ void fence_async_smem() { asm volatile("fence.proxy.async.shared::cta;" ::: "memory"); }
__device__ __forceinline__ void wg_fence() { asm volatile("wgmma.fence.sync.aligned;" ::: "memory"); }
__device__ __forceinline__ void wg_commit() { asm volatile("wgmma.commit_group.sync.aligned;" ::: "memory"); }
template <int N> __device__ __forceinline__ void wg_wait() { asm volatile("wgmma.wait_group.sync.aligned %0;" ::"n"(N) : "memory"); }
template <int R> __device__ __forceinline__ void reg_alloc() { asm volatile("setmaxnreg.inc.sync.aligned.u32 %0;" ::"n"(R)); }
template <int R> __device__ __forceinline__ void reg_dealloc() { asm volatile("setmaxnreg.dec.sync.aligned.u32 %0;" ::"n"(R)); }
__device__ __forceinline__ void cluster_bar() { asm volatile("barrier.cluster.arrive.relaxed;\nbarrier.cluster.wait;" ::: "memory"); }
template <int ID> __device__ __forceinline__ void nb_sync(int n) { asm volatile("barrier.sync %0, %1;" ::"n"(ID), "r"(n) : "memory"); }
template <int ID> __device__ __forceinline__ void nb_arrive(int n) { asm volatile("barrier.arrive %0, %1;" ::"n"(ID), "r"(n) : "memory"); }
__device__ __forceinline__ int fresh_tid() { int t; asm volatile("mov.u32 %0, %%tid.x;" : "=r"(t)); return t; }
__device__ __forceinline__ void sched_fence(uint32_t z) { asm volatile("{\n.reg .pred p;\nsetp.ne.u32 p, %0, 0;\nLAB_S:\n@p nanosleep.u32 0;\n@p bra LAB_S;\n}\n" ::"r"(z) : "memory"); }
__device__ __forceinline__ float rsq(float x) { float y; asm("rsqrt.approx.ftz.f32 %0, %1;" : "=f"(y) : "f"(x)); return y; }
__device__ __forceinline__ int opq(int v) { asm volatile("" : "+r"(v)); return v; }
template <int V> struct Int { static constexpr int value = V; };
struct True { static constexpr bool value = true; };
struct False { static constexpr bool value = false; };
template <int N> __device__ __forceinline__ void fence_regs(float (&d)[N]) {
#pragma unroll
  for (int i = 0; i < N; i++) asm volatile("" : "+f"(d[i])::"memory");
}
__host__ __device__ constexpr uint32_t DI(uint32_t off, uint32_t lbo) { return (off >> 4) + ((lbo >> 4) << 16); }
template <int K, int N, class F> __device__ __forceinline__ void static_for(F f) { if constexpr (K < N) { f(Int<K>{}); static_for<K + 1, N>(f); } }
__device__ __forceinline__ uint64_t mkdesc_vec(uint32_t addr, uint32_t sbo) { return (uint64_t)((addr & 0x3FFFF) >> 4) | ((uint64_t)(sbo >> 4) << 32); }
__device__ __forceinline__ void sts16(uint32_t a, uint32_t v) { asm volatile("st.shared.u16 [%0], %1;" ::"r"(a), "h"((uint16_t)v) : "memory"); }
__device__ __forceinline__ uint32_t pack2(float lo, float hi) { uint32_t r; asm("cvt.rn.bf16x2.f32 %0, %1, %2;" : "=r"(r) : "f"(hi), "f"(lo)); return r; }
__device__ __forceinline__ float bf_lo(uint32_t v) { return __uint_as_float(v << 16); }
__device__ __forceinline__ float bf_hi(uint32_t v) { return __uint_as_float(v & 0xffff0000u); }
__device__ __forceinline__ void stsm4(uint32_t a, uint32_t r0, uint32_t r1, uint32_t r2, uint32_t r3) {
  asm volatile("stmatrix.sync.aligned.m8n8.x4.shared.b16 [%0], {%1, %2, %3, %4};" ::"r"(a), "r"(r0), "r"(r1), "r"(r2), "r"(r3) : "memory");
}
__device__ __forceinline__ void stsm4t(uint32_t a, uint32_t r0, uint32_t r1, uint32_t r2, uint32_t r3) {
  asm volatile("stmatrix.sync.aligned.m8n8.x4.trans.shared.b16 [%0], {%1, %2, %3, %4};" ::"r"(a), "r"(r0), "r"(r1), "r"(r2), "r"(r3) : "memory");
}
__device__ __forceinline__ void ldsm4(uint32_t a, uint32_t& r0, uint32_t& r1, uint32_t& r2, uint32_t& r3) {
  asm volatile("ldmatrix.sync.aligned.m8n8.x4.shared.b16 {%0, %1, %2, %3}, [%4];" : "=r"(r0), "=r"(r1), "=r"(r2), "=r"(r3) : "r"(a) : "memory");
}
__device__ __forceinline__ void ldsm4t(uint32_t a, uint32_t& r0, uint32_t& r1, uint32_t& r2, uint32_t& r3) {
  asm volatile("ldmatrix.sync.aligned.m8n8.x4.trans.shared.b16 {%0, %1, %2, %3}, [%4];" : "=r"(r0), "=r"(r1), "=r"(r2), "=r"(r3) : "r"(a) : "memory");
}
__device__ __forceinline__ void mma16816(float (&c)[4], uint32_t a0, uint32_t a1, uint32_t a2, uint32_t a3, uint32_t b0, uint32_t b1) {
  asm volatile("mma.sync.aligned.m16n8k16.row.col.f32.bf16.bf16.f32 {%0, %1, %2, %3}, {%4, %5, %6, %7}, {%8, %9}, {%10, %11, %12, %13};"
    : "=f"(c[0]), "=f"(c[1]), "=f"(c[2]), "=f"(c[3]) : "r"(a0), "r"(a1), "r"(a2), "r"(a3), "r"(b0), "r"(b1), "f"(c[0]), "f"(c[1]), "f"(c[2]), "f"(c[3]));
}
__device__ __forceinline__ void sts128(uint32_t a, uint32_t r0, uint32_t r1, uint32_t r2, uint32_t r3) {
  asm volatile("st.shared.v4.b32 [%0], {%1, %2, %3, %4};" ::"r"(a), "r"(r0), "r"(r1), "r"(r2), "r"(r3) : "memory");
}
__device__ __forceinline__ void lds128(uint32_t a, uint32_t& r0, uint32_t& r1, uint32_t& r2, uint32_t& r3) {
  asm volatile("ld.shared.v4.b32 {%0, %1, %2, %3}, [%4];" : "=r"(r0), "=r"(r1), "=r"(r2), "=r"(r3) : "r"(a) : "memory");
}
__device__ __forceinline__ float2 lds64f(uint32_t a) { float2 v; asm volatile("ld.shared.v2.f32 {%0, %1}, [%2];" : "=f"(v.x), "=f"(v.y) : "r"(a) : "memory"); return v; }
__device__ __forceinline__ float4 lds128f(uint32_t a) { float4 v; asm volatile("ld.shared.v4.f32 {%0, %1, %2, %3}, [%4];" : "=f"(v.x), "=f"(v.y), "=f"(v.z), "=f"(v.w) : "r"(a) : "memory"); return v; }
__device__ __forceinline__ void sts64f(uint32_t a, float x, float y) { asm volatile("st.shared.v2.f32 [%0], {%1, %2};" ::"r"(a), "f"(x), "f"(y) : "memory"); }
__device__ __forceinline__ float lds32f(uint32_t a) { float v; asm volatile("ld.shared.f32 %0, [%1];" : "=f"(v) : "r"(a) : "memory"); return v; }
__device__ __forceinline__ void sts32f(uint32_t a, float x) { asm volatile("st.shared.f32 [%0], %1;" ::"r"(a), "f"(x) : "memory"); }
__device__ __forceinline__ void stat_st(uint2* p, float sum, float sq, uint32_t tag, bool on) {
  const float mean = sum * (1.f / 128), m2 = fmaxf(fmaf(-mean, sum, sq), 0.f);
  const uint32_t a = ((__float_as_uint(mean) + 8u) & ~15u) | (tag & 15u), b = ((__float_as_uint(m2) + 8u) & ~15u) | (tag & 15u);
  asm volatile("{\n.reg .b64 x;\n.reg .pred p;\nsetp.ne.u32 p, %3, 0;\nmov.b64 x, {%1, %2};\n@p st.relaxed.gpu.global.b64 [%0], x;\n}\n" ::"l"(p), "r"(a), "r"(b), "r"((uint32_t)on) : "memory");
}
__device__ __forceinline__ void stat_ld2(const uint2* p, uint32_t (&v)[4]) {
  asm volatile("{\n.reg .b64 x, y;\nld.relaxed.gpu.global.v2.b64 {x, y}, [%4];\nmov.b64 {%0, %1}, x;\nmov.b64 {%2, %3}, y;\n}\n"
    : "=r"(v[0]), "=r"(v[1]), "=r"(v[2]), "=r"(v[3]) : "l"(p) : "memory");
}
__device__ __forceinline__ float untag(uint32_t v) { return __uint_as_float(v & ~15u); }
__device__ __forceinline__ void ll_st3(uint4* p, uint32_t a, uint32_t b, uint32_t c, uint32_t tag) {
  asm volatile("{\n.reg .b64 x, y;\n.reg .b128 z;\nmov.b64 x, {%1, %2};\nmov.b64 y, {%3, %4};\nmov.b128 z, {x, y};\nst.relaxed.gpu.global.b128 [%0], z;\n}\n"
    ::"l"(p), "r"(a), "r"(b), "r"(c), "r"(tag) : "memory");
}
__device__ __forceinline__ uint32_t ll_ld3(const uint4* p, uint32_t& a, uint32_t& b, uint32_t& c, uint32_t tag) {
  uint32_t t;
  asm volatile("{\n.reg .b64 x, y;\n.reg .b128 z;\nld.relaxed.gpu.global.b128 z, [%4];\nmov.b128 {x, y}, z;\nmov.b64 {%0, %1}, x;\nmov.b64 {%2, %3}, y;\n}\n"
    : "=r"(a), "=r"(b), "=r"(c), "=r"(t) : "l"(p) : "memory");
  return t ^ tag;
}
__device__ __forceinline__ void halo_send(uint4* p, uint32_t a, const uint32_t (&tg)[6]) {
  asm volatile("{\n.reg .b64 x<6>, y<6>, w<2>;\n.reg .b32 c<4>;\n.reg .b128 z<6>;\n"
    "ld.shared.b64 w0, [%1+1536];\nld.shared.b64 w1, [%1+1792];\n"
    "ld.shared.b64 x0, [%1];\nld.shared.b64 x1, [%1+256];\nld.shared.b64 x2, [%1+512];\n"
    "ld.shared.b64 x3, [%1+768];\nld.shared.b64 x4, [%1+1024];\nld.shared.b64 x5, [%1+1280];\n"
    "mov.b64 {c0, c1}, w0;\nmov.b64 {c2, c3}, w1;\n"
    "mov.b64 y0, {c0, %2};\nmov.b64 y1, {c1, %3};\nmov.b64 y2, {c2, %4};\nmov.b64 y3, {c3, %5};\nmov.b64 y4, {%6, %6};\nmov.b64 y5, {%7, %7};\n"
    "mov.b128 z0, {x0, y0};\nmov.b128 z1, {x1, y1};\nmov.b128 z2, {x2, y2};\nmov.b128 z3, {x3, y3};\nmov.b128 z4, {x4, y4};\nmov.b128 z5, {x5, y5};\n"
    "st.relaxed.gpu.global.b128 [%0], z0;\nst.relaxed.gpu.global.b128 [%0+512], z1;\nst.relaxed.gpu.global.b128 [%0+1024], z2;\n"
    "st.relaxed.gpu.global.b128 [%0+1536], z3;\nst.relaxed.gpu.global.b128 [%0+2048], z4;\nst.relaxed.gpu.global.b128 [%0+2560], z5;\n}\n"
    ::"l"(p), "r"(a), "r"(tg[0]), "r"(tg[1]), "r"(tg[2]), "r"(tg[3]), "r"(tg[4]), "r"(tg[5]) : "memory");
}
template <int N> __device__ __forceinline__ void copy_out(uint8_t* dst, uint32_t src, int stride) {
  uint4 v[N];
#pragma unroll
  for (int k = 0; k < N; k++) lds128(src + k * stride, v[k].x, v[k].y, v[k].z, v[k].w);
#pragma unroll
  for (int k = 0; k < N; k++) asm volatile("st.global.v4.b32 [%0], {%1, %2, %3, %4};" ::"l"(dst + k * stride), "r"(v[k].x), "r"(v[k].y), "r"(v[k].z), "r"(v[k].w) : "memory");
}
__device__ __forceinline__ void warp_store(uint8_t* dst, uint32_t src, int bytes, uint32_t delay, uint32_t pace) {
  __nanosleep(delay);
#pragma unroll 1
  for (int o = 0; o < bytes; o += 2048) {
    if (pace) __nanosleep(pace);
    uint4 v[4];
#pragma unroll
    for (int k = 0; k < 4; k++) lds128(src + o + k * 512, v[k].x, v[k].y, v[k].z, v[k].w);
#pragma unroll
    for (int k = 0; k < 4; k++) asm volatile("st.global.v4.b32 [%0], {%1, %2, %3, %4};" ::"l"(dst + o + k * 512), "r"(v[k].x), "r"(v[k].y), "r"(v[k].z), "r"(v[k].w) : "memory");
  }
  __syncwarp();
}
__device__ __forceinline__ uint32_t clock32() { uint32_t t; asm volatile("mov.u32 %0, %%clock;" : "=r"(t)); return t; }
__device__ __forceinline__ void flag_set(uint32_t* p, uint32_t bit) { asm volatile("red.release.gpu.global.xor.b32 [%0], %1;" ::"l"(p), "r"(bit) : "memory"); }
__device__ __forceinline__ void flag_wait(const uint32_t* p, uint32_t inv, uint32_t need, uint32_t& ready) {
  if ((ready & need) == need) return;
  uint32_t n = 0;
  do {
    asm volatile("ld.relaxed.gpu.global.b32 %0, [%1];" : "=r"(ready) : "l"(p) : "memory");
    ready = __shfl_sync(0xffffffffu, ready, 0) ^ inv;
  } while ((ready & need) != need && ++n < SPIN_MAX);
  asm volatile("fence.acquire.gpu;\nfence.proxy.async.global;" ::: "memory");
}
__device__ __forceinline__ bool elect_one() {
  uint32_t p;
  asm volatile("{\n.reg .pred P;\nelect.sync _|P, 0xffffffff;\nselp.u32 %0, 1, 0, P;\n}\n" : "=r"(p));
  return p;
}
__device__ __forceinline__ float gelu_half(float hx) {
  const float y = hx * fmaf(hx * hx, 8.f * 0.0356774081f, 2.f * 0.7978845608f);
  float th;
  asm("tanh.approx.f32 %0, %1;" : "=f"(th) : "f"(y));
  return fmaf(hx, th, hx);
}
__device__ __forceinline__ float ex2(float x) { float y; asm("ex2.approx.ftz.f32 %0, %1;" : "=f"(y) : "f"(x)); return y; }

__device__ __forceinline__ void stat_combine(uint32_t am, uint32_t aq, uint32_t bm, uint32_t bq, float pv, float& mean, float& var) {
  const float d0 = untag(am) - pv, d1 = untag(bm) - pv;
  float s = d0 + d1, q = fmaf(fmaf(d0, d0, d1 * d1), 128.f, untag(aq) + untag(bq));
  s += __shfl_xor_sync(0xffffffffu, s, 8); q += __shfl_xor_sync(0xffffffffu, q, 8);
  s += __shfl_xor_sync(0xffffffffu, s, 16); q += __shfl_xor_sync(0xffffffffu, q, 16);
  s *= 0.125f;
  mean = pv + s;
  var = fmaxf(fmaf(-s, s, q * (1.f / D_)), 0.f);
}

__device__ __forceinline__ void attn_probs(const uint32_t* q0, const uint32_t* q1,
                                           const uint32_t* k0, const uint32_t* k1, const uint32_t* k2, const uint32_t* k3,
                                           float sc0, float sc1, float mk0, float mk1, bool e, bool zneg, const uint32_t (&sel)[3],
                                           uint32_t (&pr)[6], float (&l)[2]) {
  float s[4][4];
#pragma unroll
  for (int n = 0; n < 4; n++) {
    const uint32_t* k = n == 0 ? k0 : n == 1 ? k1 : n == 2 ? k2 : k3;
    s[n][0] = s[n][1] = n < 2 ? mk0 : 0.f; s[n][2] = s[n][3] = n < 2 ? mk1 : 0.f;
    mma16816(s[n], q0[0], q1[0], q0[1], q1[1], k[0], k[1]);
    mma16816(s[n], q0[2], q1[2], q0[3], q1[3], k[2], k[3]);
  }
  float a0 = e ? s[1][1] : s[1][0];
  float b0 = zneg ? (e ? s[0][1] : s[0][0]) : (e ? s[2][1] : s[2][0]);
  float a1 = e ? s[2][3] : s[2][2];
  float b1 = zneg ? (e ? s[1][3] : s[1][2]) : (e ? s[3][3] : s[3][2]);
  float m0 = fmaxf(a0, b0), m1 = fmaxf(a1, b1);
  m0 = fmaxf(m0, __shfl_xor_sync(0xffffffffu, m0, 1)); m1 = fmaxf(m1, __shfl_xor_sync(0xffffffffu, m1, 1));
  m0 = fmaxf(m0, __shfl_xor_sync(0xffffffffu, m0, 2)); m1 = fmaxf(m1, __shfl_xor_sync(0xffffffffu, m1, 2));
  a0 = ex2((a0 - m0) * sc0); b0 = ex2((b0 - m0) * sc0); a1 = ex2((a1 - m1) * sc1); b1 = ex2((b1 - m1) * sc1);
  l[0] = a0 + b0; l[1] = a1 + b1;
  const uint32_t p0 = pack2(a0, b0), p1 = pack2(a1, b1);
#pragma unroll
  for (int k = 0; k < 3; k++) { pr[k] = __byte_perm(p0, 0u, sel[k]); pr[3 + k] = __byte_perm(p1, 0u, sel[k]); }
}
__device__ __forceinline__ void attn_pv(const uint32_t (&pr)[6], const uint32_t* vh, const uint32_t* v, float (&o)[4][4]) {
#pragma unroll
  for (int dt = 0; dt < 4; dt++) {
    o[dt][0] = o[dt][1] = o[dt][2] = o[dt][3] = 0.f;
    mma16816(o[dt], pr[0], 0u, pr[1], pr[3], vh[2 * dt], vh[2 * dt + 1]);
    mma16816(o[dt], pr[2], pr[4], 0u, pr[5], v[2 * dt], v[2 * dt + 1]);
  }
}

#define ATT 25
#define COVER 2
#define HALO_A_NS 300
#define H1D 900
#define FO 2
#define G4GATE 1
#define PFM 7
#define PD1 3
#define PD2 5
#define PD3 3
#define PD4 5
#define FR 1
#define XG 1
#define U0D 300
#define X1D 1200
#define PACE 150
#define LEAD1 3
#define LEAD2 3
#define XLD 7
#define XST 2
#define FA 20
#define LEAD4 4
#define STAT_CLK 150
__global__ void __cluster_dims__(2, 1, 1) __launch_bounds__(384, 1) fused_kernel(const __grid_constant__ Params P) {
  extern __shared__ __align__(1024) uint8_t smem_raw[];
  const uint32_t sb = smem_u32(smem_raw);
  const uint32_t bars = sb + OFF_BAR;
  const int tid = threadIdx.x;
  if (tid == 256) S5(0);
  const int wu = __shfl_sync(0xffffffffu, tid >> 5, 0), wg = wu >> 2;
  const int r = blockIdx.x & 1, cl = blockIdx.x >> 1;
  int grp, slt;
  if (cl < 4) { grp = 0; slt = 4 + cl; }
  else if (cl < 36) { grp = (cl - 4) & 7; slt = (cl - 4) >> 3; }
  else { grp = 1 + (cl - 36) % 7; slt = 4 + (cl - 36) / 7; }
#define MAP 0
  const int m = grp, j = slt;
  const int i = 2 * m + r;
  auto BAR = [&](int k) { return bars + 8 * k; };

  auto kb1 = [&](int n) { const int h = n >= 9, t = n - 2 - 7 * h; return n < 2 ? 2 * j + n : 2 * (t + (t >= j)) + h; };
  auto first_round = [&](int u0, int u1) {
#pragma unroll 1
    for (int u = u0; u < u1; u++) {
      S5(3 + u);
      mbar_expect(BAR(F1 + u), 40960);
      tma2d(sb + slot1(u), &P.x0, BAR(F1 + u), u * 64, 128 * i);
      tma3d(sb + slot1(u) + 16384, &P.wqkv, BAR(F1 + u), 128 * j, u * 64, 0);
      tma3d(sb + slot1(u) + 28672, &P.wqkv, BAR(F1 + u), 128 * j, u * 64 + 32, 0);
    }
  };
  if (wu == 9) {
    if (elect_one()) asm volatile("prefetch.tensormap [%0];" ::"l"(&P.wqkv) : "memory");
    __syncwarp();
  } else if (wu == 8) {
    if (elect_one()) {
      S5(1);
#pragma unroll
      for (int k = 0; k < 4; k++) mbar_init(BAR(F1 + k), 1);
      asm volatile("fence.mbarrier_init.release.cluster;" ::: "memory");
      fence_async_smem();
      first_round(0, FR);
    }
    __syncwarp();
  } else if (wu == 0) {
    if (elect_one()) {
#pragma unroll
      for (int k = E1; k < 64; k++) {
        int cnt = 1;
        if (k < F2 || (k >= E2 && k < F3) || (k >= E3 && k < F4) || (k >= E4 && k < JOB) || k == JOB + 2 || k == JOB + 3) cnt = 4;
        else if ((k >= JOB && k < RD) || k == CSJ) cnt = 8;
        else if (k == RD + 1 || k == STD || k == STAT || k >= HALO) cnt = 2;
        mbar_init(BAR(k), cnt);
      }
      asm volatile("fence.mbarrier_init.release.cluster;" ::: "memory");
      fence_async_smem();
    }
    __syncwarp();
  }
  auto load_tag = [&]() { uint32_t t; asm volatile("ld.relaxed.gpu.global.u32 %0, [%1];" : "=r"(t) : "l"(&gEpoch) : "memory"); return t + 1; };
  TS(0);
  if (wu == 8) nb_arrive<NB_INIT>(384); else nb_sync<NB_INIT>(384);
  asm volatile("barrier.cluster.arrive.relaxed;" ::: "memory");

  if (wg == 2) {
    if (tid == 256) S5(2);
    reg_dealloc<40>();
    if (wu == 8) {
      if (elect_one()) first_round(FR, 4);
      __syncwarp();
    }
    asm volatile("barrier.cluster.wait;" ::: "memory");
    auto kb3 = [&](int n) { const int h = n >= 17, t = n - 2 - 15 * h; return n < 2 ? 2 * i + n : t == 14 ? 2 * (i ^ 1) + h : 2 * ((2 * m + 2 + t) & 15) + h; };
    auto v1 = [&](int L, int u) { const int u0 = L ? 2 : 10; return (u >= u0 && u < 18) ? (u < u0 + 2 ? u - u0 + 16 : u - 2) : u; };
    auto kb2 = [&](int n) { return n < 8 ? 2 * n : n == 8 ? 2 * j + 1 : 2 * (n - 9 + (n - 9 >= j)) + 1; };
    if (wu == 8) {
      const int lane = tid & 31;
      auto pf = [&](const bf16* p, bool on) { if (on) asm volatile("prefetch.global.L2 [%0];" ::"l"(p)); };

      auto k1 = [&](int L, int v) { return (L || v >= 16) ? kb1(v & 15) : v; };
      auto kb4f = [&](int n) {
        const bool own = n == 0 || n == 9 || n == 17;
        const int q = n - 10 - (n > 17), c = own ? n >> 3 : q / 15, t = q - 15 * c;
        const int ii = own ? i : t < 14 ? (2 * m + 2 + t) & 15 : i ^ 1;
        return (n >= 1 && n <= 8) ? 7 * ((m + n) & 7) + 3 : ((7 * ii + 1) >> 1) + c;
      };
      const uint32_t tab4 = kb4f(lane) | (kb4f(lane + 32) << 16);
      auto kb4 = [&](int n) { return (int)((__shfl_sync(0xffffffffu, tab4, n) >> ((n >> 1) & 16)) & 63); };
      const bf16* const q1 = P.wqkv_p + (4 * i + (lane & 3)) * 3072 + (lane >> 2) * 1024 + 128 * j;
      const bf16* const q2 = P.wo_p + (4 * i + (lane & 3)) * 1024 + (lane >> 2) * 64 + 128 * j;
      const bf16* const q3 = P.w1_p + (8 * j + (lane >> 2)) * 3584 + 64 * (7 * m + ((lane & 3) == 3 ? 3 : 4 * r + (lane & 3)));
      const bf16* const q4 = P.w2_p + (8 * j + (lane >> 1)) * 2048 + 128 * i + 64 * (lane & 1);
      auto pf1 = [&](int L, int u) { const int v = v1(L, u); pf(q1 + k1(L, v) * (64 * 3072) + 64 * (v >> 4), (PFM & 1) && lane < 12); };
      auto pf2 = [&](int n) { pf(q2 + kb2(n) * (64 * 1024), (PFM & 2) && lane < 8); };
      auto pf3 = [&](int n) { pf(q3 + kb3(n) * (64 * 3584), PFM & 4); };
      auto pf4 = [&](int n) { pf(q4 + kb4(n) * (64 * 2048), (PFM & 8) && lane < 16); };
#pragma unroll 1
      for (int u = 4; u < 4 + PD1; u++) pf1(0, u);
#pragma unroll 1
      for (int L = 0; L < 2; L++) {
#pragma unroll 1
        for (int u = L ? 0 : 4; u < 32; u++) {
          const int v = v1(L, u), p = u & 3;
          int c0 = 128 * j + 64 * (v >> 4), c1 = k1(L, v) * 64 + 32 * r; uint32_t dst = sb + slot1(p) + 16384 + r * 12288;
          asm volatile("" : "+r"(c0), "+r"(c1), "+r"(dst));
          if (XG && L && u == 4) mbar_wait(BAR(RD + 5), 0);
          if (u >= 4) mbar_wait(BAR(E1 + p), ((u >> 2) - 1) & 1);
          else mbar_wait(BAR(E4 + (u == 3 ? 0 : u + 3)), u == 3);
          if (elect_one()) {
            mbar_expect(BAR(F1 + p), (v & 15) < 2 ? 24576 : 40960);
            tma3d_mc(dst, &P.wqkv, BAR(F1 + p), c0, c1, 0);
          }
          if (u + PD1 < 32) pf1(L, u + PD1);
          if (u + PD2 >= 32) pf2(u + PD2 - 32);
        }
        int p = 0; uint32_t par = L ? 0x1e : 0;
#pragma unroll 1
        for (int n = 0; n < 16; n++) {
          int c1 = kb2(n) * 64;
          asm volatile("" : "+r"(c1));
          if (n >= 5) { mbar_wait(BAR(E2 + p), (par >> p) & 1); par ^= 1u << p; }
          else if (n < 4) mbar_wait(BAR(E1 + n), 1);
          if (elect_one()) {
            mbar_expect(BAR(F2 + p), n == 8 ? 16384 : 32768);
            tma2d_mc(sb + slot2(p) + 16384 + r * 8192, &P.wo, BAR(F2 + p), 128 * j + 64 * r, c1);
          }
          if (++p == 5) p = 0;
          if (n + PD2 < 16) pf2(n + PD2);
          if (n + PD3 + 4 >= 16) pf3(n + PD3 + 4 - 16);
        }
#pragma unroll 1
        for (int u = 0; u < 32; u++) {
          const int n = u < 4 ? (0x2031 >> (4 * u)) & 3 : u, p = n & 3;
          int kb = kb3(n);
          asm volatile("" : "+r"(kb));
          if (n == 4) mbar_wait(BAR(RD + 4), L);
          if (n >= 4) mbar_wait(BAR(E3 + p), ((n >> 2) - 1) & 1);
          else if (n == 1) mbar_wait(BAR(STD + 1), L);
          else if (n == 3) mbar_wait(BAR(E2 + 2), L);
          else if (n == 0) mbar_wait(BAR(E2 + 4), L);
          else mbar_wait(BAR(E2 + 0), 1);
          if (elect_one()) {
            mbar_expect(BAR(F3 + p), n < 2 ? 32768 : 49152);
            tma3d(sb + slot3(p) + 16384, &P.w1, BAR(F3 + p), 0, kb * 64, 7 * m + 4 * r);
            tma3d(sb + slot3(p) + 40960, &P.w1h, BAR(F3 + p), 0, kb * 64, 14 * m + 6 + r);
          }
          if (u >= 4 && u + PD3 < 32) pf3(u + PD3);
          if (u + PD4 + 6 >= 32) pf4(u + PD4 + 6 - 32);
        }
        auto g4w = [&](int n, int p, int kb) {
          if (elect_one()) {
            mbar_expect(BAR(F4 + p), (n == 0 || n == 9 || n == 17) ? 16384 : 32768);
            tma3d(sb + slot4(p), &P.w2, BAR(F4 + p), 0, kb * 64, 2 * i);
          }
        };
#pragma unroll 1
        for (int n = 0; n < 6; n++) {
          const int kb = kb4(n);
          if (n == G4GATE) mbar_wait(BAR(RD + 3), L);
          if (n < 3) mbar_wait(BAR(E3 + n), 1);
          else if (n == 4) mbar_wait(BAR(E3 + 3), 1);
          g4w(n, n, kb);
        }
        p = 0; par = L ? 0x3c : 0;
#pragma unroll 1
        for (int n = 6; n < 56; n++) {
          const int kb = kb4(n);
          if (n + PD4 < 56) pf4(n + PD4);
          mbar_wait(BAR(E4 + p), (par >> p) & 1); par ^= 1u << p;
          g4w(n, p, kb);
          if (++p == 6) p = 0;
        }
        if (L == 0)
#pragma unroll 1
          for (int u = 0; u < PD1; u++) pf1(1, u);
      }
    } else if (wu == 9) {
      uint32_t inv = 0;
#define ADDR(d, s) uint32_t dst = (d); const uint8_t* src = (s); asm volatile("" : "+r"(dst), "+l"(src))
#pragma unroll 1
      for (int L = 0; L < 2; L++) {
        uint32_t ready = 0;
#pragma unroll 1
        for (int u = 4; u < 32; u++) {
          const int p = u & 3, v = v1(L, u), nn = v & 15, kb = (L || v >= 16) ? kb1(nn) : nn;
          if (L == 0 && (u == XLD || u == XLD + XST) && elect_one()) {
            const int h = u != XLD;
            mbar_expect(BAR(XF + h), 16384);
            tma2d(sb + OFF_X + h * 16384, &P.x0, BAR(XF + h), 128 * j + 64 * h, 128 * i);
          }
          if (nn < 2) continue;
          ADDR(sb + slot1(p), gXB + (i * 16 + kb) * 16384);
          if (L && u < 12) mbar_wait(BAR(F1 + p), u >> 3);
          if (u >= 4 + 4 * L) mbar_wait(BAR(E1 + p), ((u >> 2) - 1) & 1);
          if (L) {
            flag_wait(gFlag[0][0][i], inv, 1u << kb, ready);
            if (elect_one()) bulk_ld(dst, src, 16384, BAR(F1 + p));
          } else if (elect_one()) tma2d(sb + slot1(p), &P.x0, BAR(F1 + p), kb * 64, 128 * i);
        }
        ready = 0;
        if (L == 0) inv = (__shfl_sync(0xffffffffu, load_tag(), 0) & 1) - 1;
        int p = 0; uint32_t par = L ? 0x1e : 0;
#pragma unroll 1
        for (int n = 0; n < 16; n++) {
          const int hp = kb2(n);
          if (n == 8) { par ^= 8; p = 4; continue; }
          ADDR(sb + slot2(p), gOB + (i * 16 + hp) * 16384);
          if (n >= 5) { mbar_wait(BAR(E2 + p), (par >> p) & 1); par ^= 1u << p; }
          else if (n < 4) mbar_wait(BAR(E1 + n), 1);
          flag_wait(gFlag[L][1][i], inv, 1u << hp, ready);
          if (n == 9) ST(4);
          if (elect_one()) bulk_ld(dst, src, 16384, BAR(F2 + p));
          if (++p == 5) p = 0;
        }
        ready = 0;
        mbar_wait(BAR(E2 + 0), 1);
#pragma unroll 1
        for (int n = 2; n < 32; n++) {
          const int p = n & 3, kb = kb3(n);
          const int o = (n != 16 && n != 31) ? r * 8192 : 0;
          ADDR(sb + slot3(p) + o, gHB + (j * 32 + kb) * 16384 + o);
          if (n > 3) mbar_wait(BAR(E3 + p), ((n >> 2) - 1) & 1);
          flag_wait(gFlag[L][2][j], inv, 1u << kb, ready);
          if (n == 2) ST(12);
          if (elect_one()) {
            if (n != 16 && n != 31) bulk_ld_mc(dst, src, 8192, BAR(F3 + p));
            else bulk_ld(dst, src, 16384, BAR(F3 + p));
          }
        }
        ready = 0; p = 1; par = L ? 0x3c : 0;
#pragma unroll 1
        for (int t = 0; t < 8; t++) {
          const int mm = (m + t + 1) & 7;
          ADDR(sb + slot4(p) + 16384 + r * 8192, gUB + (j * 56 + 48 + mm) * 16384 + r * 8192);
          if (t < 3) mbar_wait(BAR(E3 + 1 + t), 1);
          if (t >= 5) { mbar_wait(BAR(E4 + p), (par >> p) & 1); par ^= 1u << p; }
          flag_wait(gFlag[L][6][j], inv, 3u << (2 * mm), ready);
          if (t == 0) ST(20);
          if (elect_one()) bulk_ld_mc(dst, src, 8192, BAR(F4 + p));
          if (++p == 6) p = 0;
        }
#pragma unroll 1
        for (int c = 0; c < 3; c++) {
          ready = 0;
#pragma unroll 1
          for (int t = 0; t < 15; t++) {
            const int ii = t < 14 ? (2 * m + 2 + t) & 15 : i ^ 1;
            if (c == 0 && (t == 0 || t == 7)) { par ^= 1u << p; if (++p == 6) p = 0; }
            const int o = t < 14 ? r * 8192 : 0;
            ADDR(sb + slot4(p) + 16384 + o, gUB + (j * 56 + 16 * c + ii) * 16384 + o);
            mbar_wait(BAR(E4 + p), (par >> p) & 1); par ^= 1u << p;
            flag_wait(gFlag[L][3 + c][j], inv, 1u << ii, ready);
            if (elect_one()) {
              if (t < 14) bulk_ld_mc(dst, src, 8192, BAR(F4 + p));
              else bulk_ld(dst, src, 16384, BAR(F4 + p));
            }
            if (++p == 6) p = 0;
          }
        }
      }
    } else {
      const int h = wu - 10, i0 = i, j0 = j;
      {
      const uint32_t tag = load_tag();
      int lane = tid & 31, i = i0, j = j0;
#define FRESH asm volatile("" : "+r"(lane), "+r"(i), "+r"(j))
      auto signal = [&](int k) { if (lane == 0) mbar_arrive(BAR(k)); };
      auto publish = [&](uint32_t* f, int bit) { if (lane == 0) flag_set(f, 1u << bit); __syncwarp(); };
#pragma unroll 1
      for (int c = 32 * h + lane; c < 288; c += 64)
        sts16(sb + OFF_B1 + 2 * c, c >= 224 ? 0u : pack2(0.5f * __bfloat162float(P.b1[c < 192 ? 64 * (7 * m + 4 * r) + c : 64 * (7 * m + 3) + 32 * r + c - 192]), 0.f));
      if (h == 0) sts32f(sb + OFF_CS + 768 + 4 * lane, 0.f);
#pragma unroll 1
      for (int L = 0; L < 2; L++) {
        FRESH;
        if (L == 0) {
          mbar_wait(BAR(CSJ), 0);
          float c0 = 0.f, c1 = 0.f, c2 = 0.f;
          const uint32_t a = sb + OFF_STG + (32 * h + lane) * 4;
#pragma unroll 4
          for (int k = 0; k < 32; k++) { c0 += lds32f(a + k * 784); c1 += lds32f(a + k * 784 + 256); c2 += lds32f(a + k * 784 + 512); }
          ll_st3(&gCS[j][i][32 * h + lane], __float_as_uint(c0), __float_as_uint(c1), __float_as_uint(c2), tag);
          __nanosleep(500);
        }
        FRESH;
        if (L == 0) {
#pragma unroll 1
          for (int ab = 0; ab < 2; ab++) {
            float c0 = 0.f, c1 = 0.f, c2 = 0.f;
#pragma unroll 1
            for (int b4 = 0; b4 < 8; b4 += 4) {
              uint32_t a[4], b[4], c[4], n = 0, bad;
              do {
                bad = 0;
#pragma unroll
                for (int e = 0; e < 4; e++) bad |= ll_ld3(&gCS[j][2 * (b4 + e) + ab][32 * h + lane], a[e], b[e], c[e], tag);
              } while (bad && ++n < SPIN_MAX);
#pragma unroll
              for (int e = 0; e < 4; e++) { c0 += __uint_as_float(a[e]); c1 += __uint_as_float(b[e]); c2 += __uint_as_float(c[e]); }
            }
            const uint32_t a = sb + OFF_CS + ab * 768 + (4 * h + (lane >> 3)) * 32 + (lane & 7) * 2;
            const uint32_t h0 = pack2(c0, 0.f), h1 = pack2(c1, 0.f), h2 = pack2(c2, 0.f);
            sts16(a, h0); sts16(a + 256, h1); sts16(a + 512, h2);
            sts16(a + 16, pack2(c0 - bf_lo(h0), 0.f)); sts16(a + 272, pack2(c1 - bf_lo(h1), 0.f)); sts16(a + 528, pack2(c2 - bf_lo(h2), 0.f));
            fence_async_smem();
            __syncwarp();
            if (ab == 0) signal(STAT);
          }
        }
#pragma unroll 1
        for (int ab = 0; ab < 2; ab++) {
          FRESH;
          uint32_t v[18], tg[6];
          const uint32_t xs = sb + OFF_STG + h * 16384 + lane * 8;
          uint4* hp = &gHalo[L][i][j][6 * h][lane];
#pragma unroll
          for (int c = 0; c < 6; c++) { tg[c] = (2 * tag + ab) * 8 + c; asm volatile("" : "+r"(tg[c])); }
          asm volatile("" : "+l"(hp));
          mbar_wait(BAR(FOLD + ab), L);
          if (ab && h == 0) ST(6);
          if (i < 15) {
            halo_send(hp, xs, tg);
          }
          if (ab && h == 0) ST(26);
          if (i > 0) {
            if (!ab) __nanosleep(HALO_A_NS);
            uint32_t n = 0, bad;
            do {
              bad = 0;
#pragma unroll
              for (int c = 0; c < 6; c++) bad |= ll_ld3(hp + c * 32 - 8 * 12 * 32, v[3 * c], v[3 * c + 1], v[3 * c + 2], (2 * tag + ab) * 8);
              if (ab && h == 0 && n == 0) ST(28);
            } while (bad > 7 && ++n < SPIN_MAX);
            if (ab && h == 0) ST(27);
          } else {
#pragma unroll
            for (int c = 0; c < 18; c++) v[c] = 0u;
          }
#pragma unroll
          for (int c = 0; c < 6; c++) sts64f(xs + c * 256, __uint_as_float(v[3 * c]), __uint_as_float(v[3 * c + 1]));
          sts64f(xs + 1536, __uint_as_float(v[2]), __uint_as_float(v[5]));
          sts64f(xs + 1792, __uint_as_float(v[8]), __uint_as_float(v[11]));
          __syncwarp();
          signal(HALO + ab);
          if (ab && h == 0) ST(7);
          FRESH;
          if (ab == 0 && lane == 0) asm volatile("st.relaxed.gpu.global.u32 [%0], %1;" ::"l"(&gAck[L][i][j][h][0]), "r"(tag) : "memory");
          uint8_t* dst = gOB + (i * 16 + 2 * j + ab) * 16384;
          uint32_t* flag = gFlag[L][1][i];
          asm volatile("" : "+l"(dst), "+l"(flag));
          mbar_wait(BAR(JOB + ab), L);
          if (h == 0) {
            if (ab) ST(1);
            if (lane == 0) { bulk_st(dst, sb + OFF_STG, 16384); bulk_commit(); bulk_wait0(); }
            signal(STD + ab);
            if (ab) ST(2);
            publish(flag, 2 * j + ab);
            if (ab) ST(3);
          } else if (ab == 0) {
            if (i < 15 && lane < 2) {
              uint32_t t, n = 0;
              do { asm volatile("ld.relaxed.gpu.global.u32 %0, [%1];" : "=r"(t) : "l"(&gAck[L][i + 1][j][lane][0]) : "memory"); } while (t != tag && ++n < SPIN_MAX);
            }
            __syncwarp();
            signal(STD);
          }
        }
#pragma unroll 1
        for (int k = 0; k < 4 - L; k++) {
          FRESH;
          const int job = 2 * k + h;
          uint8_t* dst = k == 0 ? gHB + (j * 32 + 2 * i + 1) * 16384 : k == 3 ? gXB + (i * 16 + 2 * j + 1) * 16384 : gUB + (j * 56 + 16 * (job - 3) + i) * 16384;
          uint32_t* flag = k == 3 ? gFlag[0][0][i] : gFlag[L][(0x543622 >> (4 * job)) & 15][j];
          uint32_t bit = 1u << (k == 0 ? 2 * i + h : k == 3 ? 2 * j + h : i);
          asm volatile("" : "+l"(dst), "+l"(flag), "+r"(bit));
          mbar_wait(BAR(JOB + ((0x98654732 >> (4 * job)) & 15)), L);
          if (job < 3 && h == 0) ST(job ? 17 : 9);
          if ((0xba >> job) & 1) {
            if (job == 1) mbar_wait(BAR(RD + 4), L);
            if (job == 3) {
              __nanosleep(U0D);
              if (lane == 0) { bulk_st(dst, sb + OFF_X, 16384); bulk_commit(); bulk_wait0(); }
            } else warp_store(dst + lane * 16, sb + lane * 16 + OFF_X + (job == 5 ? 0 : 16384), 16384, job == 1 ? H1D : job == 7 ? X1D : 0, job == 7 ? 0 : PACE);
            if (job != 7) signal(RD + ((0x112000 >> (4 * job)) & 15));
          }
          if (lane == 0) flag_set(flag, bit);
          __syncwarp();
          if (h == 0 && k != 2) { signal(RD + (k == 3 ? 5 : 4 - k)); if (k < 2) ST(job ? 19 : 11); }
        }
      }
      if (blockIdx.x == 0 && h == 0 && lane == 0) asm volatile("st.relaxed.gpu.global.u32 [%0], %1;" ::"l"(&gEpoch), "r"(tag) : "memory");
      }
    }
    __syncwarp();
    cluster_bar();
  } else {
    reg_alloc<232>();
    asm volatile("barrier.cluster.wait;" ::: "memory");
    const uint32_t rbars = mapa(bars, tid & 1);
    const bool relp = (tid & 127) < 2;
    const uint32_t sd = (sb & 0x3FFFF) >> 4, sda = sd + wg * 512;
    uint32_t tag;
    asm volatile("ld.relaxed.gpu.global.u32 %0, [%1];" : "=r"(tag) : "l"(&gEpoch + (fresh_tid() >> 10)) : "memory");
    auto release = [&](int k) { if (relp) mbar_arrive_cl(rbars + 8 * k); };
    auto signal = [&](int k) { __syncwarp(); if ((fresh_tid() & 31) == 0) mbar_arrive(BAR(k)); };
#define GEOM const int t7 = fresh_tid() & 127, lane = t7 & 31, w = t7 >> 5, g = lane >> 2, q = lane & 3, \
                       lr = lane & 15, lt = lane >> 4, l7 = lane & 7; (void)w; (void)g; (void)q; (void)lr; (void)lt; (void)l7

#pragma unroll 1
    for (int L = 0; L < 2; L++) {
      float acca[96], accb[96], xa[64], acc3[112];
      float nmean0, nmean1, rstd0, rstd1;
      uint16_t b2a, b2b;
      uint2 *e2p, *e2s; uint8_t* e2g; uint32_t e2h;
      uint32_t Q[2][8], K[2][8], V[16];
      auto g1_issue = [&](float (&acc)[96], uint32_t a, uint32_t st, auto first) {
        const uint32_t da = sda + (a >> 4), db = sd + (st >> 4);
        wg_fence();
        static_for<0, 4>([&](auto kk) {
          constexpr uint32_t ia = DI(kk.value * 32, 16), ib = DI(16384 + (kk.value >> 1) * 12288 + (kk.value & 1) * 2048, 4096);
          if constexpr (first.value && kk.value == 0) wgmma_192z<0, 1, ia, ib>(acc, da, db); else wgmma_192<0, 1, ia, ib>(acc, da, db);
        });
        wg_commit();
      };
      auto g1_step = [&](float (&acc)[96], int u, bool rel, bool lead = false) {
        const int p = u & 3;
        mbar_wait(BAR(F1 + p), (u >> 2) & 1);
        KB(u);
        g1_issue(acc, slot1(p), slot1(p), False{});
        if (lead) nb_arrive<NB_LEAD>(256);
        wg_wait<1>();
        if (rel) release(E1 + ((u - 1) & 3));
      };
      auto g1_loop = [&](float (&acc)[96], int u0, int u1, int urel) {
        int u = u0;
#pragma unroll 1
        do { g1_step(acc, u, u > urel); } while (++u < u1);
      };
      auto load_x = [&]() {
        GEOM;
#pragma unroll
        for (int t = 0; t < 16; t += 2) {
          uint32_t v0, v1, v2, v3;
          ldsm4(sb + OFF_X + (t >> 3) * 16384 + (16 * wu + lr) * 128 + ((((t & 7) + lt) ^ l7) << 4), v0, v1, v2, v3);
          xa[4 * t + 0] = bf_lo(v0); xa[4 * t + 1] = bf_hi(v0); xa[4 * t + 2] = bf_lo(v1); xa[4 * t + 3] = bf_hi(v1);
          xa[4 * t + 4] = bf_lo(v2); xa[4 * t + 5] = bf_hi(v2); xa[4 * t + 6] = bf_lo(v3); xa[4 * t + 7] = bf_hi(v3);
        }
      };
      auto stat_base = [&]() { return &gST[0][0][0][0][0] + ((L * 16 + opq(i)) * 8 + wu) * 128; };
      auto stat_slot = [&]() { const int lane = fresh_tid() & 31; return stat_base() + 16 * j + 2 * (lane >> 2) + (lane & 1); };
      auto stat_publish = [&](uint2* sp, float s0, float q0, float s2, float q2, uint32_t tg) {
        const int q = fresh_tid() & 3;
        const bool h1 = q & 1;
        float sm = (h1 ? s2 : s0) + __shfl_xor_sync(0xffffffffu, h1 ? s0 : s2, 1);
        float sq = (h1 ? q2 : q0) + __shfl_xor_sync(0xffffffffu, h1 ? q0 : q2, 1);
        sm += __shfl_xor_sync(0xffffffffu, sm, 2); sq += __shfl_xor_sync(0xffffffffu, sq, 2);
        stat_st(sp, sm, sq, tg, q < 2);
        return sm;
      };
      auto g1_stats = [&](int u0) {
        GEOM;
        const uint32_t xr = sb + OFF_X + (16 * wu + lr) * 128;
        float s0 = 0.f, q0 = 0.f, s2 = 0.f, q2 = 0.f;
        uint32_t v[8] = {0u, 0u, 0u, 0u, 0u, 0u, 0u, 0u};
#pragma unroll 1
        for (int k = 0; k < 5; k++) {
#pragma unroll
          for (int e = 0; e < 8; e += 2) {
            const float a = bf_lo(v[e]), b = bf_hi(v[e]), c = bf_lo(v[e + 1]), d = bf_hi(v[e + 1]);
            s0 += a + b; q0 = fmaf(a, a, fmaf(b, b, q0)); s2 += c + d; q2 = fmaf(c, c, fmaf(d, d, q2));
          }
          if (k == 4) break;
          const uint32_t o = ((2 * k + lt) ^ l7) << 4;
          ldsm4(xr + o, v[0], v[1], v[2], v[3]);
          ldsm4(xr + o + 16384, v[4], v[5], v[6], v[7]);
          g1_step(acca, u0 + k, true);
        }
        stat_publish(stat_slot(), s0, q0, s2, q2, 2 * (tag + 1));
      };
      uint32_t sv0[4], sv1[4];
      auto stat_src = [&]() { return stat_base() + 2 * (fresh_tid() & 31); };
      auto stat_fetch = [&](const uint2* sp) { stat_ld2(sp, sv0); stat_ld2(sp + 64, sv1); };
      auto stat_await = [&](auto src, uint32_t tg) {
#pragma unroll 1
        for (uint32_t n = 0; (((sv0[0] ^ tg) | (sv0[2] ^ tg) | (sv1[0] ^ tg) | (sv1[2] ^ tg)) & 15u) && n < SPIN_MAX; n++) stat_fetch(src());
        __syncwarp();
      };
      auto ln_stats = [&]() {
        GEOM;
        stat_await(stat_src, 2 * (tag + 1));
        float mean0, var0, mean1, var1;
        stat_combine(sv0[0], sv0[1], sv1[0], sv1[1], untag(__shfl_sync(0xffffffffu, sv0[0], l7)), mean0, var0);
        stat_combine(sv0[2], sv0[3], sv1[2], sv1[3], untag(__shfl_sync(0xffffffffu, sv0[2], l7)), mean1, var1);
        nmean0 = -__shfl_sync(0xffffffffu, mean0, g); rstd0 = rsq(__shfl_sync(0xffffffffu, var0, g) + 1e-5f);
        nmean1 = -__shfl_sync(0xffffffffu, mean1, g); rstd1 = rsq(__shfl_sync(0xffffffffu, var1, g) + 1e-5f);
      };
      auto center = [&](float (&acc)[96], int ab) {
        const bool q0 = (fresh_tid() & 3) == 0;
        const uint32_t h0 = pack2(nmean0, nmean0), h1 = pack2(nmean1, nmean1);
        const float l0 = nmean0 - bf_lo(h0), l1 = nmean1 - bf_lo(h1);
        const uint32_t a0 = q0 ? h0 : 0u, a1 = q0 ? h1 : 0u, a2 = q0 ? pack2(l0, l0) : 0u, a3 = q0 ? pack2(l1, l1) : 0u;
        wg_fence();
        wgmma_rs_192(acc, a0, a1, a2, a3, mkdesc_vec(sb + OFF_CS + ab * 768, 32));
      };
      auto frag = [&](float (&acc)[96], int t, uint32_t& p0, uint32_t& p1) {
        if (t >= 8) { p0 = pack2(acc[4 * t] * rstd0, acc[4 * t + 1] * rstd0); p1 = pack2(acc[4 * t + 2] * rstd1, acc[4 * t + 3] * rstd1); }
        else { p0 = pack2(acc[4 * t], acc[4 * t + 1]); p1 = pack2(acc[4 * t + 2], acc[4 * t + 3]); }
      };
      auto fold_v = [&](float (&acc)[96], int t0, int t1) {
        GEOM;
        const uint32_t a = sb + OFF_STG + 16384 + ((wu + 1) & 7) * 2048 + lr * 128;
#pragma unroll
        for (int t = t0; t < t1; t += 2) {
          uint32_t p0, p1, p2, p3;
          frag(acc, 16 + t, p0, p1); frag(acc, 17 + t, p2, p3);
          stsm4(a + (((t + lt) ^ l7) << 4), p0, p1, p2, p3);
        }
        __syncwarp();
#pragma unroll
        for (int t = t0; t < t1; t += 2) ldsm4t(a + (((t + lt) ^ l7) << 4), V[2 * t], V[2 * t + 1], V[2 * t + 2], V[2 * t + 3]);
      };
      auto fold_k = [&](float (&acc)[96], int ab, int h0, int h1) {
        GEOM;
        const uint32_t a = sb + OFF_STG + ((wu + 1) & 7) * 2048 + lane * 16;
#pragma unroll
        for (int hh = h0; hh < h1; hh++) {
#pragma unroll
          for (int t = 4 * hh; t < 4 * hh + 4; t++) frag(acc, 8 + t, K[0][t], K[1][t]);
#pragma unroll
          for (int o = 0; o < 2; o++) sts128(a + (2 * o + hh) * 512, K[o][4 * hh], K[o][4 * hh + 1], K[o][4 * hh + 2], K[o][4 * hh + 3]);
        }
        if (h1 == 2 && wu == 7) signal(FOLD + ab);
      };
      auto fold_q = [&](float (&acc)[96]) {
#pragma unroll
        for (int t = 0; t < 8; t++) frag(acc, t, Q[0][t], Q[1][t]);
      };
      auto attend = [&](int ab, auto drain, auto resume) {
        GEOM;
        nb_sync<NB_BOTH>(256);
        const uint32_t xa_ = sb + OFF_STG + wu * 2048 + lane * 16;
        if (wu == 0) mbar_wait(BAR(HALO + ab), L);
        uint32_t KH[2][8], VH[16];
#pragma unroll
        for (int c = 0; c < 4; c++) {
          lds128(xa_ + c * 512, KH[c >> 1][4 * (c & 1)], KH[c >> 1][4 * (c & 1) + 1], KH[c >> 1][4 * (c & 1) + 2], KH[c >> 1][4 * (c & 1) + 3]);
          ldsm4t(sb + OFF_STG + 16384 + wu * 2048 + lr * 128 + (((2 * c + lt) ^ l7) << 4), VH[4 * c], VH[4 * c + 1], VH[4 * c + 2], VH[4 * c + 3]);
        }
        TS2(11 + ab + 32 * L);
        const bool e = g & 1, zneg = (g >> 1) < q, first = (i == 0) && (wu == 0);
        const float sc0 = rstd0 * (0.17677669530f * 1.4426950409f), sc1 = rstd1 * (0.17677669530f * 1.4426950409f);
        float mk0 = first ? __fdividef(-1.0e9f * 1.4426950409f, sc0) : 0.f, mk1 = first ? __fdividef(-1.0e9f * 1.4426950409f, sc1) : 0.f;
        const uint32_t sa = e ? 0x1044u : 0x4410u, sbb = e ? 0x3244u : 0x4432u;
        uint32_t sel[3] = {zneg ? sbb : 0x4444u, sa, zneg ? 0x4444u : sbb};
        uint32_t oa = sb + OFF_STG + (16 * wu + lr) * 128 + ((lt ^ l7) << 4);
        asm volatile("" : "+r"(sel[0]), "+r"(sel[1]), "+r"(sel[2]), "+r"(oa), "+f"(mk0), "+f"(mk1));
        drain();
        uint32_t pr[2][6];
        float l[2][2];
#pragma unroll
        for (int hh = 0; hh < 2; hh++)
          attn_probs(&Q[0][4 * hh], &Q[1][4 * hh], &KH[0][4 * hh], &KH[1][4 * hh], &K[0][4 * hh], &K[1][4 * hh], sc0, sc1, mk0, mk1, e, zneg, sel, pr[hh], l[hh]);
        float o[2][4][4];
#pragma unroll
        for (int hh = 0; hh < 2; hh++) attn_pv(pr[hh], &VH[8 * hh], &V[8 * hh], o[hh]);
#pragma unroll
        for (int hh = 0; hh < 2; hh++) {
          float l0 = l[hh][0], l1 = l[hh][1];
          l0 += __shfl_xor_sync(0xffffffffu, l0, 1); l1 += __shfl_xor_sync(0xffffffffu, l1, 1);
          l0 += __shfl_xor_sync(0xffffffffu, l0, 2); l1 += __shfl_xor_sync(0xffffffffu, l1, 2);
          asm("rcp.approx.ftz.f32 %0, %0;" : "+f"(l0)); asm("rcp.approx.ftz.f32 %0, %0;" : "+f"(l1));
#pragma unroll
          for (int dt = 0; dt < 4; dt += 2)
            stsm4(oa ^ ((4 * hh + dt) << 4),
                  pack2(o[hh][dt][0] * l0, o[hh][dt][1] * l0), pack2(o[hh][dt][2] * l1, o[hh][dt][3] * l1),
                  pack2(o[hh][dt + 1][0] * l0, o[hh][dt + 1][1] * l0), pack2(o[hh][dt + 1][2] * l1, o[hh][dt + 1][3] * l1));
        }
        fence_async_smem();
        signal(JOB + ab);
        nb_sync<NB_BOTH>(256);
        resume();
      };

      TS(1 + 32 * L);
      if (L == 0 && wu == 0) S5(7);
      mbar_wait(BAR(F1), 0); if (L == 0 && wu == 0) S5(8); KB(0);    g1_issue(acca, L ? OFF_X : slot1(0), slot1(0), True{});
      mbar_wait(BAR(F1 + 1), 0); KB(1); g1_issue(acca, L ? OFF_X + 16384 : slot1(1), slot1(1), False{});
      wg_wait<1>(); release(E1 + 0);
      if (L == 0) {
        GEOM;
        const bf16* wp = P.wqkv_p + ((128 * opq(m) + 16 * wg + (t7 >> 3)) * 3072 + 128 * opq(j) + 64 * r + l7 * 8);
        const uint32_t ca = sb + OFF_STG + (16 * wg + (t7 >> 3)) * 784 + l7 * 32;
#pragma unroll 1
        for (int p = 0; p < 3; p++) {
          uint4 wv[4];
#pragma unroll
          for (int k = 0; k < 4; k++)
            asm volatile("ld.global.nc.v4.u32 {%0, %1, %2, %3}, [%4];" : "=r"(wv[k].x), "=r"(wv[k].y), "=r"(wv[k].z), "=r"(wv[k].w)
                         : "l"(wp + k * 32 * 3072 + p * 1024));
          g1_loop(acca, 2 + 3 * p, p < 2 ? 5 + 3 * p : 10, 0);
          float cs[8];
#pragma unroll
          for (int k = 0; k < 4; k++) {
            const uint4 v = wv[k];
            const float t[8] = {bf_lo(v.x), bf_hi(v.x), bf_lo(v.y), bf_hi(v.y), bf_lo(v.z), bf_hi(v.z), bf_lo(v.w), bf_hi(v.w)};
#pragma unroll
            for (int e = 0; e < 8; e++) cs[e] = k ? cs[e] + t[e] : t[e];
          }
          sts128(ca + p * 256, __float_as_uint(cs[0]), __float_as_uint(cs[1]), __float_as_uint(cs[2]), __float_as_uint(cs[3]));
          sts128(ca + p * 256 + 16, __float_as_uint(cs[4]), __float_as_uint(cs[5]), __float_as_uint(cs[6]), __float_as_uint(cs[7]));
        }
        signal(CSJ);
        mbar_wait(BAR(XF), 0); mbar_wait(BAR(XF + 1), 0);
      }
      {
        const int u0 = L ? 2 : 10;
        mbar_wait(BAR(F1 + 2), 0); KB(u0); g1_issue(accb, OFF_X, slot1(2), True{});
        wg_wait<1>(); release(E1 + 1);
        mbar_wait(BAR(F1 + 3), 0); KB(u0 + 1); g1_issue(accb, OFF_X + 16384, slot1(3), False{});
        wg_wait<1>(); release(E1 + 2);
        g1_stats(u0 + 2);
        g1_loop(acca, u0 + 6, 18, 0);
      }
      stat_fetch(stat_src());
      const int fa = FA + (wg ? 0 : FO);
      g1_loop(accb, 18, fa, 0);
      ln_stats();
      if (L == 0) mbar_wait(BAR(STAT), 0);
      center(acca, 0); wg_commit();
      wg_wait<0>(); release(E1 + ((fa - 1) & 3));
      fence_regs(acca);
      TS(2 + 32 * L);
      fold_v(acca, 0, 8); fold_k(acca, 0, 0, 2); fold_q(acca);
      sched_fence(P.zero);
      g1_loop(accb, fa, ATT, fa);
      attend(0, [&]() { wg_wait<0>(); release(E1 + ((ATT - 1) & 3)); mbar_wait(BAR(F1 + (ATT & 3)), (ATT >> 2) & 1); },
             [&]() { KB(ATT); g1_issue(accb, slot1(ATT & 3), slot1(ATT & 3), False{});
                     mbar_wait(BAR(F1 + ((ATT + 1) & 3)), ((ATT + 1) >> 2) & 1);
                     KB(ATT + 1); g1_issue(accb, slot1((ATT + 1) & 3), slot1((ATT + 1) & 3), False{}); });
      wg_wait<1>(); release(E1 + (ATT & 3));
      TS(3 + 32 * L);
      load_x();
      fence_regs(xa);
      center(accb, 1);
#pragma unroll 1
      for (int u = ATT + 2; u < 32; u++) {
        const bool hold = u == 32 - LEAD1 && wg == 0;
        if (hold) { wg_wait<0>(); release(E1 + ((31 - LEAD1) & 3)); nb_sync<NB_LEAD>(256); }
        g1_step(accb, u, !hold, u == 31 && wg == 1);
      }
      mbar_wait(BAR(STD), L);
      wg_wait<0>(); release(E1 + 3);
      fence_regs(accb);
      TS(4 + 32 * L);
      if (wu == 7) ST(0);
      fold_v(accb, 0, 8); fold_k(accb, 1, 0, 2);
      fold_q(accb);
      TS2(29 + 32 * L);
      {
        auto g2_issue = [&](int p, bool own) {
          const uint32_t st = slot2(p);
          const uint32_t da = sda + ((own ? OFF_STG : st) >> 4), db = sd + (st >> 4);
          wg_fence();
          static_for<0, 4>([&](auto kk) { wgmma_128<0, 1, DI(kk.value * 32, 16), DI(16384 + kk.value * 2048, 8192)>(xa, da, db); });
          wg_commit();
        };
        uint32_t par = L ? 0x1e : 0;
        int p = 0, pp = 0;
        auto g2_loop = [&](int n0, int n1, int nrel) {
#pragma unroll 1
          for (int n = n0; n < n1; n++) {
            mbar_wait(BAR(F2 + p), (par >> p) & 1);
            KB(32 + n);
            if (n == 9 && wu == 0) ST(5);
            par ^= 1u << p;
            g2_issue(p, n == 8);
            if (n1 == 16 && n == 15 && wg == 0) nb_arrive<NB_LEAD>(256);
            wg_wait<1>();
            if (n > nrel) release(E2 + pp);
            pp = p; if (++p == 5) p = 0;
          }
        };
        g2_loop(0, COVER, 0);
        attend(1, [&]() { wg_wait<0>(); release(E2 + COVER - 1); mbar_wait(BAR(F2 + COVER), (par >> COVER) & 1); },
               [&]() { KB(32 + COVER); g2_issue(COVER, false);
                       mbar_wait(BAR(F2 + COVER + 1), (par >> (COVER + 1)) & 1);
                       KB(33 + COVER); g2_issue(COVER + 1, false); });
        wg_wait<1>(); release(E2 + COVER);
        par ^= 3u << COVER; pp = COVER + 1; p = (COVER + 2) % 5;
        TS(30 + 32 * L);
        {
          const bf16* bp = P.b2 + (128 * opq(i) + 16 * wu + ((fresh_tid() & 31) >> 2));
          asm volatile("ld.global.nc.u16 %0, [%1];" : "=h"(b2a) : "l"(bp));
          asm volatile("ld.global.nc.u16 %0, [%1];" : "=h"(b2b) : "l"(bp + 8));
        }
        TS2(14 + 32 * L);
        {
          GEOM;
          e2p = stat_slot(); e2s = stat_src();
          e2g = gHB + (opq(j) * 32 + 2 * i) * 16384 + w * 2048 + lane * 16;
          e2h = sb + OFF_X + wg * 16384 + (16 * w + lr) * 128 + ((lt ^ l7) << 4);
          asm volatile("" : "+l"(e2p), "+l"(e2s), "+l"(e2g), "+r"(e2h));
        }
        g2_loop(COVER + 2, 16 - LEAD2, 0);
        if (wg == 1) { wg_wait<0>(); release(E2 + pp); nb_sync<NB_LEAD>(256); }
        g2_loop(16 - LEAD2, 16, wg == 1 ? 16 - LEAD2 : 0);
        wg_wait<0>();
        release(E2 + 0);
        fence_regs(xa);
      }
      TS(5 + 32 * L);
      if (wu == 0) ST(8);
      {
        GEOM;
        const uint32_t tg = 2 * (tag + 1) + 1;
        float s0 = 0.f, s1 = 0.f, s2 = 0.f, s3 = 0.f, q0 = 0.f, q1 = 0.f, q2 = 0.f, q3 = 0.f;
#pragma unroll
        for (int t = 0; t < 16; t++) {
          s0 += xa[4 * t]; s1 += xa[4 * t + 1]; s2 += xa[4 * t + 2]; s3 += xa[4 * t + 3];
          q0 = fmaf(xa[4 * t], xa[4 * t], q0); q1 = fmaf(xa[4 * t + 1], xa[4 * t + 1], q1);
          q2 = fmaf(xa[4 * t + 2], xa[4 * t + 2], q2); q3 = fmaf(xa[4 * t + 3], xa[4 * t + 3], q3);
        }
        const float sm = stat_publish(e2p, s0 + s1, q0 + q1, s2 + s3, q2 + q3, tg);
        const uint32_t t0 = clock32();
        TS2(13 + 32 * L);
        const float pv0 = __shfl_sync(0xffffffffu, sm, 4 * l7) * (1.f / 128), pv1 = __shfl_sync(0xffffffffu, sm, 4 * l7 + 1) * (1.f / 128);
        while (clock32() - t0 < STAT_CLK) {}
        stat_fetch(e2s);
        wg_fence();
        wgmma_rs_224z(acc3, q == 0 ? 0x3f80u : 0u, q == 0 ? 0x3f80u : 0u, 0u, 0u, mkdesc_vec(sb + OFF_B1, 16));
        wg_commit();
        stat_await([&]() { return e2s; }, tg);
        float r0, m0, r1, m1;
        {
          float mean0, var0, mean1, var1;
          stat_combine(sv0[0], sv0[1], sv1[0], sv1[1], pv0, mean0, var0); stat_combine(sv0[2], sv0[3], sv1[2], sv1[3], pv1, mean1, var1);
          mean0 = __shfl_sync(0xffffffffu, mean0, g); var0 = __shfl_sync(0xffffffffu, var0, g);
          mean1 = __shfl_sync(0xffffffffu, mean1, g); var1 = __shfl_sync(0xffffffffu, var1, g);
          r0 = 0.5f * rsq(fmaf(var0 + 1e-5f, 1e-5f, var0)); r1 = 0.5f * rsq(fmaf(var1 + 1e-5f, 1e-5f, var1));
          m0 = -mean0 * r0; m1 = -mean1 * r1;
        }
        TS2(15 + 32 * L);
#pragma unroll
        for (int t = 0; t < 16; t += 2) {
          stsm4((e2h ^ ((t & 7) << 4)) + (t >> 3) * 8192,
                pack2(fmaf(xa[4 * t], r0, m0), fmaf(xa[4 * t + 1], r0, m0)), pack2(fmaf(xa[4 * t + 2], r1, m1), fmaf(xa[4 * t + 3], r1, m1)),
                pack2(fmaf(xa[4 * t + 4], r0, m0), fmaf(xa[4 * t + 5], r0, m0)), pack2(fmaf(xa[4 * t + 6], r1, m1), fmaf(xa[4 * t + 7], r1, m1)));
          if ((t & 7) == 6 && wg == 0) {
            __syncwarp();
            copy_out<4>(e2g + (t >> 3) * 8192, sb + OFF_X + (t >> 3) * 8192 + w * 2048 + lane * 16, 512);
          }
        }
        signal(JOB + 2 + wg);
        fence_async_smem();
        mbar_wait(BAR(F3 + 0), 0);
        nb_sync<NB_BOTH>(256);
      }
      TS(6 + 32 * L);
      auto g3_issue = [&](uint32_t a, int p) {
        const uint32_t da = sda + (a >> 4), db = sd + (slot3(p) >> 4);
        wg_fence();
        static_for<0, 4>([&](auto kk) { wgmma_224<1, 1, DI(kk.value * 2048, 8192), DI(16384 + kk.value * 2048, 8192)>(acc3, da, db); });
        wg_commit();
      };
      KB(48); g3_issue(OFF_X, 0);
      mbar_wait(BAR(F3 + 1), 0); KB(49); g3_issue(OFF_X + 16384, 1);
      sched_fence(P.zero);
      {
        const float c0 = __uint_as_float((uint32_t)b2a << 16), c1 = __uint_as_float((uint32_t)b2b << 16);
#pragma unroll
        for (int t = 0; t < 16; t++) { xa[4 * t] += c0; xa[4 * t + 1] += c0; xa[4 * t + 2] += c1; xa[4 * t + 3] += c1; }
        fence_regs(xa);
      }
      wg_wait<1>(); release(E3 + 0);
      auto g3_loop = [&](int n0, int n1, int nrel) {
#pragma unroll 1
        for (int n = n0; n < n1; n++) {
          const int p = n & 3;
          mbar_wait(BAR(F3 + p), (n >> 2) & 1);
          KB(48 + n);
          if (n == 3 && wu == 0) ST(13);
          if (n == 2 && wu == 0) ST(14);
          g3_issue(slot3(p), p);
          wg_wait<1>();
          if (n > nrel) release(E3 + ((n - 1) & 3));
        }
      };
      g3_loop(2, 29, 0);
      uint32_t ua;
      uint8_t* ug;
      {
        GEOM;
        ua = sb + OFF_X + wg * 8192 + (8 * lt + l7) * 128 + (((2 * w + ((lane >> 3) & 1)) ^ l7) << 4);
        ug = gUB + (opq(j) * 56 + 48 + m) * 16384 + r * 4096 + wg * 8192 + (lane >> 1) * 128 + (((2 * w + (lane & 1)) ^ ((lane >> 1) & 7)) << 4);
      }
      auto gelu8 = [&](int c, int k) {
        const int o = 32 * c + 8 * k;
        stsm4t(ua + (c & 1) * 16384 + k * 2048,
               pack2(gelu_half(acc3[o]), gelu_half(acc3[o + 1])), pack2(gelu_half(acc3[o + 2]), gelu_half(acc3[o + 3])),
               pack2(gelu_half(acc3[o + 4]), gelu_half(acc3[o + 5])), pack2(gelu_half(acc3[o + 6]), gelu_half(acc3[o + 7])));
      };
      {
        auto part = [&](auto p, auto half) {
          static_for<0, 4>([&](auto kk) {
            constexpr uint32_t o = slot3(p.value) + kk.value * 2048;
            if constexpr (half.value) wgmma_32<1, 1, DI(o, 8192), DI(o + 40960, 8192), 96>(acc3, sda, sd);
            else wgmma_192<1, 1, DI(o, 8192), DI(o + 16384, 8192), 0>(acc3, sda, sd);
          });
        };
        mbar_wait(BAR(RD), L);
        mbar_wait(BAR(F3 + 1), 1); mbar_wait(BAR(F3 + 2), 1);
        wg_wait<0>(); release(E3 + 0);
#pragma unroll
        for (int k = 0; k < 112; k++) { float t; asm volatile("mov.b32 %0, %1;" : "=f"(t) : "f"(acc3[k]) : "memory"); acc3[k] = t; }
        sched_fence(P.zero);
        KB(77);
        wg_fence(); part(Int<1>{}, True{}); part(Int<2>{}, True{});
        mbar_wait(BAR(F3 + 3), 1); wg_fence(); part(Int<3>{}, True{}); wg_commit();
        part(Int<1>{}, False{}); wg_commit();
        wg_wait<1>();
#pragma unroll
        for (int k = 96; k < 112; k++) asm volatile("" : "+f"(acc3[k])::"memory");
        gelu8(3, 0); gelu8(3, 1);
        __syncwarp();
        copy_out<2>(ug, sb + OFF_X + 16384 + (uint32_t)((ug - gUB) & 0x2fff), 2048);
        signal(JOB + 7);
        sched_fence(P.zero);
        KB(78);
        wg_fence(); part(Int<2>{}, False{}); wg_commit();
        wg_wait<1>(); release(E3 + 1);
        KB(79);
        part(Int<3>{}, False{}); wg_commit();
        wg_wait<1>(); release(E3 + 2);
        wg_wait<0>(); release(E3 + 3);
      }
      fence_regs(acc3);
      TS(7 + 32 * L);
      if (wu == 0) ST(16);
      auto g4_issue = [&](int p, uint32_t b) {
        const uint32_t da = sda + (slot4(p) >> 4), db = sd + (b >> 4);
        wg_fence();
        static_for<0, 4>([&](auto kk) { wgmma_128<1, 1, DI(kk.value * 2048, 8192), DI(kk.value * 2048, 8192)>(xa, da, db); });
        wg_commit();
      };
#pragma unroll
      for (int k = 0; k < 4; k++) gelu8(0, k);
      fence_async_smem();
      signal(JOB + 4);
      nb_sync<NB_BOTH>(256);
      TS(8 + 32 * L);
      static_for<0, 18>([&](auto nn) {
        constexpr int n = nn.value, p = n % 6;
        if (n == 9 || n == 17) mbar_wait(BAR(JOB + 4 + (n >> 3)), L);
        mbar_wait(BAR(F4 + p), (n / 6 + (p >= 2 ? L : 0)) & 1);
        KB(80 + n);
        if (n == 1 && wu == 0) ST(21);
        if (n == 0 && wu == 0) ST(22);
        wg_fence();
        static_for<0, 4>([&](auto kk) {
          wgmma_128<1, 1, DI(slot4(p) + kk.value * 2048, 8192), DI((n == 9 ? OFF_X + 16384 : n % 17 ? slot4(p) + 16384 : OFF_X) + kk.value * 2048, 8192)>(xa, sda, sd);
        });
        wg_commit();
        if (n) { wg_wait<1>(); release(E4 + (n + 5) % 6); }
        if (n == 8) mbar_wait(BAR(RD + 2), L);
        else if (n < 16 && !(n & 1)) sched_fence(P.zero);
        if constexpr (n < 16 && !(n & 1)) gelu8(1 + (n >> 3), (n >> 1) & 3);
        if ((n & 7) == 7) { fence_async_smem(); signal(JOB + 5 + (n >> 3)); }
      });
      {
        int p = 0, pp = 5;
        uint32_t par = L ? 0x03 : 0x3f;
        auto g4_loop = [&](int n0, int n1, int nrel) {
#pragma unroll 1
          for (int n = n0; n < n1; n++) {
            mbar_wait(BAR(F4 + p), (par >> p) & 1);
            KB(80 + n);
            par ^= 1u << p;
            g4_issue(p, slot4(p) + 16384);
            if (n1 == 56 && n == 55 && wg == 0) nb_arrive<NB_LEAD>(256);
            wg_wait<1>();
            if (n > nrel) release(E4 + pp);
            pp = p; if (++p == 6) p = 0;
          }
        };
        g4_loop(18, 56 - LEAD4, 0);
        if (wg == 1) { wg_wait<0>(); release(E4 + pp); nb_sync<NB_LEAD>(256); }
        g4_loop(56 - LEAD4, 56, wg == 1 ? 56 - LEAD4 : 0);
      }
      uint32_t xs;
      uint8_t* xg;
      {
        GEOM;
        xs = sb + OFF_X + wu * 2048 + (lane >> 3) * 128 + ((L ? l7 ^ (lane >> 3) : l7) << 4);
        xg = L ? P.out + (128 * opq(i) + 16 * wu + (lane >> 3)) * 2048 + 256 * j + 16 * l7 : gXB + (opq(i) * 16 + 2 * j) * 16384 + wu * 2048 + lane * 16;
        asm volatile("" : "+r"(xs), "+l"(xg));
      }
      mbar_wait(BAR(RD + 1), L);
      wg_wait<0>();
      release(E4 + 1);
      fence_regs(xa);
      TS(9 + 32 * L);
      {
        GEOM;
#pragma unroll
        for (int t = 0; t < 16; t += 2) {
          stsm4(sb + OFF_X + (t >> 3) * 16384 + (16 * wu + lr) * 128 + ((((t & 7) + lt) ^ l7) << 4),
                pack2(xa[4 * t], xa[4 * t + 1]), pack2(xa[4 * t + 2], xa[4 * t + 3]),
                pack2(xa[4 * t + 4], xa[4 * t + 5]), pack2(xa[4 * t + 6], xa[4 * t + 7]));
          if ((t & 7) == 6 && (L || t == 6)) {
            __syncwarp();
            uint4 v[4];
#pragma unroll
            for (int k = 0; k < 4; k++) lds128((xs ^ (L ? (k & 1) << 6 : 0)) + k * 512 + (t >> 3) * 16384, v[k].x, v[k].y, v[k].z, v[k].w);
#pragma unroll
            for (int k = 0; k < 4; k++)
              asm volatile("st.global.v4.b32 [%0], {%1, %2, %3, %4};" ::"l"(xg + k * (L ? 8192 : 512) + (t >> 3) * 128), "r"(v[k].x), "r"(v[k].y), "r"(v[k].z), "r"(v[k].w) : "memory");
            if (L == 0) signal(JOB + 8);
          }
        }
        if (L) break;
        fence_async_smem();
        signal(JOB + 9);
        nb_sync<NB_BOTH>(256);
      }
      TS(10 + 32 * L);
      KB(136);
    }
    cluster_bar();
    TS(32);
  }
}

typedef CUresult (*EncodeFn)(CUtensorMap*, CUtensorMapDataType, cuuint32_t, void*, const cuuint64_t*, const cuuint64_t*, const cuuint32_t*,
                             const cuuint32_t*, CUtensorMapInterleave, CUtensorMapSwizzle, CUtensorMapL2promotion, CUtensorMapFloatOOBfill);

void make_map(EncodeFn enc, CUtensorMap* mp, const void* base, int rank, cuuint64_t d0, cuuint64_t d1, cuuint64_t d2, cuuint64_t s1, cuuint64_t s2,
              cuuint32_t b0, cuuint32_t b1, cuuint32_t b2) {
  cuuint64_t dims[3] = {d0, d1, d2}, strides[2] = {s1, s2};
  cuuint32_t box[3] = {b0, b1, b2}, es[3] = {1, 1, 1};
  CUresult res = enc(mp, CU_TENSOR_MAP_DATA_TYPE_BFLOAT16, rank, const_cast<void*>(base), dims, strides, box, es, CU_TENSOR_MAP_INTERLEAVE_NONE,
                     CU_TENSOR_MAP_SWIZZLE_128B, CU_TENSOR_MAP_L2_PROMOTION_L2_128B, CU_TENSOR_MAP_FLOAT_OOB_FILL_NONE);
  (void)res;
}

}

extern "C" void kernel_launch(void* const* d_in, const int* in_sizes, int n_in, void* d_out, int out_size) {
  (void)in_sizes; (void)n_in; (void)out_size;
  static EncodeFn enc = nullptr;
  if (!enc) {
    void* fn = nullptr;
    cudaDriverEntryPointQueryResult qr;
    cudaGetDriverEntryPoint("cuTensorMapEncodeTiled", &fn, cudaEnableDefault, &qr);
    enc = (EncodeFn)fn;
    cudaFuncSetAttribute(fused_kernel, cudaFuncAttributeMaxDynamicSharedMemorySize, SMEM_BYTES);
  }
  Params P;
  make_map(enc, &P.x0, d_in[0], 2, D_, S_, 1, D_ * 2, 0, 64, 128, 1);
  make_map(enc, &P.wqkv, d_in[1], 3, D_, D_, 3, 3 * D_ * 2, D_ * 2, 64, 32, 3);
  make_map(enc, &P.wo, d_in[2], 2, D_, D_, 1, D_ * 2, 0, 64, 64, 1);
  make_map(enc, &P.w1, d_in[4], 3, 64, S_, F_ / 64, F_ * 2, 128, 64, 64, 3);
  make_map(enc, &P.w1h, d_in[4], 3, 32, S_, F_ / 32, F_ * 2, 64, 64, 64, 1);
  make_map(enc, &P.w2, d_in[6], 3, 64, F_, S_ / 64, S_ * 2, 128, 64, 64, 2);
  P.out = (uint8_t*)d_out;
  P.wqkv_p = (const bf16*)d_in[1];
  P.wo_p = (const bf16*)d_in[2];
  P.w1_p = (const bf16*)d_in[4];
  P.w2_p = (const bf16*)d_in[6];
  P.b1 = (const bf16*)d_in[5];
  P.b2 = (const bf16*)d_in[7];
  P.zero = 0;
  fused_kernel<<<128, 384, SMEM_BYTES>>>(P);
}
```

```cpp
#include <cuda_runtime.h>
#include <cuda_bf16.h>
#include <cuda.h>
#include <stdint.h>

namespace {

typedef __nv_bfloat16 bf16;
constexpr int S_ = 2048, D_ = 1024, F_ = 3584;

constexpr uint32_t OFF_STG  = 163840;
constexpr uint32_t OFF_X    = 196608;
constexpr uint32_t OFF_BAR  = 229376;
constexpr uint32_t OFF_CS   = OFF_BAR + 512;
constexpr uint32_t OFF_B1   = OFF_CS + 1536;
constexpr uint32_t SMEM_BYTES = OFF_B1 + 896 + 128;
constexpr int F1 = 0, E1 = 4, F2 = 8, E2 = 13, F3 = 18, E3 = 22, F4 = 26, E4 = 32;
constexpr int JOB = 38;
constexpr int RD = 48;
constexpr int XF = 54, STD = 56, STAT = 58, FOLD = 59, CSJ = 61, HALO = 62;
constexpr int NB_BOTH = 1, NB_HELP = 2, NB_INIT = 3, NB_LEAD = 4;

__host__ __device__ constexpr uint32_t slot1(int p) { return p * 40960; }
__host__ __device__ constexpr uint32_t slot2(int p) { return p * 32768; }
__host__ __device__ constexpr uint32_t slot3(int p) { return ((p + 2) & 3) * 49152; }
__host__ __device__ constexpr uint32_t slot4(int p) { return (p < 2 ? p + 4 : p - 2) * 32768; }

__device__ __align__(1024) uint8_t gXB[16 * 16 * 16384];
__device__ __align__(1024) uint8_t gOB[16 * 16 * 16384];
__device__ __align__(1024) uint8_t gHB[8 * 32 * 16384];
__device__ __align__(1024) uint8_t gUB[8 * 56 * 16384];
__device__ __align__(1024) uint2   gST[2][16][8][8][16];
__device__ __align__(1024) uint4   gHalo[2][16][8][12][32];
__device__ __align__(1024) uint32_t gAck[2][16][8][2][8];
__device__ __align__(1024) uint4   gCS[8][16][64];
__device__ __align__(1024) uint32_t gFlag[2][7][16][32];
__device__ uint32_t gEpoch;
#define TS(k)
#define TS2(k)

#define S5(k)
#define KB(k)
#define ST(k)
struct Params {
  CUtensorMap x0, wqkv, wo, w1, w1h, w2;
  uint8_t* out;
  const bf16 *wqkv_p, *wo_p, *w1_p, *w2_p, *b1, *b2;
  uint32_t zero;
};

template <int TA, int TB, uint32_t IA, uint32_t IB, int O = 0, int LEN> __device__ __forceinline__ void wgmma_32(float (&d)[LEN], uint32_t da, uint32_t db) {
  asm volatile("{\n.reg .b64 da, db;\n.reg .b32 la, lb;\nadd.u32 la, %16, %20;\nadd.u32 lb, %17, %21;\nmov.b64 da, {la, 0x40000040};\nmov.b64 db, {lb, 0x40000040};\n"
  "wgmma.mma_async.sync.aligned.m64n32k16.f32.bf16.bf16 {"
  "%0, %1, %2, %3, %4, %5, %6, %7, %8, %9, %10, %11, %12, %13, %14, %15"
  "}, da, db, 1, 1, 1, %18, %19;\n}\n"
  : "+f"(d[O + 0]), "+f"(d[O + 1]), "+f"(d[O + 2]), "+f"(d[O + 3]), "+f"(d[O + 4]), "+f"(d[O + 5]), "+f"(d[O + 6]), "+f"(d[O + 7]),
    "+f"(d[O + 8]), "+f"(d[O + 9]), "+f"(d[O + 10]), "+f"(d[O + 11]), "+f"(d[O + 12]), "+f"(d[O + 13]), "+f"(d[O + 14]), "+f"(d[O + 15])
  : "r"(da), "r"(db), "n"(TA), "n"(TB), "n"(IA), "n"(IB));
}
template <int TA, int TB, uint32_t IA, uint32_t IB, int O = 0, int LEN> __device__ __forceinline__ void wgmma_128(float (&d)[LEN], uint32_t da, uint32_t db) {
  asm volatile("{\n.reg .b64 da, db;\n.reg .b32 la, lb;\nadd.u32 la, %64, %68;\nadd.u32 lb, %65, %69;\nmov.b64 da, {la, 0x40000040};\nmov.b64 db, {lb, 0x40000040};\n"
  "wgmma.mma_async.sync.aligned.m64n128k16.f32.bf16.bf16 {"
  "%0, %1, %2, %3, %4, %5, %6, %7, %8, %9, %10, %11, %12, %13, %14, %15, "
  "%16, %17, %18, %19, %20, %21, %22, %23, %24, %25, %26, %27, %28, %29, %30, %31, "
  "%32, %33, %34, %35, %36, %37, %38, %39, %40, %41, %42, %43, %44, %45, %46, %47, "
  "%48, %49, %50, %51, %52, %53, %54, %55, %56, %57, %58, %59, %60, %61, %62, %63"
  "}, da, db, 1, 1, 1, %66, %67;\n}\n"
  : "+f"(d[O + 0]), "+f"(d[O + 1]), "+f"(d[O + 2]), "+f"(d[O + 3]), "+f"(d[O + 4]), "+f"(d[O + 5]), "+f"(d[O + 6]), "+f"(d[O + 7]),
    "+f"(d[O + 8]), "+f"(d[O + 9]), "+f"(d[O + 10]), "+f"(d[O + 11]), "+f"(d[O + 12]), "+f"(d[O + 13]), "+f"(d[O + 14]), "+f"(d[O + 15]),
    "+f"(d[O + 16]), "+f"(d[O + 17]), "+f"(d[O + 18]), "+f"(d[O + 19]), "+f"(d[O + 20]), "+f"(d[O + 21]), "+f"(d[O + 22]), "+f"(d[O + 23]),
    "+f"(d[O + 24]), "+f"(d[O + 25]), "+f"(d[O + 26]), "+f"(d[O + 27]), "+f"(d[O + 28]), "+f"(d[O + 29]), "+f"(d[O + 30]), "+f"(d[O + 31]),
    "+f"(d[O + 32]), "+f"(d[O + 33]), "+f"(d[O + 34]), "+f"(d[O + 35]), "+f"(d[O + 36]), "+f"(d[O + 37]), "+f"(d[O + 38]), "+f"(d[O + 39]),
    "+f"(d[O + 40]), "+f"(d[O + 41]), "+f"(d[O + 42]), "+f"(d[O + 43]), "+f"(d[O + 44]), "+f"(d[O + 45]), "+f"(d[O + 46]), "+f"(d[O + 47]),
    "+f"(d[O + 48]), "+f"(d[O + 49]), "+f"(d[O + 50]), "+f"(d[O + 51]), "+f"(d[O + 52]), "+f"(d[O + 53]), "+f"(d[O + 54]), "+f"(d[O + 55]),
    "+f"(d[O + 56]), "+f"(d[O + 57]), "+f"(d[O + 58]), "+f"(d[O + 59]), "+f"(d[O + 60]), "+f"(d[O + 61]), "+f"(d[O + 62]), "+f"(d[O + 63])
  : "r"(da), "r"(db), "n"(TA), "n"(TB), "n"(IA), "n"(IB));
}
template <int TA, int TB, uint32_t IA, uint32_t IB, int O = 0, int LEN> __device__ __forceinline__ void wgmma_192(float (&d)[LEN], uint32_t da, uint32_t db) {
  asm volatile("{\n.reg .b64 da, db;\n.reg .b32 la, lb;\nadd.u32 la, %96, %100;\nadd.u32 lb, %97, %101;\nmov.b64 da, {la, 0x40000040};\nmov.b64 db, {lb, 0x40000040};\n"
  "wgmma.mma_async.sync.aligned.m64n192k16.f32.bf16.bf16 {"
  "%0, %1, %2, %3, %4, %5, %6, %7, %8, %9, %10, %11, %12, %13, %14, %15, "
  "%16, %17, %18, %19, %20, %21, %22, %23, %24, %25, %26, %27, %28, %29, %30, %31, "
  "%32, %33, %34, %35, %36, %37, %38, %39, %40, %41, %42, %43, %44, %45, %46, %47, "
  "%48, %49, %50, %51, %52, %53, %54, %55, %56, %57, %58, %59, %60, %61, %62, %63, "
  "%64, %65, %66, %67, %68, %69, %70, %71, %72, %73, %74, %75, %76, %77, %78, %79, "
  "%80, %81, %82, %83, %84, %85, %86, %87, %88, %89, %90, %91, %92, %93, %94, %95"
  "}, da, db, 1, 1, 1, %98, %99;\n}\n"
  : "+f"(d[O + 0]), "+f"(d[O + 1]), "+f"(d[O + 2]), "+f"(d[O + 3]), "+f"(d[O + 4]), "+f"(d[O + 5]), "+f"(d[O + 6]), "+f"(d[O + 7]),
    "+f"(d[O + 8]), "+f"(d[O + 9]), "+f"(d[O + 10]), "+f"(d[O + 11]), "+f"(d[O + 12]), "+f"(d[O + 13]), "+f"(d[O + 14]), "+f"(d[O + 15]),
    "+f"(d[O + 16]), "+f"(d[O + 17]), "+f"(d[O + 18]), "+f"(d[O + 19]), "+f"(d[O + 20]), "+f"(d[O + 21]), "+f"(d[O + 22]), "+f"(d[O + 23]),
    "+f"(d[O + 24]), "+f"(d[O + 25]), "+f"(d[O + 26]), "+f"(d[O + 27]), "+f"(d[O + 28]), "+f"(d[O + 29]), "+f"(d[O + 30]), "+f"(d[O + 31]),
    "+f"(d[O + 32]), "+f"(d[O + 33]), "+f"(d[O + 34]), "+f"(d[O + 35]), "+f"(d[O + 36]), "+f"(d[O + 37]), "+f"(d[O + 38]), "+f"(d[O + 39]),
    "+f"(d[O + 40]), "+f"(d[O + 41]), "+f"(d[O + 42]), "+f"(d[O + 43]), "+f"(d[O + 44]), "+f"(d[O + 45]), "+f"(d[O + 46]), "+f"(d[O + 47]),
    "+f"(d[O + 48]), "+f"(d[O + 49]), "+f"(d[O + 50]), "+f"(d[O + 51]), "+f"(d[O + 52]), "+f"(d[O + 53]), "+f"(d[O + 54]), "+f"(d[O + 55]),
    "+f"(d[O + 56]), "+f"(d[O + 57]), "+f"(d[O + 58]), "+f"(d[O + 59]), "+f"(d[O + 60]), "+f"(d[O + 61]), "+f"(d[O + 62]), "+f"(d[O + 63]),
    "+f"(d[O + 64]), "+f"(d[O + 65]), "+f"(d[O + 66]), "+f"(d[O + 67]), "+f"(d[O + 68]), "+f"(d[O + 69]), "+f"(d[O + 70]), "+f"(d[O + 71]),
    "+f"(d[O + 72]), "+f"(d[O + 73]), "+f"(d[O + 74]), "+f"(d[O + 75]), "+f"(d[O + 76]), "+f"(d[O + 77]), "+f"(d[O + 78]), "+f"(d[O + 79]),
    "+f"(d[O + 80]), "+f"(d[O + 81]), "+f"(d[O + 82]), "+f"(d[O + 83]), "+f"(d[O + 84]), "+f"(d[O + 85]), "+f"(d[O + 86]), "+f"(d[O + 87]),
    "+f"(d[O + 88]), "+f"(d[O + 89]), "+f"(d[O + 90]), "+f"(d[O + 91]), "+f"(d[O + 92]), "+f"(d[O + 93]), "+f"(d[O + 94]), "+f"(d[O + 95])
  : "r"(da), "r"(db), "n"(TA), "n"(TB), "n"(IA), "n"(IB));
}
template <int TA, int TB, uint32_t IA, uint32_t IB, int O = 0, int LEN> __device__ __forceinline__ void wgmma_192z(float (&d)[LEN], uint32_t da, uint32_t db) {
  asm volatile("{\n.reg .b64 da, db;\n.reg .b32 la, lb;\nadd.u32 la, %96, %100;\nadd.u32 lb, %97, %101;\nmov.b64 da, {la, 0x40000040};\nmov.b64 db, {lb, 0x40000040};\n"
  "wgmma.mma_async.sync.aligned.m64n192k16.f32.bf16.bf16 {"
  "%0, %1, %2, %3, %4, %5, %6, %7, %8, %9, %10, %11, %12, %13, %14, %15, "
  "%16, %17, %18, %19, %20, %21, %22, %23, %24, %25, %26, %27, %28, %29, %30, %31, "
  "%32, %33, %34, %35, %36, %37, %38, %39, %40, %41, %42, %43, %44, %45, %46, %47, "
  "%48, %49, %50, %51, %52, %53, %54, %55, %56, %57, %58, %59, %60, %61, %62, %63, "
  "%64, %65, %66, %67, %68, %69, %70, %71, %72, %73, %74, %75, %76, %77, %78, %79, "
  "%80, %81, %82, %83, %84, %85, %86, %87, %88, %89, %90, %91, %92, %93, %94, %95"
  "}, da, db, 0, 1, 1, %98, %99;\n}\n"
  : "=f"(d[O + 0]), "=f"(d[O + 1]), "=f"(d[O + 2]), "=f"(d[O + 3]), "=f"(d[O + 4]), "=f"(d[O + 5]), "=f"(d[O + 6]), "=f"(d[O + 7]),
    "=f"(d[O + 8]), "=f"(d[O + 9]), "=f"(d[O + 10]), "=f"(d[O + 11]), "=f"(d[O + 12]), "=f"(d[O + 13]), "=f"(d[O + 14]), "=f"(d[O + 15]),
    "=f"(d[O + 16]), "=f"(d[O + 17]), "=f"(d[O + 18]), "=f"(d[O + 19]), "=f"(d[O + 20]), "=f"(d[O + 21]), "=f"(d[O + 22]), "=f"(d[O + 23]),
    "=f"(d[O + 24]), "=f"(d[O + 25]), "=f"(d[O + 26]), "=f"(d[O + 27]), "=f"(d[O + 28]), "=f"(d[O + 29]), "=f"(d[O + 30]), "=f"(d[O + 31]),
    "=f"(d[O + 32]), "=f"(d[O + 33]), "=f"(d[O + 34]), "=f"(d[O + 35]), "=f"(d[O + 36]), "=f"(d[O + 37]), "=f"(d[O + 38]), "=f"(d[O + 39]),
    "=f"(d[O + 40]), "=f"(d[O + 41]), "=f"(d[O + 42]), "=f"(d[O + 43]), "=f"(d[O + 44]), "=f"(d[O + 45]), "=f"(d[O + 46]), "=f"(d[O + 47]),
    "=f"(d[O + 48]), "=f"(d[O + 49]), "=f"(d[O + 50]), "=f"(d[O + 51]), "=f"(d[O + 52]), "=f"(d[O + 53]), "=f"(d[O + 54]), "=f"(d[O + 55]),
    "=f"(d[O + 56]), "=f"(d[O + 57]), "=f"(d[O + 58]), "=f"(d[O + 59]), "=f"(d[O + 60]), "=f"(d[O + 61]), "=f"(d[O + 62]), "=f"(d[O + 63]),
    "=f"(d[O + 64]), "=f"(d[O + 65]), "=f"(d[O + 66]), "=f"(d[O + 67]), "=f"(d[O + 68]), "=f"(d[O + 69]), "=f"(d[O + 70]), "=f"(d[O + 71]),
    "=f"(d[O + 72]), "=f"(d[O + 73]), "=f"(d[O + 74]), "=f"(d[O + 75]), "=f"(d[O + 76]), "=f"(d[O + 77]), "=f"(d[O + 78]), "=f"(d[O + 79]),
    "=f"(d[O + 80]), "=f"(d[O + 81]), "=f"(d[O + 82]), "=f"(d[O + 83]), "=f"(d[O + 84]), "=f"(d[O + 85]), "=f"(d[O + 86]), "=f"(d[O + 87]),
    "=f"(d[O + 88]), "=f"(d[O + 89]), "=f"(d[O + 90]), "=f"(d[O + 91]), "=f"(d[O + 92]), "=f"(d[O + 93]), "=f"(d[O + 94]), "=f"(d[O + 95])
  : "r"(da), "r"(db), "n"(TA), "n"(TB), "n"(IA), "n"(IB));
}
template <int TA, int TB, uint32_t IA, uint32_t IB, int O = 0, int LEN> __device__ __forceinline__ void wgmma_224(float (&d)[LEN], uint32_t da, uint32_t db) {
  asm volatile("{\n.reg .b64 da, db;\n.reg .b32 la, lb;\nadd.u32 la, %112, %116;\nadd.u32 lb, %113, %117;\nmov.b64 da, {la, 0x40000040};\nmov.b64 db, {lb, 0x40000040};\n"
  "wgmma.mma_async.sync.aligned.m64n224k16.f32.bf16.bf16 {"
  "%0, %1, %2, %3, %4, %5, %6, %7, %8, %9, %10, %11, %12, %13, %14, %15, "
  "%16, %17, %18, %19, %20, %21, %22, %23, %24, %25, %26, %27, %28, %29, %30, %31, "
  "%32, %33, %34, %35, %36, %37, %38, %39, %40, %41, %42, %43, %44, %45, %46, %47, "
  "%48, %49, %50, %51, %52, %53, %54, %55, %56, %57, %58, %59, %60, %61, %62, %63, "
  "%64, %65, %66, %67, %68, %69, %70, %71, %72, %73, %74, %75, %76, %77, %78, %79, "
  "%80, %81, %82, %83, %84, %85, %86, %87, %88, %89, %90, %91, %92, %93, %94, %95, "
  "%96, %97, %98, %99, %100, %101, %102, %103, %104, %105, %106, %107, %108, %109, %110, %111"
  "}, da, db, 1, 1, 1, %114, %115;\n}\n"
  : "+f"(d[O + 0]), "+f"(d[O + 1]), "+f"(d[O + 2]), "+f"(d[O + 3]), "+f"(d[O + 4]), "+f"(d[O + 5]), "+f"(d[O + 6]), "+f"(d[O + 7]),
    "+f"(d[O + 8]), "+f"(d[O + 9]), "+f"(d[O + 10]), "+f"(d[O + 11]), "+f"(d[O + 12]), "+f"(d[O + 13]), "+f"(d[O + 14]), "+f"(d[O + 15]),
    "+f"(d[O + 16]), "+f"(d[O + 17]), "+f"(d[O + 18]), "+f"(d[O + 19]), "+f"(d[O + 20]), "+f"(d[O + 21]), "+f"(d[O + 22]), "+f"(d[O + 23]),
    "+f"(d[O + 24]), "+f"(d[O + 25]), "+f"(d[O + 26]), "+f"(d[O + 27]), "+f"(d[O + 28]), "+f"(d[O + 29]), "+f"(d[O + 30]), "+f"(d[O + 31]),
    "+f"(d[O + 32]), "+f"(d[O + 33]), "+f"(d[O + 34]), "+f"(d[O + 35]), "+f"(d[O + 36]), "+f"(d[O + 37]), "+f"(d[O + 38]), "+f"(d[O + 39]),
    "+f"(d[O + 40]), "+f"(d[O + 41]), "+f"(d[O + 42]), "+f"(d[O + 43]), "+f"(d[O + 44]), "+f"(d[O + 45]), "+f"(d[O + 46]), "+f"(d[O + 47]),
    "+f"(d[O + 48]), "+f"(d[O + 49]), "+f"(d[O + 50]), "+f"(d[O + 51]), "+f"(d[O + 52]), "+f"(d[O + 53]), "+f"(d[O + 54]), "+f"(d[O + 55]),
    "+f"(d[O + 56]), "+f"(d[O + 57]), "+f"(d[O + 58]), "+f"(d[O + 59]), "+f"(d[O + 60]), "+f"(d[O + 61]), "+f"(d[O + 62]), "+f"(d[O + 63]),
    "+f"(d[O + 64]), "+f"(d[O + 65]), "+f"(d[O + 66]), "+f"(d[O + 67]), "+f"(d[O + 68]), "+f"(d[O + 69]), "+f"(d[O + 70]), "+f"(d[O + 71]),
    "+f"(d[O + 72]), "+f"(d[O + 73]), "+f"(d[O + 74]), "+f"(d[O + 75]), "+f"(d[O + 76]), "+f"(d[O + 77]), "+f"(d[O + 78]), "+f"(d[O + 79]),
    "+f"(d[O + 80]), "+f"(d[O + 81]), "+f"(d[O + 82]), "+f"(d[O + 83]), "+f"(d[O + 84]), "+f"(d[O + 85]), "+f"(d[O + 86]), "+f"(d[O + 87]),
    "+f"(d[O + 88]), "+f"(d[O + 89]), "+f"(d[O + 90]), "+f"(d[O + 91]), "+f"(d[O + 92]), "+f"(d[O + 93]), "+f"(d[O + 94]), "+f"(d[O + 95]),
    "+f"(d[O + 96]), "+f"(d[O + 97]), "+f"(d[O + 98]), "+f"(d[O + 99]), "+f"(d[O + 100]), "+f"(d[O + 101]), "+f"(d[O + 102]), "+f"(d[O + 103]),
    "+f"(d[O + 104]), "+f"(d[O + 105]), "+f"(d[O + 106]), "+f"(d[O + 107]), "+f"(d[O + 108]), "+f"(d[O + 109]), "+f"(d[O + 110]), "+f"(d[O + 111])
  : "r"(da), "r"(db), "n"(TA), "n"(TB), "n"(IA), "n"(IB));
}
__device__ __forceinline__ void wgmma_rs_192(float (&d)[96], uint32_t a0, uint32_t a1, uint32_t a2, uint32_t a3, uint64_t db) {
  asm volatile("wgmma.mma_async.sync.aligned.m64n192k16.f32.bf16.bf16 {"
  "%0, %1, %2, %3, %4, %5, %6, %7, %8, %9, %10, %11, %12, %13, %14, %15, "
  "%16, %17, %18, %19, %20, %21, %22, %23, %24, %25, %26, %27, %28, %29, %30, %31, "
  "%32, %33, %34, %35, %36, %37, %38, %39, %40, %41, %42, %43, %44, %45, %46, %47, "
  "%48, %49, %50, %51, %52, %53, %54, %55, %56, %57, %58, %59, %60, %61, %62, %63, "
  "%64, %65, %66, %67, %68, %69, %70, %71, %72, %73, %74, %75, %76, %77, %78, %79, "
  "%80, %81, %82, %83, %84, %85, %86, %87, %88, %89, %90, %91, %92, %93, %94, %95"
  "}, {%96, %97, %98, %99}, %100, 1, 1, 1, 1;\n"
  : "+f"(d[0]), "+f"(d[1]), "+f"(d[2]), "+f"(d[3]), "+f"(d[4]), "+f"(d[5]), "+f"(d[6]), "+f"(d[7]),
    "+f"(d[8]), "+f"(d[9]), "+f"(d[10]), "+f"(d[11]), "+f"(d[12]), "+f"(d[13]), "+f"(d[14]), "+f"(d[15]),
    "+f"(d[16]), "+f"(d[17]), "+f"(d[18]), "+f"(d[19]), "+f"(d[20]), "+f"(d[21]), "+f"(d[22]), "+f"(d[23]),
    "+f"(d[24]), "+f"(d[25]), "+f"(d[26]), "+f"(d[27]), "+f"(d[28]), "+f"(d[29]), "+f"(d[30]), "+f"(d[31]),
    "+f"(d[32]), "+f"(d[33]), "+f"(d[34]), "+f"(d[35]), "+f"(d[36]), "+f"(d[37]), "+f"(d[38]), "+f"(d[39]),
    "+f"(d[40]), "+f"(d[41]), "+f"(d[42]), "+f"(d[43]), "+f"(d[44]), "+f"(d[45]), "+f"(d[46]), "+f"(d[47]),
    "+f"(d[48]), "+f"(d[49]), "+f"(d[50]), "+f"(d[51]), "+f"(d[52]), "+f"(d[53]), "+f"(d[54]), "+f"(d[55]),
    "+f"(d[56]), "+f"(d[57]), "+f"(d[58]), "+f"(d[59]), "+f"(d[60]), "+f"(d[61]), "+f"(d[62]), "+f"(d[63]),
    "+f"(d[64]), "+f"(d[65]), "+f"(d[66]), "+f"(d[67]), "+f"(d[68]), "+f"(d[69]), "+f"(d[70]), "+f"(d[71]),
    "+f"(d[72]), "+f"(d[73]), "+f"(d[74]), "+f"(d[75]), "+f"(d[76]), "+f"(d[77]), "+f"(d[78]), "+f"(d[79]),
    "+f"(d[80]), "+f"(d[81]), "+f"(d[82]), "+f"(d[83]), "+f"(d[84]), "+f"(d[85]), "+f"(d[86]), "+f"(d[87]),
    "+f"(d[88]), "+f"(d[89]), "+f"(d[90]), "+f"(d[91]), "+f"(d[92]), "+f"(d[93]), "+f"(d[94]), "+f"(d[95])
  : "r"(a0), "r"(a1), "r"(a2), "r"(a3), "l"(db));
}
__device__ __forceinline__ void wgmma_rs_224z(float (&d)[112], uint32_t a0, uint32_t a1, uint32_t a2, uint32_t a3, uint64_t db) {
  asm volatile("wgmma.mma_async.sync.aligned.m64n224k16.f32.bf16.bf16 {"
  "%0, %1, %2, %3, %4, %5, %6, %7, %8, %9, %10, %11, %12, %13, %14, %15, "
  "%16, %17, %18, %19, %20, %21, %22, %23, %24, %25, %26, %27, %28, %29, %30, %31, "
  "%32, %33, %34, %35, %36, %37, %38, %39, %40, %41, %42, %43, %44, %45, %46, %47, "
  "%48, %49, %50, %51, %52, %53, %54, %55, %56, %57, %58, %59, %60, %61, %62, %63, "
  "%64, %65, %66, %67, %68, %69, %70, %71, %72, %73, %74, %75, %76, %77, %78, %79, "
  "%80, %81, %82, %83, %84, %85, %86, %87, %88, %89, %90, %91, %92, %93, %94, %95, "
  "%96, %97, %98, %99, %100, %101, %102, %103, %104, %105, %106, %107, %108, %109, %110, %111"
  "}, {%112, %113, %114, %115}, %116, 0, 1, 1, 1;\n"
  : "=f"(d[0]), "=f"(d[1]), "=f"(d[2]), "=f"(d[3]), "=f"(d[4]), "=f"(d[5]), "=f"(d[6]), "=f"(d[7]),
    "=f"(d[8]), "=f"(d[9]), "=f"(d[10]), "=f"(d[11]), "=f"(d[12]), "=f"(d[13]), "=f"(d[14]), "=f"(d[15]),
    "=f"(d[16]), "=f"(d[17]), "=f"(d[18]), "=f"(d[19]), "=f"(d[20]), "=f"(d[21]), "=f"(d[22]), "=f"(d[23]),
    "=f"(d[24]), "=f"(d[25]), "=f"(d[26]), "=f"(d[27]), "=f"(d[28]), "=f"(d[29]), "=f"(d[30]), "=f"(d[31]),
    "=f"(d[32]), "=f"(d[33]), "=f"(d[34]), "=f"(d[35]), "=f"(d[36]), "=f"(d[37]), "=f"(d[38]), "=f"(d[39]),
    "=f"(d[40]), "=f"(d[41]), "=f"(d[42]), "=f"(d[43]), "=f"(d[44]), "=f"(d[45]), "=f"(d[46]), "=f"(d[47]),
    "=f"(d[48]), "=f"(d[49]), "=f"(d[50]), "=f"(d[51]), "=f"(d[52]), "=f"(d[53]), "=f"(d[54]), "=f"(d[55]),
    "=f"(d[56]), "=f"(d[57]), "=f"(d[58]), "=f"(d[59]), "=f"(d[60]), "=f"(d[61]), "=f"(d[62]), "=f"(d[63]),
    "=f"(d[64]), "=f"(d[65]), "=f"(d[66]), "=f"(d[67]), "=f"(d[68]), "=f"(d[69]), "=f"(d[70]), "=f"(d[71]),
    "=f"(d[72]), "=f"(d[73]), "=f"(d[74]), "=f"(d[75]), "=f"(d[76]), "=f"(d[77]), "=f"(d[78]), "=f"(d[79]),
    "=f"(d[80]), "=f"(d[81]), "=f"(d[82]), "=f"(d[83]), "=f"(d[84]), "=f"(d[85]), "=f"(d[86]), "=f"(d[87]),
    "=f"(d[88]), "=f"(d[89]), "=f"(d[90]), "=f"(d[91]), "=f"(d[92]), "=f"(d[93]), "=f"(d[94]), "=f"(d[95]),
    "=f"(d[96]), "=f"(d[97]), "=f"(d[98]), "=f"(d[99]), "=f"(d[100]), "=f"(d[101]), "=f"(d[102]), "=f"(d[103]),
    "=f"(d[104]), "=f"(d[105]), "=f"(d[106]), "=f"(d[107]), "=f"(d[108]), "=f"(d[109]), "=f"(d[110]), "=f"(d[111])
  : "r"(a0), "r"(a1), "r"(a2), "r"(a3), "l"(db));
}

__device__ __forceinline__ uint32_t smem_u32(const void* p) { return (uint32_t)__cvta_generic_to_shared(p); }
__device__ __forceinline__ void mbar_init(uint32_t bar, uint32_t cnt) { asm volatile("mbarrier.init.shared::cta.b64 [%0], %1;" ::"r"(bar), "r"(cnt) : "memory"); }
__device__ __forceinline__ void mbar_expect(uint32_t bar, uint32_t bytes) { asm volatile("mbarrier.arrive.expect_tx.shared::cta.b64 _, [%0], %1;" ::"r"(bar), "r"(bytes) : "memory"); }
__device__ __forceinline__ void mbar_arrive(uint32_t bar) { asm volatile("mbarrier.arrive.shared::cta.b64 _, [%0];" ::"r"(bar) : "memory"); }
__device__ __forceinline__ void mbar_arrive_cl(uint32_t cbar) { asm volatile("mbarrier.arrive.shared::cluster.b64 _, [%0];" ::"r"(cbar) : "memory"); }
__device__ __forceinline__ uint32_t mapa(uint32_t a, uint32_t cta) { uint32_t r; asm("mapa.shared::cluster.u32 %0, %1, %2;" : "=r"(r) : "r"(a), "r"(cta)); return r; }
__device__ __forceinline__ void mbar_wait(uint32_t bar, uint32_t parity) {
  asm volatile("{\n.reg .pred p;\n.reg .u32 n;\nmov.u32 n, 0;\n"
    "LAB_WAIT:\n"
    "mbarrier.try_wait.parity.shared::cta.b64 p, [%0], %1;\n"
    "@p bra LAB_DONE;\n"
    "add.u32 n, n, 1;\n"
    "setp.lt.u32 p, n, 2000000;\n"
    "@p bra LAB_WAIT;\n"
    "trap;\n"
    "LAB_DONE:\n}\n" ::"r"(bar), "r"(parity) : "memory");
}
constexpr uint32_t SPIN_MAX = 2000000;
__device__ __forceinline__ void tma2d(uint32_t dst, const CUtensorMap* m, uint32_t bar, int c0, int c1) {
  asm volatile("cp.async.bulk.tensor.2d.shared::cluster.global.mbarrier::complete_tx::bytes [%0], [%1, {%3, %4}], [%2];"
    ::"r"(dst), "l"(m), "r"(bar), "r"(c0), "r"(c1) : "memory");
}
__device__ __forceinline__ void tma2d_mc(uint32_t dst, const CUtensorMap* m, uint32_t bar, int c0, int c1) {
  asm volatile("cp.async.bulk.tensor.2d.shared::cluster.global.mbarrier::complete_tx::bytes.multicast::cluster [%0], [%1, {%3, %4}], [%2], %5;"
    ::"r"(dst), "l"(m), "r"(bar), "r"(c0), "r"(c1), "h"((uint16_t)3) : "memory");
}
__device__ __forceinline__ void tma3d(uint32_t dst, const CUtensorMap* m, uint32_t bar, int c0, int c1, int c2) {
  asm volatile("cp.async.bulk.tensor.3d.shared::cluster.global.mbarrier::complete_tx::bytes [%0], [%1, {%3, %4, %5}], [%2];"
    ::"r"(dst), "l"(m), "r"(bar), "r"(c0), "r"(c1), "r"(c2) : "memory");
}
__device__ __forceinline__ void tma3d_mc(uint32_t dst, const CUtensorMap* m, uint32_t bar, int c0, int c1, int c2) {
  asm volatile("cp.async.bulk.tensor.3d.shared::cluster.global.mbarrier::complete_tx::bytes.multicast::cluster [%0], [%1, {%3, %4, %5}], [%2], %6;"
    ::"r"(dst), "l"(m), "r"(bar), "r"(c0), "r"(c1), "r"(c2), "h"((uint16_t)3) : "memory");
}
__device__ __forceinline__ void bulk_ld(uint32_t dst, const void* src, uint32_t bytes, uint32_t bar) {
  asm volatile("cp.async.bulk.shared::cluster.global.mbarrier::complete_tx::bytes [%0], [%1], %2, [%3];" ::"r"(dst), "l"(src), "r"(bytes), "r"(bar) : "memory");
}
__device__ __forceinline__ void bulk_ld_mc(uint32_t dst, const void* src, uint32_t bytes, uint32_t bar) {
  asm volatile("cp.async.bulk.shared::cluster.global.mbarrier::complete_tx::bytes.multicast::cluster [%0], [%1], %2, [%3], %4;"
    ::"r"(dst), "l"(src), "r"(bytes), "r"(bar), "h"((uint16_t)3) : "memory");
}
__device__ __forceinline__ void bulk_st(void* dst, uint32_t src, uint32_t bytes) {
  asm volatile("cp.async.bulk.global.shared::cta.bulk_group [%0], [%1], %2;" ::"l"(dst), "r"(src), "r"(bytes) : "memory");
}
__device__ __forceinline__ void bulk_commit() { asm volatile("cp.async.bulk.commit_group;" ::: "memory"); }
__device__ __forceinline__ void bulk_wait0() { asm volatile("cp.async.bulk.wait_group 0;" ::: "memory"); }
__device__ __forceinline__ void fence_async_smem() { asm volatile("fence.proxy.async.shared::cta;" ::: "memory"); }
__device__ __forceinline__ void wg_fence() { asm volatile("wgmma.fence.sync.aligned;" ::: "memory"); }
__device__ __forceinline__ void wg_commit() { asm volatile("wgmma.commit_group.sync.aligned;" ::: "memory"); }
template <int N> __device__ __forceinline__ void wg_wait() { asm volatile("wgmma.wait_group.sync.aligned %0;" ::"n"(N) : "memory"); }
template <int R> __device__ __forceinline__ void reg_alloc() { asm volatile("setmaxnreg.inc.sync.aligned.u32 %0;" ::"n"(R)); }
template <int R> __device__ __forceinline__ void reg_dealloc() { asm volatile("setmaxnreg.dec.sync.aligned.u32 %0;" ::"n"(R)); }
__device__ __forceinline__ void cluster_bar() { asm volatile("barrier.cluster.arrive.relaxed;\nbarrier.cluster.wait;" ::: "memory"); }
template <int ID> __device__ __forceinline__ void nb_sync(int n) { asm volatile("barrier.sync %0, %1;" ::"n"(ID), "r"(n) : "memory"); }
template <int ID> __device__ __forceinline__ void nb_arrive(int n) { asm volatile("barrier.arrive %0, %1;" ::"n"(ID), "r"(n) : "memory"); }
__device__ __forceinline__ int fresh_tid() { int t; asm volatile("mov.u32 %0, %%tid.x;" : "=r"(t)); return t; }
__device__ __forceinline__ void sched_fence(uint32_t z) { asm volatile("{\n.reg .pred p;\nsetp.ne.u32 p, %0, 0;\nLAB_S:\n@p nanosleep.u32 0;\n@p bra LAB_S;\n}\n" ::"r"(z) : "memory"); }
__device__ __forceinline__ float rsq(float x) { float y; asm("rsqrt.approx.ftz.f32 %0, %1;" : "=f"(y) : "f"(x)); return y; }
__device__ __forceinline__ int opq(int v) { asm volatile("" : "+r"(v)); return v; }
template <int V> struct Int { static constexpr int value = V; };
struct True { static constexpr bool value = true; };
struct False { static constexpr bool value = false; };
template <int N> __device__ __forceinline__ void fence_regs(float (&d)[N]) {
#pragma unroll
  for (int i = 0; i < N; i++) asm volatile("" : "+f"(d[i])::"memory");
}
__host__ __device__ constexpr uint32_t DI(uint32_t off, uint32_t lbo) { return (off >> 4) + ((lbo >> 4) << 16); }
template <int K, int N, class F> __device__ __forceinline__ void static_for(F f) { if constexpr (K < N) { f(Int<K>{}); static_for<K + 1, N>(f); } }
__device__ __forceinline__ uint64_t mkdesc_vec(uint32_t addr, uint32_t sbo) { return (uint64_t)((addr & 0x3FFFF) >> 4) | ((uint64_t)(sbo >> 4) << 32); }
__device__ __forceinline__ void sts16(uint32_t a, uint32_t v) { asm volatile("st.shared.u16 [%0], %1;" ::"r"(a), "h"((uint16_t)v) : "memory"); }
__device__ __forceinline__ uint32_t pack2(float lo, float hi) { uint32_t r; asm("cvt.rn.bf16x2.f32 %0, %1, %2;" : "=r"(r) : "f"(hi), "f"(lo)); return r; }
__device__ __forceinline__ float bf_lo(uint32_t v) { return __uint_as_float(v << 16); }
__device__ __forceinline__ float bf_hi(uint32_t v) { return __uint_as_float(v & 0xffff0000u); }
__device__ __forceinline__ void stsm4(uint32_t a, uint32_t r0, uint32_t r1, uint32_t r2, uint32_t r3) {
  asm volatile("stmatrix.sync.aligned.m8n8.x4.shared.b16 [%0], {%1, %2, %3, %4};" ::"r"(a), "r"(r0), "r"(r1), "r"(r2), "r"(r3) : "memory");
}
__device__ __forceinline__ void stsm4t(uint32_t a, uint32_t r0, uint32_t r1, uint32_t r2, uint32_t r3) {
  asm volatile("stmatrix.sync.aligned.m8n8.x4.trans.shared.b16 [%0], {%1, %2, %3, %4};" ::"r"(a), "r"(r0), "r"(r1), "r"(r2), "r"(r3) : "memory");
}
__device__ __forceinline__ void ldsm4(uint32_t a, uint32_t& r0, uint32_t& r1, uint32_t& r2, uint32_t& r3) {
  asm volatile("ldmatrix.sync.aligned.m8n8.x4.shared.b16 {%0, %1, %2, %3}, [%4];" : "=r"(r0), "=r"(r1), "=r"(r2), "=r"(r3) : "r"(a) : "memory");
}
__device__ __forceinline__ void ldsm4t(uint32_t a, uint32_t& r0, uint32_t& r1, uint32_t& r2, uint32_t& r3) {
  asm volatile("ldmatrix.sync.aligned.m8n8.x4.trans.shared.b16 {%0, %1, %2, %3}, [%4];" : "=r"(r0), "=r"(r1), "=r"(r2), "=r"(r3) : "r"(a) : "memory");
}
__device__ __forceinline__ void mma16816(float (&c)[4], uint32_t a0, uint32_t a1, uint32_t a2, uint32_t a3, uint32_t b0, uint32_t b1) {
  asm volatile("mma.sync.aligned.m16n8k16.row.col.f32.bf16.bf16.f32 {%0, %1, %2, %3}, {%4, %5, %6, %7}, {%8, %9}, {%10, %11, %12, %13};"
    : "=f"(c[0]), "=f"(c[1]), "=f"(c[2]), "=f"(c[3]) : "r"(a0), "r"(a1), "r"(a2), "r"(a3), "r"(b0), "r"(b1), "f"(c[0]), "f"(c[1]), "f"(c[2]), "f"(c[3]));
}
__device__ __forceinline__ void sts128(uint32_t a, uint32_t r0, uint32_t r1, uint32_t r2, uint32_t r3) {
  asm volatile("st.shared.v4.b32 [%0], {%1, %2, %3, %4};" ::"r"(a), "r"(r0), "r"(r1), "r"(r2), "r"(r3) : "memory");
}
__device__ __forceinline__ void lds128(uint32_t a, uint32_t& r0, uint32_t& r1, uint32_t& r2, uint32_t& r3) {
  asm volatile("ld.shared.v4.b32 {%0, %1, %2, %3}, [%4];" : "=r"(r0), "=r"(r1), "=r"(r2), "=r"(r3) : "r"(a) : "memory");
}
__device__ __forceinline__ float2 lds64f(uint32_t a) { float2 v; asm volatile("ld.shared.v2.f32 {%0, %1}, [%2];" : "=f"(v.x), "=f"(v.y) : "r"(a) : "memory"); return v; }
__device__ __forceinline__ float4 lds128f(uint32_t a) { float4 v; asm volatile("ld.shared.v4.f32 {%0, %1, %2, %3}, [%4];" : "=f"(v.x), "=f"(v.y), "=f"(v.z), "=f"(v.w) : "r"(a) : "memory"); return v; }
__device__ __forceinline__ void sts64f(uint32_t a, float x, float y) { asm volatile("st.shared.v2.f32 [%0], {%1, %2};" ::"r"(a), "f"(x), "f"(y) : "memory"); }
__device__ __forceinline__ float lds32f(uint32_t a) { float v; asm volatile("ld.shared.f32 %0, [%1];" : "=f"(v) : "r"(a) : "memory"); return v; }
__device__ __forceinline__ void sts32f(uint32_t a, float x) { asm volatile("st.shared.f32 [%0], %1;" ::"r"(a), "f"(x) : "memory"); }
__device__ __forceinline__ void stat_st(uint2* p, float sum, float sq, uint32_t tag, bool on) {
  const float mean = sum * (1.f / 128), m2 = fmaxf(fmaf(-mean, sum, sq), 0.f);
  const uint32_t a = ((__float_as_uint(mean) + 8u) & ~15u) | (tag & 15u), b = ((__float_as_uint(m2) + 8u) & ~15u) | (tag & 15u);
  asm volatile("{\n.reg .b64 x;\n.reg .pred p;\nsetp.ne.u32 p, %3, 0;\nmov.b64 x, {%1, %2};\n@p st.relaxed.gpu.global.b64 [%0], x;\n}\n" ::"l"(p), "r"(a), "r"(b), "r"((uint32_t)on) : "memory");
}
__device__ __forceinline__ void stat_ld2(const uint2* p, uint32_t (&v)[4]) {
  asm volatile("{\n.reg .b64 x, y;\nld.relaxed.gpu.global.v2.b64 {x, y}, [%4];\nmov.b64 {%0, %1}, x;\nmov.b64 {%2, %3}, y;\n}\n"
    : "=r"(v[0]), "=r"(v[1]), "=r"(v[2]), "=r"(v[3]) : "l"(p) : "memory");
}
__device__ __forceinline__ float untag(uint32_t v) { return __uint_as_float(v & ~15u); }
__device__ __forceinline__ void ll_st3(uint4* p, uint32_t a, uint32_t b, uint32_t c, uint32_t tag) {
  asm volatile("{\n.reg .b64 x, y;\n.reg .b128 z;\nmov.b64 x, {%1, %2};\nmov.b64 y, {%3, %4};\nmov.b128 z, {x, y};\nst.relaxed.gpu.global.b128 [%0], z;\n}\n"
    ::"l"(p), "r"(a), "r"(b), "r"(c), "r"(tag) : "memory");
}
__device__ __forceinline__ uint32_t ll_ld3(const uint4* p, uint32_t& a, uint32_t& b, uint32_t& c, uint32_t tag) {
  uint32_t t;
  asm volatile("{\n.reg .b64 x, y;\n.reg .b128 z;\nld.relaxed.gpu.global.b128 z, [%4];\nmov.b128 {x, y}, z;\nmov.b64 {%0, %1}, x;\nmov.b64 {%2, %3}, y;\n}\n"
    : "=r"(a), "=r"(b), "=r"(c), "=r"(t) : "l"(p) : "memory");
  return t ^ tag;
}
__device__ __forceinline__ void halo_send(uint4* p, uint32_t a, const uint32_t (&tg)[6]) {
  asm volatile("{\n.reg .b64 x<6>, y<6>, w<2>;\n.reg .b32 c<4>;\n.reg .b128 z<6>;\n"
    "ld.shared.b64 w0, [%1+1536];\nld.shared.b64 w1, [%1+1792];\n"
    "ld.shared.b64 x0, [%1];\nld.shared.b64 x1, [%1+256];\nld.shared.b64 x2, [%1+512];\n"
    "ld.shared.b64 x3, [%1+768];\nld.shared.b64 x4, [%1+1024];\nld.shared.b64 x5, [%1+1280];\n"
    "mov.b64 {c0, c1}, w0;\nmov.b64 {c2, c3}, w1;\n"
    "mov.b64 y0, {c0, %2};\nmov.b64 y1, {c1, %3};\nmov.b64 y2, {c2, %4};\nmov.b64 y3, {c3, %5};\nmov.b64 y4, {%6, %6};\nmov.b64 y5, {%7, %7};\n"
    "mov.b128 z0, {x0, y0};\nmov.b128 z1, {x1, y1};\nmov.b128 z2, {x2, y2};\nmov.b128 z3, {x3, y3};\nmov.b128 z4, {x4, y4};\nmov.b128 z5, {x5, y5};\n"
    "st.relaxed.gpu.global.b128 [%0], z0;\nst.relaxed.gpu.global.b128 [%0+512], z1;\nst.relaxed.gpu.global.b128 [%0+1024], z2;\n"
    "st.relaxed.gpu.global.b128 [%0+1536], z3;\nst.relaxed.gpu.global.b128 [%0+2048], z4;\nst.relaxed.gpu.global.b128 [%0+2560], z5;\n}\n"
    ::"l"(p), "r"(a), "r"(tg[0]), "r"(tg[1]), "r"(tg[2]), "r"(tg[3]), "r"(tg[4]), "r"(tg[5]) : "memory");
}
template <int N> __device__ __forceinline__ void copy_out(uint8_t* dst, uint32_t src, int stride) {
  uint4 v[N];
#pragma unroll
  for (int k = 0; k < N; k++) lds128(src + k * stride, v[k].x, v[k].y, v[k].z, v[k].w);
#pragma unroll
  for (int k = 0; k < N; k++) asm volatile("st.global.v4.b32 [%0], {%1, %2, %3, %4};" ::"l"(dst + k * stride), "r"(v[k].x), "r"(v[k].y), "r"(v[k].z), "r"(v[k].w) : "memory");
}
__device__ __forceinline__ void warp_store(uint8_t* dst, uint32_t src, int bytes, uint32_t delay, uint32_t pace) {
  __nanosleep(delay);
#pragma unroll 1
  for (int o = 0; o < bytes; o += 2048) {
    if (pace) __nanosleep(pace);
    uint4 v[4];
#pragma unroll
    for (int k = 0; k < 4; k++) lds128(src + o + k * 512, v[k].x, v[k].y, v[k].z, v[k].w);
#pragma unroll
    for (int k = 0; k < 4; k++) asm volatile("st.global.v4.b32 [%0], {%1, %2, %3, %4};" ::"l"(dst + o + k * 512), "r"(v[k].x), "r"(v[k].y), "r"(v[k].z), "r"(v[k].w) : "memory");
  }
  __syncwarp();
}
__device__ __forceinline__ uint32_t clock32() { uint32_t t; asm volatile("mov.u32 %0, %%clock;" : "=r"(t)); return t; }
__device__ __forceinline__ void flag_set(uint32_t* p, uint32_t bit) { asm volatile("red.release.gpu.global.xor.b32 [%0], %1;" ::"l"(p), "r"(bit) : "memory"); }
__device__ __forceinline__ void flag_wait(const uint32_t* p, uint32_t inv, uint32_t need, uint32_t& ready) {
  if ((ready & need) == need) return;
  uint32_t n = 0;
  do {
    asm volatile("ld.relaxed.gpu.global.b32 %0, [%1];" : "=r"(ready) : "l"(p) : "memory");
    ready = __shfl_sync(0xffffffffu, ready, 0) ^ inv;
  } while ((ready & need) != need && ++n < SPIN_MAX);
  asm volatile("fence.acquire.gpu;\nfence.proxy.async.global;" ::: "memory");
}
__device__ __forceinline__ bool elect_one() {
  uint32_t p;
  asm volatile("{\n.reg .pred P;\nelect.sync _|P, 0xffffffff;\nselp.u32 %0, 1, 0, P;\n}\n" : "=r"(p));
  return p;
}
__device__ __forceinline__ float gelu_half(float hx) {
  const float y = hx * fmaf(hx * hx, 8.f * 0.0356774081f, 2.f * 0.7978845608f);
  float th;
  asm("tanh.approx.f32 %0, %1;" : "=f"(th) : "f"(y));
  return fmaf(hx, th, hx);
}
__device__ __forceinline__ float ex2(float x) { float y; asm("ex2.approx.ftz.f32 %0, %1;" : "=f"(y) : "f"(x)); return y; }

__device__ __forceinline__ void stat_combine(uint32_t am, uint32_t aq, uint32_t bm, uint32_t bq, float pv, float& mean, float& var) {
  const float d0 = untag(am) - pv, d1 = untag(bm) - pv;
  float s = d0 + d1, q = fmaf(fmaf(d0, d0, d1 * d1), 128.f, untag(aq) + untag(bq));
  s += __shfl_xor_sync(0xffffffffu, s, 8); q += __shfl_xor_sync(0xffffffffu, q, 8);
  s += __shfl_xor_sync(0xffffffffu, s, 16); q += __shfl_xor_sync(0xffffffffu, q, 16);
  s *= 0.125f;
  mean = pv + s;
  var = fmaxf(fmaf(-s, s, q * (1.f / D_)), 0.f);
}

__device__ __forceinline__ void attn_logits(const uint32_t* q0, const uint32_t* q1,
                                            const uint32_t* k0, const uint32_t* k1, const uint32_t* k2, const uint32_t* k3,
                                            float mk0, float mk1, float (&s)[4][4]) {
#pragma unroll
  for (int n = 0; n < 4; n++) {
    const uint32_t* k = n == 0 ? k0 : n == 1 ? k1 : n == 2 ? k2 : k3;
    s[n][0] = s[n][1] = n < 2 ? mk0 : 0.f; s[n][2] = s[n][3] = n < 2 ? mk1 : 0.f;
    mma16816(s[n], q0[0], q1[0], q0[1], q1[1], k[0], k[1]);
    mma16816(s[n], q0[2], q1[2], q0[3], q1[3], k[2], k[3]);
  }
}
__device__ __forceinline__ void attn_probs(const float (&s)[4][4], float sc0, float sc1, bool e, bool zneg, const uint32_t (&sel)[3],
                                           uint32_t (&pr)[6], float (&l)[2]) {
  float a0 = e ? s[1][1] : s[1][0];
  float b0 = zneg ? (e ? s[0][1] : s[0][0]) : (e ? s[2][1] : s[2][0]);
  float a1 = e ? s[2][3] : s[2][2];
  float b1 = zneg ? (e ? s[1][3] : s[1][2]) : (e ? s[3][3] : s[3][2]);
  float m0 = fmaxf(a0, b0), m1 = fmaxf(a1, b1);
  m0 = fmaxf(m0, __shfl_xor_sync(0xffffffffu, m0, 1)); m1 = fmaxf(m1, __shfl_xor_sync(0xffffffffu, m1, 1));
  m0 = fmaxf(m0, __shfl_xor_sync(0xffffffffu, m0, 2)); m1 = fmaxf(m1, __shfl_xor_sync(0xffffffffu, m1, 2));
  a0 = ex2((a0 - m0) * sc0); b0 = ex2((b0 - m0) * sc0); a1 = ex2((a1 - m1) * sc1); b1 = ex2((b1 - m1) * sc1);
  l[0] = a0 + b0; l[1] = a1 + b1;
  const uint32_t p0 = pack2(a0, b0), p1 = pack2(a1, b1);
#pragma unroll
  for (int k = 0; k < 3; k++) { pr[k] = __byte_perm(p0, 0u, sel[k]); pr[3 + k] = __byte_perm(p1, 0u, sel[k]); }
}
__device__ __forceinline__ void attn_pv(const uint32_t (&pr)[6], const uint32_t* vh, const uint32_t* v, float (&o)[4][4]) {
#pragma unroll
  for (int dt = 0; dt < 4; dt++) {
    o[dt][0] = o[dt][1] = o[dt][2] = o[dt][3] = 0.f;
    mma16816(o[dt], pr[0], 0u, pr[1], pr[3], vh[2 * dt], vh[2 * dt + 1]);
    mma16816(o[dt], pr[2], pr[4], 0u, pr[5], v[2 * dt], v[2 * dt + 1]);
  }
}

#define ATT 25
#define COVER 2
#define HALO_A_NS 300
#define H1D 900
#define FO 2
#define G4GATE 1
#define PFM 7
#define PD1 3
#define PD2 5
#define PD3 3
#define PD4 5
#define FR 1
#define XG 1
#define KF 1
#define VL 1
#define U0D 300
#define X1D 1200
#define PACE 150
#define LEAD1 3
#define LEAD2 3
#define XLD 7
#define XST 2
#define FA 20
#define LEAD4 4
#define STAT_CLK 150
__global__ void __cluster_dims__(2, 1, 1) __launch_bounds__(384, 1) fused_kernel(const __grid_constant__ Params P) {
  extern __shared__ __align__(1024) uint8_t smem_raw[];
  const uint32_t sb = smem_u32(smem_raw);
  const uint32_t bars = sb + OFF_BAR;
  const int tid = threadIdx.x;
  if (tid == 256) S5(0);
  const int wu = __shfl_sync(0xffffffffu, tid >> 5, 0), wg = wu >> 2;
  const int r = blockIdx.x & 1, cl = blockIdx.x >> 1;
  int grp, slt;
  if (cl < 4) { grp = 0; slt = 4 + cl; }
  else if (cl < 36) { grp = (cl - 4) & 7; slt = (cl - 4) >> 3; }
  else { grp = 1 + (cl - 36) % 7; slt = 4 + (cl - 36) / 7; }
#define MAP 0
  const int m = grp, j = slt;
  const int i = 2 * m + r;
  auto BAR = [&](int k) { return bars + 8 * k; };

  auto kb1 = [&](int n) { const int h = n >= 9, t = n - 2 - 7 * h; return n < 2 ? 2 * j + n : 2 * (t == j ? 7 : t) + h; };
  auto first_round = [&](int u0, int u1) {
#pragma unroll 1
    for (int u = u0; u < u1; u++) {
      S5(3 + u);
      mbar_expect(BAR(F1 + u), 40960);
      tma2d(sb + slot1(u), &P.x0, BAR(F1 + u), u * 64, 128 * i);
      tma3d(sb + slot1(u) + 16384, &P.wqkv, BAR(F1 + u), 128 * j, u * 64, 0);
      tma3d(sb + slot1(u) + 28672, &P.wqkv, BAR(F1 + u), 128 * j, u * 64 + 32, 0);
    }
  };
  if (wu == 9) {
    if (elect_one()) asm volatile("prefetch.tensormap [%0];" ::"l"(&P.wqkv) : "memory");
    __syncwarp();
  } else if (wu == 8) {
    if (elect_one()) {
      S5(1);
#pragma unroll
      for (int k = 0; k < 4; k++) mbar_init(BAR(F1 + k), 1);
      asm volatile("fence.mbarrier_init.release.cluster;" ::: "memory");
      fence_async_smem();
      first_round(0, FR);
    }
    __syncwarp();
  } else if (wu == 0) {
    if (elect_one()) {
#pragma unroll
      for (int k = E1; k < 64; k++) {
        int cnt = 1;
        if (k < F2 || (k >= E2 && k < F3) || (k >= E3 && k < F4) || (k >= E4 && k < JOB) || k == JOB + 2 || k == JOB + 3) cnt = 4;
        else if ((k >= JOB && k < RD) || k == CSJ) cnt = 8;
        else if (k == RD + 1 || k == STD || k == STAT) cnt = 2;
        mbar_init(BAR(k), cnt);
      }
      asm volatile("fence.mbarrier_init.release.cluster;" ::: "memory");
      fence_async_smem();
    }
    __syncwarp();
  }
  auto load_tag = [&]() { uint32_t t; asm volatile("ld.relaxed.gpu.global.u32 %0, [%1];" : "=r"(t) : "l"(&gEpoch) : "memory"); return t + 1; };
  TS(0);
  if (wu == 8) nb_arrive<NB_INIT>(384); else nb_sync<NB_INIT>(384);
  asm volatile("barrier.cluster.arrive.relaxed;" ::: "memory");

  if (wg == 2) {
    if (tid == 256) S5(2);
    reg_dealloc<40>();
    if (wu == 8) {
      if (elect_one()) first_round(FR, 4);
      __syncwarp();
    }
    asm volatile("barrier.cluster.wait;" ::: "memory");
    auto kb3 = [&](int n) { const int h = n >= 17, t = n - 2 - 15 * h; return n < 2 ? 2 * i + n : t == 14 ? 2 * (i ^ 1) + h : 2 * ((2 * m + 2 + t) & 15) + h; };
    auto v1 = [&](int L, int u) { const int u0 = L ? 2 : 10; return (u >= u0 && u < 18) ? (u < u0 + 2 ? u - u0 + 16 : u - 2) : u; };
    auto kb2 = [&](int n) { return n < 8 ? 2 * n : n == 8 ? 2 * j + 1 : 2 * (n - 9 == j ? 7 : n - 9) + 1; };
    if (wu == 8) {
      const int lane = tid & 31;
      auto pf = [&](const bf16* p, bool on) { if (on) asm volatile("prefetch.global.L2 [%0];" ::"l"(p)); };

      auto k1 = [&](int L, int v) { return (L || v >= 16) ? kb1(v & 15) : v; };
      auto kb4f = [&](int n) {
        const bool own = n == 0 || n == 9 || n == 17;
        const int q = n - 10 - (n > 17), c = own ? n >> 3 : q / 15, t = q - 15 * c;
        const int ii = own ? i : t < 14 ? (2 * m + 2 + t) & 15 : i ^ 1;
        return (n >= 1 && n <= 8) ? 7 * ((m + n) & 7) + 3 : ((7 * ii + 1) >> 1) + c;
      };
      const uint32_t tab4 = kb4f(lane) | (kb4f(lane + 32) << 16);
      auto kb4 = [&](int n) { return (int)((__shfl_sync(0xffffffffu, tab4, n) >> ((n >> 1) & 16)) & 63); };
      const bf16* const q1 = P.wqkv_p + (4 * i + (lane & 3)) * 3072 + (lane >> 2) * 1024 + 128 * j;
      const bf16* const q2 = P.wo_p + (4 * i + (lane & 3)) * 1024 + (lane >> 2) * 64 + 128 * j;
      const bf16* const q3 = P.w1_p + (8 * j + (lane >> 2)) * 3584 + 64 * (7 * m + ((lane & 3) == 3 ? 3 : 4 * r + (lane & 3)));
      const bf16* const q4 = P.w2_p + (8 * j + (lane >> 1)) * 2048 + 128 * i + 64 * (lane & 1);
      auto pf1 = [&](int L, int u) { const int v = v1(L, u); pf(q1 + k1(L, v) * (64 * 3072) + 64 * (v >> 4), (PFM & 1) && lane < 12); };
      auto pf2 = [&](int n) { pf(q2 + kb2(n) * (64 * 1024), (PFM & 2) && lane < 8); };
      auto pf3 = [&](int n) { pf(q3 + kb3(n) * (64 * 3584), PFM & 4); };
      auto pf4 = [&](int n) { pf(q4 + kb4(n) * (64 * 2048), (PFM & 8) && lane < 16); };
#pragma unroll 1
      for (int u = 4; u < 4 + PD1; u++) pf1(0, u);
#pragma unroll 1
      for (int L = 0; L < 2; L++) {
#pragma unroll 1
        for (int u = L ? 0 : 4; u < 32; u++) {
          const int v = v1(L, u), p = u & 3;
          int c0 = 128 * j + 64 * (v >> 4), c1 = k1(L, v) * 64 + 32 * r; uint32_t dst = sb + slot1(p) + 16384 + r * 12288;
          asm volatile("" : "+r"(c0), "+r"(c1), "+r"(dst));
          if (XG && L && u == 4) mbar_wait(BAR(RD + 5), 0);
          if (u >= 4) mbar_wait(BAR(E1 + p), ((u >> 2) - 1) & 1);
          else mbar_wait(BAR(E4 + (u == 3 ? 0 : u + 3)), u == 3);
          if (elect_one()) {
            mbar_expect(BAR(F1 + p), (v & 15) < 2 ? 24576 : 40960);
            tma3d_mc(dst, &P.wqkv, BAR(F1 + p), c0, c1, 0);
          }
          if (u + PD1 < 32) pf1(L, u + PD1);
          if (u + PD2 >= 32) pf2(u + PD2 - 32);
        }
        int p = 0; uint32_t par = L ? 0x1e : 0;
#pragma unroll 1
        for (int n = 0; n < 16; n++) {
          int c1 = kb2(n) * 64;
          asm volatile("" : "+r"(c1));
          if (n >= 5) { mbar_wait(BAR(E2 + p), (par >> p) & 1); par ^= 1u << p; }
          else if (n < 4) mbar_wait(BAR(E1 + n), 1);
          if (elect_one()) {
            mbar_expect(BAR(F2 + p), n == 8 ? 16384 : 32768);
            tma2d_mc(sb + slot2(p) + 16384 + r * 8192, &P.wo, BAR(F2 + p), 128 * j + 64 * r, c1);
          }
          if (++p == 5) p = 0;
          if (n + PD2 < 16) pf2(n + PD2);
          if (n + PD3 + 4 >= 16) pf3(n + PD3 + 4 - 16);
        }
#pragma unroll 1
        for (int u = 0; u < 32; u++) {
          const int n = u < 4 ? (0x2031 >> (4 * u)) & 3 : u, p = n & 3;
          int kb = kb3(n);
          asm volatile("" : "+r"(kb));
          if (n == 4) mbar_wait(BAR(RD + 4), L);
          if (n >= 4) mbar_wait(BAR(E3 + p), ((n >> 2) - 1) & 1);
          else if (n == 1) mbar_wait(BAR(STD + 1), L);
          else if (n == 3) mbar_wait(BAR(E2 + 2), L);
          else if (n == 0) mbar_wait(BAR(E2 + 4), L);
          else mbar_wait(BAR(E2 + 0), 1);
          if (elect_one()) {
            mbar_expect(BAR(F3 + p), n < 2 ? 32768 : 49152);
            tma3d(sb + slot3(p) + 16384, &P.w1, BAR(F3 + p), 0, kb * 64, 7 * m + 4 * r);
            tma3d(sb + slot3(p) + 40960, &P.w1h, BAR(F3 + p), 0, kb * 64, 14 * m + 6 + r);
          }
          if (u >= 4 && u + PD3 < 32) pf3(u + PD3);
          if (u + PD4 + 6 >= 32) pf4(u + PD4 + 6 - 32);
        }
        auto g4w = [&](int n, int p, int kb) {
          if (elect_one()) {
            mbar_expect(BAR(F4 + p), (n == 0 || n == 9 || n == 17) ? 16384 : 32768);
            tma3d(sb + slot4(p), &P.w2, BAR(F4 + p), 0, kb * 64, 2 * i);
          }
        };
#pragma unroll 1
        for (int n = 0; n < 6; n++) {
          const int kb = kb4(n);
          if (n == G4GATE) mbar_wait(BAR(RD + 3), L);
          if (n < 3) mbar_wait(BAR(E3 + n), 1);
          else if (n == 4) mbar_wait(BAR(E3 + 3), 1);
          g4w(n, n, kb);
        }
        p = 0; par = L ? 0x3c : 0;
#pragma unroll 1
        for (int n = 6; n < 56; n++) {
          const int kb = kb4(n);
          if (n + PD4 < 56) pf4(n + PD4);
          mbar_wait(BAR(E4 + p), (par >> p) & 1); par ^= 1u << p;
          g4w(n, p, kb);
          if (++p == 6) p = 0;
        }
        if (L == 0)
#pragma unroll 1
          for (int u = 0; u < PD1; u++) pf1(1, u);
      }
    } else if (wu == 9) {
      uint32_t inv = 0;
#define ADDR(d, s) uint32_t dst = (d); const uint8_t* src = (s); asm volatile("" : "+r"(dst), "+l"(src))
#pragma unroll 1
      for (int L = 0; L < 2; L++) {
        uint32_t ready = 0;
#pragma unroll 1
        for (int u = 4; u < 32; u++) {
          const int p = u & 3, v = v1(L, u), nn = v & 15, kb = (L || v >= 16) ? kb1(nn) : nn;
          if (L == 0 && (u == XLD || u == XLD + XST) && elect_one()) {
            const int h = u != XLD;
            mbar_expect(BAR(XF + h), 16384);
            tma2d(sb + OFF_X + h * 16384, &P.x0, BAR(XF + h), 128 * j + 64 * h, 128 * i);
          }
          if (nn < 2) continue;
          ADDR(sb + slot1(p), gXB + (i * 16 + kb) * 16384);
          if (L && u < 12) mbar_wait(BAR(F1 + p), u >> 3);
          if (u >= 4 + 4 * L) mbar_wait(BAR(E1 + p), ((u >> 2) - 1) & 1);
          if (L) {
            flag_wait(gFlag[0][0][i], inv, 1u << kb, ready);
            if (elect_one()) bulk_ld(dst, src, 16384, BAR(F1 + p));
          } else if (elect_one()) tma2d(sb + slot1(p), &P.x0, BAR(F1 + p), kb * 64, 128 * i);
        }
        ready = 0;
        if (L == 0) inv = (__shfl_sync(0xffffffffu, load_tag(), 0) & 1) - 1;
        int p = 0; uint32_t par = L ? 0x1e : 0;
#pragma unroll 1
        for (int n = 0; n < 16; n++) {
          const int hp = kb2(n);
          if (n == 8) { par ^= 8; p = 4; continue; }
          ADDR(sb + slot2(p), gOB + (i * 16 + hp) * 16384);
          if (n >= 5) { mbar_wait(BAR(E2 + p), (par >> p) & 1); par ^= 1u << p; }
          else if (n < 4) mbar_wait(BAR(E1 + n), 1);
          flag_wait(gFlag[L][1][i], inv, 1u << hp, ready);
          if (n == 9) ST(4);
          if (elect_one()) bulk_ld(dst, src, 16384, BAR(F2 + p));
          if (++p == 5) p = 0;
        }
        ready = 0;
        mbar_wait(BAR(E2 + 0), 1);
#pragma unroll 1
        for (int n = 2; n < 32; n++) {
          const int p = n & 3, kb = kb3(n);
          const int o = (n != 16 && n != 31) ? r * 8192 : 0;
          ADDR(sb + slot3(p) + o, gHB + (j * 32 + kb) * 16384 + o);
          if (n > 3) mbar_wait(BAR(E3 + p), ((n >> 2) - 1) & 1);
          flag_wait(gFlag[L][2][j], inv, 1u << kb, ready);
          if (n == 2) ST(12);
          if (elect_one()) {
            if (n != 16 && n != 31) bulk_ld_mc(dst, src, 8192, BAR(F3 + p));
            else bulk_ld(dst, src, 16384, BAR(F3 + p));
          }
        }
        ready = 0; p = 1; par = L ? 0x3c : 0;
#pragma unroll 1
        for (int t = 0; t < 8; t++) {
          const int mm = (m + t + 1) & 7;
          ADDR(sb + slot4(p) + 16384 + r * 8192, gUB + (j * 56 + 48 + mm) * 16384 + r * 8192);
          if (t < 3) mbar_wait(BAR(E3 + 1 + t), 1);
          if (t >= 5) { mbar_wait(BAR(E4 + p), (par >> p) & 1); par ^= 1u << p; }
          flag_wait(gFlag[L][6][j], inv, 3u << (2 * mm), ready);
          if (t == 0) ST(20);
          if (elect_one()) bulk_ld_mc(dst, src, 8192, BAR(F4 + p));
          if (++p == 6) p = 0;
        }
#pragma unroll 1
        for (int c = 0; c < 3; c++) {
          ready = 0;
#pragma unroll 1
          for (int t = 0; t < 15; t++) {
            const int ii = t < 14 ? (2 * m + 2 + t) & 15 : i ^ 1;
            if (c == 0 && (t == 0 || t == 7)) { par ^= 1u << p; if (++p == 6) p = 0; }
            const int o = t < 14 ? r * 8192 : 0;
            ADDR(sb + slot4(p) + 16384 + o, gUB + (j * 56 + 16 * c + ii) * 16384 + o);
            mbar_wait(BAR(E4 + p), (par >> p) & 1); par ^= 1u << p;
            flag_wait(gFlag[L][3 + c][j], inv, 1u << ii, ready);
            if (elect_one()) {
              if (t < 14) bulk_ld_mc(dst, src, 8192, BAR(F4 + p));
              else bulk_ld(dst, src, 16384, BAR(F4 + p));
            }
            if (++p == 6) p = 0;
          }
        }
      }
    } else {
      const int h = wu - 10, i0 = i, j0 = j;
      {
      const uint32_t tag = load_tag();
      int lane = tid & 31, i = i0, j = j0;
#define FRESH asm volatile("" : "+r"(lane), "+r"(i), "+r"(j))
      auto signal = [&](int k) { if (lane == 0) mbar_arrive(BAR(k)); };
      auto publish = [&](uint32_t* f, int bit) { if (lane == 0) flag_set(f, 1u << bit); __syncwarp(); };
#pragma unroll 1
      for (int c = 32 * h + lane; c < 288; c += 64)
        sts16(sb + OFF_B1 + 2 * c, c >= 224 ? 0u : pack2(0.5f * __bfloat162float(P.b1[c < 192 ? 64 * (7 * m + 4 * r) + c : 64 * (7 * m + 3) + 32 * r + c - 192]), 0.f));
      if (h == 0) sts32f(sb + OFF_CS + 768 + 4 * lane, 0.f);
#pragma unroll 1
      for (int L = 0; L < 2; L++) {
        FRESH;
        if (L == 0) {
          mbar_wait(BAR(CSJ), 0);
          float c0 = 0.f, c1 = 0.f, c2 = 0.f;
          const uint32_t a = sb + OFF_STG + (32 * h + lane) * 4;
#pragma unroll 4
          for (int k = 0; k < 32; k++) { c0 += lds32f(a + k * 784); c1 += lds32f(a + k * 784 + 256); c2 += lds32f(a + k * 784 + 512); }
          ll_st3(&gCS[j][i][32 * h + lane], __float_as_uint(c0), __float_as_uint(c1), __float_as_uint(c2), tag);
          __nanosleep(500);
        }
        FRESH;
        if (L == 0) {
#pragma unroll 1
          for (int ab = 0; ab < 2; ab++) {
            float c0 = 0.f, c1 = 0.f, c2 = 0.f;
#pragma unroll 1
            for (int b4 = 0; b4 < 8; b4 += 4) {
              uint32_t a[4], b[4], c[4], n = 0, bad;
              do {
                bad = 0;
#pragma unroll
                for (int e = 0; e < 4; e++) bad |= ll_ld3(&gCS[j][2 * (b4 + e) + ab][32 * h + lane], a[e], b[e], c[e], tag);
              } while (bad && ++n < SPIN_MAX);
#pragma unroll
              for (int e = 0; e < 4; e++) { c0 += __uint_as_float(a[e]); c1 += __uint_as_float(b[e]); c2 += __uint_as_float(c[e]); }
            }
            const uint32_t a = sb + OFF_CS + ab * 768 + (4 * h + (lane >> 3)) * 32 + (lane & 7) * 2;
            const uint32_t h0 = pack2(c0, 0.f), h1 = pack2(c1, 0.f), h2 = pack2(c2, 0.f);
            sts16(a, h0); sts16(a + 256, h1); sts16(a + 512, h2);
            sts16(a + 16, pack2(c0 - bf_lo(h0), 0.f)); sts16(a + 272, pack2(c1 - bf_lo(h1), 0.f)); sts16(a + 528, pack2(c2 - bf_lo(h2), 0.f));
            fence_async_smem();
            __syncwarp();
            if (ab == 0) signal(STAT);
          }
        }
#pragma unroll 1
        for (int ab = 0; ab < 2; ab++) {
          FRESH;
          uint32_t v[18], tg[6];
          const uint32_t xs = sb + OFF_STG + h * 16384 + lane * 8;
          uint4* hp = &gHalo[L][i][j][6 * h][lane];
#pragma unroll
          for (int c = 0; c < 6; c++) { tg[c] = (2 * tag + ab) * 8 + c; asm volatile("" : "+r"(tg[c])); }
          asm volatile("" : "+l"(hp));
          mbar_wait(BAR(FOLD + h), ab);
          if (ab && h == 0) ST(6);
          if (i < 15) {
            halo_send(hp, xs, tg);
          }
          if (ab && h == 0) ST(26);
          if (i > 0) {
            if (!ab) __nanosleep(HALO_A_NS);
            uint32_t n = 0, bad;
            do {
              bad = 0;
#pragma unroll
              for (int c = 0; c < 6; c++) bad |= ll_ld3(hp + c * 32 - 8 * 12 * 32, v[3 * c], v[3 * c + 1], v[3 * c + 2], (2 * tag + ab) * 8);
              if (ab && h == 0 && n == 0) ST(28);
            } while (bad > 7 && ++n < SPIN_MAX);
            if (ab && h == 0) ST(27);
          } else {
#pragma unroll
            for (int c = 0; c < 18; c++) v[c] = 0u;
          }
#pragma unroll
          for (int c = 0; c < 6; c++) sts64f(xs + c * 256, __uint_as_float(v[3 * c]), __uint_as_float(v[3 * c + 1]));
          sts64f(xs + 1536, __uint_as_float(v[2]), __uint_as_float(v[5]));
          sts64f(xs + 1792, __uint_as_float(v[8]), __uint_as_float(v[11]));
          __syncwarp();
          signal(HALO + h);
          if (ab && h == 0) ST(7);
          FRESH;
          if (ab == 0 && lane == 0) asm volatile("st.relaxed.gpu.global.u32 [%0], %1;" ::"l"(&gAck[L][i][j][h][0]), "r"(tag) : "memory");
          uint8_t* dst = gOB + (i * 16 + 2 * j + ab) * 16384;
          uint32_t* flag = gFlag[L][1][i];
          asm volatile("" : "+l"(dst), "+l"(flag));
          mbar_wait(BAR(JOB + ab), L);
          if (h == 0) {
            if (ab) ST(1);
            if (lane == 0) { bulk_st(dst, sb + OFF_STG, 16384); bulk_commit(); bulk_wait0(); }
            signal(STD + ab);
            if (ab) ST(2);
            publish(flag, 2 * j + ab);
            if (ab) ST(3);
          } else if (ab == 0) {
            if (i < 15 && lane < 2) {
              uint32_t t, n = 0;
              do { asm volatile("ld.relaxed.gpu.global.u32 %0, [%1];" : "=r"(t) : "l"(&gAck[L][i + 1][j][lane][0]) : "memory"); } while (t != tag && ++n < SPIN_MAX);
            }
            __syncwarp();
            signal(STD);
          }
        }
#pragma unroll 1
        for (int k = 0; k < 4 - L; k++) {
          FRESH;
          const int job = 2 * k + h;
          uint8_t* dst = k == 0 ? gHB + (j * 32 + 2 * i + 1) * 16384 : k == 3 ? gXB + (i * 16 + 2 * j + 1) * 16384 : gUB + (j * 56 + 16 * (job - 3) + i) * 16384;
          uint32_t* flag = k == 3 ? gFlag[0][0][i] : gFlag[L][(0x543622 >> (4 * job)) & 15][j];
          uint32_t bit = 1u << (k == 0 ? 2 * i + h : k == 3 ? 2 * j + h : i);
          asm volatile("" : "+l"(dst), "+l"(flag), "+r"(bit));
          mbar_wait(BAR(JOB + ((0x98654732 >> (4 * job)) & 15)), L);
          if (job < 3 && h == 0) ST(job ? 17 : 9);
          if ((0xba >> job) & 1) {
            if (job == 1) mbar_wait(BAR(RD + 4), L);
            if (job == 3) {
              __nanosleep(U0D);
              if (lane == 0) { bulk_st(dst, sb + OFF_X, 16384); bulk_commit(); bulk_wait0(); }
            } else warp_store(dst + lane * 16, sb + lane * 16 + OFF_X + (job == 5 ? 0 : 16384), 16384, job == 1 ? H1D : job == 7 ? X1D : 0, job == 7 ? 0 : PACE);
            if (job != 7) signal(RD + ((0x112000 >> (4 * job)) & 15));
          }
          if (lane == 0) flag_set(flag, bit);
          __syncwarp();
          if (h == 0 && k != 2) { signal(RD + (k == 3 ? 5 : 4 - k)); if (k < 2) ST(job ? 19 : 11); }
        }
      }
      if (blockIdx.x == 0 && h == 0 && lane == 0) asm volatile("st.relaxed.gpu.global.u32 [%0], %1;" ::"l"(&gEpoch), "r"(tag) : "memory");
      }
    }
    __syncwarp();
    cluster_bar();
  } else {
    reg_alloc<232>();
    asm volatile("barrier.cluster.wait;" ::: "memory");
    const uint32_t rbars = mapa(bars, tid & 1);
    const bool relp = (tid & 127) < 2;
    const uint32_t sd = (sb & 0x3FFFF) >> 4, sda = sd + wg * 512;
    uint32_t tag;
    asm volatile("ld.relaxed.gpu.global.u32 %0, [%1];" : "=r"(tag) : "l"(&gEpoch + (fresh_tid() >> 10)) : "memory");
    auto release = [&](int k) { if (relp) mbar_arrive_cl(rbars + 8 * k); };
    auto signal = [&](int k) { __syncwarp(); if ((fresh_tid() & 31) == 0) mbar_arrive(BAR(k)); };
#define GEOM const int t7 = fresh_tid() & 127, lane = t7 & 31, w = t7 >> 5, g = lane >> 2, q = lane & 3, \
                       lr = lane & 15, lt = lane >> 4, l7 = lane & 7; (void)w; (void)g; (void)q; (void)lr; (void)lt; (void)l7

#pragma unroll 1
    for (int L = 0; L < 2; L++) {
      float acca[96], accb[96], xa[64], acc3[112];
      float nmean0, nmean1, rstd0, rstd1;
      uint16_t b2a, b2b;
      uint2 *e2p, *e2s; uint8_t* e2g; uint32_t e2h;
      uint32_t Q[2][8], K[2][8], V[16];
      auto g1_issue = [&](float (&acc)[96], uint32_t a, uint32_t st, auto first) {
        const uint32_t da = sda + (a >> 4), db = sd + (st >> 4);
        wg_fence();
        static_for<0, 4>([&](auto kk) {
          constexpr uint32_t ia = DI(kk.value * 32, 16), ib = DI(16384 + (kk.value >> 1) * 12288 + (kk.value & 1) * 2048, 4096);
          if constexpr (first.value && kk.value == 0) wgmma_192z<0, 1, ia, ib>(acc, da, db); else wgmma_192<0, 1, ia, ib>(acc, da, db);
        });
        wg_commit();
      };
      auto g1_step = [&](float (&acc)[96], int u, bool rel, bool lead = false) {
        const int p = u & 3;
        mbar_wait(BAR(F1 + p), (u >> 2) & 1);
        KB(u);
        g1_issue(acc, slot1(p), slot1(p), False{});
        if (lead) nb_arrive<NB_LEAD>(256);
        wg_wait<1>();
        if (rel) release(E1 + ((u - 1) & 3));
      };
      auto g1_loop = [&](float (&acc)[96], int u0, int u1, int urel) {
        int u = u0;
#pragma unroll 1
        do { g1_step(acc, u, u > urel); } while (++u < u1);
      };
      auto load_x = [&]() {
        GEOM;
#pragma unroll
        for (int t = 0; t < 16; t += 2) {
          uint32_t v0, v1, v2, v3;
          ldsm4(sb + OFF_X + (t >> 3) * 16384 + (16 * wu + lr) * 128 + ((((t & 7) + lt) ^ l7) << 4), v0, v1, v2, v3);
          xa[4 * t + 0] = bf_lo(v0); xa[4 * t + 1] = bf_hi(v0); xa[4 * t + 2] = bf_lo(v1); xa[4 * t + 3] = bf_hi(v1);
          xa[4 * t + 4] = bf_lo(v2); xa[4 * t + 5] = bf_hi(v2); xa[4 * t + 6] = bf_lo(v3); xa[4 * t + 7] = bf_hi(v3);
        }
      };
      auto stat_base = [&]() { return &gST[0][0][0][0][0] + ((L * 16 + opq(i)) * 8 + wu) * 128; };
      auto stat_slot = [&]() { const int lane = fresh_tid() & 31; return stat_base() + 16 * j + 2 * (lane >> 2) + (lane & 1); };
      auto stat_publish = [&](uint2* sp, float s0, float q0, float s2, float q2, uint32_t tg) {
        const int q = fresh_tid() & 3;
        const bool h1 = q & 1;
        float sm = (h1 ? s2 : s0) + __shfl_xor_sync(0xffffffffu, h1 ? s0 : s2, 1);
        float sq = (h1 ? q2 : q0) + __shfl_xor_sync(0xffffffffu, h1 ? q0 : q2, 1);
        sm += __shfl_xor_sync(0xffffffffu, sm, 2); sq += __shfl_xor_sync(0xffffffffu, sq, 2);
        stat_st(sp, sm, sq, tg, q < 2);
        return sm;
      };
      auto g1_stats = [&](int u0) {
        GEOM;
        const uint32_t xr = sb + OFF_X + (16 * wu + lr) * 128;
        float s0 = 0.f, q0 = 0.f, s2 = 0.f, q2 = 0.f;
        uint32_t v[8] = {0u, 0u, 0u, 0u, 0u, 0u, 0u, 0u};
#pragma unroll 1
        for (int k = 0; k < 5; k++) {
#pragma unroll
          for (int e = 0; e < 8; e += 2) {
            const float a = bf_lo(v[e]), b = bf_hi(v[e]), c = bf_lo(v[e + 1]), d = bf_hi(v[e + 1]);
            s0 += a + b; q0 = fmaf(a, a, fmaf(b, b, q0)); s2 += c + d; q2 = fmaf(c, c, fmaf(d, d, q2));
          }
          if (k == 4) break;
          const uint32_t o = ((2 * k + lt) ^ l7) << 4;
          ldsm4(xr + o, v[0], v[1], v[2], v[3]);
          ldsm4(xr + o + 16384, v[4], v[5], v[6], v[7]);
          g1_step(acca, u0 + k, true);
        }
        stat_publish(stat_slot(), s0, q0, s2, q2, 2 * (tag + 1));
      };
      uint32_t sv0[4], sv1[4];
      auto stat_src = [&]() { return stat_base() + 2 * (fresh_tid() & 31); };
      auto stat_fetch = [&](const uint2* sp) { stat_ld2(sp, sv0); stat_ld2(sp + 64, sv1); };
      auto stat_await = [&](auto src, uint32_t tg) {
#pragma unroll 1
        for (uint32_t n = 0; (((sv0[0] ^ tg) | (sv0[2] ^ tg) | (sv1[0] ^ tg) | (sv1[2] ^ tg)) & 15u) && n < SPIN_MAX; n++) stat_fetch(src());
        __syncwarp();
      };
      auto ln_stats = [&]() {
        GEOM;
        stat_await(stat_src, 2 * (tag + 1));
        float mean0, var0, mean1, var1;
        stat_combine(sv0[0], sv0[1], sv1[0], sv1[1], untag(__shfl_sync(0xffffffffu, sv0[0], l7)), mean0, var0);
        stat_combine(sv0[2], sv0[3], sv1[2], sv1[3], untag(__shfl_sync(0xffffffffu, sv0[2], l7)), mean1, var1);
        nmean0 = -__shfl_sync(0xffffffffu, mean0, g); rstd0 = rsq(__shfl_sync(0xffffffffu, var0, g) + 1e-5f);
        nmean1 = -__shfl_sync(0xffffffffu, mean1, g); rstd1 = rsq(__shfl_sync(0xffffffffu, var1, g) + 1e-5f);
      };
      auto center = [&](float (&acc)[96], int ab) {
        const bool q0 = (fresh_tid() & 3) == 0;
        const uint32_t h0 = pack2(nmean0, nmean0), h1 = pack2(nmean1, nmean1);
        const float l0 = nmean0 - bf_lo(h0), l1 = nmean1 - bf_lo(h1);
        const uint32_t a0 = q0 ? h0 : 0u, a1 = q0 ? h1 : 0u, a2 = q0 ? pack2(l0, l0) : 0u, a3 = q0 ? pack2(l1, l1) : 0u;
        wg_fence();
        wgmma_rs_192(acc, a0, a1, a2, a3, mkdesc_vec(sb + OFF_CS + ab * 768, 32));
      };
      auto frag = [&](float (&acc)[96], int t, uint32_t& p0, uint32_t& p1) {
        if (t >= 8) { p0 = pack2(acc[4 * t] * rstd0, acc[4 * t + 1] * rstd0); p1 = pack2(acc[4 * t + 2] * rstd1, acc[4 * t + 3] * rstd1); }
        else { p0 = pack2(acc[4 * t], acc[4 * t + 1]); p1 = pack2(acc[4 * t + 2], acc[4 * t + 3]); }
      };
      auto fold_v = [&](float (&acc)[96], int t0, int t1) {
        GEOM;
        const uint32_t a = sb + OFF_STG + 16384 + ((wu + 1) & 7) * 2048 + lr * 128;
#pragma unroll
        for (int t = t0; t < t1; t += 2) {
          uint32_t p0, p1, p2, p3;
          frag(acc, 16 + t, p0, p1); frag(acc, 17 + t, p2, p3);
          stsm4(a + (((t + lt) ^ l7) << 4), p0, p1, p2, p3);
        }
        __syncwarp();
#pragma unroll
        for (int t = t0; t < t1; t += 2) ldsm4t(a + (((t + lt) ^ l7) << 4), V[2 * t], V[2 * t + 1], V[2 * t + 2], V[2 * t + 3]);
        if (wu == 7) signal(FOLD + 1);
      };
      auto fold_k = [&](float (&acc)[96], int ab, int h0, int h1) {
        GEOM;
        const uint32_t a = sb + OFF_STG + ((wu + 1) & 7) * 2048 + lane * 16;
#pragma unroll
        for (int hh = h0; hh < h1; hh++) {
#pragma unroll
          for (int t = 4 * hh; t < 4 * hh + 4; t++) frag(acc, 8 + t, K[0][t], K[1][t]);
#pragma unroll
          for (int o = 0; o < 2; o++) sts128(a + (2 * o + hh) * 512, K[o][4 * hh], K[o][4 * hh + 1], K[o][4 * hh + 2], K[o][4 * hh + 3]);
        }
        if (wu == 7) signal(FOLD);
      };
      auto fold_q = [&](float (&acc)[96]) {
#pragma unroll
        for (int t = 0; t < 8; t++) frag(acc, t, Q[0][t], Q[1][t]);
      };
      auto attend = [&](int ab, auto drain, auto resume) {
        GEOM;
        nb_sync<NB_BOTH>(256);
        const uint32_t xa_ = sb + OFF_STG + wu * 2048 + lane * 16;
        if (wu == 0) mbar_wait(BAR(HALO), ab);
        uint32_t KH[2][8], VH[16];
#pragma unroll
        for (int c = 0; c < 4; c++)
          lds128(xa_ + c * 512, KH[c >> 1][4 * (c & 1)], KH[c >> 1][4 * (c & 1) + 1], KH[c >> 1][4 * (c & 1) + 2], KH[c >> 1][4 * (c & 1) + 3]);
        auto load_vh = [&]() {
          if (wu == 0) mbar_wait(BAR(HALO + 1), ab);
#pragma unroll
          for (int c = 0; c < 4; c++)
            ldsm4t(sb + OFF_STG + 16384 + wu * 2048 + lr * 128 + (((2 * c + lt) ^ l7) << 4), VH[4 * c], VH[4 * c + 1], VH[4 * c + 2], VH[4 * c + 3]);
        };
        if (!(VL && ab)) load_vh();
        TS2(11 + ab + 32 * L);
        const bool e = g & 1, zneg = (g >> 1) < q, first = (i == 0) && (wu == 0);
        const float sc0 = rstd0 * (0.17677669530f * 1.4426950409f), sc1 = rstd1 * (0.17677669530f * 1.4426950409f);
        float mk0 = first ? __fdividef(-1.0e9f * 1.4426950409f, sc0) : 0.f, mk1 = first ? __fdividef(-1.0e9f * 1.4426950409f, sc1) : 0.f;
        const uint32_t sa = e ? 0x1044u : 0x4410u, sbb = e ? 0x3244u : 0x4432u;
        uint32_t sel[3] = {zneg ? sbb : 0x4444u, sa, zneg ? 0x4444u : sbb};
        uint32_t oa = sb + OFF_STG + (16 * wu + lr) * 128 + ((lt ^ l7) << 4);
        asm volatile("" : "+r"(sel[0]), "+r"(sel[1]), "+r"(sel[2]), "+r"(oa), "+f"(mk0), "+f"(mk1));
        drain();
        uint32_t pr[2][6];
        float l[2][2], sl[2][4][4];
#pragma unroll
        for (int hh = 0; hh < 2; hh++)
          attn_logits(&Q[0][4 * hh], &Q[1][4 * hh], &KH[0][4 * hh], &KH[1][4 * hh], &K[0][4 * hh], &K[1][4 * hh], mk0, mk1, sl[hh]);
        if (VL && ab) load_vh();
#pragma unroll
        for (int hh = 0; hh < 2; hh++) attn_probs(sl[hh], sc0, sc1, e, zneg, sel, pr[hh], l[hh]);
        float o[2][4][4];
#pragma unroll
        for (int hh = 0; hh < 2; hh++) attn_pv(pr[hh], &VH[8 * hh], &V[8 * hh], o[hh]);
#pragma unroll
        for (int hh = 0; hh < 2; hh++) {
          float l0 = l[hh][0], l1 = l[hh][1];
          l0 += __shfl_xor_sync(0xffffffffu, l0, 1); l1 += __shfl_xor_sync(0xffffffffu, l1, 1);
          l0 += __shfl_xor_sync(0xffffffffu, l0, 2); l1 += __shfl_xor_sync(0xffffffffu, l1, 2);
          asm("rcp.approx.ftz.f32 %0, %0;" : "+f"(l0)); asm("rcp.approx.ftz.f32 %0, %0;" : "+f"(l1));
#pragma unroll
          for (int dt = 0; dt < 4; dt += 2)
            stsm4(oa ^ ((4 * hh + dt) << 4),
                  pack2(o[hh][dt][0] * l0, o[hh][dt][1] * l0), pack2(o[hh][dt][2] * l1, o[hh][dt][3] * l1),
                  pack2(o[hh][dt + 1][0] * l0, o[hh][dt + 1][1] * l0), pack2(o[hh][dt + 1][2] * l1, o[hh][dt + 1][3] * l1));
        }
        fence_async_smem();
        signal(JOB + ab);
        nb_sync<NB_BOTH>(256);
        resume();
      };

      TS(1 + 32 * L);
      if (L == 0 && wu == 0) S5(7);
      mbar_wait(BAR(F1), 0); if (L == 0 && wu == 0) S5(8); KB(0);    g1_issue(acca, L ? OFF_X : slot1(0), slot1(0), True{});
      mbar_wait(BAR(F1 + 1), 0); KB(1); g1_issue(acca, L ? OFF_X + 16384 : slot1(1), slot1(1), False{});
      wg_wait<1>(); release(E1 + 0);
      if (L == 0) {
        GEOM;
        const bf16* wp = P.wqkv_p + ((128 * opq(m) + 16 * wg + (t7 >> 3)) * 3072 + 128 * opq(j) + 64 * r + l7 * 8);
        const uint32_t ca = sb + OFF_STG + (16 * wg + (t7 >> 3)) * 784 + l7 * 32;
#pragma unroll 1
        for (int p = 0; p < 3; p++) {
          uint4 wv[4];
#pragma unroll
          for (int k = 0; k < 4; k++)
            asm volatile("ld.global.nc.v4.u32 {%0, %1, %2, %3}, [%4];" : "=r"(wv[k].x), "=r"(wv[k].y), "=r"(wv[k].z), "=r"(wv[k].w)
                         : "l"(wp + k * 32 * 3072 + p * 1024));
          g1_loop(acca, 2 + 3 * p, p < 2 ? 5 + 3 * p : 10, 0);
          float cs[8];
#pragma unroll
          for (int k = 0; k < 4; k++) {
            const uint4 v = wv[k];
            const float t[8] = {bf_lo(v.x), bf_hi(v.x), bf_lo(v.y), bf_hi(v.y), bf_lo(v.z), bf_hi(v.z), bf_lo(v.w), bf_hi(v.w)};
#pragma unroll
            for (int e = 0; e < 8; e++) cs[e] = k ? cs[e] + t[e] : t[e];
          }
          sts128(ca + p * 256, __float_as_uint(cs[0]), __float_as_uint(cs[1]), __float_as_uint(cs[2]), __float_as_uint(cs[3]));
          sts128(ca + p * 256 + 16, __float_as_uint(cs[4]), __float_as_uint(cs[5]), __float_as_uint(cs[6]), __float_as_uint(cs[7]));
        }
        signal(CSJ);
        mbar_wait(BAR(XF), 0); mbar_wait(BAR(XF + 1), 0);
      }
      {
        const int u0 = L ? 2 : 10;
        mbar_wait(BAR(F1 + 2), 0); KB(u0); g1_issue(accb, OFF_X, slot1(2), True{});
        wg_wait<1>(); release(E1 + 1);
        mbar_wait(BAR(F1 + 3), 0); KB(u0 + 1); g1_issue(accb, OFF_X + 16384, slot1(3), False{});
        wg_wait<1>(); release(E1 + 2);
        g1_stats(u0 + 2);
        g1_loop(acca, u0 + 6, 18, 0);
      }
      stat_fetch(stat_src());
      const int fa = FA + (wg ? 0 : FO);
      g1_loop(accb, 18, fa, 0);
      ln_stats();
      if (L == 0) mbar_wait(BAR(STAT), 0);
      center(acca, 0); wg_commit();
      wg_wait<0>(); release(E1 + ((fa - 1) & 3));
      fence_regs(acca);
      TS(2 + 32 * L);
      fold_k(acca, 0, 0, 2); fold_v(acca, 0, 8); fold_q(acca);
      sched_fence(P.zero);
      g1_loop(accb, fa, ATT, fa);
      attend(0, [&]() { wg_wait<0>(); release(E1 + ((ATT - 1) & 3)); mbar_wait(BAR(F1 + (ATT & 3)), (ATT >> 2) & 1); },
             [&]() { KB(ATT); g1_issue(accb, slot1(ATT & 3), slot1(ATT & 3), False{});
                     mbar_wait(BAR(F1 + ((ATT + 1) & 3)), ((ATT + 1) >> 2) & 1);
                     KB(ATT + 1); g1_issue(accb, slot1((ATT + 1) & 3), slot1((ATT + 1) & 3), False{}); });
      wg_wait<1>(); release(E1 + (ATT & 3));
      TS(3 + 32 * L);
      load_x();
      fence_regs(xa);
      center(accb, 1);
#pragma unroll 1
      for (int u = ATT + 2; u < 32; u++) {
        const bool hold = u == 32 - LEAD1 && wg == 0;
        if (hold) { wg_wait<0>(); release(E1 + ((31 - LEAD1) & 3)); nb_sync<NB_LEAD>(256); }
        g1_step(accb, u, !hold, u == 31 && wg == 1);
      }
      mbar_wait(BAR(STD), L);
      wg_wait<0>(); release(E1 + 3);
      fence_regs(accb);
      TS(4 + 32 * L);
      if (wu == 7) ST(0);
      fold_k(accb, 1, 0, 2);
      if (KF) sched_fence(P.zero);
      fold_v(accb, 0, 8);
      fold_q(accb);
      TS2(29 + 32 * L);
      {
        auto g2_issue = [&](int p, bool own) {
          const uint32_t st = slot2(p);
          const uint32_t da = sda + ((own ? OFF_STG : st) >> 4), db = sd + (st >> 4);
          wg_fence();
          static_for<0, 4>([&](auto kk) { wgmma_128<0, 1, DI(kk.value * 32, 16), DI(16384 + kk.value * 2048, 8192)>(xa, da, db); });
          wg_commit();
        };
        uint32_t par = L ? 0x1e : 0;
        int p = 0, pp = 0;
        auto g2_loop = [&](int n0, int n1, int nrel) {
#pragma unroll 1
          for (int n = n0; n < n1; n++) {
            mbar_wait(BAR(F2 + p), (par >> p) & 1);
            KB(32 + n);
            if (n == 9 && wu == 0) ST(5);
            par ^= 1u << p;
            g2_issue(p, n == 8);
            if (n1 == 16 && n == 15 && wg == 0) nb_arrive<NB_LEAD>(256);
            wg_wait<1>();
            if (n > nrel) release(E2 + pp);
            pp = p; if (++p == 5) p = 0;
          }
        };
        g2_loop(0, COVER, 0);
        attend(1, [&]() { wg_wait<0>(); release(E2 + COVER - 1); mbar_wait(BAR(F2 + COVER), (par >> COVER) & 1); },
               [&]() { KB(32 + COVER); g2_issue(COVER, false);
                       mbar_wait(BAR(F2 + COVER + 1), (par >> (COVER + 1)) & 1);
                       KB(33 + COVER); g2_issue(COVER + 1, false); });
        wg_wait<1>(); release(E2 + COVER);
        par ^= 3u << COVER; pp = COVER + 1; p = (COVER + 2) % 5;
        TS(30 + 32 * L);
        {
          const bf16* bp = P.b2 + (128 * opq(i) + 16 * wu + ((fresh_tid() & 31) >> 2));
          asm volatile("ld.global.nc.u16 %0, [%1];" : "=h"(b2a) : "l"(bp));
          asm volatile("ld.global.nc.u16 %0, [%1];" : "=h"(b2b) : "l"(bp + 8));
        }
        TS2(14 + 32 * L);
        {
          GEOM;
          e2p = stat_slot(); e2s = stat_src();
          e2g = gHB + (opq(j) * 32 + 2 * i) * 16384 + w * 2048 + lane * 16;
          e2h = sb + OFF_X + wg * 16384 + (16 * w + lr) * 128 + ((lt ^ l7) << 4);
          asm volatile("" : "+l"(e2p), "+l"(e2s), "+l"(e2g), "+r"(e2h));
        }
        g2_loop(COVER + 2, 16 - LEAD2, 0);
        if (wg == 1) { wg_wait<0>(); release(E2 + pp); nb_sync<NB_LEAD>(256); }
        g2_loop(16 - LEAD2, 16, wg == 1 ? 16 - LEAD2 : 0);
        wg_wait<0>();
        release(E2 + 0);
        fence_regs(xa);
      }
      TS(5 + 32 * L);
      if (wu == 0) ST(8);
      {
        GEOM;
        const uint32_t tg = 2 * (tag + 1) + 1;
        float s0 = 0.f, s1 = 0.f, s2 = 0.f, s3 = 0.f, q0 = 0.f, q1 = 0.f, q2 = 0.f, q3 = 0.f;
#pragma unroll
        for (int t = 0; t < 16; t++) {
          s0 += xa[4 * t]; s1 += xa[4 * t + 1]; s2 += xa[4 * t + 2]; s3 += xa[4 * t + 3];
          q0 = fmaf(xa[4 * t], xa[4 * t], q0); q1 = fmaf(xa[4 * t + 1], xa[4 * t + 1], q1);
          q2 = fmaf(xa[4 * t + 2], xa[4 * t + 2], q2); q3 = fmaf(xa[4 * t + 3], xa[4 * t + 3], q3);
        }
        const float sm = stat_publish(e2p, s0 + s1, q0 + q1, s2 + s3, q2 + q3, tg);
        const uint32_t t0 = clock32();
        TS2(13 + 32 * L);
        const float pv0 = __shfl_sync(0xffffffffu, sm, 4 * l7) * (1.f / 128), pv1 = __shfl_sync(0xffffffffu, sm, 4 * l7 + 1) * (1.f / 128);
        while (clock32() - t0 < STAT_CLK) {}
        stat_fetch(e2s);
        wg_fence();
        wgmma_rs_224z(acc3, q == 0 ? 0x3f80u : 0u, q == 0 ? 0x3f80u : 0u, 0u, 0u, mkdesc_vec(sb + OFF_B1, 16));
        wg_commit();
        stat_await([&]() { return e2s; }, tg);
        float r0, m0, r1, m1;
        {
          float mean0, var0, mean1, var1;
          stat_combine(sv0[0], sv0[1], sv1[0], sv1[1], pv0, mean0, var0); stat_combine(sv0[2], sv0[3], sv1[2], sv1[3], pv1, mean1, var1);
          mean0 = __shfl_sync(0xffffffffu, mean0, g); var0 = __shfl_sync(0xffffffffu, var0, g);
          mean1 = __shfl_sync(0xffffffffu, mean1, g); var1 = __shfl_sync(0xffffffffu, var1, g);
          r0 = 0.5f * rsq(fmaf(var0 + 1e-5f, 1e-5f, var0)); r1 = 0.5f * rsq(fmaf(var1 + 1e-5f, 1e-5f, var1));
          m0 = -mean0 * r0; m1 = -mean1 * r1;
        }
        TS2(15 + 32 * L);
#pragma unroll
        for (int t = 0; t < 16; t += 2) {
          stsm4((e2h ^ ((t & 7) << 4)) + (t >> 3) * 8192,
                pack2(fmaf(xa[4 * t], r0, m0), fmaf(xa[4 * t + 1], r0, m0)), pack2(fmaf(xa[4 * t + 2], r1, m1), fmaf(xa[4 * t + 3], r1, m1)),
                pack2(fmaf(xa[4 * t + 4], r0, m0), fmaf(xa[4 * t + 5], r0, m0)), pack2(fmaf(xa[4 * t + 6], r1, m1), fmaf(xa[4 * t + 7], r1, m1)));
          if ((t & 7) == 6 && wg == 0) {
            __syncwarp();
            copy_out<4>(e2g + (t >> 3) * 8192, sb + OFF_X + (t >> 3) * 8192 + w * 2048 + lane * 16, 512);
          }
        }
        signal(JOB + 2 + wg);
        fence_async_smem();
        mbar_wait(BAR(F3 + 0), 0);
        nb_sync<NB_BOTH>(256);
      }
      TS(6 + 32 * L);
      auto g3_issue = [&](uint32_t a, int p) {
        const uint32_t da = sda + (a >> 4), db = sd + (slot3(p) >> 4);
        wg_fence();
        static_for<0, 4>([&](auto kk) { wgmma_224<1, 1, DI(kk.value * 2048, 8192), DI(16384 + kk.value * 2048, 8192)>(acc3, da, db); });
        wg_commit();
      };
      KB(48); g3_issue(OFF_X, 0);
      mbar_wait(BAR(F3 + 1), 0); KB(49); g3_issue(OFF_X + 16384, 1);
      sched_fence(P.zero);
      {
        const float c0 = __uint_as_float((uint32_t)b2a << 16), c1 = __uint_as_float((uint32_t)b2b << 16);
#pragma unroll
        for (int t = 0; t < 16; t++) { xa[4 * t] += c0; xa[4 * t + 1] += c0; xa[4 * t + 2] += c1; xa[4 * t + 3] += c1; }
        fence_regs(xa);
      }
      wg_wait<1>(); release(E3 + 0);
      auto g3_loop = [&](int n0, int n1, int nrel) {
#pragma unroll 1
        for (int n = n0; n < n1; n++) {
          const int p = n & 3;
          mbar_wait(BAR(F3 + p), (n >> 2) & 1);
          KB(48 + n);
          if (n == 3 && wu == 0) ST(13);
          if (n == 2 && wu == 0) ST(14);
          g3_issue(slot3(p), p);
          wg_wait<1>();
          if (n > nrel) release(E3 + ((n - 1) & 3));
        }
      };
      g3_loop(2, 29, 0);
      uint32_t ua;
      uint8_t* ug;
      {
        GEOM;
        ua = sb + OFF_X + wg * 8192 + (8 * lt + l7) * 128 + (((2 * w + ((lane >> 3) & 1)) ^ l7) << 4);
        ug = gUB + (opq(j) * 56 + 48 + m) * 16384 + r * 4096 + wg * 8192 + (lane >> 1) * 128 + (((2 * w + (lane & 1)) ^ ((lane >> 1) & 7)) << 4);
      }
      auto gelu8 = [&](int c, int k) {
        const int o = 32 * c + 8 * k;
        stsm4t(ua + (c & 1) * 16384 + k * 2048,
               pack2(gelu_half(acc3[o]), gelu_half(acc3[o + 1])), pack2(gelu_half(acc3[o + 2]), gelu_half(acc3[o + 3])),
               pack2(gelu_half(acc3[o + 4]), gelu_half(acc3[o + 5])), pack2(gelu_half(acc3[o + 6]), gelu_half(acc3[o + 7])));
      };
      {
        auto part = [&](auto p, auto half) {
          static_for<0, 4>([&](auto kk) {
            constexpr uint32_t o = slot3(p.value) + kk.value * 2048;
            if constexpr (half.value) wgmma_32<1, 1, DI(o, 8192), DI(o + 40960, 8192), 96>(acc3, sda, sd);
            else wgmma_192<1, 1, DI(o, 8192), DI(o + 16384, 8192), 0>(acc3, sda, sd);
          });
        };
        mbar_wait(BAR(RD), L);
        mbar_wait(BAR(F3 + 1), 1); mbar_wait(BAR(F3 + 2), 1);
        wg_wait<0>(); release(E3 + 0);
#pragma unroll
        for (int k = 0; k < 112; k++) { float t; asm volatile("mov.b32 %0, %1;" : "=f"(t) : "f"(acc3[k]) : "memory"); acc3[k] = t; }
        sched_fence(P.zero);
        KB(77);
        wg_fence(); part(Int<1>{}, True{}); part(Int<2>{}, True{});
        mbar_wait(BAR(F3 + 3), 1); wg_fence(); part(Int<3>{}, True{}); wg_commit();
        part(Int<1>{}, False{}); wg_commit();
        wg_wait<1>();
#pragma unroll
        for (int k = 96; k < 112; k++) asm volatile("" : "+f"(acc3[k])::"memory");
        gelu8(3, 0); gelu8(3, 1);
        __syncwarp();
        copy_out<2>(ug, sb + OFF_X + 16384 + (uint32_t)((ug - gUB) & 0x2fff), 2048);
        signal(JOB + 7);
        sched_fence(P.zero);
        KB(78);
        wg_fence(); part(Int<2>{}, False{}); wg_commit();
        wg_wait<1>(); release(E3 + 1);
        KB(79);
        part(Int<3>{}, False{}); wg_commit();
        wg_wait<1>(); release(E3 + 2);
        wg_wait<0>(); release(E3 + 3);
      }
      fence_regs(acc3);
      TS(7 + 32 * L);
      if (wu == 0) ST(16);
      auto g4_issue = [&](int p, uint32_t b) {
        const uint32_t da = sda + (slot4(p) >> 4), db = sd + (b >> 4);
        wg_fence();
        static_for<0, 4>([&](auto kk) { wgmma_128<1, 1, DI(kk.value * 2048, 8192), DI(kk.value * 2048, 8192)>(xa, da, db); });
        wg_commit();
      };
#pragma unroll
      for (int k = 0; k < 4; k++) gelu8(0, k);
      fence_async_smem();
      signal(JOB + 4);
      nb_sync<NB_BOTH>(256);
      TS(8 + 32 * L);
      static_for<0, 18>([&](auto nn) {
        constexpr int n = nn.value, p = n % 6;
        if (n == 9 || n == 17) mbar_wait(BAR(JOB + 4 + (n >> 3)), L);
        mbar_wait(BAR(F4 + p), (n / 6 + (p >= 2 ? L : 0)) & 1);
        KB(80 + n);
        if (n == 1 && wu == 0) ST(21);
        if (n == 0 && wu == 0) ST(22);
        wg_fence();
        static_for<0, 4>([&](auto kk) {
          wgmma_128<1, 1, DI(slot4(p) + kk.value * 2048, 8192), DI((n == 9 ? OFF_X + 16384 : n % 17 ? slot4(p) + 16384 : OFF_X) + kk.value * 2048, 8192)>(xa, sda, sd);
        });
        wg_commit();
        if (n) { wg_wait<1>(); release(E4 + (n + 5) % 6); }
        if (n == 8) mbar_wait(BAR(RD + 2), L);
        else if (n < 16 && !(n & 1)) sched_fence(P.zero);
        if constexpr (n < 16 && !(n & 1)) gelu8(1 + (n >> 3), (n >> 1) & 3);
        if ((n & 7) == 7) { fence_async_smem(); signal(JOB + 5 + (n >> 3)); }
      });
      {
        int p = 0, pp = 5;
        uint32_t par = L ? 0x03 : 0x3f;
        auto g4_loop = [&](int n0, int n1, int nrel) {
#pragma unroll 1
          for (int n = n0; n < n1; n++) {
            mbar_wait(BAR(F4 + p), (par >> p) & 1);
            KB(80 + n);
            par ^= 1u << p;
            g4_issue(p, slot4(p) + 16384);
            if (n1 == 56 && n == 55 && wg == 0) nb_arrive<NB_LEAD>(256);
            wg_wait<1>();
            if (n > nrel) release(E4 + pp);
            pp = p; if (++p == 6) p = 0;
          }
        };
        g4_loop(18, 56 - LEAD4, 0);
        if (wg == 1) { wg_wait<0>(); release(E4 + pp); nb_sync<NB_LEAD>(256); }
        g4_loop(56 - LEAD4, 56, wg == 1 ? 56 - LEAD4 : 0);
      }
      uint32_t xs;
      uint8_t* xg;
      {
        GEOM;
        xs = sb + OFF_X + wu * 2048 + (lane >> 3) * 128 + ((L ? l7 ^ (lane >> 3) : l7) << 4);
        xg = L ? P.out + (128 * opq(i) + 16 * wu + (lane >> 3)) * 2048 + 256 * j + 16 * l7 : gXB + (opq(i) * 16 + 2 * j) * 16384 + wu * 2048 + lane * 16;
        asm volatile("" : "+r"(xs), "+l"(xg));
      }
      mbar_wait(BAR(RD + 1), L);
      wg_wait<0>();
      release(E4 + 1);
      fence_regs(xa);
      TS(9 + 32 * L);
      {
        GEOM;
#pragma unroll
        for (int t = 0; t < 16; t += 2) {
          stsm4(sb + OFF_X + (t >> 3) * 16384 + (16 * wu + lr) * 128 + ((((t & 7) + lt) ^ l7) << 4),
                pack2(xa[4 * t], xa[4 * t + 1]), pack2(xa[4 * t + 2], xa[4 * t + 3]),
                pack2(xa[4 * t + 4], xa[4 * t + 5]), pack2(xa[4 * t + 6], xa[4 * t + 7]));
          if ((t & 7) == 6 && (L || t == 6)) {
            __syncwarp();
            uint4 v[4];
#pragma unroll
            for (int k = 0; k < 4; k++) lds128((xs ^ (L ? (k & 1) << 6 : 0)) + k * 512 + (t >> 3) * 16384, v[k].x, v[k].y, v[k].z, v[k].w);
#pragma unroll
            for (int k = 0; k < 4; k++)
              asm volatile("st.global.v4.b32 [%0], {%1, %2, %3, %4};" ::"l"(xg + k * (L ? 8192 : 512) + (t >> 3) * 128), "r"(v[k].x), "r"(v[k].y), "r"(v[k].z), "r"(v[k].w) : "memory");
            if (L == 0) signal(JOB + 8);
          }
        }
        if (L) break;
        fence_async_smem();
        signal(JOB + 9);
        nb_sync<NB_BOTH>(256);
      }
      TS(10 + 32 * L);
      KB(136);
    }
    cluster_bar();
    TS(32);
  }
}

typedef CUresult (*EncodeFn)(CUtensorMap*, CUtensorMapDataType, cuuint32_t, void*, const cuuint64_t*, const cuuint64_t*, const cuuint32_t*,
                             const cuuint32_t*, CUtensorMapInterleave, CUtensorMapSwizzle, CUtensorMapL2promotion, CUtensorMapFloatOOBfill);

void make_map(EncodeFn enc, CUtensorMap* mp, const void* base, int rank, cuuint64_t d0, cuuint64_t d1, cuuint64_t d2, cuuint64_t s1, cuuint64_t s2,
              cuuint32_t b0, cuuint32_t b1, cuuint32_t b2) {
  cuuint64_t dims[3] = {d0, d1, d2}, strides[2] = {s1, s2};
  cuuint32_t box[3] = {b0, b1, b2}, es[3] = {1, 1, 1};
  CUresult res = enc(mp, CU_TENSOR_MAP_DATA_TYPE_BFLOAT16, rank, const_cast<void*>(base), dims, strides, box, es, CU_TENSOR_MAP_INTERLEAVE_NONE,
                     CU_TENSOR_MAP_SWIZZLE_128B, CU_TENSOR_MAP_L2_PROMOTION_L2_128B, CU_TENSOR_MAP_FLOAT_OOB_FILL_NONE);
  (void)res;
}

}

extern "C" void kernel_launch(void* const* d_in, const int* in_sizes, int n_in, void* d_out, int out_size) {
  (void)in_sizes; (void)n_in; (void)out_size;
  static EncodeFn enc = nullptr;
  if (!enc) {
    void* fn = nullptr;
    cudaDriverEntryPointQueryResult qr;
    cudaGetDriverEntryPoint("cuTensorMapEncodeTiled", &fn, cudaEnableDefault, &qr);
    enc = (EncodeFn)fn;
    cudaFuncSetAttribute(fused_kernel, cudaFuncAttributeMaxDynamicSharedMemorySize, SMEM_BYTES);
  }
  Params P;
  make_map(enc, &P.x0, d_in[0], 2, D_, S_, 1, D_ * 2, 0, 64, 128, 1);
  make_map(enc, &P.wqkv, d_in[1], 3, D_, D_, 3, 3 * D_ * 2, D_ * 2, 64, 32, 3);
  make_map(enc, &P.wo, d_in[2], 2, D_, D_, 1, D_ * 2, 0, 64, 64, 1);
  make_map(enc, &P.w1, d_in[4], 3, 64, S_, F_ / 64, F_ * 2, 128, 64, 64, 3);
  make_map(enc, &P.w1h, d_in[4], 3, 32, S_, F_ / 32, F_ * 2, 64, 64, 64, 1);
  make_map(enc, &P.w2, d_in[6], 3, 64, F_, S_ / 64, S_ * 2, 128, 64, 64, 2);
  P.out = (uint8_t*)d_out;
  P.wqkv_p = (const bf16*)d_in[1];
  P.wo_p = (const bf16*)d_in[2];
  P.w1_p = (const bf16*)d_in[4];
  P.w2_p = (const bf16*)d_in[6];
  P.b1 = (const bf16*)d_in[5];
  P.b2 = (const bf16*)d_in[7];
  P.zero = 0;
  fused_kernel<<<128, 384, SMEM_BYTES>>>(P);
}
```

```cpp
#include <cuda_runtime.h>
#include <cuda_bf16.h>
#include <cuda.h>
#include <stdint.h>

namespace {

typedef __nv_bfloat16 bf16;
constexpr int S_ = 2048, D_ = 1024, F_ = 3584;

constexpr uint32_t OFF_STG  = 163840;
constexpr uint32_t OFF_X    = 196608;
constexpr uint32_t OFF_BAR  = 229376;
constexpr uint32_t OFF_CS   = OFF_BAR + 512;
constexpr uint32_t OFF_B1   = OFF_CS + 1536;
constexpr uint32_t SMEM_BYTES = OFF_B1 + 896 + 128;
constexpr int F1 = 0, E1 = 4, F2 = 8, E2 = 13, F3 = 18, E3 = 22, F4 = 26, E4 = 32;
constexpr int JOB = 38;
constexpr int RD = 48;
constexpr int XF = 54, STD = 56, STAT = 58, FOLD = 59, CSJ = 61, HALO = 62;
constexpr int NB_BOTH = 1, NB_HELP = 2, NB_INIT = 3, NB_LEAD = 4, NB_WG0 = 5;

__host__ __device__ constexpr uint32_t slot1(int p) { return p * 40960; }
__host__ __device__ constexpr uint32_t slot2(int p) { return p * 32768; }
__host__ __device__ constexpr uint32_t slot3(int p) { return ((p + 2) & 3) * 49152; }
__host__ __device__ constexpr uint32_t slot4(int p) { return (p < 2 ? p + 4 : p - 2) * 32768; }

__device__ __align__(1024) uint8_t gXB[16 * 16 * 16384];
__device__ __align__(1024) uint8_t gOB[16 * 16 * 16384];
__device__ __align__(1024) uint8_t gHB[8 * 32 * 16384];
__device__ __align__(1024) uint8_t gUB[8 * 56 * 16384];
__device__ __align__(1024) uint2   gST[2][16][8][8][16];
__device__ __align__(1024) uint4   gHalo[2][16][8][12][32];
__device__ __align__(1024) uint32_t gAck[2][16][8][2][8];
__device__ __align__(1024) uint4   gCS[8][16][64];
__device__ __align__(1024) uint32_t gFlag[2][7][16][32];
__device__ uint32_t gEpoch;
#define TS(k)
#define TS2(k)

#define S5(k)
#define KB(k)
#define ST(k)
struct Params {
  CUtensorMap x0, wqkv, wo, w1, w1h, w2;
  uint8_t* out;
  const bf16 *wqkv_p, *wo_p, *w1_p, *w2_p, *b1, *b2;
  uint32_t zero;
};

template <int TA, int TB, uint32_t IA, uint32_t IB, int O = 0, int LEN> __device__ __forceinline__ void wgmma_32(float (&d)[LEN], uint32_t da, uint32_t db) {
  asm volatile("{\n.reg .b64 da, db;\n.reg .b32 la, lb;\nadd.u32 la, %16, %20;\nadd.u32 lb, %17, %21;\nmov.b64 da, {la, 0x40000040};\nmov.b64 db, {lb, 0x40000040};\n"
  "wgmma.mma_async.sync.aligned.m64n32k16.f32.bf16.bf16 {"
  "%0, %1, %2, %3, %4, %5, %6, %7, %8, %9, %10, %11, %12, %13, %14, %15"
  "}, da, db, 1, 1, 1, %18, %19;\n}\n"
  : "+f"(d[O + 0]), "+f"(d[O + 1]), "+f"(d[O + 2]), "+f"(d[O + 3]), "+f"(d[O + 4]), "+f"(d[O + 5]), "+f"(d[O + 6]), "+f"(d[O + 7]),
    "+f"(d[O + 8]), "+f"(d[O + 9]), "+f"(d[O + 10]), "+f"(d[O + 11]), "+f"(d[O + 12]), "+f"(d[O + 13]), "+f"(d[O + 14]), "+f"(d[O + 15])
  : "r"(da), "r"(db), "n"(TA), "n"(TB), "n"(IA), "n"(IB));
}
template <int TA, int TB, uint32_t IA, uint32_t IB, int O = 0, int LEN> __device__ __forceinline__ void wgmma_128(float (&d)[LEN], uint32_t da, uint32_t db) {
  asm volatile("{\n.reg .b64 da, db;\n.reg .b32 la, lb;\nadd.u32 la, %64, %68;\nadd.u32 lb, %65, %69;\nmov.b64 da, {la, 0x40000040};\nmov.b64 db, {lb, 0x40000040};\n"
  "wgmma.mma_async.sync.aligned.m64n128k16.f32.bf16.bf16 {"
  "%0, %1, %2, %3, %4, %5, %6, %7, %8, %9, %10, %11, %12, %13, %14, %15, "
  "%16, %17, %18, %19, %20, %21, %22, %23, %24, %25, %26, %27, %28, %29, %30, %31, "
  "%32, %33, %34, %35, %36, %37, %38, %39, %40, %41, %42, %43, %44, %45, %46, %47, "
  "%48, %49, %50, %51, %52, %53, %54, %55, %56, %57, %58, %59, %60, %61, %62, %63"
  "}, da, db, 1, 1, 1, %66, %67;\n}\n"
  : "+f"(d[O + 0]), "+f"(d[O + 1]), "+f"(d[O + 2]), "+f"(d[O + 3]), "+f"(d[O + 4]), "+f"(d[O + 5]), "+f"(d[O + 6]), "+f"(d[O + 7]),
    "+f"(d[O + 8]), "+f"(d[O + 9]), "+f"(d[O + 10]), "+f"(d[O + 11]), "+f"(d[O + 12]), "+f"(d[O + 13]), "+f"(d[O + 14]), "+f"(d[O + 15]),
    "+f"(d[O + 16]), "+f"(d[O + 17]), "+f"(d[O + 18]), "+f"(d[O + 19]), "+f"(d[O + 20]), "+f"(d[O + 21]), "+f"(d[O + 22]), "+f"(d[O + 23]),
    "+f"(d[O + 24]), "+f"(d[O + 25]), "+f"(d[O + 26]), "+f"(d[O + 27]), "+f"(d[O + 28]), "+f"(d[O + 29]), "+f"(d[O + 30]), "+f"(d[O + 31]),
    "+f"(d[O + 32]), "+f"(d[O + 33]), "+f"(d[O + 34]), "+f"(d[O + 35]), "+f"(d[O + 36]), "+f"(d[O + 37]), "+f"(d[O + 38]), "+f"(d[O + 39]),
    "+f"(d[O + 40]), "+f"(d[O + 41]), "+f"(d[O + 42]), "+f"(d[O + 43]), "+f"(d[O + 44]), "+f"(d[O + 45]), "+f"(d[O + 46]), "+f"(d[O + 47]),
    "+f"(d[O + 48]), "+f"(d[O + 49]), "+f"(d[O + 50]), "+f"(d[O + 51]), "+f"(d[O + 52]), "+f"(d[O + 53]), "+f"(d[O + 54]), "+f"(d[O + 55]),
    "+f"(d[O + 56]), "+f"(d[O + 57]), "+f"(d[O + 58]), "+f"(d[O + 59]), "+f"(d[O + 60]), "+f"(d[O + 61]), "+f"(d[O + 62]), "+f"(d[O + 63])
  : "r"(da), "r"(db), "n"(TA), "n"(TB), "n"(IA), "n"(IB));
}
template <int TA, int TB, uint32_t IA, uint32_t IB, int O = 0, int LEN> __device__ __forceinline__ void wgmma_192(float (&d)[LEN], uint32_t da, uint32_t db) {
  asm volatile("{\n.reg .b64 da, db;\n.reg .b32 la, lb;\nadd.u32 la, %96, %100;\nadd.u32 lb, %97, %101;\nmov.b64 da, {la, 0x40000040};\nmov.b64 db, {lb, 0x40000040};\n"
  "wgmma.mma_async.sync.aligned.m64n192k16.f32.bf16.bf16 {"
  "%0, %1, %2, %3, %4, %5, %6, %7, %8, %9, %10, %11, %12, %13, %14, %15, "
  "%16, %17, %18, %19, %20, %21, %22, %23, %24, %25, %26, %27, %28, %29, %30, %31, "
  "%32, %33, %34, %35, %36, %37, %38, %39, %40, %41, %42, %43, %44, %45, %46, %47, "
  "%48, %49, %50, %51, %52, %53, %54, %55, %56, %57, %58, %59, %60, %61, %62, %63, "
  "%64, %65, %66, %67, %68, %69, %70, %71, %72, %73, %74, %75, %76, %77, %78, %79, "
  "%80, %81, %82, %83, %84, %85, %86, %87, %88, %89, %90, %91, %92, %93, %94, %95"
  "}, da, db, 1, 1, 1, %98, %99;\n}\n"
  : "+f"(d[O + 0]), "+f"(d[O + 1]), "+f"(d[O + 2]), "+f"(d[O + 3]), "+f"(d[O + 4]), "+f"(d[O + 5]), "+f"(d[O + 6]), "+f"(d[O + 7]),
    "+f"(d[O + 8]), "+f"(d[O + 9]), "+f"(d[O + 10]), "+f"(d[O + 11]), "+f"(d[O + 12]), "+f"(d[O + 13]), "+f"(d[O + 14]), "+f"(d[O + 15]),
    "+f"(d[O + 16]), "+f"(d[O + 17]), "+f"(d[O + 18]), "+f"(d[O + 19]), "+f"(d[O + 20]), "+f"(d[O + 21]), "+f"(d[O + 22]), "+f"(d[O + 23]),
    "+f"(d[O + 24]), "+f"(d[O + 25]), "+f"(d[O + 26]), "+f"(d[O + 27]), "+f"(d[O + 28]), "+f"(d[O + 29]), "+f"(d[O + 30]), "+f"(d[O + 31]),
    "+f"(d[O + 32]), "+f"(d[O + 33]), "+f"(d[O + 34]), "+f"(d[O + 35]), "+f"(d[O + 36]), "+f"(d[O + 37]), "+f"(d[O + 38]), "+f"(d[O + 39]),
    "+f"(d[O + 40]), "+f"(d[O + 41]), "+f"(d[O + 42]), "+f"(d[O + 43]), "+f"(d[O + 44]), "+f"(d[O + 45]), "+f"(d[O + 46]), "+f"(d[O + 47]),
    "+f"(d[O + 48]), "+f"(d[O + 49]), "+f"(d[O + 50]), "+f"(d[O + 51]), "+f"(d[O + 52]), "+f"(d[O + 53]), "+f"(d[O + 54]), "+f"(d[O + 55]),
    "+f"(d[O + 56]), "+f"(d[O + 57]), "+f"(d[O + 58]), "+f"(d[O + 59]), "+f"(d[O + 60]), "+f"(d[O + 61]), "+f"(d[O + 62]), "+f"(d[O + 63]),
    "+f"(d[O + 64]), "+f"(d[O + 65]), "+f"(d[O + 66]), "+f"(d[O + 67]), "+f"(d[O + 68]), "+f"(d[O + 69]), "+f"(d[O + 70]), "+f"(d[O + 71]),
    "+f"(d[O + 72]), "+f"(d[O + 73]), "+f"(d[O + 74]), "+f"(d[O + 75]), "+f"(d[O + 76]), "+f"(d[O + 77]), "+f"(d[O + 78]), "+f"(d[O + 79]),
    "+f"(d[O + 80]), "+f"(d[O + 81]), "+f"(d[O + 82]), "+f"(d[O + 83]), "+f"(d[O + 84]), "+f"(d[O + 85]), "+f"(d[O + 86]), "+f"(d[O + 87]),
    "+f"(d[O + 88]), "+f"(d[O + 89]), "+f"(d[O + 90]), "+f"(d[O + 91]), "+f"(d[O + 92]), "+f"(d[O + 93]), "+f"(d[O + 94]), "+f"(d[O + 95])
  : "r"(da), "r"(db), "n"(TA), "n"(TB), "n"(IA), "n"(IB));
}
template <int TA, int TB, uint32_t IA, uint32_t IB, int O = 0, int LEN> __device__ __forceinline__ void wgmma_192z(float (&d)[LEN], uint32_t da, uint32_t db) {
  asm volatile("{\n.reg .b64 da, db;\n.reg .b32 la, lb;\nadd.u32 la, %96, %100;\nadd.u32 lb, %97, %101;\nmov.b64 da, {la, 0x40000040};\nmov.b64 db, {lb, 0x40000040};\n"
  "wgmma.mma_async.sync.aligned.m64n192k16.f32.bf16.bf16 {"
  "%0, %1, %2, %3, %4, %5, %6, %7, %8, %9, %10, %11, %12, %13, %14, %15, "
  "%16, %17, %18, %19, %20, %21, %22, %23, %24, %25, %26, %27, %28, %29, %30, %31, "
  "%32, %33, %34, %35, %36, %37, %38, %39, %40, %41, %42, %43, %44, %45, %46, %47, "
  "%48, %49, %50, %51, %52, %53, %54, %55, %56, %57, %58, %59, %60, %61, %62, %63, "
  "%64, %65, %66, %67, %68, %69, %70, %71, %72, %73, %74, %75, %76, %77, %78, %79, "
  "%80, %81, %82, %83, %84, %85, %86, %87, %88, %89, %90, %91, %92, %93, %94, %95"
  "}, da, db, 0, 1, 1, %98, %99;\n}\n"
  : "=f"(d[O + 0]), "=f"(d[O + 1]), "=f"(d[O + 2]), "=f"(d[O + 3]), "=f"(d[O + 4]), "=f"(d[O + 5]), "=f"(d[O + 6]), "=f"(d[O + 7]),
    "=f"(d[O + 8]), "=f"(d[O + 9]), "=f"(d[O + 10]), "=f"(d[O + 11]), "=f"(d[O + 12]), "=f"(d[O + 13]), "=f"(d[O + 14]), "=f"(d[O + 15]),
    "=f"(d[O + 16]), "=f"(d[O + 17]), "=f"(d[O + 18]), "=f"(d[O + 19]), "=f"(d[O + 20]), "=f"(d[O + 21]), "=f"(d[O + 22]), "=f"(d[O + 23]),
    "=f"(d[O + 24]), "=f"(d[O + 25]), "=f"(d[O + 26]), "=f"(d[O + 27]), "=f"(d[O + 28]), "=f"(d[O + 29]), "=f"(d[O + 30]), "=f"(d[O + 31]),
    "=f"(d[O + 32]), "=f"(d[O + 33]), "=f"(d[O + 34]), "=f"(d[O + 35]), "=f"(d[O + 36]), "=f"(d[O + 37]), "=f"(d[O + 38]), "=f"(d[O + 39]),
    "=f"(d[O + 40]), "=f"(d[O + 41]), "=f"(d[O + 42]), "=f"(d[O + 43]), "=f"(d[O + 44]), "=f"(d[O + 45]), "=f"(d[O + 46]), "=f"(d[O + 47]),
    "=f"(d[O + 48]), "=f"(d[O + 49]), "=f"(d[O + 50]), "=f"(d[O + 51]), "=f"(d[O + 52]), "=f"(d[O + 53]), "=f"(d[O + 54]), "=f"(d[O + 55]),
    "=f"(d[O + 56]), "=f"(d[O + 57]), "=f"(d[O + 58]), "=f"(d[O + 59]), "=f"(d[O + 60]), "=f"(d[O + 61]), "=f"(d[O + 62]), "=f"(d[O + 63]),
    "=f"(d[O + 64]), "=f"(d[O + 65]), "=f"(d[O + 66]), "=f"(d[O + 67]), "=f"(d[O + 68]), "=f"(d[O + 69]), "=f"(d[O + 70]), "=f"(d[O + 71]),
    "=f"(d[O + 72]), "=f"(d[O + 73]), "=f"(d[O + 74]), "=f"(d[O + 75]), "=f"(d[O + 76]), "=f"(d[O + 77]), "=f"(d[O + 78]), "=f"(d[O + 79]),
    "=f"(d[O + 80]), "=f"(d[O + 81]), "=f"(d[O + 82]), "=f"(d[O + 83]), "=f"(d[O + 84]), "=f"(d[O + 85]), "=f"(d[O + 86]), "=f"(d[O + 87]),
    "=f"(d[O + 88]), "=f"(d[O + 89]), "=f"(d[O + 90]), "=f"(d[O + 91]), "=f"(d[O + 92]), "=f"(d[O + 93]), "=f"(d[O + 94]), "=f"(d[O + 95])
  : "r"(da), "r"(db), "n"(TA), "n"(TB), "n"(IA), "n"(IB));
}
template <int TA, int TB, uint32_t IA, uint32_t IB, int O = 0, int LEN> __device__ __forceinline__ void wgmma_224(float (&d)[LEN], uint32_t da, uint32_t db) {
  asm volatile("{\n.reg .b64 da, db;\n.reg .b32 la, lb;\nadd.u32 la, %112, %116;\nadd.u32 lb, %113, %117;\nmov.b64 da, {la, 0x40000040};\nmov.b64 db, {lb, 0x40000040};\n"
  "wgmma.mma_async.sync.aligned.m64n224k16.f32.bf16.bf16 {"
  "%0, %1, %2, %3, %4, %5, %6, %7, %8, %9, %10, %11, %12, %13, %14, %15, "
  "%16, %17, %18, %19, %20, %21, %22, %23, %24, %25, %26, %27, %28, %29, %30, %31, "
  "%32, %33, %34, %35, %36, %37, %38, %39, %40, %41, %42, %43, %44, %45, %46, %47, "
  "%48, %49, %50, %51, %52, %53, %54, %55, %56, %57, %58, %59, %60, %61, %62, %63, "
  "%64, %65, %66, %67, %68, %69, %70, %71, %72, %73, %74, %75, %76, %77, %78, %79, "
  "%80, %81, %82, %83, %84, %85, %86, %87, %88, %89, %90, %91, %92, %93, %94, %95, "
  "%96, %97, %98, %99, %100, %101, %102, %103, %104, %105, %106, %107, %108, %109, %110, %111"
  "}, da, db, 1, 1, 1, %114, %115;\n}\n"
  : "+f"(d[O + 0]), "+f"(d[O + 1]), "+f"(d[O + 2]), "+f"(d[O + 3]), "+f"(d[O + 4]), "+f"(d[O + 5]), "+f"(d[O + 6]), "+f"(d[O + 7]),
    "+f"(d[O + 8]), "+f"(d[O + 9]), "+f"(d[O + 10]), "+f"(d[O + 11]), "+f"(d[O + 12]), "+f"(d[O + 13]), "+f"(d[O + 14]), "+f"(d[O + 15]),
    "+f"(d[O + 16]), "+f"(d[O + 17]), "+f"(d[O + 18]), "+f"(d[O + 19]), "+f"(d[O + 20]), "+f"(d[O + 21]), "+f"(d[O + 22]), "+f"(d[O + 23]),
    "+f"(d[O + 24]), "+f"(d[O + 25]), "+f"(d[O + 26]), "+f"(d[O + 27]), "+f"(d[O + 28]), "+f"(d[O + 29]), "+f"(d[O + 30]), "+f"(d[O + 31]),
    "+f"(d[O + 32]), "+f"(d[O + 33]), "+f"(d[O + 34]), "+f"(d[O + 35]), "+f"(d[O + 36]), "+f"(d[O + 37]), "+f"(d[O + 38]), "+f"(d[O + 39]),
    "+f"(d[O + 40]), "+f"(d[O + 41]), "+f"(d[O + 42]), "+f"(d[O + 43]), "+f"(d[O + 44]), "+f"(d[O + 45]), "+f"(d[O + 46]), "+f"(d[O + 47]),
    "+f"(d[O + 48]), "+f"(d[O + 49]), "+f"(d[O + 50]), "+f"(d[O + 51]), "+f"(d[O + 52]), "+f"(d[O + 53]), "+f"(d[O + 54]), "+f"(d[O + 55]),
    "+f"(d[O + 56]), "+f"(d[O + 57]), "+f"(d[O + 58]), "+f"(d[O + 59]), "+f"(d[O + 60]), "+f"(d[O + 61]), "+f"(d[O + 62]), "+f"(d[O + 63]),
    "+f"(d[O + 64]), "+f"(d[O + 65]), "+f"(d[O + 66]), "+f"(d[O + 67]), "+f"(d[O + 68]), "+f"(d[O + 69]), "+f"(d[O + 70]), "+f"(d[O + 71]),
    "+f"(d[O + 72]), "+f"(d[O + 73]), "+f"(d[O + 74]), "+f"(d[O + 75]), "+f"(d[O + 76]), "+f"(d[O + 77]), "+f"(d[O + 78]), "+f"(d[O + 79]),
    "+f"(d[O + 80]), "+f"(d[O + 81]), "+f"(d[O + 82]), "+f"(d[O + 83]), "+f"(d[O + 84]), "+f"(d[O + 85]), "+f"(d[O + 86]), "+f"(d[O + 87]),
    "+f"(d[O + 88]), "+f"(d[O + 89]), "+f"(d[O + 90]), "+f"(d[O + 91]), "+f"(d[O + 92]), "+f"(d[O + 93]), "+f"(d[O + 94]), "+f"(d[O + 95]),
    "+f"(d[O + 96]), "+f"(d[O + 97]), "+f"(d[O + 98]), "+f"(d[O + 99]), "+f"(d[O + 100]), "+f"(d[O + 101]), "+f"(d[O + 102]), "+f"(d[O + 103]),
    "+f"(d[O + 104]), "+f"(d[O + 105]), "+f"(d[O + 106]), "+f"(d[O + 107]), "+f"(d[O + 108]), "+f"(d[O + 109]), "+f"(d[O + 110]), "+f"(d[O + 111])
  : "r"(da), "r"(db), "n"(TA), "n"(TB), "n"(IA), "n"(IB));
}
__device__ __forceinline__ void wgmma_rs_192(float (&d)[96], uint32_t a0, uint32_t a1, uint32_t a2, uint32_t a3, uint64_t db) {
  asm volatile("wgmma.mma_async.sync.aligned.m64n192k16.f32.bf16.bf16 {"
  "%0, %1, %2, %3, %4, %5, %6, %7, %8, %9, %10, %11, %12, %13, %14, %15, "
  "%16, %17, %18, %19, %20, %21, %22, %23, %24, %25, %26, %27, %28, %29, %30, %31, "
  "%32, %33, %34, %35, %36, %37, %38, %39, %40, %41, %42, %43, %44, %45, %46, %47, "
  "%48, %49, %50, %51, %52, %53, %54, %55, %56, %57, %58, %59, %60, %61, %62, %63, "
  "%64, %65, %66, %67, %68, %69, %70, %71, %72, %73, %74, %75, %76, %77, %78, %79, "
  "%80, %81, %82, %83, %84, %85, %86, %87, %88, %89, %90, %91, %92, %93, %94, %95"
  "}, {%96, %97, %98, %99}, %100, 1, 1, 1, 1;\n"
  : "+f"(d[0]), "+f"(d[1]), "+f"(d[2]), "+f"(d[3]), "+f"(d[4]), "+f"(d[5]), "+f"(d[6]), "+f"(d[7]),
    "+f"(d[8]), "+f"(d[9]), "+f"(d[10]), "+f"(d[11]), "+f"(d[12]), "+f"(d[13]), "+f"(d[14]), "+f"(d[15]),
    "+f"(d[16]), "+f"(d[17]), "+f"(d[18]), "+f"(d[19]), "+f"(d[20]), "+f"(d[21]), "+f"(d[22]), "+f"(d[23]),
    "+f"(d[24]), "+f"(d[25]), "+f"(d[26]), "+f"(d[27]), "+f"(d[28]), "+f"(d[29]), "+f"(d[30]), "+f"(d[31]),
    "+f"(d[32]), "+f"(d[33]), "+f"(d[34]), "+f"(d[35]), "+f"(d[36]), "+f"(d[37]), "+f"(d[38]), "+f"(d[39]),
    "+f"(d[40]), "+f"(d[41]), "+f"(d[42]), "+f"(d[43]), "+f"(d[44]), "+f"(d[45]), "+f"(d[46]), "+f"(d[47]),
    "+f"(d[48]), "+f"(d[49]), "+f"(d[50]), "+f"(d[51]), "+f"(d[52]), "+f"(d[53]), "+f"(d[54]), "+f"(d[55]),
    "+f"(d[56]), "+f"(d[57]), "+f"(d[58]), "+f"(d[59]), "+f"(d[60]), "+f"(d[61]), "+f"(d[62]), "+f"(d[63]),
    "+f"(d[64]), "+f"(d[65]), "+f"(d[66]), "+f"(d[67]), "+f"(d[68]), "+f"(d[69]), "+f"(d[70]), "+f"(d[71]),
    "+f"(d[72]), "+f"(d[73]), "+f"(d[74]), "+f"(d[75]), "+f"(d[76]), "+f"(d[77]), "+f"(d[78]), "+f"(d[79]),
    "+f"(d[80]), "+f"(d[81]), "+f"(d[82]), "+f"(d[83]), "+f"(d[84]), "+f"(d[85]), "+f"(d[86]), "+f"(d[87]),
    "+f"(d[88]), "+f"(d[89]), "+f"(d[90]), "+f"(d[91]), "+f"(d[92]), "+f"(d[93]), "+f"(d[94]), "+f"(d[95])
  : "r"(a0), "r"(a1), "r"(a2), "r"(a3), "l"(db));
}
__device__ __forceinline__ void wgmma_rs_224z(float (&d)[112], uint32_t a0, uint32_t a1, uint32_t a2, uint32_t a3, uint64_t db) {
  asm volatile("wgmma.mma_async.sync.aligned.m64n224k16.f32.bf16.bf16 {"
  "%0, %1, %2, %3, %4, %5, %6, %7, %8, %9, %10, %11, %12, %13, %14, %15, "
  "%16, %17, %18, %19, %20, %21, %22, %23, %24, %25, %26, %27, %28, %29, %30, %31, "
  "%32, %33, %34, %35, %36, %37, %38, %39, %40, %41, %42, %43, %44, %45, %46, %47, "
  "%48, %49, %50, %51, %52, %53, %54, %55, %56, %57, %58, %59, %60, %61, %62, %63, "
  "%64, %65, %66, %67, %68, %69, %70, %71, %72, %73, %74, %75, %76, %77, %78, %79, "
  "%80, %81, %82, %83, %84, %85, %86, %87, %88, %89, %90, %91, %92, %93, %94, %95, "
  "%96, %97, %98, %99, %100, %101, %102, %103, %104, %105, %106, %107, %108, %109, %110, %111"
  "}, {%112, %113, %114, %115}, %116, 0, 1, 1, 1;\n"
  : "=f"(d[0]), "=f"(d[1]), "=f"(d[2]), "=f"(d[3]), "=f"(d[4]), "=f"(d[5]), "=f"(d[6]), "=f"(d[7]),
    "=f"(d[8]), "=f"(d[9]), "=f"(d[10]), "=f"(d[11]), "=f"(d[12]), "=f"(d[13]), "=f"(d[14]), "=f"(d[15]),
    "=f"(d[16]), "=f"(d[17]), "=f"(d[18]), "=f"(d[19]), "=f"(d[20]), "=f"(d[21]), "=f"(d[22]), "=f"(d[23]),
    "=f"(d[24]), "=f"(d[25]), "=f"(d[26]), "=f"(d[27]), "=f"(d[28]), "=f"(d[29]), "=f"(d[30]), "=f"(d[31]),
    "=f"(d[32]), "=f"(d[33]), "=f"(d[34]), "=f"(d[35]), "=f"(d[36]), "=f"(d[37]), "=f"(d[38]), "=f"(d[39]),
    "=f"(d[40]), "=f"(d[41]), "=f"(d[42]), "=f"(d[43]), "=f"(d[44]), "=f"(d[45]), "=f"(d[46]), "=f"(d[47]),
    "=f"(d[48]), "=f"(d[49]), "=f"(d[50]), "=f"(d[51]), "=f"(d[52]), "=f"(d[53]), "=f"(d[54]), "=f"(d[55]),
    "=f"(d[56]), "=f"(d[57]), "=f"(d[58]), "=f"(d[59]), "=f"(d[60]), "=f"(d[61]), "=f"(d[62]), "=f"(d[63]),
    "=f"(d[64]), "=f"(d[65]), "=f"(d[66]), "=f"(d[67]), "=f"(d[68]), "=f"(d[69]), "=f"(d[70]), "=f"(d[71]),
    "=f"(d[72]), "=f"(d[73]), "=f"(d[74]), "=f"(d[75]), "=f"(d[76]), "=f"(d[77]), "=f"(d[78]), "=f"(d[79]),
    "=f"(d[80]), "=f"(d[81]), "=f"(d[82]), "=f"(d[83]), "=f"(d[84]), "=f"(d[85]), "=f"(d[86]), "=f"(d[87]),
    "=f"(d[88]), "=f"(d[89]), "=f"(d[90]), "=f"(d[91]), "=f"(d[92]), "=f"(d[93]), "=f"(d[94]), "=f"(d[95]),
    "=f"(d[96]), "=f"(d[97]), "=f"(d[98]), "=f"(d[99]), "=f"(d[100]), "=f"(d[101]), "=f"(d[102]), "=f"(d[103]),
    "=f"(d[104]), "=f"(d[105]), "=f"(d[106]), "=f"(d[107]), "=f"(d[108]), "=f"(d[109]), "=f"(d[110]), "=f"(d[111])
  : "r"(a0), "r"(a1), "r"(a2), "r"(a3), "l"(db));
}

__device__ __forceinline__ uint32_t smem_u32(const void* p) { return (uint32_t)__cvta_generic_to_shared(p); }
__device__ __forceinline__ void mbar_init(uint32_t bar, uint32_t cnt) { asm volatile("mbarrier.init.shared::cta.b64 [%0], %1;" ::"r"(bar), "r"(cnt) : "memory"); }
__device__ __forceinline__ void mbar_expect(uint32_t bar, uint32_t bytes) { asm volatile("mbarrier.arrive.expect_tx.shared::cta.b64 _, [%0], %1;" ::"r"(bar), "r"(bytes) : "memory"); }
__device__ __forceinline__ void mbar_arrive(uint32_t bar) { asm volatile("mbarrier.arrive.shared::cta.b64 _, [%0];" ::"r"(bar) : "memory"); }
__device__ __forceinline__ void mbar_arrive_cl(uint32_t cbar) { asm volatile("mbarrier.arrive.shared::cluster.b64 _, [%0];" ::"r"(cbar) : "memory"); }
__device__ __forceinline__ uint32_t mapa(uint32_t a, uint32_t cta) { uint32_t r; asm("mapa.shared::cluster.u32 %0, %1, %2;" : "=r"(r) : "r"(a), "r"(cta)); return r; }
__device__ __forceinline__ void mbar_wait(uint32_t bar, uint32_t parity) {
  asm volatile("{\n.reg .pred p;\n.reg .u32 n;\nmov.u32 n, 0;\n"
    "LAB_WAIT:\n"
    "mbarrier.try_wait.parity.shared::cta.b64 p, [%0], %1;\n"
    "@p bra LAB_DONE;\n"
    "add.u32 n, n, 1;\n"
    "setp.lt.u32 p, n, 2000000;\n"
    "@p bra LAB_WAIT;\n"
    "trap;\n"
    "LAB_DONE:\n}\n" ::"r"(bar), "r"(parity) : "memory");
}
constexpr uint32_t SPIN_MAX = 2000000;
__device__ __forceinline__ void tma2d(uint32_t dst, const CUtensorMap* m, uint32_t bar, int c0, int c1) {
  asm volatile("cp.async.bulk.tensor.2d.shared::cluster.global.mbarrier::complete_tx::bytes [%0], [%1, {%3, %4}], [%2];"
    ::"r"(dst), "l"(m), "r"(bar), "r"(c0), "r"(c1) : "memory");
}
__device__ __forceinline__ void tma2d_mc(uint32_t dst, const CUtensorMap* m, uint32_t bar, int c0, int c1) {
  asm volatile("cp.async.bulk.tensor.2d.shared::cluster.global.mbarrier::complete_tx::bytes.multicast::cluster [%0], [%1, {%3, %4}], [%2], %5;"
    ::"r"(dst), "l"(m), "r"(bar), "r"(c0), "r"(c1), "h"((uint16_t)3) : "memory");
}
__device__ __forceinline__ void tma3d(uint32_t dst, const CUtensorMap* m, uint32_t bar, int c0, int c1, int c2) {
  asm volatile("cp.async.bulk.tensor.3d.shared::cluster.global.mbarrier::complete_tx::bytes [%0], [%1, {%3, %4, %5}], [%2];"
    ::"r"(dst), "l"(m), "r"(bar), "r"(c0), "r"(c1), "r"(c2) : "memory");
}
__device__ __forceinline__ void tma3d_mc(uint32_t dst, const CUtensorMap* m, uint32_t bar, int c0, int c1, int c2) {
  asm volatile("cp.async.bulk.tensor.3d.shared::cluster.global.mbarrier::complete_tx::bytes.multicast::cluster [%0], [%1, {%3, %4, %5}], [%2], %6;"
    ::"r"(dst), "l"(m), "r"(bar), "r"(c0), "r"(c1), "r"(c2), "h"((uint16_t)3) : "memory");
}
__device__ __forceinline__ void bulk_ld(uint32_t dst, const void* src, uint32_t bytes, uint32_t bar) {
  asm volatile("cp.async.bulk.shared::cluster.global.mbarrier::complete_tx::bytes [%0], [%1], %2, [%3];" ::"r"(dst), "l"(src), "r"(bytes), "r"(bar) : "memory");
}
__device__ __forceinline__ void bulk_ld_mc(uint32_t dst, const void* src, uint32_t bytes, uint32_t bar) {
  asm volatile("cp.async.bulk.shared::cluster.global.mbarrier::complete_tx::bytes.multicast::cluster [%0], [%1], %2, [%3], %4;"
    ::"r"(dst), "l"(src), "r"(bytes), "r"(bar), "h"((uint16_t)3) : "memory");
}
__device__ __forceinline__ void bulk_st(void* dst, uint32_t src, uint32_t bytes) {
  asm volatile("cp.async.bulk.global.shared::cta.bulk_group [%0], [%1], %2;" ::"l"(dst), "r"(src), "r"(bytes) : "memory");
}
__device__ __forceinline__ void bulk_s2s(uint32_t cdst, uint32_t src, uint32_t bytes, uint32_t cbar) {
  asm volatile("cp.async.bulk.shared::cluster.shared::cta.mbarrier::complete_tx::bytes [%0], [%1], %2, [%3];" ::"r"(cdst), "r"(src), "r"(bytes), "r"(cbar) : "memory");
}
__device__ __forceinline__ void bulk_commit() { asm volatile("cp.async.bulk.commit_group;" ::: "memory"); }
__device__ __forceinline__ void bulk_wait0() { asm volatile("cp.async.bulk.wait_group 0;" ::: "memory"); }
__device__ __forceinline__ void fence_async_smem() { asm volatile("fence.proxy.async.shared::cta;" ::: "memory"); }
__device__ __forceinline__ void wg_fence() { asm volatile("wgmma.fence.sync.aligned;" ::: "memory"); }
__device__ __forceinline__ void wg_commit() { asm volatile("wgmma.commit_group.sync.aligned;" ::: "memory"); }
template <int N> __device__ __forceinline__ void wg_wait() { asm volatile("wgmma.wait_group.sync.aligned %0;" ::"n"(N) : "memory"); }
template <int R> __device__ __forceinline__ void reg_alloc() { asm volatile("setmaxnreg.inc.sync.aligned.u32 %0;" ::"n"(R)); }
template <int R> __device__ __forceinline__ void reg_dealloc() { asm volatile("setmaxnreg.dec.sync.aligned.u32 %0;" ::"n"(R)); }
__device__ __forceinline__ void cluster_bar() { asm volatile("barrier.cluster.arrive.relaxed;\nbarrier.cluster.wait;" ::: "memory"); }
template <int ID> __device__ __forceinline__ void nb_sync(int n) { asm volatile("barrier.sync %0, %1;" ::"n"(ID), "r"(n) : "memory"); }
template <int ID> __device__ __forceinline__ void nb_arrive(int n) { asm volatile("barrier.arrive %0, %1;" ::"n"(ID), "r"(n) : "memory"); }
__device__ __forceinline__ int fresh_tid() { int t; asm volatile("mov.u32 %0, %%tid.x;" : "=r"(t)); return t; }
__device__ __forceinline__ void sched_fence(uint32_t z) { asm volatile("{\n.reg .pred p;\nsetp.ne.u32 p, %0, 0;\nLAB_S:\n@p nanosleep.u32 0;\n@p bra LAB_S;\n}\n" ::"r"(z) : "memory"); }
__device__ __forceinline__ float rsq(float x) { float y; asm("rsqrt.approx.ftz.f32 %0, %1;" : "=f"(y) : "f"(x)); return y; }
__device__ __forceinline__ int opq(int v) { asm volatile("" : "+r"(v)); return v; }
template <int V> struct Int { static constexpr int value = V; };
struct True { static constexpr bool value = true; };
struct False { static constexpr bool value = false; };
template <int N> __device__ __forceinline__ void fence_regs(float (&d)[N]) {
#pragma unroll
  for (int i = 0; i < N; i++) asm volatile("" : "+f"(d[i])::"memory");
}
__host__ __device__ constexpr uint32_t DI(uint32_t off, uint32_t lbo) { return (off >> 4) + ((lbo >> 4) << 16); }
template <int K, int N, class F> __device__ __forceinline__ void static_for(F f) { if constexpr (K < N) { f(Int<K>{}); static_for<K + 1, N>(f); } }
__device__ __forceinline__ uint64_t mkdesc_vec(uint32_t addr, uint32_t sbo) { return (uint64_t)((addr & 0x3FFFF) >> 4) | ((uint64_t)(sbo >> 4) << 32); }
__device__ __forceinline__ void sts16(uint32_t a, uint32_t v) { asm volatile("st.shared.u16 [%0], %1;" ::"r"(a), "h"((uint16_t)v) : "memory"); }
__device__ __forceinline__ uint32_t pack2(float lo, float hi) { uint32_t r; asm("cvt.rn.bf16x2.f32 %0, %1, %2;" : "=r"(r) : "f"(hi), "f"(lo)); return r; }
__device__ __forceinline__ float bf_lo(uint32_t v) { return __uint_as_float(v << 16); }
__device__ __forceinline__ float bf_hi(uint32_t v) { return __uint_as_float(v & 0xffff0000u); }
__device__ __forceinline__ void stsm4(uint32_t a, uint32_t r0, uint32_t r1, uint32_t r2, uint32_t r3) {
  asm volatile("stmatrix.sync.aligned.m8n8.x4.shared.b16 [%0], {%1, %2, %3, %4};" ::"r"(a), "r"(r0), "r"(r1), "r"(r2), "r"(r3) : "memory");
}
__device__ __forceinline__ void stsm4t(uint32_t a, uint32_t r0, uint32_t r1, uint32_t r2, uint32_t r3) {
  asm volatile("stmatrix.sync.aligned.m8n8.x4.trans.shared.b16 [%0], {%1, %2, %3, %4};" ::"r"(a), "r"(r0), "r"(r1), "r"(r2), "r"(r3) : "memory");
}
__device__ __forceinline__ void ldsm4(uint32_t a, uint32_t& r0, uint32_t& r1, uint32_t& r2, uint32_t& r3) {
  asm volatile("ldmatrix.sync.aligned.m8n8.x4.shared.b16 {%0, %1, %2, %3}, [%4];" : "=r"(r0), "=r"(r1), "=r"(r2), "=r"(r3) : "r"(a) : "memory");
}
__device__ __forceinline__ void ldsm4t(uint32_t a, uint32_t& r0, uint32_t& r1, uint32_t& r2, uint32_t& r3) {
  asm volatile("ldmatrix.sync.aligned.m8n8.x4.trans.shared.b16 {%0, %1, %2, %3}, [%4];" : "=r"(r0), "=r"(r1), "=r"(r2), "=r"(r3) : "r"(a) : "memory");
}
__device__ __forceinline__ void mma16816(float (&c)[4], uint32_t a0, uint32_t a1, uint32_t a2, uint32_t a3, uint32_t b0, uint32_t b1) {
  asm volatile("mma.sync.aligned.m16n8k16.row.col.f32.bf16.bf16.f32 {%0, %1, %2, %3}, {%4, %5, %6, %7}, {%8, %9}, {%10, %11, %12, %13};"
    : "=f"(c[0]), "=f"(c[1]), "=f"(c[2]), "=f"(c[3]) : "r"(a0), "r"(a1), "r"(a2), "r"(a3), "r"(b0), "r"(b1), "f"(c[0]), "f"(c[1]), "f"(c[2]), "f"(c[3]));
}
__device__ __forceinline__ void sts128(uint32_t a, uint32_t r0, uint32_t r1, uint32_t r2, uint32_t r3) {
  asm volatile("st.shared.v4.b32 [%0], {%1, %2, %3, %4};" ::"r"(a), "r"(r0), "r"(r1), "r"(r2), "r"(r3) : "memory");
}
__device__ __forceinline__ void lds128(uint32_t a, uint32_t& r0, uint32_t& r1, uint32_t& r2, uint32_t& r3) {
  asm volatile("ld.shared.v4.b32 {%0, %1, %2, %3}, [%4];" : "=r"(r0), "=r"(r1), "=r"(r2), "=r"(r3) : "r"(a) : "memory");
}
__device__ __forceinline__ float2 lds64f(uint32_t a) { float2 v; asm volatile("ld.shared.v2.f32 {%0, %1}, [%2];" : "=f"(v.x), "=f"(v.y) : "r"(a) : "memory"); return v; }
__device__ __forceinline__ float4 lds128f(uint32_t a) { float4 v; asm volatile("ld.shared.v4.f32 {%0, %1, %2, %3}, [%4];" : "=f"(v.x), "=f"(v.y), "=f"(v.z), "=f"(v.w) : "r"(a) : "memory"); return v; }
__device__ __forceinline__ void sts64f(uint32_t a, float x, float y) { asm volatile("st.shared.v2.f32 [%0], {%1, %2};" ::"r"(a), "f"(x), "f"(y) : "memory"); }
__device__ __forceinline__ float lds32f(uint32_t a) { float v; asm volatile("ld.shared.f32 %0, [%1];" : "=f"(v) : "r"(a) : "memory"); return v; }
__device__ __forceinline__ void sts32f(uint32_t a, float x) { asm volatile("st.shared.f32 [%0], %1;" ::"r"(a), "f"(x) : "memory"); }
__device__ __forceinline__ void stat_st(uint2* p, float sum, float sq, uint32_t tag, bool on) {
  const float mean = sum * (1.f / 128), m2 = fmaxf(fmaf(-mean, sum, sq), 0.f);
  const uint32_t a = ((__float_as_uint(mean) + 8u) & ~15u) | (tag & 15u), b = ((__float_as_uint(m2) + 8u) & ~15u) | (tag & 15u);
  asm volatile("{\n.reg .b64 x;\n.reg .pred p;\nsetp.ne.u32 p, %3, 0;\nmov.b64 x, {%1, %2};\n@p st.relaxed.gpu.global.b64 [%0], x;\n}\n" ::"l"(p), "r"(a), "r"(b), "r"((uint32_t)on) : "memory");
}
__device__ __forceinline__ void stat_ld2(const uint2* p, uint32_t (&v)[4]) {
  asm volatile("{\n.reg .b64 x, y;\nld.relaxed.gpu.global.v2.b64 {x, y}, [%4];\nmov.b64 {%0, %1}, x;\nmov.b64 {%2, %3}, y;\n}\n"
    : "=r"(v[0]), "=r"(v[1]), "=r"(v[2]), "=r"(v[3]) : "l"(p) : "memory");
}
__device__ __forceinline__ float untag(uint32_t v) { return __uint_as_float(v & ~15u); }
__device__ __forceinline__ void ll_st3(uint4* p, uint32_t a, uint32_t b, uint32_t c, uint32_t tag) {
  asm volatile("{\n.reg .b64 x, y;\n.reg .b128 z;\nmov.b64 x, {%1, %2};\nmov.b64 y, {%3, %4};\nmov.b128 z, {x, y};\nst.relaxed.gpu.global.b128 [%0], z;\n}\n"
    ::"l"(p), "r"(a), "r"(b), "r"(c), "r"(tag) : "memory");
}
__device__ __forceinline__ uint32_t ll_ld3(const uint4* p, uint32_t& a, uint32_t& b, uint32_t& c, uint32_t tag) {
  uint32_t t;
  asm volatile("{\n.reg .b64 x, y;\n.reg .b128 z;\nld.relaxed.gpu.global.b128 z, [%4];\nmov.b128 {x, y}, z;\nmov.b64 {%0, %1}, x;\nmov.b64 {%2, %3}, y;\n}\n"
    : "=r"(a), "=r"(b), "=r"(c), "=r"(t) : "l"(p) : "memory");
  return t ^ tag;
}
__device__ __forceinline__ void halo_send(uint4* p, uint32_t a, const uint32_t (&tg)[6]) {
  asm volatile("{\n.reg .b64 x<6>, y<6>, w<2>;\n.reg .b32 c<4>;\n.reg .b128 z<6>;\n"
    "ld.shared.b64 w0, [%1+1536];\nld.shared.b64 w1, [%1+1792];\n"
    "ld.shared.b64 x0, [%1];\nld.shared.b64 x1, [%1+256];\nld.shared.b64 x2, [%1+512];\n"
    "ld.shared.b64 x3, [%1+768];\nld.shared.b64 x4, [%1+1024];\nld.shared.b64 x5, [%1+1280];\n"
    "mov.b64 {c0, c1}, w0;\nmov.b64 {c2, c3}, w1;\n"
    "mov.b64 y0, {c0, %2};\nmov.b64 y1, {c1, %3};\nmov.b64 y2, {c2, %4};\nmov.b64 y3, {c3, %5};\nmov.b64 y4, {%6, %6};\nmov.b64 y5, {%7, %7};\n"
    "mov.b128 z0, {x0, y0};\nmov.b128 z1, {x1, y1};\nmov.b128 z2, {x2, y2};\nmov.b128 z3, {x3, y3};\nmov.b128 z4, {x4, y4};\nmov.b128 z5, {x5, y5};\n"
    "st.relaxed.gpu.global.b128 [%0], z0;\nst.relaxed.gpu.global.b128 [%0+512], z1;\nst.relaxed.gpu.global.b128 [%0+1024], z2;\n"
    "st.relaxed.gpu.global.b128 [%0+1536], z3;\nst.relaxed.gpu.global.b128 [%0+2048], z4;\nst.relaxed.gpu.global.b128 [%0+2560], z5;\n}\n"
    ::"l"(p), "r"(a), "r"(tg[0]), "r"(tg[1]), "r"(tg[2]), "r"(tg[3]), "r"(tg[4]), "r"(tg[5]) : "memory");
}
template <int N> __device__ __forceinline__ void copy_out(uint8_t* dst, uint32_t src, int stride) {
  uint4 v[N];
#pragma unroll
  for (int k = 0; k < N; k++) lds128(src + k * stride, v[k].x, v[k].y, v[k].z, v[k].w);
#pragma unroll
  for (int k = 0; k < N; k++) asm volatile("st.global.v4.b32 [%0], {%1, %2, %3, %4};" ::"l"(dst + k * stride), "r"(v[k].x), "r"(v[k].y), "r"(v[k].z), "r"(v[k].w) : "memory");
}
__device__ __forceinline__ void warp_store(uint8_t* dst, uint32_t src, int bytes, uint32_t delay, uint32_t pace) {
  __nanosleep(delay);
#pragma unroll 1
  for (int o = 0; o < bytes; o += 2048) {
    if (pace) __nanosleep(pace);
    uint4 v[4];
#pragma unroll
    for (int k = 0; k < 4; k++) lds128(src + o + k * 512, v[k].x, v[k].y, v[k].z, v[k].w);
#pragma unroll
    for (int k = 0; k < 4; k++) asm volatile("st.global.v4.b32 [%0], {%1, %2, %3, %4};" ::"l"(dst + o + k * 512), "r"(v[k].x), "r"(v[k].y), "r"(v[k].z), "r"(v[k].w) : "memory");
  }
  __syncwarp();
}
__device__ __forceinline__ uint32_t clock32() { uint32_t t; asm volatile("mov.u32 %0, %%clock;" : "=r"(t)); return t; }
__device__ __forceinline__ void flag_set(uint32_t* p, uint32_t bit) { asm volatile("red.release.gpu.global.xor.b32 [%0], %1;" ::"l"(p), "r"(bit) : "memory"); }
__device__ __forceinline__ void flag_wait(const uint32_t* p, uint32_t inv, uint32_t need, uint32_t& ready) {
  if ((ready & need) == need) return;
  uint32_t n = 0;
  do {
    asm volatile("ld.relaxed.gpu.global.b32 %0, [%1];" : "=r"(ready) : "l"(p) : "memory");
    ready = __shfl_sync(0xffffffffu, ready, 0) ^ inv;
  } while ((ready & need) != need && ++n < SPIN_MAX);
  asm volatile("fence.acquire.gpu;\nfence.proxy.async.global;" ::: "memory");
}
__device__ __forceinline__ bool elect_one() {
  uint32_t p;
  asm volatile("{\n.reg .pred P;\nelect.sync _|P, 0xffffffff;\nselp.u32 %0, 1, 0, P;\n}\n" : "=r"(p));
  return p;
}
__device__ __forceinline__ float gelu_half(float hx) {
  const float y = hx * fmaf(hx * hx, 8.f * 0.0356774081f, 2.f * 0.7978845608f);
  float th;
  asm("tanh.approx.f32 %0, %1;" : "=f"(th) : "f"(y));
  return fmaf(hx, th, hx);
}
__device__ __forceinline__ float ex2(float x) { float y; asm("ex2.approx.ftz.f32 %0, %1;" : "=f"(y) : "f"(x)); return y; }

__device__ __forceinline__ void stat_combine(uint32_t am, uint32_t aq, uint32_t bm, uint32_t bq, float pv, float& mean, float& var) {
  const float d0 = untag(am) - pv, d1 = untag(bm) - pv;
  float s = d0 + d1, q = fmaf(fmaf(d0, d0, d1 * d1), 128.f, untag(aq) + untag(bq));
  s += __shfl_xor_sync(0xffffffffu, s, 8); q += __shfl_xor_sync(0xffffffffu, q, 8);
  s += __shfl_xor_sync(0xffffffffu, s, 16); q += __shfl_xor_sync(0xffffffffu, q, 16);
  s *= 0.125f;
  mean = pv + s;
  var = fmaxf(fmaf(-s, s, q * (1.f / D_)), 0.f);
}

__device__ __forceinline__ void attn_logits(const uint32_t* q0, const uint32_t* q1,
                                            const uint32_t* k0, const uint32_t* k1, const uint32_t* k2, const uint32_t* k3,
                                            float mk0, float mk1, float (&s)[4][4]) {
#pragma unroll
  for (int n = 0; n < 4; n++) {
    const uint32_t* k = n == 0 ? k0 : n == 1 ? k1 : n == 2 ? k2 : k3;
    s[n][0] = s[n][1] = n < 2 ? mk0 : 0.f; s[n][2] = s[n][3] = n < 2 ? mk1 : 0.f;
    mma16816(s[n], q0[0], q1[0], q0[1], q1[1], k[0], k[1]);
    mma16816(s[n], q0[2], q1[2], q0[3], q1[3], k[2], k[3]);
  }
}
__device__ __forceinline__ void attn_probs(const float (&s)[4][4], float sc0, float sc1, bool e, bool zneg, const uint32_t (&sel)[3],
                                           uint32_t (&pr)[6], float (&l)[2]) {
  float a0 = e ? s[1][1] : s[1][0];
  float b0 = zneg ? (e ? s[0][1] : s[0][0]) : (e ? s[2][1] : s[2][0]);
  float a1 = e ? s[2][3] : s[2][2];
  float b1 = zneg ? (e ? s[1][3] : s[1][2]) : (e ? s[3][3] : s[3][2]);
  float m0 = fmaxf(a0, b0), m1 = fmaxf(a1, b1);
  m0 = fmaxf(m0, __shfl_xor_sync(0xffffffffu, m0, 1)); m1 = fmaxf(m1, __shfl_xor_sync(0xffffffffu, m1, 1));
  m0 = fmaxf(m0, __shfl_xor_sync(0xffffffffu, m0, 2)); m1 = fmaxf(m1, __shfl_xor_sync(0xffffffffu, m1, 2));
  a0 = ex2((a0 - m0) * sc0); b0 = ex2((b0 - m0) * sc0); a1 = ex2((a1 - m1) * sc1); b1 = ex2((b1 - m1) * sc1);
  l[0] = a0 + b0; l[1] = a1 + b1;
  const uint32_t p0 = pack2(a0, b0), p1 = pack2(a1, b1);
#pragma unroll
  for (int k = 0; k < 3; k++) { pr[k] = __byte_perm(p0, 0u, sel[k]); pr[3 + k] = __byte_perm(p1, 0u, sel[k]); }
}
__device__ __forceinline__ void attn_pv(const uint32_t (&pr)[6], const uint32_t* vh, const uint32_t* v, float (&o)[4][4]) {
#pragma unroll
  for (int dt = 0; dt < 4; dt++) {
    o[dt][0] = o[dt][1] = o[dt][2] = o[dt][3] = 0.f;
    mma16816(o[dt], pr[0], 0u, pr[1], pr[3], vh[2 * dt], vh[2 * dt + 1]);
    mma16816(o[dt], pr[2], pr[4], 0u, pr[5], v[2 * dt], v[2 * dt + 1]);
  }
}

#define ATT 25
#define COVER 2
#define HALO_A_NS 300
#define H1D 900
#define FO 2
#define G4GATE 1
#define PFM 7
#define PD1 3
#define PD2 5
#define PD3 3
#define PD4 5
#define FR 1
#define XG 1
#define KF 1
#define VL 1
#define S2S 1
#define EI 1
#define U0D 300
#define X1D 1200
#define PACE 150
#define LEAD1 3
#define LEAD2 3
#define XLD 7
#define XST 2
#define FA 20
#define LEAD4 4
#define STAT_CLK 150
__global__ void __cluster_dims__(2, 1, 1) __launch_bounds__(384, 1) fused_kernel(const __grid_constant__ Params P) {
  extern __shared__ __align__(1024) uint8_t smem_raw[];
  const uint32_t sb = smem_u32(smem_raw);
  const uint32_t bars = sb + OFF_BAR;
  const int tid = threadIdx.x;
  if (tid == 256) S5(0);
  const int wu = __shfl_sync(0xffffffffu, tid >> 5, 0), wg = wu >> 2;
  const int r = blockIdx.x & 1, cl = blockIdx.x >> 1;
  int grp, slt;
  if (cl < 4) { grp = 0; slt = 4 + cl; }
  else if (cl < 36) { grp = (cl - 4) & 7; slt = (cl - 4) >> 3; }
  else { grp = 1 + (cl - 36) % 7; slt = 4 + (cl - 36) / 7; }
#define MAP 0
  const int m = grp, j = slt;
  const int i = 2 * m + r;
  auto BAR = [&](int k) { return bars + 8 * k; };

  auto kb1 = [&](int n) { const int h = n >= 9, t = n - 2 - 7 * h; return n < 2 ? 2 * j + n : 2 * (t == j ? 7 : t) + h; };
  auto first_round = [&](int u0, int u1) {
#pragma unroll 1
    for (int u = u0; u < u1; u++) {
      S5(3 + u);
      mbar_expect(BAR(F1 + u), 40960);
      tma2d(sb + slot1(u), &P.x0, BAR(F1 + u), u * 64, 128 * i);
      tma3d(sb + slot1(u) + 16384, &P.wqkv, BAR(F1 + u), 128 * j, u * 64, 0);
      tma3d(sb + slot1(u) + 28672, &P.wqkv, BAR(F1 + u), 128 * j, u * 64 + 32, 0);
    }
  };
  if (wu == 9) {
    if (elect_one()) asm volatile("prefetch.tensormap [%0];" ::"l"(&P.wqkv) : "memory");
    __syncwarp();
  } else if (wu == 8) {
    if (elect_one()) {
      S5(1);
#pragma unroll
      for (int k = 0; k < 4; k++) mbar_init(BAR(F1 + k), 1);
      asm volatile("fence.mbarrier_init.release.cluster;" ::: "memory");
      fence_async_smem();
      first_round(0, FR);
    }
    __syncwarp();
  } else if (wu == 0) {
    if (elect_one()) {
#pragma unroll
      for (int k = E1; k < 64; k++) {
        int cnt = 1;
        if (k < F2 || (k >= E2 && k < F3) || (k >= E3 && k < F4) || (k >= E4 && k < JOB) || k == JOB + 2 || k == JOB + 3) cnt = 4;
        else if ((k >= JOB && k < RD) || k == CSJ) cnt = 8;
        else if (k == RD + 1 || k == STD || k == STAT) cnt = 2;
        mbar_init(BAR(k), cnt);
      }
      asm volatile("fence.mbarrier_init.release.cluster;" ::: "memory");
      fence_async_smem();
    }
    __syncwarp();
  }
  auto load_tag = [&]() { uint32_t t; asm volatile("ld.relaxed.gpu.global.u32 %0, [%1];" : "=r"(t) : "l"(&gEpoch) : "memory"); return t + 1; };
  TS(0);
  if (wu == 8) nb_arrive<NB_INIT>(384); else nb_sync<NB_INIT>(384);
  asm volatile("barrier.cluster.arrive.relaxed;" ::: "memory");

  if (wg == 2) {
    if (tid == 256) S5(2);
    reg_dealloc<40>();
    if (wu == 8) {
      if (elect_one()) first_round(FR, 4);
      __syncwarp();
    }
    asm volatile("barrier.cluster.wait;" ::: "memory");
    auto kb3 = [&](int n) { const int h = n >= 17, t = S2S ? n - 3 - 14 * h : n - 2 - 15 * h; return n < 2 ? 2 * i + n : (n == (S2S ? 2 : 16) || n == 31) ? 2 * (i ^ 1) + h : 2 * ((2 * m + 2 + t) & 15) + h; };
    auto v1 = [&](int L, int u) { const int u0 = L ? 2 : 10; return (u >= u0 && u < 18) ? (u < u0 + 2 ? u - u0 + 16 : u - 2) : u; };
    auto kb2 = [&](int n) { return n < 8 ? 2 * n : n == 8 ? 2 * j + 1 : 2 * (n - 9 == j ? 7 : n - 9) + 1; };
    if (wu == 8) {
      const int lane = tid & 31;
      auto pf = [&](const bf16* p, bool on) { if (on) asm volatile("prefetch.global.L2 [%0];" ::"l"(p)); };

      auto k1 = [&](int L, int v) { return (L || v >= 16) ? kb1(v & 15) : v; };
      auto kb4f = [&](int n) {
        const bool own = n == 0 || n == 9 || n == 17;
        const int q = n - 10 - (n > 17), c = own ? n >> 3 : q / 15, t = q - 15 * c;
        const int ii = own ? i : t < 14 ? (2 * m + 2 + t) & 15 : i ^ 1;
        return (n >= 1 && n <= 8) ? 7 * ((m + n) & 7) + 3 : ((7 * ii + 1) >> 1) + c;
      };
      const uint32_t tab4 = kb4f(lane) | (kb4f(lane + 32) << 16);
      auto kb4 = [&](int n) { return (int)((__shfl_sync(0xffffffffu, tab4, n) >> ((n >> 1) & 16)) & 63); };
      const bf16* const q1 = P.wqkv_p + (4 * i + (lane & 3)) * 3072 + (lane >> 2) * 1024 + 128 * j;
      const bf16* const q2 = P.wo_p + (4 * i + (lane & 3)) * 1024 + (lane >> 2) * 64 + 128 * j;
      const bf16* const q3 = P.w1_p + (8 * j + (lane >> 2)) * 3584 + 64 * (7 * m + ((lane & 3) == 3 ? 3 : 4 * r + (lane & 3)));
      const bf16* const q4 = P.w2_p + (8 * j + (lane >> 1)) * 2048 + 128 * i + 64 * (lane & 1);
      auto pf1 = [&](int L, int u) { const int v = v1(L, u); pf(q1 + k1(L, v) * (64 * 3072) + 64 * (v >> 4), (PFM & 1) && lane < 12); };
      auto pf2 = [&](int n) { pf(q2 + kb2(n) * (64 * 1024), (PFM & 2) && lane < 8); };
      auto pf3 = [&](int n) { pf(q3 + kb3(n) * (64 * 3584), PFM & 4); };
      auto pf4 = [&](int n) { pf(q4 + kb4(n) * (64 * 2048), (PFM & 8) && lane < 16); };
#pragma unroll 1
      for (int u = 4; u < 4 + PD1; u++) pf1(0, u);
#pragma unroll 1
      for (int L = 0; L < 2; L++) {
#pragma unroll 1
        for (int u = L ? 0 : 4; u < 32; u++) {
          const int v = v1(L, u), p = u & 3;
          int c0 = 128 * j + 64 * (v >> 4), c1 = k1(L, v) * 64 + 32 * r; uint32_t dst = sb + slot1(p) + 16384 + r * 12288;
          asm volatile("" : "+r"(c0), "+r"(c1), "+r"(dst));
          if (XG && L && u == 4) mbar_wait(BAR(RD + 5), 0);
          if (u >= 4) mbar_wait(BAR(E1 + p), ((u >> 2) - 1) & 1);
          else mbar_wait(BAR(E4 + (u == 3 ? 0 : u + 3)), u == 3);
          if (elect_one()) {
            mbar_expect(BAR(F1 + p), (v & 15) < 2 ? 24576 : 40960);
            tma3d_mc(dst, &P.wqkv, BAR(F1 + p), c0, c1, 0);
          }
          if (u + PD1 < 32) pf1(L, u + PD1);
          if (u + PD2 >= 32) pf2(u + PD2 - 32);
        }
        int p = 0; uint32_t par = L ? 0x1e : 0;
#pragma unroll 1
        for (int n = 0; n < 16; n++) {
          int c1 = kb2(n) * 64;
          asm volatile("" : "+r"(c1));
          if (n >= 5) { mbar_wait(BAR(E2 + p), (par >> p) & 1); par ^= 1u << p; }
          else if (n < 4) mbar_wait(BAR(E1 + n), 1);
          if (elect_one()) {
            mbar_expect(BAR(F2 + p), n == 8 ? 16384 : 32768);
            tma2d_mc(sb + slot2(p) + 16384 + r * 8192, &P.wo, BAR(F2 + p), 128 * j + 64 * r, c1);
          }
          if (++p == 5) p = 0;
          if (n + PD2 < 16) pf2(n + PD2);
          if (n + PD3 + 4 >= 16) pf3(n + PD3 + 4 - 16);
        }
#pragma unroll 1
        for (int u = 0; u < 32; u++) {
          const int n = u < 4 ? (0x2031 >> (4 * u)) & 3 : u, p = n & 3;
          int kb = kb3(n);
          asm volatile("" : "+r"(kb));
          if (n == 4) {
            if (S2S == 2) mbar_wait(BAR(RD + 4), L);
            if (S2S) {
              mbar_wait(BAR(XF + 1), L ^ 1);
              const uint32_t rs = mapa(sb, r ^ 1);
              if (elect_one()) bulk_s2s(rs + slot3(2), sb + OFF_X, 16384, rs + OFF_BAR + 8 * (F3 + 2));
            }
            mbar_wait(BAR(RD + 4), L);
          }
          if (n >= 4) mbar_wait(BAR(E3 + p), ((n >> 2) - 1) & 1);
          else if (n == 1) mbar_wait(BAR(STD + 1), L);
          else if (n == 3) mbar_wait(BAR(E2 + 2), L);
          else if (n == 0) mbar_wait(BAR(E2 + 4), L);
          else mbar_wait(BAR(E2 + 0), 1);
          if (elect_one()) {
            mbar_expect(BAR(F3 + p), n < 2 ? 32768 : 49152);
            tma3d(sb + slot3(p) + 16384, &P.w1, BAR(F3 + p), 0, kb * 64, 7 * m + 4 * r);
            tma3d(sb + slot3(p) + 40960, &P.w1h, BAR(F3 + p), 0, kb * 64, 14 * m + 6 + r);
          }
          if (u >= 4 && u + PD3 < 32) pf3(u + PD3);
          if (u + PD4 + 6 >= 32) pf4(u + PD4 + 6 - 32);
        }
        auto g4w = [&](int n, int p, int kb) {
          if (elect_one()) {
            mbar_expect(BAR(F4 + p), (n == 0 || n == 9 || n == 17) ? 16384 : 32768);
            tma3d(sb + slot4(p), &P.w2, BAR(F4 + p), 0, kb * 64, 2 * i);
          }
        };
#pragma unroll 1
        for (int n = 0; n < 6; n++) {
          const int kb = kb4(n);
          if (n == G4GATE) mbar_wait(BAR(RD + 3), L);
          if (n < 3) mbar_wait(BAR(E3 + n), 1);
          else if (n == 4) mbar_wait(BAR(E3 + 3), 1);
          g4w(n, n, kb);
        }
        p = 0; par = L ? 0x3c : 0;
#pragma unroll 1
        for (int n = 6; n < 56; n++) {
          const int kb = kb4(n);
          if (n + PD4 < 56) pf4(n + PD4);
          mbar_wait(BAR(E4 + p), (par >> p) & 1); par ^= 1u << p;
          g4w(n, p, kb);
          if (++p == 6) p = 0;
        }
        if (L == 0)
#pragma unroll 1
          for (int u = 0; u < PD1; u++) pf1(1, u);
      }
    } else if (wu == 9) {
      uint32_t inv = 0;
#define ADDR(d, s) uint32_t dst = (d); const uint8_t* src = (s); asm volatile("" : "+r"(dst), "+l"(src))
#pragma unroll 1
      for (int L = 0; L < 2; L++) {
        uint32_t ready = 0;
#pragma unroll 1
        for (int u = 4; u < 32; u++) {
          const int p = u & 3, v = v1(L, u), nn = v & 15, kb = (L || v >= 16) ? kb1(nn) : nn;
          if (L == 0 && (u == XLD || u == XLD + XST) && elect_one()) {
            const int h = u != XLD;
            mbar_expect(BAR(XF + h), 16384);
            tma2d(sb + OFF_X + h * 16384, &P.x0, BAR(XF + h), 128 * j + 64 * h, 128 * i);
          }
          if (nn < 2) continue;
          ADDR(sb + slot1(p), gXB + (i * 16 + kb) * 16384);
          if (L && u < 12) mbar_wait(BAR(F1 + p), u >> 3);
          if (u >= 4 + 4 * L) mbar_wait(BAR(E1 + p), ((u >> 2) - 1) & 1);
          if (L) {
            flag_wait(gFlag[0][0][i], inv, 1u << kb, ready);
            if (elect_one()) bulk_ld(dst, src, 16384, BAR(F1 + p));
          } else if (elect_one()) tma2d(sb + slot1(p), &P.x0, BAR(F1 + p), kb * 64, 128 * i);
        }
        ready = 0;
        if (L == 0) inv = (__shfl_sync(0xffffffffu, load_tag(), 0) & 1) - 1;
        int p = 0; uint32_t par = L ? 0x1e : 0;
#pragma unroll 1
        for (int n = 0; n < 16; n++) {
          const int hp = kb2(n);
          if (n == 8) { par ^= 8; p = 4; continue; }
          ADDR(sb + slot2(p), gOB + (i * 16 + hp) * 16384);
          if (n >= 5) { mbar_wait(BAR(E2 + p), (par >> p) & 1); par ^= 1u << p; }
          else if (n < 4) mbar_wait(BAR(E1 + n), 1);
          flag_wait(gFlag[L][1][i], inv, 1u << hp, ready);
          if (n == 9) ST(4);
          if (elect_one()) bulk_ld(dst, src, 16384, BAR(F2 + p));
          if (++p == 5) p = 0;
        }
        ready = 0;
        mbar_wait(BAR(E2 + 0), 1);
#pragma unroll 1
        for (int n = S2S ? 3 : 2; n < 32; n++) {
          const int p = n & 3, kb = kb3(n);
          const int o = ((S2S || n != 16) && n != 31) ? r * 8192 : 0;
          ADDR(sb + slot3(p) + o, gHB + (j * 32 + kb) * 16384 + o);
          if (n > 3) mbar_wait(BAR(E3 + p), ((n >> 2) - 1) & 1);
          flag_wait(gFlag[L][2][j], inv, 1u << kb, ready);
          if (n == 2) ST(12);
          if (elect_one()) {
            if ((S2S || n != 16) && n != 31) bulk_ld_mc(dst, src, 8192, BAR(F3 + p));
            else bulk_ld(dst, src, 16384, BAR(F3 + p));
          }
        }
        ready = 0; p = 1; par = L ? 0x3c : 0;
#pragma unroll 1
        for (int t = 0; t < 8; t++) {
          const int mm = (m + t + 1) & 7;
          ADDR(sb + slot4(p) + 16384 + r * 8192, gUB + (j * 56 + 48 + mm) * 16384 + r * 8192);
          if (t < 3) mbar_wait(BAR(E3 + 1 + t), 1);
          if (t >= 5) { mbar_wait(BAR(E4 + p), (par >> p) & 1); par ^= 1u << p; }
          flag_wait(gFlag[L][6][j], inv, 3u << (2 * mm), ready);
          if (t == 0) ST(20);
          if (elect_one()) bulk_ld_mc(dst, src, 8192, BAR(F4 + p));
          if (++p == 6) p = 0;
        }
#pragma unroll 1
        for (int c = 0; c < 3; c++) {
          ready = 0;
#pragma unroll 1
          for (int t = 0; t < 15; t++) {
            const int ii = t < 14 ? (2 * m + 2 + t) & 15 : i ^ 1;
            if (c == 0 && (t == 0 || t == 7)) { par ^= 1u << p; if (++p == 6) p = 0; }
            const int o = t < 14 ? r * 8192 : 0;
            ADDR(sb + slot4(p) + 16384 + o, gUB + (j * 56 + 16 * c + ii) * 16384 + o);
            mbar_wait(BAR(E4 + p), (par >> p) & 1); par ^= 1u << p;
            flag_wait(gFlag[L][3 + c][j], inv, 1u << ii, ready);
            if (elect_one()) {
              if (t < 14) bulk_ld_mc(dst, src, 8192, BAR(F4 + p));
              else bulk_ld(dst, src, 16384, BAR(F4 + p));
            }
            if (++p == 6) p = 0;
          }
        }
      }
    } else {
      const int h = wu - 10, i0 = i, j0 = j;
      {
      const uint32_t tag = load_tag();
      int lane = tid & 31, i = i0, j = j0;
#define FRESH asm volatile("" : "+r"(lane), "+r"(i), "+r"(j))
      auto signal = [&](int k) { if (lane == 0) mbar_arrive(BAR(k)); };
      auto publish = [&](uint32_t* f, int bit) { if (lane == 0) flag_set(f, 1u << bit); __syncwarp(); };
#pragma unroll 1
      for (int c = 32 * h + lane; c < 288; c += 64)
        sts16(sb + OFF_B1 + 2 * c, c >= 224 ? 0u : pack2(0.5f * __bfloat162float(P.b1[c < 192 ? 64 * (7 * m + 4 * r) + c : 64 * (7 * m + 3) + 32 * r + c - 192]), 0.f));
      if (h == 0) sts32f(sb + OFF_CS + 768 + 4 * lane, 0.f);
#pragma unroll 1
      for (int L = 0; L < 2; L++) {
        FRESH;
        if (L == 0) {
          mbar_wait(BAR(CSJ), 0);
          float c0 = 0.f, c1 = 0.f, c2 = 0.f;
          const uint32_t a = sb + OFF_STG + (32 * h + lane) * 4;
#pragma unroll 4
          for (int k = 0; k < 32; k++) { c0 += lds32f(a + k * 784); c1 += lds32f(a + k * 784 + 256); c2 += lds32f(a + k * 784 + 512); }
          ll_st3(&gCS[j][i][32 * h + lane], __float_as_uint(c0), __float_as_uint(c1), __float_as_uint(c2), tag);
          __nanosleep(500);
        }
        FRESH;
        if (L == 0) {
#pragma unroll 1
          for (int ab = 0; ab < 2; ab++) {
            float c0 = 0.f, c1 = 0.f, c2 = 0.f;
#pragma unroll 1
            for (int b4 = 0; b4 < 8; b4 += 4) {
              uint32_t a[4], b[4], c[4], n = 0, bad;
              do {
                bad = 0;
#pragma unroll
                for (int e = 0; e < 4; e++) bad |= ll_ld3(&gCS[j][2 * (b4 + e) + ab][32 * h + lane], a[e], b[e], c[e], tag);
              } while (bad && ++n < SPIN_MAX);
#pragma unroll
              for (int e = 0; e < 4; e++) { c0 += __uint_as_float(a[e]); c1 += __uint_as_float(b[e]); c2 += __uint_as_float(c[e]); }
            }
            const uint32_t a = sb + OFF_CS + ab * 768 + (4 * h + (lane >> 3)) * 32 + (lane & 7) * 2;
            const uint32_t h0 = pack2(c0, 0.f), h1 = pack2(c1, 0.f), h2 = pack2(c2, 0.f);
            sts16(a, h0); sts16(a + 256, h1); sts16(a + 512, h2);
            sts16(a + 16, pack2(c0 - bf_lo(h0), 0.f)); sts16(a + 272, pack2(c1 - bf_lo(h1), 0.f)); sts16(a + 528, pack2(c2 - bf_lo(h2), 0.f));
            fence_async_smem();
            __syncwarp();
            if (ab == 0) signal(STAT);
          }
        }
#pragma unroll 1
        for (int ab = 0; ab < 2; ab++) {
          FRESH;
          uint32_t v[18], tg[6];
          const uint32_t xs = sb + OFF_STG + h * 16384 + lane * 8;
          uint4* hp = &gHalo[L][i][j][6 * h][lane];
#pragma unroll
          for (int c = 0; c < 6; c++) { tg[c] = (2 * tag + ab) * 8 + c; asm volatile("" : "+r"(tg[c])); }
          asm volatile("" : "+l"(hp));
          mbar_wait(BAR(FOLD + h), ab);
          if (ab && h == 0) ST(6);
          if (i < 15) {
            halo_send(hp, xs, tg);
          }
          if (ab && h == 0) ST(26);
          if (i > 0) {
            if (!ab) __nanosleep(HALO_A_NS);
            uint32_t n = 0, bad;
            do {
              bad = 0;
#pragma unroll
              for (int c = 0; c < 6; c++) bad |= ll_ld3(hp + c * 32 - 8 * 12 * 32, v[3 * c], v[3 * c + 1], v[3 * c + 2], (2 * tag + ab) * 8);
              if (ab && h == 0 && n == 0) ST(28);
            } while (bad > 7 && ++n < SPIN_MAX);
            if (ab && h == 0) ST(27);
          } else {
#pragma unroll
            for (int c = 0; c < 18; c++) v[c] = 0u;
          }
#pragma unroll
          for (int c = 0; c < 6; c++) sts64f(xs + c * 256, __uint_as_float(v[3 * c]), __uint_as_float(v[3 * c + 1]));
          sts64f(xs + 1536, __uint_as_float(v[2]), __uint_as_float(v[5]));
          sts64f(xs + 1792, __uint_as_float(v[8]), __uint_as_float(v[11]));
          __syncwarp();
          signal(HALO + h);
          if (ab && h == 0) ST(7);
          FRESH;
          if (ab == 0 && lane == 0) asm volatile("st.relaxed.gpu.global.u32 [%0], %1;" ::"l"(&gAck[L][i][j][h][0]), "r"(tag) : "memory");
          uint8_t* dst = gOB + (i * 16 + 2 * j + ab) * 16384;
          uint32_t* flag = gFlag[L][1][i];
          asm volatile("" : "+l"(dst), "+l"(flag));
          mbar_wait(BAR(JOB + ab), L);
          if (h == 0) {
            if (ab) ST(1);
            if (lane == 0) { bulk_st(dst, sb + OFF_STG, 16384); bulk_commit(); bulk_wait0(); }
            signal(STD + ab);
            if (ab) ST(2);
            publish(flag, 2 * j + ab);
            if (ab) ST(3);
          } else if (ab == 0) {
            if (i < 15 && lane < 2) {
              uint32_t t, n = 0;
              do { asm volatile("ld.relaxed.gpu.global.u32 %0, [%1];" : "=r"(t) : "l"(&gAck[L][i + 1][j][lane][0]) : "memory"); } while (t != tag && ++n < SPIN_MAX);
            }
            __syncwarp();
            signal(STD);
          }
        }
#pragma unroll 1
        for (int k = 0; k < 4 - L; k++) {
          FRESH;
          const int job = 2 * k + h;
          uint8_t* dst = k == 0 ? gHB + (j * 32 + 2 * i + 1) * 16384 : k == 3 ? gXB + (i * 16 + 2 * j + 1) * 16384 : gUB + (j * 56 + 16 * (job - 3) + i) * 16384;
          uint32_t* flag = k == 3 ? gFlag[0][0][i] : gFlag[L][(0x543622 >> (4 * job)) & 15][j];
          uint32_t bit = 1u << (k == 0 ? 2 * i + h : k == 3 ? 2 * j + h : i);
          asm volatile("" : "+l"(dst), "+l"(flag), "+r"(bit));
          mbar_wait(BAR(JOB + ((0x98654732 >> (4 * job)) & 15)), L);
          if (job < 3 && h == 0) ST(job ? 17 : 9);
          if ((0xba >> job) & 1) {
            if (job == 1) mbar_wait(BAR(RD + 4), L);
            if (job == 3) {
              __nanosleep(U0D);
              if (lane == 0) { bulk_st(dst, sb + OFF_X, 16384); bulk_commit(); bulk_wait0(); }
            } else warp_store(dst + lane * 16, sb + lane * 16 + OFF_X + (job == 5 ? 0 : 16384), 16384, job == 1 ? H1D : job == 7 ? X1D : 0, job == 7 ? 0 : PACE);
            if (job != 7) signal(RD + ((0x112000 >> (4 * job)) & 15));
          }
          if (lane == 0) flag_set(flag, bit);
          __syncwarp();
          if (h == 0 && k != 2) { signal(RD + (k == 3 ? 5 : 4 - k)); if (k < 2) ST(job ? 19 : 11); }
        }
      }
      if (blockIdx.x == 0 && h == 0 && lane == 0) asm volatile("st.relaxed.gpu.global.u32 [%0], %1;" ::"l"(&gEpoch), "r"(tag) : "memory");
      }
    }
    __syncwarp();
    cluster_bar();
  } else {
    reg_alloc<232>();
    asm volatile("barrier.cluster.wait;" ::: "memory");
    const uint32_t rbars = mapa(bars, tid & 1);
    const bool relp = (tid & 127) < 2;
    const uint32_t sd = (sb & 0x3FFFF) >> 4, sda = sd + wg * 512;
    uint32_t tag;
    asm volatile("ld.relaxed.gpu.global.u32 %0, [%1];" : "=r"(tag) : "l"(&gEpoch + (fresh_tid() >> 10)) : "memory");
    auto release = [&](int k) { if (relp) mbar_arrive_cl(rbars + 8 * k); };
    auto signal = [&](int k) { __syncwarp(); if ((fresh_tid() & 31) == 0) mbar_arrive(BAR(k)); };
#define GEOM const int t7 = fresh_tid() & 127, lane = t7 & 31, w = t7 >> 5, g = lane >> 2, q = lane & 3, \
                       lr = lane & 15, lt = lane >> 4, l7 = lane & 7; (void)w; (void)g; (void)q; (void)lr; (void)lt; (void)l7

#pragma unroll 1
    for (int L = 0; L < 2; L++) {
      float acca[96], accb[96], xa[64], acc3[112];
      float nmean0, nmean1, rstd0, rstd1;
      uint16_t b2a, b2b;
      uint2 *e2p, *e2s; uint8_t* e2g; uint32_t e2h;
      uint32_t Q[2][8], K[2][8], V[16];
      auto g1_issue = [&](float (&acc)[96], uint32_t a, uint32_t st, auto first) {
        const uint32_t da = sda + (a >> 4), db = sd + (st >> 4);
        wg_fence();
        static_for<0, 4>([&](auto kk) {
          constexpr uint32_t ia = DI(kk.value * 32, 16), ib = DI(16384 + (kk.value >> 1) * 12288 + (kk.value & 1) * 2048, 4096);
          if constexpr (first.value && kk.value == 0) wgmma_192z<0, 1, ia, ib>(acc, da, db); else wgmma_192<0, 1, ia, ib>(acc, da, db);
        });
        wg_commit();
      };
      auto g1_step = [&](float (&acc)[96], int u, bool rel, bool lead = false) {
        const int p = u & 3;
        mbar_wait(BAR(F1 + p), (u >> 2) & 1);
        KB(u);
        g1_issue(acc, slot1(p), slot1(p), False{});
        if (lead) nb_arrive<NB_LEAD>(256);
        wg_wait<1>();
        if (rel) release(E1 + ((u - 1) & 3));
      };
      auto g1_loop = [&](float (&acc)[96], int u0, int u1, int urel) {
        int u = u0;
#pragma unroll 1
        do { g1_step(acc, u, u > urel); } while (++u < u1);
      };
      auto load_x = [&]() {
        GEOM;
#pragma unroll
        for (int t = 0; t < 16; t += 2) {
          uint32_t v0, v1, v2, v3;
          ldsm4(sb + OFF_X + (t >> 3) * 16384 + (16 * wu + lr) * 128 + ((((t & 7) + lt) ^ l7) << 4), v0, v1, v2, v3);
          xa[4 * t + 0] = bf_lo(v0); xa[4 * t + 1] = bf_hi(v0); xa[4 * t + 2] = bf_lo(v1); xa[4 * t + 3] = bf_hi(v1);
          xa[4 * t + 4] = bf_lo(v2); xa[4 * t + 5] = bf_hi(v2); xa[4 * t + 6] = bf_lo(v3); xa[4 * t + 7] = bf_hi(v3);
        }
      };
      auto stat_base = [&]() { return &gST[0][0][0][0][0] + ((L * 16 + opq(i)) * 8 + wu) * 128; };
      auto stat_slot = [&]() { const int lane = fresh_tid() & 31; return stat_base() + 16 * j + 2 * (lane >> 2) + (lane & 1); };
      auto stat_publish = [&](uint2* sp, float s0, float q0, float s2, float q2, uint32_t tg) {
        const int q = fresh_tid() & 3;
        const bool h1 = q & 1;
        float sm = (h1 ? s2 : s0) + __shfl_xor_sync(0xffffffffu, h1 ? s0 : s2, 1);
        float sq = (h1 ? q2 : q0) + __shfl_xor_sync(0xffffffffu, h1 ? q0 : q2, 1);
        sm += __shfl_xor_sync(0xffffffffu, sm, 2); sq += __shfl_xor_sync(0xffffffffu, sq, 2);
        stat_st(sp, sm, sq, tg, q < 2);
        return sm;
      };
      auto g1_stats = [&](int u0) {
        GEOM;
        const uint32_t xr = sb + OFF_X + (16 * wu + lr) * 128;
        float s0 = 0.f, q0 = 0.f, s2 = 0.f, q2 = 0.f;
        uint32_t v[8] = {0u, 0u, 0u, 0u, 0u, 0u, 0u, 0u};
#pragma unroll 1
        for (int k = 0; k < 5; k++) {
#pragma unroll
          for (int e = 0; e < 8; e += 2) {
            const float a = bf_lo(v[e]), b = bf_hi(v[e]), c = bf_lo(v[e + 1]), d = bf_hi(v[e + 1]);
            s0 += a + b; q0 = fmaf(a, a, fmaf(b, b, q0)); s2 += c + d; q2 = fmaf(c, c, fmaf(d, d, q2));
          }
          if (k == 4) break;
          const uint32_t o = ((2 * k + lt) ^ l7) << 4;
          ldsm4(xr + o, v[0], v[1], v[2], v[3]);
          ldsm4(xr + o + 16384, v[4], v[5], v[6], v[7]);
          g1_step(acca, u0 + k, true);
        }
        stat_publish(stat_slot(), s0, q0, s2, q2, 2 * (tag + 1));
      };
      uint32_t sv0[4], sv1[4];
      auto stat_src = [&]() { return stat_base() + 2 * (fresh_tid() & 31); };
      auto stat_fetch = [&](const uint2* sp) { stat_ld2(sp, sv0); stat_ld2(sp + 64, sv1); };
      auto stat_await = [&](auto src, uint32_t tg) {
#pragma unroll 1
        for (uint32_t n = 0; (((sv0[0] ^ tg) | (sv0[2] ^ tg) | (sv1[0] ^ tg) | (sv1[2] ^ tg)) & 15u) && n < SPIN_MAX; n++) stat_fetch(src());
        __syncwarp();
      };
      auto ln_stats = [&]() {
        GEOM;
        stat_await(stat_src, 2 * (tag + 1));
        float mean0, var0, mean1, var1;
        stat_combine(sv0[0], sv0[1], sv1[0], sv1[1], untag(__shfl_sync(0xffffffffu, sv0[0], l7)), mean0, var0);
        stat_combine(sv0[2], sv0[3], sv1[2], sv1[3], untag(__shfl_sync(0xffffffffu, sv0[2], l7)), mean1, var1);
        nmean0 = -__shfl_sync(0xffffffffu, mean0, g); rstd0 = rsq(__shfl_sync(0xffffffffu, var0, g) + 1e-5f);
        nmean1 = -__shfl_sync(0xffffffffu, mean1, g); rstd1 = rsq(__shfl_sync(0xffffffffu, var1, g) + 1e-5f);
      };
      auto center = [&](float (&acc)[96], int ab) {
        const bool q0 = (fresh_tid() & 3) == 0;
        const uint32_t h0 = pack2(nmean0, nmean0), h1 = pack2(nmean1, nmean1);
        const float l0 = nmean0 - bf_lo(h0), l1 = nmean1 - bf_lo(h1);
        const uint32_t a0 = q0 ? h0 : 0u, a1 = q0 ? h1 : 0u, a2 = q0 ? pack2(l0, l0) : 0u, a3 = q0 ? pack2(l1, l1) : 0u;
        wg_fence();
        wgmma_rs_192(acc, a0, a1, a2, a3, mkdesc_vec(sb + OFF_CS + ab * 768, 32));
      };
      auto frag = [&](float (&acc)[96], int t, uint32_t& p0, uint32_t& p1) {
        if (t >= 8) { p0 = pack2(acc[4 * t] * rstd0, acc[4 * t + 1] * rstd0); p1 = pack2(acc[4 * t + 2] * rstd1, acc[4 * t + 3] * rstd1); }
        else { p0 = pack2(acc[4 * t], acc[4 * t + 1]); p1 = pack2(acc[4 * t + 2], acc[4 * t + 3]); }
      };
      auto fold_v = [&](float (&acc)[96], int t0, int t1) {
        GEOM;
        const uint32_t a = sb + OFF_STG + 16384 + ((wu + 1) & 7) * 2048 + lr * 128;
#pragma unroll
        for (int t = t0; t < t1; t += 2) {
          uint32_t p0, p1, p2, p3;
          frag(acc, 16 + t, p0, p1); frag(acc, 17 + t, p2, p3);
          stsm4(a + (((t + lt) ^ l7) << 4), p0, p1, p2, p3);
        }
        __syncwarp();
#pragma unroll
        for (int t = t0; t < t1; t += 2) ldsm4t(a + (((t + lt) ^ l7) << 4), V[2 * t], V[2 * t + 1], V[2 * t + 2], V[2 * t + 3]);
        if (wu == 7) signal(FOLD + 1);
      };
      auto fold_k = [&](float (&acc)[96], int ab, int h0, int h1) {
        GEOM;
        const uint32_t a = sb + OFF_STG + ((wu + 1) & 7) * 2048 + lane * 16;
#pragma unroll
        for (int hh = h0; hh < h1; hh++) {
#pragma unroll
          for (int t = 4 * hh; t < 4 * hh + 4; t++) frag(acc, 8 + t, K[0][t], K[1][t]);
#pragma unroll
          for (int o = 0; o < 2; o++) sts128(a + (2 * o + hh) * 512, K[o][4 * hh], K[o][4 * hh + 1], K[o][4 * hh + 2], K[o][4 * hh + 3]);
        }
        if (wu == 7) signal(FOLD);
      };
      auto fold_q = [&](float (&acc)[96]) {
#pragma unroll
        for (int t = 0; t < 8; t++) frag(acc, t, Q[0][t], Q[1][t]);
      };
      auto attend = [&](int ab, auto drain, auto resume) {
        GEOM;
        nb_sync<NB_BOTH>(256);
        const uint32_t xa_ = sb + OFF_STG + wu * 2048 + lane * 16;
        if (wu == 0) mbar_wait(BAR(HALO), ab);
        uint32_t KH[2][8], VH[16];
#pragma unroll
        for (int c = 0; c < 4; c++)
          lds128(xa_ + c * 512, KH[c >> 1][4 * (c & 1)], KH[c >> 1][4 * (c & 1) + 1], KH[c >> 1][4 * (c & 1) + 2], KH[c >> 1][4 * (c & 1) + 3]);
        auto load_vh = [&]() {
          if (wu == 0) mbar_wait(BAR(HALO + 1), ab);
#pragma unroll
          for (int c = 0; c < 4; c++)
            ldsm4t(sb + OFF_STG + 16384 + wu * 2048 + lr * 128 + (((2 * c + lt) ^ l7) << 4), VH[4 * c], VH[4 * c + 1], VH[4 * c + 2], VH[4 * c + 3]);
        };
        if (!(VL && ab)) load_vh();
        TS2(11 + ab + 32 * L);
        const bool e = g & 1, zneg = (g >> 1) < q, first = (i == 0) && (wu == 0);
        const float sc0 = rstd0 * (0.17677669530f * 1.4426950409f), sc1 = rstd1 * (0.17677669530f * 1.4426950409f);
        float mk0 = first ? __fdividef(-1.0e9f * 1.4426950409f, sc0) : 0.f, mk1 = first ? __fdividef(-1.0e9f * 1.4426950409f, sc1) : 0.f;
        const uint32_t sa = e ? 0x1044u : 0x4410u, sbb = e ? 0x3244u : 0x4432u;
        uint32_t sel[3] = {zneg ? sbb : 0x4444u, sa, zneg ? 0x4444u : sbb};
        uint32_t oa = sb + OFF_STG + (16 * wu + lr) * 128 + ((lt ^ l7) << 4);
        asm volatile("" : "+r"(sel[0]), "+r"(sel[1]), "+r"(sel[2]), "+r"(oa), "+f"(mk0), "+f"(mk1));
        drain();
        uint32_t pr[2][6];
        float l[2][2], sl[2][4][4];
#pragma unroll
        for (int hh = 0; hh < 2; hh++)
          attn_logits(&Q[0][4 * hh], &Q[1][4 * hh], &KH[0][4 * hh], &KH[1][4 * hh], &K[0][4 * hh], &K[1][4 * hh], mk0, mk1, sl[hh]);
        if (VL && ab) load_vh();
#pragma unroll
        for (int hh = 0; hh < 2; hh++) attn_probs(sl[hh], sc0, sc1, e, zneg, sel, pr[hh], l[hh]);
        float o[2][4][4];
#pragma unroll
        for (int hh = 0; hh < 2; hh++) attn_pv(pr[hh], &VH[8 * hh], &V[8 * hh], o[hh]);
#pragma unroll
        for (int hh = 0; hh < 2; hh++) {
          float l0 = l[hh][0], l1 = l[hh][1];
          l0 += __shfl_xor_sync(0xffffffffu, l0, 1); l1 += __shfl_xor_sync(0xffffffffu, l1, 1);
          l0 += __shfl_xor_sync(0xffffffffu, l0, 2); l1 += __shfl_xor_sync(0xffffffffu, l1, 2);
          asm("rcp.approx.ftz.f32 %0, %0;" : "+f"(l0)); asm("rcp.approx.ftz.f32 %0, %0;" : "+f"(l1));
#pragma unroll
          for (int dt = 0; dt < 4; dt += 2)
            stsm4(oa ^ ((4 * hh + dt) << 4),
                  pack2(o[hh][dt][0] * l0, o[hh][dt][1] * l0), pack2(o[hh][dt][2] * l1, o[hh][dt][3] * l1),
                  pack2(o[hh][dt + 1][0] * l0, o[hh][dt + 1][1] * l0), pack2(o[hh][dt + 1][2] * l1, o[hh][dt + 1][3] * l1));
        }
        fence_async_smem();
        signal(JOB + ab);
        nb_sync<NB_BOTH>(256);
        resume();
      };

      TS(1 + 32 * L);
      if (L == 0 && wu == 0) S5(7);
      mbar_wait(BAR(F1), 0); if (L == 0 && wu == 0) S5(8); KB(0);    g1_issue(acca, L ? OFF_X : slot1(0), slot1(0), True{});
      mbar_wait(BAR(F1 + 1), 0); KB(1); g1_issue(acca, L ? OFF_X + 16384 : slot1(1), slot1(1), False{});
      wg_wait<1>(); release(E1 + 0);
      if (L == 0) {
        GEOM;
        const bf16* wp = P.wqkv_p + ((128 * opq(m) + 16 * wg + (t7 >> 3)) * 3072 + 128 * opq(j) + 64 * r + l7 * 8);
        const uint32_t ca = sb + OFF_STG + (16 * wg + (t7 >> 3)) * 784 + l7 * 32;
#pragma unroll 1
        for (int p = 0; p < 3; p++) {
          uint4 wv[4];
#pragma unroll
          for (int k = 0; k < 4; k++)
            asm volatile("ld.global.nc.v4.u32 {%0, %1, %2, %3}, [%4];" : "=r"(wv[k].x), "=r"(wv[k].y), "=r"(wv[k].z), "=r"(wv[k].w)
                         : "l"(wp + k * 32 * 3072 + p * 1024));
          g1_loop(acca, 2 + 3 * p, p < 2 ? 5 + 3 * p : 10, 0);
          float cs[8];
#pragma unroll
          for (int k = 0; k < 4; k++) {
            const uint4 v = wv[k];
            const float t[8] = {bf_lo(v.x), bf_hi(v.x), bf_lo(v.y), bf_hi(v.y), bf_lo(v.z), bf_hi(v.z), bf_lo(v.w), bf_hi(v.w)};
#pragma unroll
            for (int e = 0; e < 8; e++) cs[e] = k ? cs[e] + t[e] : t[e];
          }
          sts128(ca + p * 256, __float_as_uint(cs[0]), __float_as_uint(cs[1]), __float_as_uint(cs[2]), __float_as_uint(cs[3]));
          sts128(ca + p * 256 + 16, __float_as_uint(cs[4]), __float_as_uint(cs[5]), __float_as_uint(cs[6]), __float_as_uint(cs[7]));
        }
        signal(CSJ);
        mbar_wait(BAR(XF), 0); mbar_wait(BAR(XF + 1), 0);
      }
      {
        const int u0 = L ? 2 : 10;
        mbar_wait(BAR(F1 + 2), 0); KB(u0); g1_issue(accb, OFF_X, slot1(2), True{});
        wg_wait<1>(); release(E1 + 1);
        mbar_wait(BAR(F1 + 3), 0); KB(u0 + 1); g1_issue(accb, OFF_X + 16384, slot1(3), False{});
        wg_wait<1>(); release(E1 + 2);
        g1_stats(u0 + 2);
        g1_loop(acca, u0 + 6, 18, 0);
      }
      stat_fetch(stat_src());
      const int fa = FA + (wg ? 0 : FO);
      g1_loop(accb, 18, fa, 0);
      ln_stats();
      if (L == 0) mbar_wait(BAR(STAT), 0);
      center(acca, 0); wg_commit();
      wg_wait<0>(); release(E1 + ((fa - 1) & 3));
      fence_regs(acca);
      TS(2 + 32 * L);
      fold_k(acca, 0, 0, 2); fold_v(acca, 0, 8); fold_q(acca);
      sched_fence(P.zero);
      g1_loop(accb, fa, ATT, fa);
      attend(0, [&]() { wg_wait<0>(); release(E1 + ((ATT - 1) & 3)); mbar_wait(BAR(F1 + (ATT & 3)), (ATT >> 2) & 1); },
             [&]() { KB(ATT); g1_issue(accb, slot1(ATT & 3), slot1(ATT & 3), False{});
                     mbar_wait(BAR(F1 + ((ATT + 1) & 3)), ((ATT + 1) >> 2) & 1);
                     KB(ATT + 1); g1_issue(accb, slot1((ATT + 1) & 3), slot1((ATT + 1) & 3), False{}); });
      wg_wait<1>(); release(E1 + (ATT & 3));
      TS(3 + 32 * L);
      load_x();
      fence_regs(xa);
      center(accb, 1);
#pragma unroll 1
      for (int u = ATT + 2; u < 32; u++) {
        const bool hold = u == 32 - LEAD1 && wg == 0;
        if (hold) { wg_wait<0>(); release(E1 + ((31 - LEAD1) & 3)); nb_sync<NB_LEAD>(256); }
        g1_step(accb, u, !hold, u == 31 && wg == 1);
      }
      mbar_wait(BAR(STD), L);
      wg_wait<0>(); release(E1 + 3);
      fence_regs(accb);
      TS(4 + 32 * L);
      if (wu == 7) ST(0);
      fold_k(accb, 1, 0, 2);
      if (KF) sched_fence(P.zero);
      fold_v(accb, 0, 8);
      fold_q(accb);
      TS2(29 + 32 * L);
      {
        auto g2_issue = [&](int p, bool own) {
          const uint32_t st = slot2(p);
          const uint32_t da = sda + ((own ? OFF_STG : st) >> 4), db = sd + (st >> 4);
          wg_fence();
          static_for<0, 4>([&](auto kk) { wgmma_128<0, 1, DI(kk.value * 32, 16), DI(16384 + kk.value * 2048, 8192)>(xa, da, db); });
          wg_commit();
        };
        uint32_t par = L ? 0x1e : 0;
        int p = 0, pp = 0;
        auto g2_loop = [&](int n0, int n1, int nrel) {
#pragma unroll 1
          for (int n = n0; n < n1; n++) {
            mbar_wait(BAR(F2 + p), (par >> p) & 1);
            KB(32 + n);
            if (n == 9 && wu == 0) ST(5);
            par ^= 1u << p;
            g2_issue(p, n == 8);
            if (n1 == 16 && n == 15 && wg == 0) nb_arrive<NB_LEAD>(256);
            wg_wait<1>();
            if (n > nrel) release(E2 + pp);
            pp = p; if (++p == 5) p = 0;
          }
        };
        g2_loop(0, COVER, 0);
        attend(1, [&]() { wg_wait<0>(); release(E2 + COVER - 1); mbar_wait(BAR(F2 + COVER), (par >> COVER) & 1); },
               [&]() { KB(32 + COVER); g2_issue(COVER, false);
                       mbar_wait(BAR(F2 + COVER + 1), (par >> (COVER + 1)) & 1);
                       KB(33 + COVER); g2_issue(COVER + 1, false); });
        wg_wait<1>(); release(E2 + COVER);
        par ^= 3u << COVER; pp = COVER + 1; p = (COVER + 2) % 5;
        TS(30 + 32 * L);
        {
          const bf16* bp = P.b2 + (128 * opq(i) + 16 * wu + ((fresh_tid() & 31) >> 2));
          asm volatile("ld.global.nc.u16 %0, [%1];" : "=h"(b2a) : "l"(bp));
          asm volatile("ld.global.nc.u16 %0, [%1];" : "=h"(b2b) : "l"(bp + 8));
        }
        TS2(14 + 32 * L);
        {
          GEOM;
          e2p = stat_slot(); e2s = stat_src();
          e2g = gHB + (opq(j) * 32 + 2 * i) * 16384 + w * 2048 + lane * 16;
          e2h = sb + OFF_X + wg * 16384 + (16 * w + lr) * 128 + ((lt ^ l7) << 4);
          asm volatile("" : "+l"(e2p), "+l"(e2s), "+l"(e2g), "+r"(e2h));
        }
        g2_loop(COVER + 2, 16 - LEAD2, 0);
        if (wg == 1) { wg_wait<0>(); release(E2 + pp); nb_sync<NB_LEAD>(256); }
        g2_loop(16 - LEAD2, 16, wg == 1 ? 16 - LEAD2 : 0);
        wg_wait<0>();
        release(E2 + 0);
        fence_regs(xa);
      }
      TS(5 + 32 * L);
      if (wu == 0) ST(8);
      {
        GEOM;
        const uint32_t tg = 2 * (tag + 1) + 1;
        float s0 = 0.f, s1 = 0.f, s2 = 0.f, s3 = 0.f, q0 = 0.f, q1 = 0.f, q2 = 0.f, q3 = 0.f;
#pragma unroll
        for (int t = 0; t < 16; t++) {
          s0 += xa[4 * t]; s1 += xa[4 * t + 1]; s2 += xa[4 * t + 2]; s3 += xa[4 * t + 3];
          q0 = fmaf(xa[4 * t], xa[4 * t], q0); q1 = fmaf(xa[4 * t + 1], xa[4 * t + 1], q1);
          q2 = fmaf(xa[4 * t + 2], xa[4 * t + 2], q2); q3 = fmaf(xa[4 * t + 3], xa[4 * t + 3], q3);
        }
        const float sm = stat_publish(e2p, s0 + s1, q0 + q1, s2 + s3, q2 + q3, tg);
        const uint32_t t0 = clock32();
        TS2(13 + 32 * L);
        const float pv0 = __shfl_sync(0xffffffffu, sm, 4 * l7) * (1.f / 128), pv1 = __shfl_sync(0xffffffffu, sm, 4 * l7 + 1) * (1.f / 128);
        while (clock32() - t0 < STAT_CLK) {}
        stat_fetch(e2s);
        wg_fence();
        wgmma_rs_224z(acc3, q == 0 ? 0x3f80u : 0u, q == 0 ? 0x3f80u : 0u, 0u, 0u, mkdesc_vec(sb + OFF_B1, 16));
        wg_commit();
        stat_await([&]() { return e2s; }, tg);
        float r0, m0, r1, m1;
        {
          float mean0, var0, mean1, var1;
          stat_combine(sv0[0], sv0[1], sv1[0], sv1[1], pv0, mean0, var0); stat_combine(sv0[2], sv0[3], sv1[2], sv1[3], pv1, mean1, var1);
          mean0 = __shfl_sync(0xffffffffu, mean0, g); var0 = __shfl_sync(0xffffffffu, var0, g);
          mean1 = __shfl_sync(0xffffffffu, mean1, g); var1 = __shfl_sync(0xffffffffu, var1, g);
          r0 = 0.5f * rsq(fmaf(var0 + 1e-5f, 1e-5f, var0)); r1 = 0.5f * rsq(fmaf(var1 + 1e-5f, 1e-5f, var1));
          m0 = -mean0 * r0; m1 = -mean1 * r1;
        }
        TS2(15 + 32 * L);
#pragma unroll
        for (int t = 0; t < 16; t += 2) {
          stsm4((e2h ^ ((t & 7) << 4)) + (t >> 3) * 8192,
                pack2(fmaf(xa[4 * t], r0, m0), fmaf(xa[4 * t + 1], r0, m0)), pack2(fmaf(xa[4 * t + 2], r1, m1), fmaf(xa[4 * t + 3], r1, m1)),
                pack2(fmaf(xa[4 * t + 4], r0, m0), fmaf(xa[4 * t + 5], r0, m0)), pack2(fmaf(xa[4 * t + 6], r1, m1), fmaf(xa[4 * t + 7], r1, m1)));
          if ((t & 7) == 6 && wg == 0) {
            __syncwarp();
            copy_out<4>(e2g + (t >> 3) * 8192, sb + OFF_X + (t >> 3) * 8192 + w * 2048 + lane * 16, 512);
          }
        }
        signal(JOB + 2 + wg);
        fence_async_smem();
        mbar_wait(BAR(F3 + 0), 0);
        if (EI) {
          if (wg == 0) { nb_sync<NB_WG0>(128); if (S2S && t7 == 0) mbar_arrive(BAR(XF + 1)); }
          else nb_sync<NB_BOTH>(256);
        } else {
          if (S2S && wg == 0) { nb_sync<NB_WG0>(128); if (t7 == 0) mbar_arrive(BAR(XF + 1)); }
          nb_sync<NB_BOTH>(256);
        }
      }
      TS(6 + 32 * L);
      auto g3_issue = [&](uint32_t a, int p) {
        const uint32_t da = sda + (a >> 4), db = sd + (slot3(p) >> 4);
        wg_fence();
        static_for<0, 4>([&](auto kk) { wgmma_224<1, 1, DI(kk.value * 2048, 8192), DI(16384 + kk.value * 2048, 8192)>(acc3, da, db); });
        wg_commit();
      };
      KB(48); g3_issue(OFF_X, 0);
      if (EI && wg == 0) nb_sync<NB_BOTH>(256);
      mbar_wait(BAR(F3 + 1), 0); KB(49); g3_issue(OFF_X + 16384, 1);
      sched_fence(P.zero);
      {
        const float c0 = __uint_as_float((uint32_t)b2a << 16), c1 = __uint_as_float((uint32_t)b2b << 16);
#pragma unroll
        for (int t = 0; t < 16; t++) { xa[4 * t] += c0; xa[4 * t + 1] += c0; xa[4 * t + 2] += c1; xa[4 * t + 3] += c1; }
        fence_regs(xa);
      }
      wg_wait<1>(); release(E3 + 0);
      auto g3_loop = [&](int n0, int n1, int nrel) {
#pragma unroll 1
        for (int n = n0; n < n1; n++) {
          const int p = n & 3;
          mbar_wait(BAR(F3 + p), (n >> 2) & 1);
          KB(48 + n);
          if (n == 3 && wu == 0) ST(13);
          if (n == 2 && wu == 0) ST(14);
          g3_issue(slot3(p), p);
          wg_wait<1>();
          if (n > nrel) release(E3 + ((n - 1) & 3));
        }
      };
      g3_loop(2, 29, 0);
      uint32_t ua;
      uint8_t* ug;
      {
        GEOM;
        ua = sb + OFF_X + wg * 8192 + (8 * lt + l7) * 128 + (((2 * w + ((lane >> 3) & 1)) ^ l7) << 4);
        ug = gUB + (opq(j) * 56 + 48 + m) * 16384 + r * 4096 + wg * 8192 + (lane >> 1) * 128 + (((2 * w + (lane & 1)) ^ ((lane >> 1) & 7)) << 4);
      }
      auto gelu8 = [&](int c, int k) {
        const int o = 32 * c + 8 * k;
        stsm4t(ua + (c & 1) * 16384 + k * 2048,
               pack2(gelu_half(acc3[o]), gelu_half(acc3[o + 1])), pack2(gelu_half(acc3[o + 2]), gelu_half(acc3[o + 3])),
               pack2(gelu_half(acc3[o + 4]), gelu_half(acc3[o + 5])), pack2(gelu_half(acc3[o + 6]), gelu_half(acc3[o + 7])));
      };
      {
        auto part = [&](auto p, auto half) {
          static_for<0, 4>([&](auto kk) {
            constexpr uint32_t o = slot3(p.value) + kk.value * 2048;
            if constexpr (half.value) wgmma_32<1, 1, DI(o, 8192), DI(o + 40960, 8192), 96>(acc3, sda, sd);
            else wgmma_192<1, 1, DI(o, 8192), DI(o + 16384, 8192), 0>(acc3, sda, sd);
          });
        };
        mbar_wait(BAR(RD), L);
        mbar_wait(BAR(F3 + 1), 1); mbar_wait(BAR(F3 + 2), 1);
        wg_wait<0>(); release(E3 + 0);
#pragma unroll
        for (int k = 0; k < 112; k++) { float t; asm volatile("mov.b32 %0, %1;" : "=f"(t) : "f"(acc3[k]) : "memory"); acc3[k] = t; }
        sched_fence(P.zero);
        KB(77);
        wg_fence(); part(Int<1>{}, True{}); part(Int<2>{}, True{});
        mbar_wait(BAR(F3 + 3), 1); wg_fence(); part(Int<3>{}, True{}); wg_commit();
        part(Int<1>{}, False{}); wg_commit();
        wg_wait<1>();
#pragma unroll
        for (int k = 96; k < 112; k++) asm volatile("" : "+f"(acc3[k])::"memory");
        gelu8(3, 0); gelu8(3, 1);
        __syncwarp();
        copy_out<2>(ug, sb + OFF_X + 16384 + (uint32_t)((ug - gUB) & 0x2fff), 2048);
        signal(JOB + 7);
        sched_fence(P.zero);
        KB(78);
        wg_fence(); part(Int<2>{}, False{}); wg_commit();
        wg_wait<1>(); release(E3 + 1);
        KB(79);
        part(Int<3>{}, False{}); wg_commit();
        wg_wait<1>(); release(E3 + 2);
        wg_wait<0>(); release(E3 + 3);
      }
      fence_regs(acc3);
      TS(7 + 32 * L);
      if (wu == 0) ST(16);
      auto g4_issue = [&](int p, uint32_t b) {
        const uint32_t da = sda + (slot4(p) >> 4), db = sd + (b >> 4);
        wg_fence();
        static_for<0, 4>([&](auto kk) { wgmma_128<1, 1, DI(kk.value * 2048, 8192), DI(kk.value * 2048, 8192)>(xa, da, db); });
        wg_commit();
      };
#pragma unroll
      for (int k = 0; k < 4; k++) gelu8(0, k);
      fence_async_smem();
      signal(JOB + 4);
      nb_sync<NB_BOTH>(256);
      TS(8 + 32 * L);
      static_for<0, 18>([&](auto nn) {
        constexpr int n = nn.value, p = n % 6;
        if (n == 9 || n == 17) mbar_wait(BAR(JOB + 4 + (n >> 3)), L);
        mbar_wait(BAR(F4 + p), (n / 6 + (p >= 2 ? L : 0)) & 1);
        KB(80 + n);
        if (n == 1 && wu == 0) ST(21);
        if (n == 0 && wu == 0) ST(22);
        wg_fence();
        static_for<0, 4>([&](auto kk) {
          wgmma_128<1, 1, DI(slot4(p) + kk.value * 2048, 8192), DI((n == 9 ? OFF_X + 16384 : n % 17 ? slot4(p) + 16384 : OFF_X) + kk.value * 2048, 8192)>(xa, sda, sd);
        });
        wg_commit();
        if (n) { wg_wait<1>(); release(E4 + (n + 5) % 6); }
        if (n == 8) mbar_wait(BAR(RD + 2), L);
        else if (n < 16 && !(n & 1)) sched_fence(P.zero);
        if constexpr (n < 16 && !(n & 1)) gelu8(1 + (n >> 3), (n >> 1) & 3);
        if ((n & 7) == 7) { fence_async_smem(); signal(JOB + 5 + (n >> 3)); }
      });
      {
        int p = 0, pp = 5;
        uint32_t par = L ? 0x03 : 0x3f;
        auto g4_loop = [&](int n0, int n1, int nrel) {
#pragma unroll 1
          for (int n = n0; n < n1; n++) {
            mbar_wait(BAR(F4 + p), (par >> p) & 1);
            KB(80 + n);
            par ^= 1u << p;
            g4_issue(p, slot4(p) + 16384);
            if (n1 == 56 && n == 55 && wg == 0) nb_arrive<NB_LEAD>(256);
            wg_wait<1>();
            if (n > nrel) release(E4 + pp);
            pp = p; if (++p == 6) p = 0;
          }
        };
        g4_loop(18, 56 - LEAD4, 0);
        if (wg == 1) { wg_wait<0>(); release(E4 + pp); nb_sync<NB_LEAD>(256); }
        g4_loop(56 - LEAD4, 56, wg == 1 ? 56 - LEAD4 : 0);
      }
      uint32_t xs;
      uint8_t* xg;
      {
        GEOM;
        xs = sb + OFF_X + wu * 2048 + (lane >> 3) * 128 + ((L ? l7 ^ (lane >> 3) : l7) << 4);
        xg = L ? P.out + (128 * opq(i) + 16 * wu + (lane >> 3)) * 2048 + 256 * j + 16 * l7 : gXB + (opq(i) * 16 + 2 * j) * 16384 + wu * 2048 + lane * 16;
        asm volatile("" : "+r"(xs), "+l"(xg));
      }
      mbar_wait(BAR(RD + 1), L);
      wg_wait<0>();
      release(E4 + 1);
      fence_regs(xa);
      TS(9 + 32 * L);
      {
        GEOM;
#pragma unroll
        for (int t = 0; t < 16; t += 2) {
          stsm4(sb + OFF_X + (t >> 3) * 16384 + (16 * wu + lr) * 128 + ((((t & 7) + lt) ^ l7) << 4),
                pack2(xa[4 * t], xa[4 * t + 1]), pack2(xa[4 * t + 2], xa[4 * t + 3]),
                pack2(xa[4 * t + 4], xa[4 * t + 5]), pack2(xa[4 * t + 6], xa[4 * t + 7]));
          if ((t & 7) == 6 && (L || t == 6)) {
            __syncwarp();
            uint4 v[4];
#pragma unroll
            for (int k = 0; k < 4; k++) lds128((xs ^ (L ? (k & 1) << 6 : 0)) + k * 512 + (t >> 3) * 16384, v[k].x, v[k].y, v[k].z, v[k].w);
#pragma unroll
            for (int k = 0; k < 4; k++)
              asm volatile("st.global.v4.b32 [%0], {%1, %2, %3, %4};" ::"l"(xg + k * (L ? 8192 : 512) + (t >> 3) * 128), "r"(v[k].x), "r"(v[k].y), "r"(v[k].z), "r"(v[k].w) : "memory");
            if (L == 0) signal(JOB + 8);
          }
        }
        if (L) break;
        fence_async_smem();
        signal(JOB + 9);
        nb_sync<NB_BOTH>(256);
      }
      TS(10 + 32 * L);
      KB(136);
    }
    cluster_bar();
    TS(32);
  }
}

typedef CUresult (*EncodeFn)(CUtensorMap*, CUtensorMapDataType, cuuint32_t, void*, const cuuint64_t*, const cuuint64_t*, const cuuint32_t*,
                             const cuuint32_t*, CUtensorMapInterleave, CUtensorMapSwizzle, CUtensorMapL2promotion, CUtensorMapFloatOOBfill);

void make_map(EncodeFn enc, CUtensorMap* mp, const void* base, int rank, cuuint64_t d0, cuuint64_t d1, cuuint64_t d2, cuuint64_t s1, cuuint64_t s2,
              cuuint32_t b0, cuuint32_t b1, cuuint32_t b2) {
  cuuint64_t dims[3] = {d0, d1, d2}, strides[2] = {s1, s2};
  cuuint32_t box[3] = {b0, b1, b2}, es[3] = {1, 1, 1};
  CUresult res = enc(mp, CU_TENSOR_MAP_DATA_TYPE_BFLOAT16, rank, const_cast<void*>(base), dims, strides, box, es, CU_TENSOR_MAP_INTERLEAVE_NONE,
                     CU_TENSOR_MAP_SWIZZLE_128B, CU_TENSOR_MAP_L2_PROMOTION_L2_128B, CU_TENSOR_MAP_FLOAT_OOB_FILL_NONE);
  (void)res;
}

}

extern "C" void kernel_launch(void* const* d_in, const int* in_sizes, int n_in, void* d_out, int out_size) {
  (void)in_sizes; (void)n_in; (void)out_size;
  static EncodeFn enc = nullptr;
  if (!enc) {
    void* fn = nullptr;
    cudaDriverEntryPointQueryResult qr;
    cudaGetDriverEntryPoint("cuTensorMapEncodeTiled", &fn, cudaEnableDefault, &qr);
    enc = (EncodeFn)fn;
    cudaFuncSetAttribute(fused_kernel, cudaFuncAttributeMaxDynamicSharedMemorySize, SMEM_BYTES);
  }
  Params P;
  make_map(enc, &P.x0, d_in[0], 2, D_, S_, 1, D_ * 2, 0, 64, 128, 1);
  make_map(enc, &P.wqkv, d_in[1], 3, D_, D_, 3, 3 * D_ * 2, D_ * 2, 64, 32, 3);
  make_map(enc, &P.wo, d_in[2], 2, D_, D_, 1, D_ * 2, 0, 64, 64, 1);
  make_map(enc, &P.w1, d_in[4], 3, 64, S_, F_ / 64, F_ * 2, 128, 64, 64, 3);
  make_map(enc, &P.w1h, d_in[4], 3, 32, S_, F_ / 32, F_ * 2, 64, 64, 64, 1);
  make_map(enc, &P.w2, d_in[6], 3, 64, F_, S_ / 64, S_ * 2, 128, 64, 64, 2);
  P.out = (uint8_t*)d_out;
  P.wqkv_p = (const bf16*)d_in[1];
  P.wo_p = (const bf16*)d_in[2];
  P.w1_p = (const bf16*)d_in[4];
  P.w2_p = (const bf16*)d_in[6];
  P.b1 = (const bf16*)d_in[5];
  P.b2 = (const bf16*)d_in[7];
  P.zero = 0;
  fused_kernel<<<128, 384, SMEM_BYTES>>>(P);
}
```

```cpp
#include <cuda_runtime.h>
#include <cuda_bf16.h>
#include <cuda.h>
#include <stdint.h>

namespace {

typedef __nv_bfloat16 bf16;
constexpr int S_ = 2048, D_ = 1024, F_ = 3584;

constexpr uint32_t OFF_STG  = 163840;
constexpr uint32_t OFF_X    = 196608;
constexpr uint32_t OFF_BAR  = 229376;
constexpr uint32_t OFF_CS   = OFF_BAR + 512;
constexpr uint32_t OFF_B1   = OFF_CS + 1536;
constexpr uint32_t SMEM_BYTES = OFF_B1 + 896 + 128;
constexpr int F1 = 0, E1 = 4, F2 = 8, E2 = 13, F3 = 18, E3 = 22, F4 = 26, E4 = 32;
constexpr int JOB = 38;
constexpr int RD = 48;
constexpr int XF = 54, STD = 56, STAT = 58, FOLD = 59, CSJ = 61, HALO = 62;
constexpr int NB_BOTH = 1, NB_INIT = 2, NB_LEAD = 3, NB_WG0 = 4;

__host__ __device__ constexpr uint32_t slot1(int p) { return p * 40960; }
__host__ __device__ constexpr uint32_t slot2(int p) { return p * 32768; }
__host__ __device__ constexpr uint32_t slot3(int p) { return ((p + 2) & 3) * 49152; }
__host__ __device__ constexpr uint32_t slot4(int p) { return (p < 2 ? p + 4 : p - 2) * 32768; }

__device__ __align__(1024) uint8_t gXB[16 * 16 * 16384];
__device__ __align__(1024) uint8_t gOB[16 * 16 * 16384];
__device__ __align__(1024) uint8_t gHB[8 * 32 * 16384];
__device__ __align__(1024) uint8_t gUB[8 * 56 * 16384];
__device__ __align__(1024) uint2   gST[2][16][8][8][16];
__device__ __align__(1024) uint4   gHalo[2][16][8][12][32];
__device__ __align__(1024) uint32_t gAck[2][16][8][2][8];
__device__ __align__(1024) uint4   gCS[8][16][64];
__device__ __align__(1024) uint32_t gFlag[2][7][16][32];
__device__ uint32_t gEpoch;

struct Params {
  CUtensorMap x0, wqkv, wo, w1, w1h, w2;
  uint8_t* out;
  const bf16 *wqkv_p, *wo_p, *w1_p, *b1, *b2;
  uint32_t zero;
};

template <int TA, int TB, uint32_t IA, uint32_t IB, int O = 0, int LEN> __device__ __forceinline__ void wgmma_32(float (&d)[LEN], uint32_t da, uint32_t db) {
  asm volatile("{\n.reg .b64 da, db;\n.reg .b32 la, lb;\nadd.u32 la, %16, %20;\nadd.u32 lb, %17, %21;\nmov.b64 da, {la, 0x40000040};\nmov.b64 db, {lb, 0x40000040};\n"
  "wgmma.mma_async.sync.aligned.m64n32k16.f32.bf16.bf16 {"
  "%0, %1, %2, %3, %4, %5, %6, %7, %8, %9, %10, %11, %12, %13, %14, %15"
  "}, da, db, 1, 1, 1, %18, %19;\n}\n"
  : "+f"(d[O + 0]), "+f"(d[O + 1]), "+f"(d[O + 2]), "+f"(d[O + 3]), "+f"(d[O + 4]), "+f"(d[O + 5]), "+f"(d[O + 6]), "+f"(d[O + 7]),
    "+f"(d[O + 8]), "+f"(d[O + 9]), "+f"(d[O + 10]), "+f"(d[O + 11]), "+f"(d[O + 12]), "+f"(d[O + 13]), "+f"(d[O + 14]), "+f"(d[O + 15])
  : "r"(da), "r"(db), "n"(TA), "n"(TB), "n"(IA), "n"(IB));
}
template <int TA, int TB, uint32_t IA, uint32_t IB, int O = 0, int LEN> __device__ __forceinline__ void wgmma_128(float (&d)[LEN], uint32_t da, uint32_t db) {
  asm volatile("{\n.reg .b64 da, db;\n.reg .b32 la, lb;\nadd.u32 la, %64, %68;\nadd.u32 lb, %65, %69;\nmov.b64 da, {la, 0x40000040};\nmov.b64 db, {lb, 0x40000040};\n"
  "wgmma.mma_async.sync.aligned.m64n128k16.f32.bf16.bf16 {"
  "%0, %1, %2, %3, %4, %5, %6, %7, %8, %9, %10, %11, %12, %13, %14, %15, "
  "%16, %17, %18, %19, %20, %21, %22, %23, %24, %25, %26, %27, %28, %29, %30, %31, "
  "%32, %33, %34, %35, %36, %37, %38, %39, %40, %41, %42, %43, %44, %45, %46, %47, "
  "%48, %49, %50, %51, %52, %53, %54, %55, %56, %57, %58, %59, %60, %61, %62, %63"
  "}, da, db, 1, 1, 1, %66, %67;\n}\n"
  : "+f"(d[O + 0]), "+f"(d[O + 1]), "+f"(d[O + 2]), "+f"(d[O + 3]), "+f"(d[O + 4]), "+f"(d[O + 5]), "+f"(d[O + 6]), "+f"(d[O + 7]),
    "+f"(d[O + 8]), "+f"(d[O + 9]), "+f"(d[O + 10]), "+f"(d[O + 11]), "+f"(d[O + 12]), "+f"(d[O + 13]), "+f"(d[O + 14]), "+f"(d[O + 15]),
    "+f"(d[O + 16]), "+f"(d[O + 17]), "+f"(d[O + 18]), "+f"(d[O + 19]), "+f"(d[O + 20]), "+f"(d[O + 21]), "+f"(d[O + 22]), "+f"(d[O + 23]),
    "+f"(d[O + 24]), "+f"(d[O + 25]), "+f"(d[O + 26]), "+f"(d[O + 27]), "+f"(d[O + 28]), "+f"(d[O + 29]), "+f"(d[O + 30]), "+f"(d[O + 31]),
    "+f"(d[O + 32]), "+f"(d[O + 33]), "+f"(d[O + 34]), "+f"(d[O + 35]), "+f"(d[O + 36]), "+f"(d[O + 37]), "+f"(d[O + 38]), "+f"(d[O + 39]),
    "+f"(d[O + 40]), "+f"(d[O + 41]), "+f"(d[O + 42]), "+f"(d[O + 43]), "+f"(d[O + 44]), "+f"(d[O + 45]), "+f"(d[O + 46]), "+f"(d[O + 47]),
    "+f"(d[O + 48]), "+f"(d[O + 49]), "+f"(d[O + 50]), "+f"(d[O + 51]), "+f"(d[O + 52]), "+f"(d[O + 53]), "+f"(d[O + 54]), "+f"(d[O + 55]),
    "+f"(d[O + 56]), "+f"(d[O + 57]), "+f"(d[O + 58]), "+f"(d[O + 59]), "+f"(d[O + 60]), "+f"(d[O + 61]), "+f"(d[O + 62]), "+f"(d[O + 63])
  : "r"(da), "r"(db), "n"(TA), "n"(TB), "n"(IA), "n"(IB));
}
template <int TA, int TB, uint32_t IA, uint32_t IB, int O = 0, int LEN> __device__ __forceinline__ void wgmma_192(float (&d)[LEN], uint32_t da, uint32_t db) {
  asm volatile("{\n.reg .b64 da, db;\n.reg .b32 la, lb;\nadd.u32 la, %96, %100;\nadd.u32 lb, %97, %101;\nmov.b64 da, {la, 0x40000040};\nmov.b64 db, {lb, 0x40000040};\n"
  "wgmma.mma_async.sync.aligned.m64n192k16.f32.bf16.bf16 {"
  "%0, %1, %2, %3, %4, %5, %6, %7, %8, %9, %10, %11, %12, %13, %14, %15, "
  "%16, %17, %18, %19, %20, %21, %22, %23, %24, %25, %26, %27, %28, %29, %30, %31, "
  "%32, %33, %34, %35, %36, %37, %38, %39, %40, %41, %42, %43, %44, %45, %46, %47, "
  "%48, %49, %50, %51, %52, %53, %54, %55, %56, %57, %58, %59, %60, %61, %62, %63, "
  "%64, %65, %66, %67, %68, %69, %70, %71, %72, %73, %74, %75, %76, %77, %78, %79, "
  "%80, %81, %82, %83, %84, %85, %86, %87, %88, %89, %90, %91, %92, %93, %94, %95"
  "}, da, db, 1, 1, 1, %98, %99;\n}\n"
  : "+f"(d[O + 0]), "+f"(d[O + 1]), "+f"(d[O + 2]), "+f"(d[O + 3]), "+f"(d[O + 4]), "+f"(d[O + 5]), "+f"(d[O + 6]), "+f"(d[O + 7]),
    "+f"(d[O + 8]), "+f"(d[O + 9]), "+f"(d[O + 10]), "+f"(d[O + 11]), "+f"(d[O + 12]), "+f"(d[O + 13]), "+f"(d[O + 14]), "+f"(d[O + 15]),
    "+f"(d[O + 16]), "+f"(d[O + 17]), "+f"(d[O + 18]), "+f"(d[O + 19]), "+f"(d[O + 20]), "+f"(d[O + 21]), "+f"(d[O + 22]), "+f"(d[O + 23]),
    "+f"(d[O + 24]), "+f"(d[O + 25]), "+f"(d[O + 26]), "+f"(d[O + 27]), "+f"(d[O + 28]), "+f"(d[O + 29]), "+f"(d[O + 30]), "+f"(d[O + 31]),
    "+f"(d[O + 32]), "+f"(d[O + 33]), "+f"(d[O + 34]), "+f"(d[O + 35]), "+f"(d[O + 36]), "+f"(d[O + 37]), "+f"(d[O + 38]), "+f"(d[O + 39]),
    "+f"(d[O + 40]), "+f"(d[O + 41]), "+f"(d[O + 42]), "+f"(d[O + 43]), "+f"(d[O + 44]), "+f"(d[O + 45]), "+f"(d[O + 46]), "+f"(d[O + 47]),
    "+f"(d[O + 48]), "+f"(d[O + 49]), "+f"(d[O + 50]), "+f"(d[O + 51]), "+f"(d[O + 52]), "+f"(d[O + 53]), "+f"(d[O + 54]), "+f"(d[O + 55]),
    "+f"(d[O + 56]), "+f"(d[O + 57]), "+f"(d[O + 58]), "+f"(d[O + 59]), "+f"(d[O + 60]), "+f"(d[O + 61]), "+f"(d[O + 62]), "+f"(d[O + 63]),
    "+f"(d[O + 64]), "+f"(d[O + 65]), "+f"(d[O + 66]), "+f"(d[O + 67]), "+f"(d[O + 68]), "+f"(d[O + 69]), "+f"(d[O + 70]), "+f"(d[O + 71]),
    "+f"(d[O + 72]), "+f"(d[O + 73]), "+f"(d[O + 74]), "+f"(d[O + 75]), "+f"(d[O + 76]), "+f"(d[O + 77]), "+f"(d[O + 78]), "+f"(d[O + 79]),
    "+f"(d[O + 80]), "+f"(d[O + 81]), "+f"(d[O + 82]), "+f"(d[O + 83]), "+f"(d[O + 84]), "+f"(d[O + 85]), "+f"(d[O + 86]), "+f"(d[O + 87]),
    "+f"(d[O + 88]), "+f"(d[O + 89]), "+f"(d[O + 90]), "+f"(d[O + 91]), "+f"(d[O + 92]), "+f"(d[O + 93]), "+f"(d[O + 94]), "+f"(d[O + 95])
  : "r"(da), "r"(db), "n"(TA), "n"(TB), "n"(IA), "n"(IB));
}
template <int TA, int TB, uint32_t IA, uint32_t IB, int O = 0, int LEN> __device__ __forceinline__ void wgmma_192z(float (&d)[LEN], uint32_t da, uint32_t db) {
  asm volatile("{\n.reg .b64 da, db;\n.reg .b32 la, lb;\nadd.u32 la, %96, %100;\nadd.u32 lb, %97, %101;\nmov.b64 da, {la, 0x40000040};\nmov.b64 db, {lb, 0x40000040};\n"
  "wgmma.mma_async.sync.aligned.m64n192k16.f32.bf16.bf16 {"
  "%0, %1, %2, %3, %4, %5, %6, %7, %8, %9, %10, %11, %12, %13, %14, %15, "
  "%16, %17, %18, %19, %20, %21, %22, %23, %24, %25, %26, %27, %28, %29, %30, %31, "
  "%32, %33, %34, %35, %36, %37, %38, %39, %40, %41, %42, %43, %44, %45, %46, %47, "
  "%48, %49, %50, %51, %52, %53, %54, %55, %56, %57, %58, %59, %60, %61, %62, %63, "
  "%64, %65, %66, %67, %68, %69, %70, %71, %72, %73, %74, %75, %76, %77, %78, %79, "
  "%80, %81, %82, %83, %84, %85, %86, %87, %88, %89, %90, %91, %92, %93, %94, %95"
  "}, da, db, 0, 1, 1, %98, %99;\n}\n"
  : "=f"(d[O + 0]), "=f"(d[O + 1]), "=f"(d[O + 2]), "=f"(d[O + 3]), "=f"(d[O + 4]), "=f"(d[O + 5]), "=f"(d[O + 6]), "=f"(d[O + 7]),
    "=f"(d[O + 8]), "=f"(d[O + 9]), "=f"(d[O + 10]), "=f"(d[O + 11]), "=f"(d[O + 12]), "=f"(d[O + 13]), "=f"(d[O + 14]), "=f"(d[O + 15]),
    "=f"(d[O + 16]), "=f"(d[O + 17]), "=f"(d[O + 18]), "=f"(d[O + 19]), "=f"(d[O + 20]), "=f"(d[O + 21]), "=f"(d[O + 22]), "=f"(d[O + 23]),
    "=f"(d[O + 24]), "=f"(d[O + 25]), "=f"(d[O + 26]), "=f"(d[O + 27]), "=f"(d[O + 28]), "=f"(d[O + 29]), "=f"(d[O + 30]), "=f"(d[O + 31]),
    "=f"(d[O + 32]), "=f"(d[O + 33]), "=f"(d[O + 34]), "=f"(d[O + 35]), "=f"(d[O + 36]), "=f"(d[O + 37]), "=f"(d[O + 38]), "=f"(d[O + 39]),
    "=f"(d[O + 40]), "=f"(d[O + 41]), "=f"(d[O + 42]), "=f"(d[O + 43]), "=f"(d[O + 44]), "=f"(d[O + 45]), "=f"(d[O + 46]), "=f"(d[O + 47]),
    "=f"(d[O + 48]), "=f"(d[O + 49]), "=f"(d[O + 50]), "=f"(d[O + 51]), "=f"(d[O + 52]), "=f"(d[O + 53]), "=f"(d[O + 54]), "=f"(d[O + 55]),
    "=f"(d[O + 56]), "=f"(d[O + 57]), "=f"(d[O + 58]), "=f"(d[O + 59]), "=f"(d[O + 60]), "=f"(d[O + 61]), "=f"(d[O + 62]), "=f"(d[O + 63]),
    "=f"(d[O + 64]), "=f"(d[O + 65]), "=f"(d[O + 66]), "=f"(d[O + 67]), "=f"(d[O + 68]), "=f"(d[O + 69]), "=f"(d[O + 70]), "=f"(d[O + 71]),
    "=f"(d[O + 72]), "=f"(d[O + 73]), "=f"(d[O + 74]), "=f"(d[O + 75]), "=f"(d[O + 76]), "=f"(d[O + 77]), "=f"(d[O + 78]), "=f"(d[O + 79]),
    "=f"(d[O + 80]), "=f"(d[O + 81]), "=f"(d[O + 82]), "=f"(d[O + 83]), "=f"(d[O + 84]), "=f"(d[O + 85]), "=f"(d[O + 86]), "=f"(d[O + 87]),
    "=f"(d[O + 88]), "=f"(d[O + 89]), "=f"(d[O + 90]), "=f"(d[O + 91]), "=f"(d[O + 92]), "=f"(d[O + 93]), "=f"(d[O + 94]), "=f"(d[O + 95])
  : "r"(da), "r"(db), "n"(TA), "n"(TB), "n"(IA), "n"(IB));
}
template <int TA, int TB, uint32_t IA, uint32_t IB, int O = 0, int LEN> __device__ __forceinline__ void wgmma_224(float (&d)[LEN], uint32_t da, uint32_t db) {
  asm volatile("{\n.reg .b64 da, db;\n.reg .b32 la, lb;\nadd.u32 la, %112, %116;\nadd.u32 lb, %113, %117;\nmov.b64 da, {la, 0x40000040};\nmov.b64 db, {lb, 0x40000040};\n"
  "wgmma.mma_async.sync.aligned.m64n224k16.f32.bf16.bf16 {"
  "%0, %1, %2, %3, %4, %5, %6, %7, %8, %9, %10, %11, %12, %13, %14, %15, "
  "%16, %17, %18, %19, %20, %21, %22, %23, %24, %25, %26, %27, %28, %29, %30, %31, "
  "%32, %33, %34, %35, %36, %37, %38, %39, %40, %41, %42, %43, %44, %45, %46, %47, "
  "%48, %49, %50, %51, %52, %53, %54, %55, %56, %57, %58, %59, %60, %61, %62, %63, "
  "%64, %65, %66, %67, %68, %69, %70, %71, %72, %73, %74, %75, %76, %77, %78, %79, "
  "%80, %81, %82, %83, %84, %85, %86, %87, %88, %89, %90, %91, %92, %93, %94, %95, "
  "%96, %97, %98, %99, %100, %101, %102, %103, %104, %105, %106, %107, %108, %109, %110, %111"
  "}, da, db, 1, 1, 1, %114, %115;\n}\n"
  : "+f"(d[O + 0]), "+f"(d[O + 1]), "+f"(d[O + 2]), "+f"(d[O + 3]), "+f"(d[O + 4]), "+f"(d[O + 5]), "+f"(d[O + 6]), "+f"(d[O + 7]),
    "+f"(d[O + 8]), "+f"(d[O + 9]), "+f"(d[O + 10]), "+f"(d[O + 11]), "+f"(d[O + 12]), "+f"(d[O + 13]), "+f"(d[O + 14]), "+f"(d[O + 15]),
    "+f"(d[O + 16]), "+f"(d[O + 17]), "+f"(d[O + 18]), "+f"(d[O + 19]), "+f"(d[O + 20]), "+f"(d[O + 21]), "+f"(d[O + 22]), "+f"(d[O + 23]),
    "+f"(d[O + 24]), "+f"(d[O + 25]), "+f"(d[O + 26]), "+f"(d[O + 27]), "+f"(d[O + 28]), "+f"(d[O + 29]), "+f"(d[O + 30]), "+f"(d[O + 31]),
    "+f"(d[O + 32]), "+f"(d[O + 33]), "+f"(d[O + 34]), "+f"(d[O + 35]), "+f"(d[O + 36]), "+f"(d[O + 37]), "+f"(d[O + 38]), "+f"(d[O + 39]),
    "+f"(d[O + 40]), "+f"(d[O + 41]), "+f"(d[O + 42]), "+f"(d[O + 43]), "+f"(d[O + 44]), "+f"(d[O + 45]), "+f"(d[O + 46]), "+f"(d[O + 47]),
    "+f"(d[O + 48]), "+f"(d[O + 49]), "+f"(d[O + 50]), "+f"(d[O + 51]), "+f"(d[O + 52]), "+f"(d[O + 53]), "+f"(d[O + 54]), "+f"(d[O + 55]),
    "+f"(d[O + 56]), "+f"(d[O + 57]), "+f"(d[O + 58]), "+f"(d[O + 59]), "+f"(d[O + 60]), "+f"(d[O + 61]), "+f"(d[O + 62]), "+f"(d[O + 63]),
    "+f"(d[O + 64]), "+f"(d[O + 65]), "+f"(d[O + 66]), "+f"(d[O + 67]), "+f"(d[O + 68]), "+f"(d[O + 69]), "+f"(d[O + 70]), "+f"(d[O + 71]),
    "+f"(d[O + 72]), "+f"(d[O + 73]), "+f"(d[O + 74]), "+f"(d[O + 75]), "+f"(d[O + 76]), "+f"(d[O + 77]), "+f"(d[O + 78]), "+f"(d[O + 79]),
    "+f"(d[O + 80]), "+f"(d[O + 81]), "+f"(d[O + 82]), "+f"(d[O + 83]), "+f"(d[O + 84]), "+f"(d[O + 85]), "+f"(d[O + 86]), "+f"(d[O + 87]),
    "+f"(d[O + 88]), "+f"(d[O + 89]), "+f"(d[O + 90]), "+f"(d[O + 91]), "+f"(d[O + 92]), "+f"(d[O + 93]), "+f"(d[O + 94]), "+f"(d[O + 95]),
    "+f"(d[O + 96]), "+f"(d[O + 97]), "+f"(d[O + 98]), "+f"(d[O + 99]), "+f"(d[O + 100]), "+f"(d[O + 101]), "+f"(d[O + 102]), "+f"(d[O + 103]),
    "+f"(d[O + 104]), "+f"(d[O + 105]), "+f"(d[O + 106]), "+f"(d[O + 107]), "+f"(d[O + 108]), "+f"(d[O + 109]), "+f"(d[O + 110]), "+f"(d[O + 111])
  : "r"(da), "r"(db), "n"(TA), "n"(TB), "n"(IA), "n"(IB));
}
__device__ __forceinline__ void wgmma_rs_192(float (&d)[96], uint32_t a0, uint32_t a1, uint32_t a2, uint32_t a3, uint64_t db) {
  asm volatile("wgmma.mma_async.sync.aligned.m64n192k16.f32.bf16.bf16 {"
  "%0, %1, %2, %3, %4, %5, %6, %7, %8, %9, %10, %11, %12, %13, %14, %15, "
  "%16, %17, %18, %19, %20, %21, %22, %23, %24, %25, %26, %27, %28, %29, %30, %31, "
  "%32, %33, %34, %35, %36, %37, %38, %39, %40, %41, %42, %43, %44, %45, %46, %47, "
  "%48, %49, %50, %51, %52, %53, %54, %55, %56, %57, %58, %59, %60, %61, %62, %63, "
  "%64, %65, %66, %67, %68, %69, %70, %71, %72, %73, %74, %75, %76, %77, %78, %79, "
  "%80, %81, %82, %83, %84, %85, %86, %87, %88, %89, %90, %91, %92, %93, %94, %95"
  "}, {%96, %97, %98, %99}, %100, 1, 1, 1, 1;\n"
  : "+f"(d[0]), "+f"(d[1]), "+f"(d[2]), "+f"(d[3]), "+f"(d[4]), "+f"(d[5]), "+f"(d[6]), "+f"(d[7]),
    "+f"(d[8]), "+f"(d[9]), "+f"(d[10]), "+f"(d[11]), "+f"(d[12]), "+f"(d[13]), "+f"(d[14]), "+f"(d[15]),
    "+f"(d[16]), "+f"(d[17]), "+f"(d[18]), "+f"(d[19]), "+f"(d[20]), "+f"(d[21]), "+f"(d[22]), "+f"(d[23]),
    "+f"(d[24]), "+f"(d[25]), "+f"(d[26]), "+f"(d[27]), "+f"(d[28]), "+f"(d[29]), "+f"(d[30]), "+f"(d[31]),
    "+f"(d[32]), "+f"(d[33]), "+f"(d[34]), "+f"(d[35]), "+f"(d[36]), "+f"(d[37]), "+f"(d[38]), "+f"(d[39]),
    "+f"(d[40]), "+f"(d[41]), "+f"(d[42]), "+f"(d[43]), "+f"(d[44]), "+f"(d[45]), "+f"(d[46]), "+f"(d[47]),
    "+f"(d[48]), "+f"(d[49]), "+f"(d[50]), "+f"(d[51]), "+f"(d[52]), "+f"(d[53]), "+f"(d[54]), "+f"(d[55]),
    "+f"(d[56]), "+f"(d[57]), "+f"(d[58]), "+f"(d[59]), "+f"(d[60]), "+f"(d[61]), "+f"(d[62]), "+f"(d[63]),
    "+f"(d[64]), "+f"(d[65]), "+f"(d[66]), "+f"(d[67]), "+f"(d[68]), "+f"(d[69]), "+f"(d[70]), "+f"(d[71]),
    "+f"(d[72]), "+f"(d[73]), "+f"(d[74]), "+f"(d[75]), "+f"(d[76]), "+f"(d[77]), "+f"(d[78]), "+f"(d[79]),
    "+f"(d[80]), "+f"(d[81]), "+f"(d[82]), "+f"(d[83]), "+f"(d[84]), "+f"(d[85]), "+f"(d[86]), "+f"(d[87]),
    "+f"(d[88]), "+f"(d[89]), "+f"(d[90]), "+f"(d[91]), "+f"(d[92]), "+f"(d[93]), "+f"(d[94]), "+f"(d[95])
  : "r"(a0), "r"(a1), "r"(a2), "r"(a3), "l"(db));
}
__device__ __forceinline__ void wgmma_rs_224z(float (&d)[112], uint32_t a0, uint32_t a1, uint32_t a2, uint32_t a3, uint64_t db) {
  asm volatile("wgmma.mma_async.sync.aligned.m64n224k16.f32.bf16.bf16 {"
  "%0, %1, %2, %3, %4, %5, %6, %7, %8, %9, %10, %11, %12, %13, %14, %15, "
  "%16, %17, %18, %19, %20, %21, %22, %23, %24, %25, %26, %27, %28, %29, %30, %31, "
  "%32, %33, %34, %35, %36, %37, %38, %39, %40, %41, %42, %43, %44, %45, %46, %47, "
  "%48, %49, %50, %51, %52, %53, %54, %55, %56, %57, %58, %59, %60, %61, %62, %63, "
  "%64, %65, %66, %67, %68, %69, %70, %71, %72, %73, %74, %75, %76, %77, %78, %79, "
  "%80, %81, %82, %83, %84, %85, %86, %87, %88, %89, %90, %91, %92, %93, %94, %95, "
  "%96, %97, %98, %99, %100, %101, %102, %103, %104, %105, %106, %107, %108, %109, %110, %111"
  "}, {%112, %113, %114, %115}, %116, 0, 1, 1, 1;\n"
  : "=f"(d[0]), "=f"(d[1]), "=f"(d[2]), "=f"(d[3]), "=f"(d[4]), "=f"(d[5]), "=f"(d[6]), "=f"(d[7]),
    "=f"(d[8]), "=f"(d[9]), "=f"(d[10]), "=f"(d[11]), "=f"(d[12]), "=f"(d[13]), "=f"(d[14]), "=f"(d[15]),
    "=f"(d[16]), "=f"(d[17]), "=f"(d[18]), "=f"(d[19]), "=f"(d[20]), "=f"(d[21]), "=f"(d[22]), "=f"(d[23]),
    "=f"(d[24]), "=f"(d[25]), "=f"(d[26]), "=f"(d[27]), "=f"(d[28]), "=f"(d[29]), "=f"(d[30]), "=f"(d[31]),
    "=f"(d[32]), "=f"(d[33]), "=f"(d[34]), "=f"(d[35]), "=f"(d[36]), "=f"(d[37]), "=f"(d[38]), "=f"(d[39]),
    "=f"(d[40]), "=f"(d[41]), "=f"(d[42]), "=f"(d[43]), "=f"(d[44]), "=f"(d[45]), "=f"(d[46]), "=f"(d[47]),
    "=f"(d[48]), "=f"(d[49]), "=f"(d[50]), "=f"(d[51]), "=f"(d[52]), "=f"(d[53]), "=f"(d[54]), "=f"(d[55]),
    "=f"(d[56]), "=f"(d[57]), "=f"(d[58]), "=f"(d[59]), "=f"(d[60]), "=f"(d[61]), "=f"(d[62]), "=f"(d[63]),
    "=f"(d[64]), "=f"(d[65]), "=f"(d[66]), "=f"(d[67]), "=f"(d[68]), "=f"(d[69]), "=f"(d[70]), "=f"(d[71]),
    "=f"(d[72]), "=f"(d[73]), "=f"(d[74]), "=f"(d[75]), "=f"(d[76]), "=f"(d[77]), "=f"(d[78]), "=f"(d[79]),
    "=f"(d[80]), "=f"(d[81]), "=f"(d[82]), "=f"(d[83]), "=f"(d[84]), "=f"(d[85]), "=f"(d[86]), "=f"(d[87]),
    "=f"(d[88]), "=f"(d[89]), "=f"(d[90]), "=f"(d[91]), "=f"(d[92]), "=f"(d[93]), "=f"(d[94]), "=f"(d[95]),
    "=f"(d[96]), "=f"(d[97]), "=f"(d[98]), "=f"(d[99]), "=f"(d[100]), "=f"(d[101]), "=f"(d[102]), "=f"(d[103]),
    "=f"(d[104]), "=f"(d[105]), "=f"(d[106]), "=f"(d[107]), "=f"(d[108]), "=f"(d[109]), "=f"(d[110]), "=f"(d[111])
  : "r"(a0), "r"(a1), "r"(a2), "r"(a3), "l"(db));
}

__device__ __forceinline__ uint32_t smem_u32(const void* p) { return (uint32_t)__cvta_generic_to_shared(p); }
__device__ __forceinline__ void mbar_init(uint32_t bar, uint32_t cnt) { asm volatile("mbarrier.init.shared::cta.b64 [%0], %1;" ::"r"(bar), "r"(cnt) : "memory"); }
__device__ __forceinline__ void mbar_expect(uint32_t bar, uint32_t bytes) { asm volatile("mbarrier.arrive.expect_tx.shared::cta.b64 _, [%0], %1;" ::"r"(bar), "r"(bytes) : "memory"); }
__device__ __forceinline__ void mbar_arrive(uint32_t bar) { asm volatile("mbarrier.arrive.shared::cta.b64 _, [%0];" ::"r"(bar) : "memory"); }
__device__ __forceinline__ void mbar_arrive_cl(uint32_t cbar) { asm volatile("mbarrier.arrive.shared::cluster.b64 _, [%0];" ::"r"(cbar) : "memory"); }
__device__ __forceinline__ uint32_t mapa(uint32_t a, uint32_t cta) { uint32_t r; asm("mapa.shared::cluster.u32 %0, %1, %2;" : "=r"(r) : "r"(a), "r"(cta)); return r; }
__device__ __forceinline__ void mbar_wait(uint32_t bar, uint32_t parity) {
  asm volatile("{\n.reg .pred p;\n.reg .u32 n;\nmov.u32 n, 0;\n"
    "LAB_WAIT:\n"
    "mbarrier.try_wait.parity.shared::cta.b64 p, [%0], %1;\n"
    "@p bra LAB_DONE;\n"
    "add.u32 n, n, 1;\n"
    "setp.lt.u32 p, n, 2000000;\n"
    "@p bra LAB_WAIT;\n"
    "trap;\n"
    "LAB_DONE:\n}\n" ::"r"(bar), "r"(parity) : "memory");
}
constexpr uint32_t SPIN_MAX = 2000000;
__device__ __forceinline__ void tma2d(uint32_t dst, const CUtensorMap* m, uint32_t bar, int c0, int c1) {
  asm volatile("cp.async.bulk.tensor.2d.shared::cluster.global.mbarrier::complete_tx::bytes [%0], [%1, {%3, %4}], [%2];"
    ::"r"(dst), "l"(m), "r"(bar), "r"(c0), "r"(c1) : "memory");
}
__device__ __forceinline__ void tma2d_mc(uint32_t dst, const CUtensorMap* m, uint32_t bar, int c0, int c1) {
  asm volatile("cp.async.bulk.tensor.2d.shared::cluster.global.mbarrier::complete_tx::bytes.multicast::cluster [%0], [%1, {%3, %4}], [%2], %5;"
    ::"r"(dst), "l"(m), "r"(bar), "r"(c0), "r"(c1), "h"((uint16_t)3) : "memory");
}
__device__ __forceinline__ void tma3d(uint32_t dst, const CUtensorMap* m, uint32_t bar, int c0, int c1, int c2) {
  asm volatile("cp.async.bulk.tensor.3d.shared::cluster.global.mbarrier::complete_tx::bytes [%0], [%1, {%3, %4, %5}], [%2];"
    ::"r"(dst), "l"(m), "r"(bar), "r"(c0), "r"(c1), "r"(c2) : "memory");
}
__device__ __forceinline__ void tma3d_mc(uint32_t dst, const CUtensorMap* m, uint32_t bar, int c0, int c1, int c2) {
  asm volatile("cp.async.bulk.tensor.3d.shared::cluster.global.mbarrier::complete_tx::bytes.multicast::cluster [%0], [%1, {%3, %4, %5}], [%2], %6;"
    ::"r"(dst), "l"(m), "r"(bar), "r"(c0), "r"(c1), "r"(c2), "h"((uint16_t)3) : "memory");
}
__device__ __forceinline__ void bulk_ld(uint32_t dst, const void* src, uint32_t bytes, uint32_t bar) {
  asm volatile("cp.async.bulk.shared::cluster.global.mbarrier::complete_tx::bytes [%0], [%1], %2, [%3];" ::"r"(dst), "l"(src), "r"(bytes), "r"(bar) : "memory");
}
__device__ __forceinline__ void bulk_ld_mc(uint32_t dst, const void* src, uint32_t bytes, uint32_t bar) {
  asm volatile("cp.async.bulk.shared::cluster.global.mbarrier::complete_tx::bytes.multicast::cluster [%0], [%1], %2, [%3], %4;"
    ::"r"(dst), "l"(src), "r"(bytes), "r"(bar), "h"((uint16_t)3) : "memory");
}
__device__ __forceinline__ void bulk_st(void* dst, uint32_t src, uint32_t bytes) {
  asm volatile("cp.async.bulk.global.shared::cta.bulk_group [%0], [%1], %2;" ::"l"(dst), "r"(src), "r"(bytes) : "memory");
}
__device__ __forceinline__ void bulk_s2s(uint32_t cdst, uint32_t src, uint32_t bytes, uint32_t cbar) {
  asm volatile("cp.async.bulk.shared::cluster.shared::cta.mbarrier::complete_tx::bytes [%0], [%1], %2, [%3];" ::"r"(cdst), "r"(src), "r"(bytes), "r"(cbar) : "memory");
}
__device__ __forceinline__ void bulk_commit() { asm volatile("cp.async.bulk.commit_group;" ::: "memory"); }
__device__ __forceinline__ void bulk_wait0() { asm volatile("cp.async.bulk.wait_group 0;" ::: "memory"); }
__device__ __forceinline__ void fence_async_smem() { asm volatile("fence.proxy.async.shared::cta;" ::: "memory"); }
__device__ __forceinline__ void wg_fence() { asm volatile("wgmma.fence.sync.aligned;" ::: "memory"); }
__device__ __forceinline__ void wg_commit() { asm volatile("wgmma.commit_group.sync.aligned;" ::: "memory"); }
template <int N> __device__ __forceinline__ void wg_wait() { asm volatile("wgmma.wait_group.sync.aligned %0;" ::"n"(N) : "memory"); }
template <int R> __device__ __forceinline__ void reg_alloc() { asm volatile("setmaxnreg.inc.sync.aligned.u32 %0;" ::"n"(R)); }
template <int R> __device__ __forceinline__ void reg_dealloc() { asm volatile("setmaxnreg.dec.sync.aligned.u32 %0;" ::"n"(R)); }
__device__ __forceinline__ void cluster_bar() { asm volatile("barrier.cluster.arrive.relaxed;\nbarrier.cluster.wait;" ::: "memory"); }
template <int ID> __device__ __forceinline__ void nb_sync(int n) { asm volatile("barrier.sync %0, %1;" ::"n"(ID), "r"(n) : "memory"); }
template <int ID> __device__ __forceinline__ void nb_arrive(int n) { asm volatile("barrier.arrive %0, %1;" ::"n"(ID), "r"(n) : "memory"); }
__device__ __forceinline__ int fresh_tid() { int t; asm volatile("mov.u32 %0, %%tid.x;" : "=r"(t)); return t; }
__device__ __forceinline__ void sched_fence(uint32_t z) { asm volatile("{\n.reg .pred p;\nsetp.ne.u32 p, %0, 0;\nLAB_S:\n@p nanosleep.u32 0;\n@p bra LAB_S;\n}\n" ::"r"(z) : "memory"); }
__device__ __forceinline__ float rsq(float x) { float y; asm("rsqrt.approx.ftz.f32 %0, %1;" : "=f"(y) : "f"(x)); return y; }
__device__ __forceinline__ int opq(int v) { asm volatile("" : "+r"(v)); return v; }
template <int V> struct Int { static constexpr int value = V; };
struct True { static constexpr bool value = true; };
struct False { static constexpr bool value = false; };
template <int N> __device__ __forceinline__ void fence_regs(float (&d)[N]) {
#pragma unroll
  for (int i = 0; i < N; i++) asm volatile("" : "+f"(d[i])::"memory");
}
__host__ __device__ constexpr uint32_t DI(uint32_t off, uint32_t lbo) { return (off >> 4) + ((lbo >> 4) << 16); }
template <int K, int N, class F> __device__ __forceinline__ void static_for(F f) { if constexpr (K < N) { f(Int<K>{}); static_for<K + 1, N>(f); } }
__device__ __forceinline__ uint64_t mkdesc_vec(uint32_t addr, uint32_t sbo) { return (uint64_t)((addr & 0x3FFFF) >> 4) | ((uint64_t)(sbo >> 4) << 32); }
__device__ __forceinline__ void sts16(uint32_t a, uint32_t v) { asm volatile("st.shared.u16 [%0], %1;" ::"r"(a), "h"((uint16_t)v) : "memory"); }
__device__ __forceinline__ uint32_t pack2(float lo, float hi) { uint32_t r; asm("cvt.rn.bf16x2.f32 %0, %1, %2;" : "=r"(r) : "f"(hi), "f"(lo)); return r; }
__device__ __forceinline__ float bf_lo(uint32_t v) { return __uint_as_float(v << 16); }
__device__ __forceinline__ float bf_hi(uint32_t v) { return __uint_as_float(v & 0xffff0000u); }
__device__ __forceinline__ void stsm4(uint32_t a, uint32_t r0, uint32_t r1, uint32_t r2, uint32_t r3) {
  asm volatile("stmatrix.sync.aligned.m8n8.x4.shared.b16 [%0], {%1, %2, %3, %4};" ::"r"(a), "r"(r0), "r"(r1), "r"(r2), "r"(r3) : "memory");
}
__device__ __forceinline__ void stsm4t(uint32_t a, uint32_t r0, uint32_t r1, uint32_t r2, uint32_t r3) {
  asm volatile("stmatrix.sync.aligned.m8n8.x4.trans.shared.b16 [%0], {%1, %2, %3, %4};" ::"r"(a), "r"(r0), "r"(r1), "r"(r2), "r"(r3) : "memory");
}
__device__ __forceinline__ void ldsm4(uint32_t a, uint32_t& r0, uint32_t& r1, uint32_t& r2, uint32_t& r3) {
  asm volatile("ldmatrix.sync.aligned.m8n8.x4.shared.b16 {%0, %1, %2, %3}, [%4];" : "=r"(r0), "=r"(r1), "=r"(r2), "=r"(r3) : "r"(a) : "memory");
}
__device__ __forceinline__ void ldsm4t(uint32_t a, uint32_t& r0, uint32_t& r1, uint32_t& r2, uint32_t& r3) {
  asm volatile("ldmatrix.sync.aligned.m8n8.x4.trans.shared.b16 {%0, %1, %2, %3}, [%4];" : "=r"(r0), "=r"(r1), "=r"(r2), "=r"(r3) : "r"(a) : "memory");
}
__device__ __forceinline__ void mma16816(float (&c)[4], uint32_t a0, uint32_t a1, uint32_t a2, uint32_t a3, uint32_t b0, uint32_t b1) {
  asm volatile("mma.sync.aligned.m16n8k16.row.col.f32.bf16.bf16.f32 {%0, %1, %2, %3}, {%4, %5, %6, %7}, {%8, %9}, {%10, %11, %12, %13};"
    : "=f"(c[0]), "=f"(c[1]), "=f"(c[2]), "=f"(c[3]) : "r"(a0), "r"(a1), "r"(a2), "r"(a3), "r"(b0), "r"(b1), "f"(c[0]), "f"(c[1]), "f"(c[2]), "f"(c[3]));
}
__device__ __forceinline__ void sts128(uint32_t a, uint32_t r0, uint32_t r1, uint32_t r2, uint32_t r3) {
  asm volatile("st.shared.v4.b32 [%0], {%1, %2, %3, %4};" ::"r"(a), "r"(r0), "r"(r1), "r"(r2), "r"(r3) : "memory");
}
__device__ __forceinline__ void lds128(uint32_t a, uint32_t& r0, uint32_t& r1, uint32_t& r2, uint32_t& r3) {
  asm volatile("ld.shared.v4.b32 {%0, %1, %2, %3}, [%4];" : "=r"(r0), "=r"(r1), "=r"(r2), "=r"(r3) : "r"(a) : "memory");
}
__device__ __forceinline__ void sts64f(uint32_t a, float x, float y) { asm volatile("st.shared.v2.f32 [%0], {%1, %2};" ::"r"(a), "f"(x), "f"(y) : "memory"); }
__device__ __forceinline__ float lds32f(uint32_t a) { float v; asm volatile("ld.shared.f32 %0, [%1];" : "=f"(v) : "r"(a) : "memory"); return v; }
__device__ __forceinline__ void sts32f(uint32_t a, float x) { asm volatile("st.shared.f32 [%0], %1;" ::"r"(a), "f"(x) : "memory"); }
__device__ __forceinline__ void stat_st(uint2* p, float sum, float sq, uint32_t tag, bool on) {
  const float mean = sum * (1.f / 128), m2 = fmaxf(fmaf(-mean, sum, sq), 0.f);
  const uint32_t a = ((__float_as_uint(mean) + 8u) & ~15u) | (tag & 15u), b = ((__float_as_uint(m2) + 8u) & ~15u) | (tag & 15u);
  asm volatile("{\n.reg .b64 x;\n.reg .pred p;\nsetp.ne.u32 p, %3, 0;\nmov.b64 x, {%1, %2};\n@p st.relaxed.gpu.global.b64 [%0], x;\n}\n" ::"l"(p), "r"(a), "r"(b), "r"((uint32_t)on) : "memory");
}
__device__ __forceinline__ void stat_ld2(const uint2* p, uint32_t (&v)[4]) {
  asm volatile("{\n.reg .b64 x, y;\nld.relaxed.gpu.global.v2.b64 {x, y}, [%4];\nmov.b64 {%0, %1}, x;\nmov.b64 {%2, %3}, y;\n}\n"
    : "=r"(v[0]), "=r"(v[1]), "=r"(v[2]), "=r"(v[3]) : "l"(p) : "memory");
}
__device__ __forceinline__ float untag(uint32_t v) { return __uint_as_float(v & ~15u); }
__device__ __forceinline__ void ll_st3(uint4* p, uint32_t a, uint32_t b, uint32_t c, uint32_t tag) {
  asm volatile("{\n.reg .b64 x, y;\n.reg .b128 z;\nmov.b64 x, {%1, %2};\nmov.b64 y, {%3, %4};\nmov.b128 z, {x, y};\nst.relaxed.gpu.global.b128 [%0], z;\n}\n"
    ::"l"(p), "r"(a), "r"(b), "r"(c), "r"(tag) : "memory");
}
__device__ __forceinline__ uint32_t ll_ld3(const uint4* p, uint32_t& a, uint32_t& b, uint32_t& c, uint32_t tag) {
  uint32_t t;
  asm volatile("{\n.reg .b64 x, y;\n.reg .b128 z;\nld.relaxed.gpu.global.b128 z, [%4];\nmov.b128 {x, y}, z;\nmov.b64 {%0, %1}, x;\nmov.b64 {%2, %3}, y;\n}\n"
    : "=r"(a), "=r"(b), "=r"(c), "=r"(t) : "l"(p) : "memory");
  return t ^ tag;
}
__device__ __forceinline__ void halo_send(uint4* p, uint32_t a, const uint32_t (&tg)[6]) {
  asm volatile("{\n.reg .b64 x<6>, y<6>, w<2>;\n.reg .b32 c<4>;\n.reg .b128 z<6>;\n"
    "ld.shared.b64 w0, [%1+1536];\nld.shared.b64 w1, [%1+1792];\n"
    "ld.shared.b64 x0, [%1];\nld.shared.b64 x1, [%1+256];\nld.shared.b64 x2, [%1+512];\n"
    "ld.shared.b64 x3, [%1+768];\nld.shared.b64 x4, [%1+1024];\nld.shared.b64 x5, [%1+1280];\n"
    "mov.b64 {c0, c1}, w0;\nmov.b64 {c2, c3}, w1;\n"
    "mov.b64 y0, {c0, %2};\nmov.b64 y1, {c1, %3};\nmov.b64 y2, {c2, %4};\nmov.b64 y3, {c3, %5};\nmov.b64 y4, {%6, %6};\nmov.b64 y5, {%7, %7};\n"
    "mov.b128 z0, {x0, y0};\nmov.b128 z1, {x1, y1};\nmov.b128 z2, {x2, y2};\nmov.b128 z3, {x3, y3};\nmov.b128 z4, {x4, y4};\nmov.b128 z5, {x5, y5};\n"
    "st.relaxed.gpu.global.b128 [%0], z0;\nst.relaxed.gpu.global.b128 [%0+512], z1;\nst.relaxed.gpu.global.b128 [%0+1024], z2;\n"
    "st.relaxed.gpu.global.b128 [%0+1536], z3;\nst.relaxed.gpu.global.b128 [%0+2048], z4;\nst.relaxed.gpu.global.b128 [%0+2560], z5;\n}\n"
    ::"l"(p), "r"(a), "r"(tg[0]), "r"(tg[1]), "r"(tg[2]), "r"(tg[3]), "r"(tg[4]), "r"(tg[5]) : "memory");
}
template <int N> __device__ __forceinline__ void copy_out(uint8_t* dst, uint32_t src, int stride) {
  uint4 v[N];
#pragma unroll
  for (int k = 0; k < N; k++) lds128(src + k * stride, v[k].x, v[k].y, v[k].z, v[k].w);
#pragma unroll
  for (int k = 0; k < N; k++) asm volatile("st.global.v4.b32 [%0], {%1, %2, %3, %4};" ::"l"(dst + k * stride), "r"(v[k].x), "r"(v[k].y), "r"(v[k].z), "r"(v[k].w) : "memory");
}
__device__ __forceinline__ void warp_store(uint8_t* dst, uint32_t src, int bytes, uint32_t delay, uint32_t pace) {
  __nanosleep(delay);
#pragma unroll 1
  for (int o = 0; o < bytes; o += 2048) {
    if (pace) __nanosleep(pace);
    uint4 v[4];
#pragma unroll
    for (int k = 0; k < 4; k++) lds128(src + o + k * 512, v[k].x, v[k].y, v[k].z, v[k].w);
#pragma unroll
    for (int k = 0; k < 4; k++) asm volatile("st.global.v4.b32 [%0], {%1, %2, %3, %4};" ::"l"(dst + o + k * 512), "r"(v[k].x), "r"(v[k].y), "r"(v[k].z), "r"(v[k].w) : "memory");
  }
  __syncwarp();
}
__device__ __forceinline__ uint32_t clock32() { uint32_t t; asm volatile("mov.u32 %0, %%clock;" : "=r"(t)); return t; }
__device__ __forceinline__ void flag_set(uint32_t* p, uint32_t bit) { asm volatile("red.release.gpu.global.xor.b32 [%0], %1;" ::"l"(p), "r"(bit) : "memory"); }
__device__ __forceinline__ void flag_wait(const uint32_t* p, uint32_t inv, uint32_t need, uint32_t& ready) {
  if ((ready & need) == need) return;
  uint32_t n = 0;
  do {
    asm volatile("ld.relaxed.gpu.global.b32 %0, [%1];" : "=r"(ready) : "l"(p) : "memory");
    ready = __shfl_sync(0xffffffffu, ready, 0) ^ inv;
  } while ((ready & need) != need && ++n < SPIN_MAX);
  asm volatile("fence.acquire.gpu;\nfence.proxy.async.global;" ::: "memory");
}
__device__ __forceinline__ bool elect_one() {
  uint32_t p;
  asm volatile("{\n.reg .pred P;\nelect.sync _|P, 0xffffffff;\nselp.u32 %0, 1, 0, P;\n}\n" : "=r"(p));
  return p;
}
__device__ __forceinline__ float gelu_half(float hx) {
  const float y = hx * fmaf(hx * hx, 8.f * 0.0356774081f, 2.f * 0.7978845608f);
  float th;
  asm("tanh.approx.f32 %0, %1;" : "=f"(th) : "f"(y));
  return fmaf(hx, th, hx);
}
__device__ __forceinline__ float ex2(float x) { float y; asm("ex2.approx.ftz.f32 %0, %1;" : "=f"(y) : "f"(x)); return y; }

__device__ __forceinline__ void stat_combine(uint32_t am, uint32_t aq, uint32_t bm, uint32_t bq, float pv, float& mean, float& var) {
  const float d0 = untag(am) - pv, d1 = untag(bm) - pv;
  float s = d0 + d1, q = fmaf(fmaf(d0, d0, d1 * d1), 128.f, untag(aq) + untag(bq));
  s += __shfl_xor_sync(0xffffffffu, s, 8); q += __shfl_xor_sync(0xffffffffu, q, 8);
  s += __shfl_xor_sync(0xffffffffu, s, 16); q += __shfl_xor_sync(0xffffffffu, q, 16);
  s *= 0.125f;
  mean = pv + s;
  var = fmaxf(fmaf(-s, s, q * (1.f / D_)), 0.f);
}

__device__ __forceinline__ void attn_logits(const uint32_t* q0, const uint32_t* q1,
                                            const uint32_t* k0, const uint32_t* k1, const uint32_t* k2, const uint32_t* k3,
                                            float mk0, float mk1, float (&s)[4][4]) {
#pragma unroll
  for (int n = 0; n < 4; n++) {
    const uint32_t* k = n == 0 ? k0 : n == 1 ? k1 : n == 2 ? k2 : k3;
    s[n][0] = s[n][1] = n < 2 ? mk0 : 0.f; s[n][2] = s[n][3] = n < 2 ? mk1 : 0.f;
    mma16816(s[n], q0[0], q1[0], q0[1], q1[1], k[0], k[1]);
    mma16816(s[n], q0[2], q1[2], q0[3], q1[3], k[2], k[3]);
  }
}
__device__ __forceinline__ void attn_probs(const float (&s)[4][4], float sc0, float sc1, bool e, bool zneg, const uint32_t (&sel)[3],
                                           uint32_t (&pr)[6], float (&l)[2]) {
  float a0 = e ? s[1][1] : s[1][0];
  float b0 = zneg ? (e ? s[0][1] : s[0][0]) : (e ? s[2][1] : s[2][0]);
  float a1 = e ? s[2][3] : s[2][2];
  float b1 = zneg ? (e ? s[1][3] : s[1][2]) : (e ? s[3][3] : s[3][2]);
  float m0 = fmaxf(a0, b0), m1 = fmaxf(a1, b1);
  m0 = fmaxf(m0, __shfl_xor_sync(0xffffffffu, m0, 1)); m1 = fmaxf(m1, __shfl_xor_sync(0xffffffffu, m1, 1));
  m0 = fmaxf(m0, __shfl_xor_sync(0xffffffffu, m0, 2)); m1 = fmaxf(m1, __shfl_xor_sync(0xffffffffu, m1, 2));
  a0 = ex2((a0 - m0) * sc0); b0 = ex2((b0 - m0) * sc0); a1 = ex2((a1 - m1) * sc1); b1 = ex2((b1 - m1) * sc1);
  l[0] = a0 + b0; l[1] = a1 + b1;
  const uint32_t p0 = pack2(a0, b0), p1 = pack2(a1, b1);
#pragma unroll
  for (int k = 0; k < 3; k++) { pr[k] = __byte_perm(p0, 0u, sel[k]); pr[3 + k] = __byte_perm(p1, 0u, sel[k]); }
}
__device__ __forceinline__ void attn_pv(const uint32_t (&pr)[6], const uint32_t* vh, const uint32_t* v, float (&o)[4][4]) {
#pragma unroll
  for (int dt = 0; dt < 4; dt++) {
    o[dt][0] = o[dt][1] = o[dt][2] = o[dt][3] = 0.f;
    mma16816(o[dt], pr[0], 0u, pr[1], pr[3], vh[2 * dt], vh[2 * dt + 1]);
    mma16816(o[dt], pr[2], pr[4], 0u, pr[5], v[2 * dt], v[2 * dt + 1]);
  }
}

constexpr int FR = 1;
constexpr int XLD = 7;
constexpr int XST = 2;
constexpr int FA = 20;
constexpr int FO = 2;
constexpr int ATT = 25;
constexpr int COVER = 2;
constexpr int LEAD1 = 3;
constexpr int LEAD2 = 3;
constexpr int LEAD4 = 4;
constexpr int PD1 = 3;
constexpr int PD2 = 5;
constexpr int PD3 = 3;
constexpr int HALO_A_NS = 300;
constexpr int STAT_CLK = 150;
constexpr int H1D = 900;
constexpr int U0D = 300;
constexpr int X1D = 1200;
constexpr int PACE = 150;

__global__ void __cluster_dims__(2, 1, 1) __launch_bounds__(384, 1) fused_kernel(const __grid_constant__ Params P) {
  extern __shared__ __align__(1024) uint8_t smem_raw[];
  const uint32_t sb = smem_u32(smem_raw);
  const uint32_t bars = sb + OFF_BAR;
  const int tid = threadIdx.x;
  const int wu = __shfl_sync(0xffffffffu, tid >> 5, 0), wg = wu >> 2;
  const int r = blockIdx.x & 1, cl = blockIdx.x >> 1;
  int grp, slt;
  if (cl < 4) { grp = 0; slt = 4 + cl; }
  else if (cl < 36) { grp = (cl - 4) & 7; slt = (cl - 4) >> 3; }
  else { grp = 1 + (cl - 36) % 7; slt = 4 + (cl - 36) / 7; }
  const int m = grp, j = slt;
  const int i = 2 * m + r;
  auto BAR = [&](int k) { return bars + 8 * k; };

  auto kb1 = [&](int n) { const int h = n >= 9, t = n - 2 - 7 * h; return n < 2 ? 2 * j + n : 2 * (t == j ? 7 : t) + h; };
  auto first_round = [&](int u0, int u1) {
#pragma unroll 1
    for (int u = u0; u < u1; u++) {
      mbar_expect(BAR(F1 + u), 40960);
      tma2d(sb + slot1(u), &P.x0, BAR(F1 + u), u * 64, 128 * i);
      tma3d(sb + slot1(u) + 16384, &P.wqkv, BAR(F1 + u), 128 * j, u * 64, 0);
      tma3d(sb + slot1(u) + 28672, &P.wqkv, BAR(F1 + u), 128 * j, u * 64 + 32, 0);
    }
  };
  if (wu == 9) {
    if (elect_one()) asm volatile("prefetch.tensormap [%0];" ::"l"(&P.wqkv) : "memory");
    __syncwarp();
  } else if (wu == 8) {
    if (elect_one()) {
#pragma unroll
      for (int k = 0; k < 4; k++) mbar_init(BAR(F1 + k), 1);
      asm volatile("fence.mbarrier_init.release.cluster;" ::: "memory");
      fence_async_smem();
      first_round(0, FR);
    }
    __syncwarp();
  } else if (wu == 0) {
    if (elect_one()) {
#pragma unroll
      for (int k = E1; k < 64; k++) {
        int cnt = 1;
        if (k < F2 || (k >= E2 && k < F3) || (k >= E3 && k < F4) || (k >= E4 && k < JOB) || k == JOB + 2 || k == JOB + 3) cnt = 4;
        else if ((k >= JOB && k < RD) || k == CSJ) cnt = 8;
        else if (k == RD + 1 || k == STD || k == STAT) cnt = 2;
        mbar_init(BAR(k), cnt);
      }
      asm volatile("fence.mbarrier_init.release.cluster;" ::: "memory");
      fence_async_smem();
    }
    __syncwarp();
  }
  auto load_tag = [&]() { uint32_t t; asm volatile("ld.relaxed.gpu.global.u32 %0, [%1];" : "=r"(t) : "l"(&gEpoch) : "memory"); return t + 1; };
  if (wu == 8) nb_arrive<NB_INIT>(384); else nb_sync<NB_INIT>(384);
  asm volatile("barrier.cluster.arrive.relaxed;" ::: "memory");

  if (wg == 2) {
    reg_dealloc<40>();
    if (wu == 8) {
      if (elect_one()) first_round(FR, 4);
      __syncwarp();
    }
    asm volatile("barrier.cluster.wait;" ::: "memory");
    auto kb3 = [&](int n) { const int h = n >= 17, t = n - 3 - 14 * h; return n < 2 ? 2 * i + n : (n == 2 || n == 31) ? 2 * (i ^ 1) + h : 2 * ((2 * m + 2 + t) & 15) + h; };
    auto v1 = [&](int L, int u) { const int u0 = L ? 2 : 10; return (u >= u0 && u < 18) ? (u < u0 + 2 ? u - u0 + 16 : u - 2) : u; };
    auto kb2 = [&](int n) { return n < 8 ? 2 * n : n == 8 ? 2 * j + 1 : 2 * (n - 9 == j ? 7 : n - 9) + 1; };
    if (wu == 8) {
      const int lane = tid & 31;
      auto pf = [&](const bf16* p, bool on) { if (on) asm volatile("prefetch.global.L2 [%0];" ::"l"(p)); };
      auto k1 = [&](int L, int v) { return (L || v >= 16) ? kb1(v & 15) : v; };
      auto kb4f = [&](int n) {
        const bool own = n == 0 || n == 9 || n == 17;
        const int q = n - 10 - (n > 17), c = own ? n >> 3 : q / 15, t = q - 15 * c;
        const int ii = own ? i : t < 14 ? (2 * m + 2 + t) & 15 : i ^ 1;
        return (n >= 1 && n <= 8) ? 7 * ((m + n) & 7) + 3 : ((7 * ii + 1) >> 1) + c;
      };
      const uint32_t tab4 = kb4f(lane) | (kb4f(lane + 32) << 16);
      auto kb4 = [&](int n) { return (int)((__shfl_sync(0xffffffffu, tab4, n) >> ((n >> 1) & 16)) & 63); };
      const bf16* const q1 = P.wqkv_p + (4 * i + (lane & 3)) * 3072 + (lane >> 2) * 1024 + 128 * j;
      const bf16* const q2 = P.wo_p + (4 * i + (lane & 3)) * 1024 + (lane >> 2) * 64 + 128 * j;
      const bf16* const q3 = P.w1_p + (8 * j + (lane >> 2)) * 3584 + 64 * (7 * m + ((lane & 3) == 3 ? 3 : 4 * r + (lane & 3)));
      auto pf1 = [&](int L, int u) { const int v = v1(L, u); pf(q1 + k1(L, v) * (64 * 3072) + 64 * (v >> 4), lane < 12); };
      auto pf2 = [&](int n) { pf(q2 + kb2(n) * (64 * 1024), lane < 8); };
      auto pf3 = [&](int n) { pf(q3 + kb3(n) * (64 * 3584), true); };
#pragma unroll 1
      for (int u = 4; u < 4 + PD1; u++) pf1(0, u);
#pragma unroll 1
      for (int L = 0; L < 2; L++) {
#pragma unroll 1
        for (int u = L ? 0 : 4; u < 32; u++) {
          const int v = v1(L, u), p = u & 3;
          int c0 = 128 * j + 64 * (v >> 4), c1 = k1(L, v) * 64 + 32 * r; uint32_t dst = sb + slot1(p) + 16384 + r * 12288;
          asm volatile("" : "+r"(c0), "+r"(c1), "+r"(dst));
          if (L && u == 4) mbar_wait(BAR(RD + 5), 0);
          if (u >= 4) mbar_wait(BAR(E1 + p), ((u >> 2) - 1) & 1);
          else mbar_wait(BAR(E4 + (u == 3 ? 0 : u + 3)), u == 3);
          if (elect_one()) {
            mbar_expect(BAR(F1 + p), (v & 15) < 2 ? 24576 : 40960);
            tma3d_mc(dst, &P.wqkv, BAR(F1 + p), c0, c1, 0);
          }
          if (u + PD1 < 32) pf1(L, u + PD1);
          if (u + PD2 >= 32) pf2(u + PD2 - 32);
        }
        int p = 0; uint32_t par = L ? 0x1e : 0;
#pragma unroll 1
        for (int n = 0; n < 16; n++) {
          int c1 = kb2(n) * 64;
          asm volatile("" : "+r"(c1));
          if (n >= 5) { mbar_wait(BAR(E2 + p), (par >> p) & 1); par ^= 1u << p; }
          else if (n < 4) mbar_wait(BAR(E1 + n), 1);
          if (elect_one()) {
            mbar_expect(BAR(F2 + p), n == 8 ? 16384 : 32768);
            tma2d_mc(sb + slot2(p) + 16384 + r * 8192, &P.wo, BAR(F2 + p), 128 * j + 64 * r, c1);
          }
          if (++p == 5) p = 0;
          if (n + PD2 < 16) pf2(n + PD2);
          if (n + PD3 + 4 >= 16) pf3(n + PD3 + 4 - 16);
        }
#pragma unroll 1
        for (int u = 0; u < 32; u++) {
          const int n = u < 4 ? (0x2031 >> (4 * u)) & 3 : u, p = n & 3;
          int kb = kb3(n);
          asm volatile("" : "+r"(kb));
          if (n == 4) {
            mbar_wait(BAR(XF + 1), L ^ 1);
            const uint32_t rs = mapa(sb, r ^ 1);
            if (elect_one()) bulk_s2s(rs + slot3(2), sb + OFF_X, 16384, rs + OFF_BAR + 8 * (F3 + 2));
            mbar_wait(BAR(RD + 4), L);
          }
          if (n >= 4) mbar_wait(BAR(E3 + p), ((n >> 2) - 1) & 1);
          else if (n == 1) mbar_wait(BAR(STD + 1), L);
          else if (n == 3) mbar_wait(BAR(E2 + 2), L);
          else if (n == 0) mbar_wait(BAR(E2 + 4), L);
          else mbar_wait(BAR(E2 + 0), 1);
          if (elect_one()) {
            mbar_expect(BAR(F3 + p), n < 2 ? 32768 : 49152);
            tma3d(sb + slot3(p) + 16384, &P.w1, BAR(F3 + p), 0, kb * 64, 7 * m + 4 * r);
            tma3d(sb + slot3(p) + 40960, &P.w1h, BAR(F3 + p), 0, kb * 64, 14 * m + 6 + r);
          }
          if (u >= 4 && u + PD3 < 32) pf3(u + PD3);
        }
        auto g4w = [&](int n, int p, int kb) {
          if (elect_one()) {
            mbar_expect(BAR(F4 + p), (n == 0 || n == 9 || n == 17) ? 16384 : 32768);
            tma3d(sb + slot4(p), &P.w2, BAR(F4 + p), 0, kb * 64, 2 * i);
          }
        };
#pragma unroll 1
        for (int n = 0; n < 6; n++) {
          const int kb = kb4(n);
          if (n == 1) mbar_wait(BAR(RD + 3), L);
          if (n < 3) mbar_wait(BAR(E3 + n), 1);
          else if (n == 4) mbar_wait(BAR(E3 + 3), 1);
          g4w(n, n, kb);
        }
        p = 0; par = L ? 0x3c : 0;
#pragma unroll 1
        for (int n = 6; n < 56; n++) {
          const int kb = kb4(n);
          mbar_wait(BAR(E4 + p), (par >> p) & 1); par ^= 1u << p;
          g4w(n, p, kb);
          if (++p == 6) p = 0;
        }
        if (L == 0)
#pragma unroll 1
          for (int u = 0; u < PD1; u++) pf1(1, u);
      }
    } else if (wu == 9) {
      uint32_t inv = 0;
#define ADDR(d, s) uint32_t dst = (d); const uint8_t* src = (s); asm volatile("" : "+r"(dst), "+l"(src))
#pragma unroll 1
      for (int L = 0; L < 2; L++) {
        uint32_t ready = 0;
#pragma unroll 1
        for (int u = 4; u < 32; u++) {
          const int p = u & 3, v = v1(L, u), nn = v & 15, kb = (L || v >= 16) ? kb1(nn) : nn;
          if (L == 0 && (u == XLD || u == XLD + XST) && elect_one()) {
            const int h = u != XLD;
            mbar_expect(BAR(XF + h), 16384);
            tma2d(sb + OFF_X + h * 16384, &P.x0, BAR(XF + h), 128 * j + 64 * h, 128 * i);
          }
          if (nn < 2) continue;
          ADDR(sb + slot1(p), gXB + (i * 16 + kb) * 16384);
          if (L && u < 12) mbar_wait(BAR(F1 + p), u >> 3);
          if (u >= 4 + 4 * L) mbar_wait(BAR(E1 + p), ((u >> 2) - 1) & 1);
          if (L) {
            flag_wait(gFlag[0][0][i], inv, 1u << kb, ready);
            if (elect_one()) bulk_ld(dst, src, 16384, BAR(F1 + p));
          } else if (elect_one()) tma2d(sb + slot1(p), &P.x0, BAR(F1 + p), kb * 64, 128 * i);
        }
        ready = 0;
        if (L == 0) inv = (__shfl_sync(0xffffffffu, load_tag(), 0) & 1) - 1;
        int p = 0; uint32_t par = L ? 0x1e : 0;
#pragma unroll 1
        for (int n = 0; n < 16; n++) {
          const int hp = kb2(n);
          if (n == 8) { par ^= 8; p = 4; continue; }
          ADDR(sb + slot2(p), gOB + (i * 16 + hp) * 16384);
          if (n >= 5) { mbar_wait(BAR(E2 + p), (par >> p) & 1); par ^= 1u << p; }
          else if (n < 4) mbar_wait(BAR(E1 + n), 1);
          flag_wait(gFlag[L][1][i], inv, 1u << hp, ready);
          if (elect_one()) bulk_ld(dst, src, 16384, BAR(F2 + p));
          if (++p == 5) p = 0;
        }
        ready = 0;
        mbar_wait(BAR(E2 + 0), 1);
#pragma unroll 1
        for (int n = 3; n < 32; n++) {
          const int p = n & 3, kb = kb3(n);
          const int o = n != 31 ? r * 8192 : 0;
          ADDR(sb + slot3(p) + o, gHB + (j * 32 + kb) * 16384 + o);
          if (n > 3) mbar_wait(BAR(E3 + p), ((n >> 2) - 1) & 1);
          flag_wait(gFlag[L][2][j], inv, 1u << kb, ready);
          if (elect_one()) {
            if (n != 31) bulk_ld_mc(dst, src, 8192, BAR(F3 + p));
            else bulk_ld(dst, src, 16384, BAR(F3 + p));
          }
        }
        ready = 0; p = 1; par = L ? 0x3c : 0;
#pragma unroll 1
        for (int t = 0; t < 8; t++) {
          const int mm = (m + t + 1) & 7;
          ADDR(sb + slot4(p) + 16384 + r * 8192, gUB + (j * 56 + 48 + mm) * 16384 + r * 8192);
          if (t < 3) mbar_wait(BAR(E3 + 1 + t), 1);
          if (t >= 5) { mbar_wait(BAR(E4 + p), (par >> p) & 1); par ^= 1u << p; }
          flag_wait(gFlag[L][6][j], inv, 3u << (2 * mm), ready);
          if (elect_one()) bulk_ld_mc(dst, src, 8192, BAR(F4 + p));
          if (++p == 6) p = 0;
        }
#pragma unroll 1
        for (int c = 0; c < 3; c++) {
          ready = 0;
#pragma unroll 1
          for (int t = 0; t < 15; t++) {
            const int ii = t < 14 ? (2 * m + 2 + t) & 15 : i ^ 1;
            if (c == 0 && (t == 0 || t == 7)) { par ^= 1u << p; if (++p == 6) p = 0; }
            const int o = t < 14 ? r * 8192 : 0;
            ADDR(sb + slot4(p) + 16384 + o, gUB + (j * 56 + 16 * c + ii) * 16384 + o);
            mbar_wait(BAR(E4 + p), (par >> p) & 1); par ^= 1u << p;
            flag_wait(gFlag[L][3 + c][j], inv, 1u << ii, ready);
            if (elect_one()) {
              if (t < 14) bulk_ld_mc(dst, src, 8192, BAR(F4 + p));
              else bulk_ld(dst, src, 16384, BAR(F4 + p));
            }
            if (++p == 6) p = 0;
          }
        }
      }
    } else {
      const int h = wu - 10, i0 = i, j0 = j;
      {
      const uint32_t tag = load_tag();
      int lane = tid & 31, i = i0, j = j0;
#define FRESH asm volatile("" : "+r"(lane), "+r"(i), "+r"(j))
      auto signal = [&](int k) { if (lane == 0) mbar_arrive(BAR(k)); };
      auto publish = [&](uint32_t* f, int bit) { if (lane == 0) flag_set(f, 1u << bit); __syncwarp(); };
#pragma unroll 1
      for (int c = 32 * h + lane; c < 288; c += 64)
        sts16(sb + OFF_B1 + 2 * c, c >= 224 ? 0u : pack2(0.5f * __bfloat162float(P.b1[c < 192 ? 64 * (7 * m + 4 * r) + c : 64 * (7 * m + 3) + 32 * r + c - 192]), 0.f));
      if (h == 0) sts32f(sb + OFF_CS + 768 + 4 * lane, 0.f);
#pragma unroll 1
      for (int L = 0; L < 2; L++) {
        FRESH;
        if (L == 0) {
          mbar_wait(BAR(CSJ), 0);
          float c0 = 0.f, c1 = 0.f, c2 = 0.f;
          const uint32_t a = sb + OFF_STG + (32 * h + lane) * 4;
#pragma unroll 4
          for (int k = 0; k < 32; k++) { c0 += lds32f(a + k * 784); c1 += lds32f(a + k * 784 + 256); c2 += lds32f(a + k * 784 + 512); }
          ll_st3(&gCS[j][i][32 * h + lane], __float_as_uint(c0), __float_as_uint(c1), __float_as_uint(c2), tag);
          __nanosleep(500);
        }
        FRESH;
        if (L == 0) {
#pragma unroll 1
          for (int ab = 0; ab < 2; ab++) {
            float c0 = 0.f, c1 = 0.f, c2 = 0.f;
#pragma unroll 1
            for (int b4 = 0; b4 < 8; b4 += 4) {
              uint32_t a[4], b[4], c[4], n = 0, bad;
              do {
                bad = 0;
#pragma unroll
                for (int e = 0; e < 4; e++) bad |= ll_ld3(&gCS[j][2 * (b4 + e) + ab][32 * h + lane], a[e], b[e], c[e], tag);
              } while (bad && ++n < SPIN_MAX);
#pragma unroll
              for (int e = 0; e < 4; e++) { c0 += __uint_as_float(a[e]); c1 += __uint_as_float(b[e]); c2 += __uint_as_float(c[e]); }
            }
            const uint32_t a = sb + OFF_CS + ab * 768 + (4 * h + (lane >> 3)) * 32 + (lane & 7) * 2;
            const uint32_t h0 = pack2(c0, 0.f), h1 = pack2(c1, 0.f), h2 = pack2(c2, 0.f);
            sts16(a, h0); sts16(a + 256, h1); sts16(a + 512, h2);
            sts16(a + 16, pack2(c0 - bf_lo(h0), 0.f)); sts16(a + 272, pack2(c1 - bf_lo(h1), 0.f)); sts16(a + 528, pack2(c2 - bf_lo(h2), 0.f));
            fence_async_smem();
            __syncwarp();
            if (ab == 0) signal(STAT);
          }
        }
#pragma unroll 1
        for (int ab = 0; ab < 2; ab++) {
          FRESH;
          uint32_t v[18], tg[6];
          const uint32_t xs = sb + OFF_STG + h * 16384 + lane * 8;
          uint4* hp = &gHalo[L][i][j][6 * h][lane];
#pragma unroll
          for (int c = 0; c < 6; c++) { tg[c] = (2 * tag + ab) * 8 + c; asm volatile("" : "+r"(tg[c])); }
          asm volatile("" : "+l"(hp));
          mbar_wait(BAR(FOLD + h), ab);
          if (i < 15) {
            halo_send(hp, xs, tg);
          }
          if (i > 0) {
            if (!ab) __nanosleep(HALO_A_NS);
            uint32_t n = 0, bad;
            do {
              bad = 0;
#pragma unroll
              for (int c = 0; c < 6; c++) bad |= ll_ld3(hp + c * 32 - 8 * 12 * 32, v[3 * c], v[3 * c + 1], v[3 * c + 2], (2 * tag + ab) * 8);
            } while (bad > 7 && ++n < SPIN_MAX);
          } else {
#pragma unroll
            for (int c = 0; c < 18; c++) v[c] = 0u;
          }
#pragma unroll
          for (int c = 0; c < 6; c++) sts64f(xs + c * 256, __uint_as_float(v[3 * c]), __uint_as_float(v[3 * c + 1]));
          sts64f(xs + 1536, __uint_as_float(v[2]), __uint_as_float(v[5]));
          sts64f(xs + 1792, __uint_as_float(v[8]), __uint_as_float(v[11]));
          __syncwarp();
          signal(HALO + h);
          FRESH;
          if (ab == 0 && lane == 0) asm volatile("st.relaxed.gpu.global.u32 [%0], %1;" ::"l"(&gAck[L][i][j][h][0]), "r"(tag) : "memory");
          uint8_t* dst = gOB + (i * 16 + 2 * j + ab) * 16384;
          uint32_t* flag = gFlag[L][1][i];
          asm volatile("" : "+l"(dst), "+l"(flag));
          mbar_wait(BAR(JOB + ab), L);
          if (h == 0) {
            if (lane == 0) { bulk_st(dst, sb + OFF_STG, 16384); bulk_commit(); bulk_wait0(); }
            signal(STD + ab);
            publish(flag, 2 * j + ab);
          } else if (ab == 0) {
            if (i < 15 && lane < 2) {
              uint32_t t, n = 0;
              do { asm volatile("ld.relaxed.gpu.global.u32 %0, [%1];" : "=r"(t) : "l"(&gAck[L][i + 1][j][lane][0]) : "memory"); } while (t != tag && ++n < SPIN_MAX);
            }
            __syncwarp();
            signal(STD);
          }
        }
#pragma unroll 1
        for (int k = 0; k < 4 - L; k++) {
          FRESH;
          const int job = 2 * k + h;
          uint8_t* dst = k == 0 ? gHB + (j * 32 + 2 * i + 1) * 16384 : k == 3 ? gXB + (i * 16 + 2 * j + 1) * 16384 : gUB + (j * 56 + 16 * (job - 3) + i) * 16384;
          uint32_t* flag = k == 3 ? gFlag[0][0][i] : gFlag[L][(0x543622 >> (4 * job)) & 15][j];
          uint32_t bit = 1u << (k == 0 ? 2 * i + h : k == 3 ? 2 * j + h : i);
          asm volatile("" : "+l"(dst), "+l"(flag), "+r"(bit));
          mbar_wait(BAR(JOB + ((0x98654732 >> (4 * job)) & 15)), L);
          if ((0xba >> job) & 1) {
            if (job == 1) mbar_wait(BAR(RD + 4), L);
            if (job == 3) {
              __nanosleep(U0D);
              if (lane == 0) { bulk_st(dst, sb + OFF_X, 16384); bulk_commit(); bulk_wait0(); }
            } else warp_store(dst + lane * 16, sb + lane * 16 + OFF_X + (job == 5 ? 0 : 16384), 16384, job == 1 ? H1D : job == 7 ? X1D : 0, job == 7 ? 0 : PACE);
            if (job != 7) signal(RD + ((0x112000 >> (4 * job)) & 15));
          }
          if (lane == 0) flag_set(flag, bit);
          __syncwarp();
          if (h == 0 && k != 2) { signal(RD + (k == 3 ? 5 : 4 - k)); }
        }
      }
      if (blockIdx.x == 0 && h == 0 && lane == 0) asm volatile("st.relaxed.gpu.global.u32 [%0], %1;" ::"l"(&gEpoch), "r"(tag) : "memory");
      }
    }
    __syncwarp();
    cluster_bar();
  } else {
    reg_alloc<232>();
    asm volatile("barrier.cluster.wait;" ::: "memory");
    const uint32_t rbars = mapa(bars, tid & 1);
    const bool relp = (tid & 127) < 2;
    const uint32_t sd = (sb & 0x3FFFF) >> 4, sda = sd + wg * 512;
    uint32_t tag;
    asm volatile("ld.relaxed.gpu.global.u32 %0, [%1];" : "=r"(tag) : "l"(&gEpoch + (fresh_tid() >> 10)) : "memory");
    auto release = [&](int k) { if (relp) mbar_arrive_cl(rbars + 8 * k); };
    auto signal = [&](int k) { __syncwarp(); if ((fresh_tid() & 31) == 0) mbar_arrive(BAR(k)); };
#define GEOM const int t7 = fresh_tid() & 127, lane = t7 & 31, w = t7 >> 5, g = lane >> 2, q = lane & 3, \
                       lr = lane & 15, lt = lane >> 4, l7 = lane & 7; (void)w; (void)g; (void)q; (void)lr; (void)lt; (void)l7

#pragma unroll 1
    for (int L = 0; L < 2; L++) {
      float acca[96], accb[96], xa[64], acc3[112];
      float nmean0, nmean1, rstd0, rstd1;
      uint16_t b2a, b2b;
      uint2 *e2p, *e2s; uint8_t* e2g; uint32_t e2h;
      uint32_t Q[2][8], K[2][8], V[16];
      auto g1_issue = [&](float (&acc)[96], uint32_t a, uint32_t st, auto first) {
        const uint32_t da = sda + (a >> 4), db = sd + (st >> 4);
        wg_fence();
        static_for<0, 4>([&](auto kk) {
          constexpr uint32_t ia = DI(kk.value * 32, 16), ib = DI(16384 + (kk.value >> 1) * 12288 + (kk.value & 1) * 2048, 4096);
          if constexpr (first.value && kk.value == 0) wgmma_192z<0, 1, ia, ib>(acc, da, db); else wgmma_192<0, 1, ia, ib>(acc, da, db);
        });
        wg_commit();
      };
      auto g1_step = [&](float (&acc)[96], int u, bool rel, bool lead = false) {
        const int p = u & 3;
        mbar_wait(BAR(F1 + p), (u >> 2) & 1);
        g1_issue(acc, slot1(p), slot1(p), False{});
        if (lead) nb_arrive<NB_LEAD>(256);
        wg_wait<1>();
        if (rel) release(E1 + ((u - 1) & 3));
      };
      auto g1_loop = [&](float (&acc)[96], int u0, int u1, int urel) {
        int u = u0;
#pragma unroll 1
        do { g1_step(acc, u, u > urel); } while (++u < u1);
      };
      auto load_x = [&]() {
        GEOM;
#pragma unroll
        for (int t = 0; t < 16; t += 2) {
          uint32_t v0, v1, v2, v3;
          ldsm4(sb + OFF_X + (t >> 3) * 16384 + (16 * wu + lr) * 128 + ((((t & 7) + lt) ^ l7) << 4), v0, v1, v2, v3);
          xa[4 * t + 0] = bf_lo(v0); xa[4 * t + 1] = bf_hi(v0); xa[4 * t + 2] = bf_lo(v1); xa[4 * t + 3] = bf_hi(v1);
          xa[4 * t + 4] = bf_lo(v2); xa[4 * t + 5] = bf_hi(v2); xa[4 * t + 6] = bf_lo(v3); xa[4 * t + 7] = bf_hi(v3);
        }
      };
      auto stat_base = [&]() { return &gST[0][0][0][0][0] + ((L * 16 + opq(i)) * 8 + wu) * 128; };
      auto stat_slot = [&]() { const int lane = fresh_tid() & 31; return stat_base() + 16 * j + 2 * (lane >> 2) + (lane & 1); };
      auto stat_publish = [&](uint2* sp, float s0, float q0, float s2, float q2, uint32_t tg) {
        const int q = fresh_tid() & 3;
        const bool h1 = q & 1;
        float sm = (h1 ? s2 : s0) + __shfl_xor_sync(0xffffffffu, h1 ? s0 : s2, 1);
        float sq = (h1 ? q2 : q0) + __shfl_xor_sync(0xffffffffu, h1 ? q0 : q2, 1);
        sm += __shfl_xor_sync(0xffffffffu, sm, 2); sq += __shfl_xor_sync(0xffffffffu, sq, 2);
        stat_st(sp, sm, sq, tg, q < 2);
        return sm;
      };
      auto g1_stats = [&](int u0) {
        GEOM;
        const uint32_t xr = sb + OFF_X + (16 * wu + lr) * 128;
        float s0 = 0.f, q0 = 0.f, s2 = 0.f, q2 = 0.f;
        uint32_t v[8] = {0u, 0u, 0u, 0u, 0u, 0u, 0u, 0u};
#pragma unroll 1
        for (int k = 0; k < 5; k++) {
#pragma unroll
          for (int e = 0; e < 8; e += 2) {
            const float a = bf_lo(v[e]), b = bf_hi(v[e]), c = bf_lo(v[e + 1]), d = bf_hi(v[e + 1]);
            s0 += a + b; q0 = fmaf(a, a, fmaf(b, b, q0)); s2 += c + d; q2 = fmaf(c, c, fmaf(d, d, q2));
          }
          if (k == 4) break;
          const uint32_t o = ((2 * k + lt) ^ l7) << 4;
          ldsm4(xr + o, v[0], v[1], v[2], v[3]);
          ldsm4(xr + o + 16384, v[4], v[5], v[6], v[7]);
          g1_step(acca, u0 + k, true);
        }
        stat_publish(stat_slot(), s0, q0, s2, q2, 2 * (tag + 1));
      };
      uint32_t sv0[4], sv1[4];
      auto stat_src = [&]() { return stat_base() + 2 * (fresh_tid() & 31); };
      auto stat_fetch = [&](const uint2* sp) { stat_ld2(sp, sv0); stat_ld2(sp + 64, sv1); };
      auto stat_await = [&](auto src, uint32_t tg) {
#pragma unroll 1
        for (uint32_t n = 0; (((sv0[0] ^ tg) | (sv0[2] ^ tg) | (sv1[0] ^ tg) | (sv1[2] ^ tg)) & 15u) && n < SPIN_MAX; n++) stat_fetch(src());
        __syncwarp();
      };
      auto ln_stats = [&]() {
        GEOM;
        stat_await(stat_src, 2 * (tag + 1));
        float mean0, var0, mean1, var1;
        stat_combine(sv0[0], sv0[1], sv1[0], sv1[1], untag(__shfl_sync(0xffffffffu, sv0[0], l7)), mean0, var0);
        stat_combine(sv0[2], sv0[3], sv1[2], sv1[3], untag(__shfl_sync(0xffffffffu, sv0[2], l7)), mean1, var1);
        nmean0 = -__shfl_sync(0xffffffffu, mean0, g); rstd0 = rsq(__shfl_sync(0xffffffffu, var0, g) + 1e-5f);
        nmean1 = -__shfl_sync(0xffffffffu, mean1, g); rstd1 = rsq(__shfl_sync(0xffffffffu, var1, g) + 1e-5f);
      };
      auto center = [&](float (&acc)[96], int ab) {
        const bool q0 = (fresh_tid() & 3) == 0;
        const uint32_t h0 = pack2(nmean0, nmean0), h1 = pack2(nmean1, nmean1);
        const float l0 = nmean0 - bf_lo(h0), l1 = nmean1 - bf_lo(h1);
        const uint32_t a0 = q0 ? h0 : 0u, a1 = q0 ? h1 : 0u, a2 = q0 ? pack2(l0, l0) : 0u, a3 = q0 ? pack2(l1, l1) : 0u;
        wg_fence();
        wgmma_rs_192(acc, a0, a1, a2, a3, mkdesc_vec(sb + OFF_CS + ab * 768, 32));
      };
      auto frag = [&](float (&acc)[96], int t, uint32_t& p0, uint32_t& p1) {
        if (t >= 8) { p0 = pack2(acc[4 * t] * rstd0, acc[4 * t + 1] * rstd0); p1 = pack2(acc[4 * t + 2] * rstd1, acc[4 * t + 3] * rstd1); }
        else { p0 = pack2(acc[4 * t], acc[4 * t + 1]); p1 = pack2(acc[4 * t + 2], acc[4 * t + 3]); }
      };
      auto fold_v = [&](float (&acc)[96]) {
        GEOM;
        const uint32_t a = sb + OFF_STG + 16384 + ((wu + 1) & 7) * 2048 + lr * 128;
#pragma unroll
        for (int t = 0; t < 8; t += 2) {
          uint32_t p0, p1, p2, p3;
          frag(acc, 16 + t, p0, p1); frag(acc, 17 + t, p2, p3);
          stsm4(a + (((t + lt) ^ l7) << 4), p0, p1, p2, p3);
        }
        __syncwarp();
#pragma unroll
        for (int t = 0; t < 8; t += 2) ldsm4t(a + (((t + lt) ^ l7) << 4), V[2 * t], V[2 * t + 1], V[2 * t + 2], V[2 * t + 3]);
        if (wu == 7) signal(FOLD + 1);
      };
      auto fold_k = [&](float (&acc)[96]) {
        GEOM;
        const uint32_t a = sb + OFF_STG + ((wu + 1) & 7) * 2048 + lane * 16;
#pragma unroll
        for (int hh = 0; hh < 2; hh++) {
#pragma unroll
          for (int t = 4 * hh; t < 4 * hh + 4; t++) frag(acc, 8 + t, K[0][t], K[1][t]);
#pragma unroll
          for (int o = 0; o < 2; o++) sts128(a + (2 * o + hh) * 512, K[o][4 * hh], K[o][4 * hh + 1], K[o][4 * hh + 2], K[o][4 * hh + 3]);
        }
        if (wu == 7) signal(FOLD);
      };
      auto fold_q = [&](float (&acc)[96]) {
#pragma unroll
        for (int t = 0; t < 8; t++) frag(acc, t, Q[0][t], Q[1][t]);
      };
      auto attend = [&](int ab, auto drain, auto resume) {
        GEOM;
        nb_sync<NB_BOTH>(256);
        const uint32_t xa_ = sb + OFF_STG + wu * 2048 + lane * 16;
        if (wu == 0) mbar_wait(BAR(HALO), ab);
        uint32_t KH[2][8], VH[16];
#pragma unroll
        for (int c = 0; c < 4; c++)
          lds128(xa_ + c * 512, KH[c >> 1][4 * (c & 1)], KH[c >> 1][4 * (c & 1) + 1], KH[c >> 1][4 * (c & 1) + 2], KH[c >> 1][4 * (c & 1) + 3]);
        auto load_vh = [&]() {
          if (wu == 0) mbar_wait(BAR(HALO + 1), ab);
#pragma unroll
          for (int c = 0; c < 4; c++)
            ldsm4t(sb + OFF_STG + 16384 + wu * 2048 + lr * 128 + (((2 * c + lt) ^ l7) << 4), VH[4 * c], VH[4 * c + 1], VH[4 * c + 2], VH[4 * c + 3]);
        };
        if (!ab) load_vh();
        const bool e = g & 1, zneg = (g >> 1) < q, first = (i == 0) && (wu == 0);
        const float sc0 = rstd0 * (0.17677669530f * 1.4426950409f), sc1 = rstd1 * (0.17677669530f * 1.4426950409f);
        float mk0 = first ? __fdividef(-1.0e9f * 1.4426950409f, sc0) : 0.f, mk1 = first ? __fdividef(-1.0e9f * 1.4426950409f, sc1) : 0.f;
        const uint32_t sa = e ? 0x1044u : 0x4410u, sbb = e ? 0x3244u : 0x4432u;
        uint32_t sel[3] = {zneg ? sbb : 0x4444u, sa, zneg ? 0x4444u : sbb};
        uint32_t oa = sb + OFF_STG + (16 * wu + lr) * 128 + ((lt ^ l7) << 4);
        asm volatile("" : "+r"(sel[0]), "+r"(sel[1]), "+r"(sel[2]), "+r"(oa), "+f"(mk0), "+f"(mk1));
        drain();
        uint32_t pr[2][6];
        float l[2][2], sl[2][4][4];
#pragma unroll
        for (int hh = 0; hh < 2; hh++)
          attn_logits(&Q[0][4 * hh], &Q[1][4 * hh], &KH[0][4 * hh], &KH[1][4 * hh], &K[0][4 * hh], &K[1][4 * hh], mk0, mk1, sl[hh]);
        if (ab) load_vh();
#pragma unroll
        for (int hh = 0; hh < 2; hh++) attn_probs(sl[hh], sc0, sc1, e, zneg, sel, pr[hh], l[hh]);
        float o[2][4][4];
#pragma unroll
        for (int hh = 0; hh < 2; hh++) attn_pv(pr[hh], &VH[8 * hh], &V[8 * hh], o[hh]);
#pragma unroll
        for (int hh = 0; hh < 2; hh++) {
          float l0 = l[hh][0], l1 = l[hh][1];
          l0 += __shfl_xor_sync(0xffffffffu, l0, 1); l1 += __shfl_xor_sync(0xffffffffu, l1, 1);
          l0 += __shfl_xor_sync(0xffffffffu, l0, 2); l1 += __shfl_xor_sync(0xffffffffu, l1, 2);
          asm("rcp.approx.ftz.f32 %0, %0;" : "+f"(l0)); asm("rcp.approx.ftz.f32 %0, %0;" : "+f"(l1));
#pragma unroll
          for (int dt = 0; dt < 4; dt += 2)
            stsm4(oa ^ ((4 * hh + dt) << 4),
                  pack2(o[hh][dt][0] * l0, o[hh][dt][1] * l0), pack2(o[hh][dt][2] * l1, o[hh][dt][3] * l1),
                  pack2(o[hh][dt + 1][0] * l0, o[hh][dt + 1][1] * l0), pack2(o[hh][dt + 1][2] * l1, o[hh][dt + 1][3] * l1));
        }
        fence_async_smem();
        signal(JOB + ab);
        nb_sync<NB_BOTH>(256);
        resume();
      };

      mbar_wait(BAR(F1), 0);    g1_issue(acca, L ? OFF_X : slot1(0), slot1(0), True{});
      mbar_wait(BAR(F1 + 1), 0); g1_issue(acca, L ? OFF_X + 16384 : slot1(1), slot1(1), False{});
      wg_wait<1>(); release(E1 + 0);
      if (L == 0) {
        GEOM;
        const bf16* wp = P.wqkv_p + ((128 * opq(m) + 16 * wg + (t7 >> 3)) * 3072 + 128 * opq(j) + 64 * r + l7 * 8);
        const uint32_t ca = sb + OFF_STG + (16 * wg + (t7 >> 3)) * 784 + l7 * 32;
#pragma unroll 1
        for (int p = 0; p < 3; p++) {
          uint4 wv[4];
#pragma unroll
          for (int k = 0; k < 4; k++)
            asm volatile("ld.global.nc.v4.u32 {%0, %1, %2, %3}, [%4];" : "=r"(wv[k].x), "=r"(wv[k].y), "=r"(wv[k].z), "=r"(wv[k].w)
                         : "l"(wp + k * 32 * 3072 + p * 1024));
          g1_loop(acca, 2 + 3 * p, p < 2 ? 5 + 3 * p : 10, 0);
          float cs[8];
#pragma unroll
          for (int k = 0; k < 4; k++) {
            const uint4 v = wv[k];
            const float t[8] = {bf_lo(v.x), bf_hi(v.x), bf_lo(v.y), bf_hi(v.y), bf_lo(v.z), bf_hi(v.z), bf_lo(v.w), bf_hi(v.w)};
#pragma unroll
            for (int e = 0; e < 8; e++) cs[e] = k ? cs[e] + t[e] : t[e];
          }
          sts128(ca + p * 256, __float_as_uint(cs[0]), __float_as_uint(cs[1]), __float_as_uint(cs[2]), __float_as_uint(cs[3]));
          sts128(ca + p * 256 + 16, __float_as_uint(cs[4]), __float_as_uint(cs[5]), __float_as_uint(cs[6]), __float_as_uint(cs[7]));
        }
        signal(CSJ);
        mbar_wait(BAR(XF), 0); mbar_wait(BAR(XF + 1), 0);
      }
      {
        const int u0 = L ? 2 : 10;
        mbar_wait(BAR(F1 + 2), 0); g1_issue(accb, OFF_X, slot1(2), True{});
        wg_wait<1>(); release(E1 + 1);
        mbar_wait(BAR(F1 + 3), 0); g1_issue(accb, OFF_X + 16384, slot1(3), False{});
        wg_wait<1>(); release(E1 + 2);
        g1_stats(u0 + 2);
        g1_loop(acca, u0 + 6, 18, 0);
      }
      stat_fetch(stat_src());
      const int fa = FA + (wg ? 0 : FO);
      g1_loop(accb, 18, fa, 0);
      ln_stats();
      if (L == 0) mbar_wait(BAR(STAT), 0);
      center(acca, 0); wg_commit();
      wg_wait<0>(); release(E1 + ((fa - 1) & 3));
      fence_regs(acca);
      fold_k(acca); fold_v(acca); fold_q(acca);
      sched_fence(P.zero);
      g1_loop(accb, fa, ATT, fa);
      attend(0, [&]() { wg_wait<0>(); release(E1 + ((ATT - 1) & 3)); mbar_wait(BAR(F1 + (ATT & 3)), (ATT >> 2) & 1); },
             [&]() { g1_issue(accb, slot1(ATT & 3), slot1(ATT & 3), False{});
                     mbar_wait(BAR(F1 + ((ATT + 1) & 3)), ((ATT + 1) >> 2) & 1);
 g1_issue(accb, slot1((ATT + 1) & 3), slot1((ATT + 1) & 3), False{}); });
      wg_wait<1>(); release(E1 + (ATT & 3));
      load_x();
      fence_regs(xa);
      center(accb, 1);
#pragma unroll 1
      for (int u = ATT + 2; u < 32; u++) {
        const bool hold = u == 32 - LEAD1 && wg == 0;
        if (hold) { wg_wait<0>(); release(E1 + ((31 - LEAD1) & 3)); nb_sync<NB_LEAD>(256); }
        g1_step(accb, u, !hold, u == 31 && wg == 1);
      }
      mbar_wait(BAR(STD), L);
      wg_wait<0>(); release(E1 + 3);
      fence_regs(accb);
      fold_k(accb);
      sched_fence(P.zero);
      fold_v(accb);
      fold_q(accb);
      {
        auto g2_issue = [&](int p, bool own) {
          const uint32_t st = slot2(p);
          const uint32_t da = sda + ((own ? OFF_STG : st) >> 4), db = sd + (st >> 4);
          wg_fence();
          static_for<0, 4>([&](auto kk) { wgmma_128<0, 1, DI(kk.value * 32, 16), DI(16384 + kk.value * 2048, 8192)>(xa, da, db); });
          wg_commit();
        };
        uint32_t par = L ? 0x1e : 0;
        int p = 0, pp = 0;
        auto g2_loop = [&](int n0, int n1, int nrel) {
#pragma unroll 1
          for (int n = n0; n < n1; n++) {
            mbar_wait(BAR(F2 + p), (par >> p) & 1);
            par ^= 1u << p;
            g2_issue(p, n == 8);
            if (n1 == 16 && n == 15 && wg == 0) nb_arrive<NB_LEAD>(256);
            wg_wait<1>();
            if (n > nrel) release(E2 + pp);
            pp = p; if (++p == 5) p = 0;
          }
        };
        g2_loop(0, COVER, 0);
        attend(1, [&]() { wg_wait<0>(); release(E2 + COVER - 1); mbar_wait(BAR(F2 + COVER), (par >> COVER) & 1); },
               [&]() { g2_issue(COVER, false);
                       mbar_wait(BAR(F2 + COVER + 1), (par >> (COVER + 1)) & 1);
 g2_issue(COVER + 1, false); });
        wg_wait<1>(); release(E2 + COVER);
        par ^= 3u << COVER; pp = COVER + 1; p = (COVER + 2) % 5;
        {
          const bf16* bp = P.b2 + (128 * opq(i) + 16 * wu + ((fresh_tid() & 31) >> 2));
          asm volatile("ld.global.nc.u16 %0, [%1];" : "=h"(b2a) : "l"(bp));
          asm volatile("ld.global.nc.u16 %0, [%1];" : "=h"(b2b) : "l"(bp + 8));
        }
        {
          GEOM;
          e2p = stat_slot(); e2s = stat_src();
          e2g = gHB + (opq(j) * 32 + 2 * i) * 16384 + w * 2048 + lane * 16;
          e2h = sb + OFF_X + wg * 16384 + (16 * w + lr) * 128 + ((lt ^ l7) << 4);
          asm volatile("" : "+l"(e2p), "+l"(e2s), "+l"(e2g), "+r"(e2h));
        }
        g2_loop(COVER + 2, 16 - LEAD2, 0);
        if (wg == 1) { wg_wait<0>(); release(E2 + pp); nb_sync<NB_LEAD>(256); }
        g2_loop(16 - LEAD2, 16, wg == 1 ? 16 - LEAD2 : 0);
        wg_wait<0>();
        release(E2 + 0);
        fence_regs(xa);
      }
      {
        GEOM;
        const uint32_t tg = 2 * (tag + 1) + 1;
        float s0 = 0.f, s1 = 0.f, s2 = 0.f, s3 = 0.f, q0 = 0.f, q1 = 0.f, q2 = 0.f, q3 = 0.f;
#pragma unroll
        for (int t = 0; t < 16; t++) {
          s0 += xa[4 * t]; s1 += xa[4 * t + 1]; s2 += xa[4 * t + 2]; s3 += xa[4 * t + 3];
          q0 = fmaf(xa[4 * t], xa[4 * t], q0); q1 = fmaf(xa[4 * t + 1], xa[4 * t + 1], q1);
          q2 = fmaf(xa[4 * t + 2], xa[4 * t + 2], q2); q3 = fmaf(xa[4 * t + 3], xa[4 * t + 3], q3);
        }
        const float sm = stat_publish(e2p, s0 + s1, q0 + q1, s2 + s3, q2 + q3, tg);
        const uint32_t t0 = clock32();
        const float pv0 = __shfl_sync(0xffffffffu, sm, 4 * l7) * (1.f / 128), pv1 = __shfl_sync(0xffffffffu, sm, 4 * l7 + 1) * (1.f / 128);
        while (clock32() - t0 < STAT_CLK) {}
        stat_fetch(e2s);
        wg_fence();
        wgmma_rs_224z(acc3, q == 0 ? 0x3f80u : 0u, q == 0 ? 0x3f80u : 0u, 0u, 0u, mkdesc_vec(sb + OFF_B1, 16));
        wg_commit();
        stat_await([&]() { return e2s; }, tg);
        float r0, m0, r1, m1;
        {
          float mean0, var0, mean1, var1;
          stat_combine(sv0[0], sv0[1], sv1[0], sv1[1], pv0, mean0, var0); stat_combine(sv0[2], sv0[3], sv1[2], sv1[3], pv1, mean1, var1);
          mean0 = __shfl_sync(0xffffffffu, mean0, g); var0 = __shfl_sync(0xffffffffu, var0, g);
          mean1 = __shfl_sync(0xffffffffu, mean1, g); var1 = __shfl_sync(0xffffffffu, var1, g);
          r0 = 0.5f * rsq(fmaf(var0 + 1e-5f, 1e-5f, var0)); r1 = 0.5f * rsq(fmaf(var1 + 1e-5f, 1e-5f, var1));
          m0 = -mean0 * r0; m1 = -mean1 * r1;
        }
#pragma unroll
        for (int t = 0; t < 16; t += 2) {
          stsm4((e2h ^ ((t & 7) << 4)) + (t >> 3) * 8192,
                pack2(fmaf(xa[4 * t], r0, m0), fmaf(xa[4 * t + 1], r0, m0)), pack2(fmaf(xa[4 * t + 2], r1, m1), fmaf(xa[4 * t + 3], r1, m1)),
                pack2(fmaf(xa[4 * t + 4], r0, m0), fmaf(xa[4 * t + 5], r0, m0)), pack2(fmaf(xa[4 * t + 6], r1, m1), fmaf(xa[4 * t + 7], r1, m1)));
          if ((t & 7) == 6 && wg == 0) {
            __syncwarp();
            copy_out<4>(e2g + (t >> 3) * 8192, sb + OFF_X + (t >> 3) * 8192 + w * 2048 + lane * 16, 512);
          }
        }
        signal(JOB + 2 + wg);
        fence_async_smem();
        mbar_wait(BAR(F3 + 0), 0);
        if (wg == 0) { nb_sync<NB_WG0>(128); if (t7 == 0) mbar_arrive(BAR(XF + 1)); }
        else nb_sync<NB_BOTH>(256);
      }
      auto g3_issue = [&](uint32_t a, int p) {
        const uint32_t da = sda + (a >> 4), db = sd + (slot3(p) >> 4);
        wg_fence();
        static_for<0, 4>([&](auto kk) { wgmma_224<1, 1, DI(kk.value * 2048, 8192), DI(16384 + kk.value * 2048, 8192)>(acc3, da, db); });
        wg_commit();
      };
 g3_issue(OFF_X, 0);
      if (wg == 0) nb_sync<NB_BOTH>(256);
      mbar_wait(BAR(F3 + 1), 0); g3_issue(OFF_X + 16384, 1);
      sched_fence(P.zero);
      {
        const float c0 = __uint_as_float((uint32_t)b2a << 16), c1 = __uint_as_float((uint32_t)b2b << 16);
#pragma unroll
        for (int t = 0; t < 16; t++) { xa[4 * t] += c0; xa[4 * t + 1] += c0; xa[4 * t + 2] += c1; xa[4 * t + 3] += c1; }
        fence_regs(xa);
      }
      wg_wait<1>(); release(E3 + 0);
      auto g3_loop = [&](int n0, int n1, int nrel) {
#pragma unroll 1
        for (int n = n0; n < n1; n++) {
          const int p = n & 3;
          mbar_wait(BAR(F3 + p), (n >> 2) & 1);
          g3_issue(slot3(p), p);
          wg_wait<1>();
          if (n > nrel) release(E3 + ((n - 1) & 3));
        }
      };
      g3_loop(2, 29, 0);
      uint32_t ua;
      uint8_t* ug;
      {
        GEOM;
        ua = sb + OFF_X + wg * 8192 + (8 * lt + l7) * 128 + (((2 * w + ((lane >> 3) & 1)) ^ l7) << 4);
        ug = gUB + (opq(j) * 56 + 48 + m) * 16384 + r * 4096 + wg * 8192 + (lane >> 1) * 128 + (((2 * w + (lane & 1)) ^ ((lane >> 1) & 7)) << 4);
      }
      auto gelu8 = [&](int c, int k) {
        const int o = 32 * c + 8 * k;
        stsm4t(ua + (c & 1) * 16384 + k * 2048,
               pack2(gelu_half(acc3[o]), gelu_half(acc3[o + 1])), pack2(gelu_half(acc3[o + 2]), gelu_half(acc3[o + 3])),
               pack2(gelu_half(acc3[o + 4]), gelu_half(acc3[o + 5])), pack2(gelu_half(acc3[o + 6]), gelu_half(acc3[o + 7])));
      };
      {
        auto part = [&](auto p, auto half) {
          static_for<0, 4>([&](auto kk) {
            constexpr uint32_t o = slot3(p.value) + kk.value * 2048;
            if constexpr (half.value) wgmma_32<1, 1, DI(o, 8192), DI(o + 40960, 8192), 96>(acc3, sda, sd);
            else wgmma_192<1, 1, DI(o, 8192), DI(o + 16384, 8192), 0>(acc3, sda, sd);
          });
        };
        mbar_wait(BAR(RD), L);
        mbar_wait(BAR(F3 + 1), 1); mbar_wait(BAR(F3 + 2), 1);
        wg_wait<0>(); release(E3 + 0);
#pragma unroll
        for (int k = 0; k < 112; k++) { float t; asm volatile("mov.b32 %0, %1;" : "=f"(t) : "f"(acc3[k]) : "memory"); acc3[k] = t; }
        sched_fence(P.zero);
        wg_fence(); part(Int<1>{}, True{}); part(Int<2>{}, True{});
        mbar_wait(BAR(F3 + 3), 1); wg_fence(); part(Int<3>{}, True{}); wg_commit();
        part(Int<1>{}, False{}); wg_commit();
        wg_wait<1>();
#pragma unroll
        for (int k = 96; k < 112; k++) asm volatile("" : "+f"(acc3[k])::"memory");
        gelu8(3, 0); gelu8(3, 1);
        __syncwarp();
        copy_out<2>(ug, sb + OFF_X + 16384 + (uint32_t)((ug - gUB) & 0x2fff), 2048);
        signal(JOB + 7);
        sched_fence(P.zero);
        wg_fence(); part(Int<2>{}, False{}); wg_commit();
        wg_wait<1>(); release(E3 + 1);
        part(Int<3>{}, False{}); wg_commit();
        wg_wait<1>(); release(E3 + 2);
        wg_wait<0>(); release(E3 + 3);
      }
      fence_regs(acc3);
      auto g4_issue = [&](int p, uint32_t b) {
        const uint32_t da = sda + (slot4(p) >> 4), db = sd + (b >> 4);
        wg_fence();
        static_for<0, 4>([&](auto kk) { wgmma_128<1, 1, DI(kk.value * 2048, 8192), DI(kk.value * 2048, 8192)>(xa, da, db); });
        wg_commit();
      };
#pragma unroll
      for (int k = 0; k < 4; k++) gelu8(0, k);
      fence_async_smem();
      signal(JOB + 4);
      nb_sync<NB_BOTH>(256);
      static_for<0, 18>([&](auto nn) {
        constexpr int n = nn.value, p = n % 6;
        if (n == 9 || n == 17) mbar_wait(BAR(JOB + 4 + (n >> 3)), L);
        mbar_wait(BAR(F4 + p), (n / 6 + (p >= 2 ? L : 0)) & 1);
        wg_fence();
        static_for<0, 4>([&](auto kk) {
          wgmma_128<1, 1, DI(slot4(p) + kk.value * 2048, 8192), DI((n == 9 ? OFF_X + 16384 : n % 17 ? slot4(p) + 16384 : OFF_X) + kk.value * 2048, 8192)>(xa, sda, sd);
        });
        wg_commit();
        if (n) { wg_wait<1>(); release(E4 + (n + 5) % 6); }
        if (n == 8) mbar_wait(BAR(RD + 2), L);
        else if (n < 16 && !(n & 1)) sched_fence(P.zero);
        if constexpr (n < 16 && !(n & 1)) gelu8(1 + (n >> 3), (n >> 1) & 3);
        if ((n & 7) == 7) { fence_async_smem(); signal(JOB + 5 + (n >> 3)); }
      });
      {
        int p = 0, pp = 5;
        uint32_t par = L ? 0x03 : 0x3f;
        auto g4_loop = [&](int n0, int n1, int nrel) {
#pragma unroll 1
          for (int n = n0; n < n1; n++) {
            mbar_wait(BAR(F4 + p), (par >> p) & 1);
            par ^= 1u << p;
            g4_issue(p, slot4(p) + 16384);
            if (n1 == 56 && n == 55 && wg == 0) nb_arrive<NB_LEAD>(256);
            wg_wait<1>();
            if (n > nrel) release(E4 + pp);
            pp = p; if (++p == 6) p = 0;
          }
        };
        g4_loop(18, 56 - LEAD4, 0);
        if (wg == 1) { wg_wait<0>(); release(E4 + pp); nb_sync<NB_LEAD>(256); }
        g4_loop(56 - LEAD4, 56, wg == 1 ? 56 - LEAD4 : 0);
      }
      uint32_t xs;
      uint8_t* xg;
      {
        GEOM;
        xs = sb + OFF_X + wu * 2048 + (lane >> 3) * 128 + ((L ? l7 ^ (lane >> 3) : l7) << 4);
        xg = L ? P.out + (128 * opq(i) + 16 * wu + (lane >> 3)) * 2048 + 256 * j + 16 * l7 : gXB + (opq(i) * 16 + 2 * j) * 16384 + wu * 2048 + lane * 16;
        asm volatile("" : "+r"(xs), "+l"(xg));
      }
      mbar_wait(BAR(RD + 1), L);
      wg_wait<0>();
      release(E4 + 1);
      fence_regs(xa);
      {
        GEOM;
#pragma unroll
        for (int t = 0; t < 16; t += 2) {
          stsm4(sb + OFF_X + (t >> 3) * 16384 + (16 * wu + lr) * 128 + ((((t & 7) + lt) ^ l7) << 4),
                pack2(xa[4 * t], xa[4 * t + 1]), pack2(xa[4 * t + 2], xa[4 * t + 3]),
                pack2(xa[4 * t + 4], xa[4 * t + 5]), pack2(xa[4 * t + 6], xa[4 * t + 7]));
          if ((t & 7) == 6 && (L || t == 6)) {
            __syncwarp();
            uint4 v[4];
#pragma unroll
            for (int k = 0; k < 4; k++) lds128((xs ^ (L ? (k & 1) << 6 : 0)) + k * 512 + (t >> 3) * 16384, v[k].x, v[k].y, v[k].z, v[k].w);
#pragma unroll
            for (int k = 0; k < 4; k++)
              asm volatile("st.global.v4.b32 [%0], {%1, %2, %3, %4};" ::"l"(xg + k * (L ? 8192 : 512) + (t >> 3) * 128), "r"(v[k].x), "r"(v[k].y), "r"(v[k].z), "r"(v[k].w) : "memory");
            if (L == 0) signal(JOB + 8);
          }
        }
        if (L) break;
        fence_async_smem();
        signal(JOB + 9);
        nb_sync<NB_BOTH>(256);
      }
    }
    cluster_bar();
  }
}

typedef CUresult (*EncodeFn)(CUtensorMap*, CUtensorMapDataType, cuuint32_t, void*, const cuuint64_t*, const cuuint64_t*, const cuuint32_t*,
                             const cuuint32_t*, CUtensorMapInterleave, CUtensorMapSwizzle, CUtensorMapL2promotion, CUtensorMapFloatOOBfill);

void make_map(EncodeFn enc, CUtensorMap* mp, const void* base, int rank, cuuint64_t d0, cuuint64_t d1, cuuint64_t d2, cuuint64_t s1, cuuint64_t s2,
              cuuint32_t b0, cuuint32_t b1, cuuint32_t b2) {
  cuuint64_t dims[3] = {d0, d1, d2}, strides[2] = {s1, s2};
  cuuint32_t box[3] = {b0, b1, b2}, es[3] = {1, 1, 1};
  CUresult res = enc(mp, CU_TENSOR_MAP_DATA_TYPE_BFLOAT16, rank, const_cast<void*>(base), dims, strides, box, es, CU_TENSOR_MAP_INTERLEAVE_NONE,
                     CU_TENSOR_MAP_SWIZZLE_128B, CU_TENSOR_MAP_L2_PROMOTION_L2_128B, CU_TENSOR_MAP_FLOAT_OOB_FILL_NONE);
  (void)res;
}

}

extern "C" void kernel_launch(void* const* d_in, const int* in_sizes, int n_in, void* d_out, int out_size) {
  (void)in_sizes; (void)n_in; (void)out_size;
  static EncodeFn enc = nullptr;
  if (!enc) {
    void* fn = nullptr;
    cudaDriverEntryPointQueryResult qr;
    cudaGetDriverEntryPoint("cuTensorMapEncodeTiled", &fn, cudaEnableDefault, &qr);
    enc = (EncodeFn)fn;
    cudaFuncSetAttribute(fused_kernel, cudaFuncAttributeMaxDynamicSharedMemorySize, SMEM_BYTES);
  }
  Params P;
  make_map(enc, &P.x0, d_in[0], 2, D_, S_, 1, D_ * 2, 0, 64, 128, 1);
  make_map(enc, &P.wqkv, d_in[1], 3, D_, D_, 3, 3 * D_ * 2, D_ * 2, 64, 32, 3);
  make_map(enc, &P.wo, d_in[2], 2, D_, D_, 1, D_ * 2, 0, 64, 64, 1);
  make_map(enc, &P.w1, d_in[4], 3, 64, S_, F_ / 64, F_ * 2, 128, 64, 64, 3);
  make_map(enc, &P.w1h, d_in[4], 3, 32, S_, F_ / 32, F_ * 2, 64, 64, 64, 1);
  make_map(enc, &P.w2, d_in[6], 3, 64, F_, S_ / 64, S_ * 2, 128, 64, 64, 2);
  P.out = (uint8_t*)d_out;
  P.wqkv_p = (const bf16*)d_in[1];
  P.wo_p = (const bf16*)d_in[2];
  P.w1_p = (const bf16*)d_in[4];
  P.b1 = (const bf16*)d_in[5];
  P.b2 = (const bf16*)d_in[7];
  P.zero = 0;
  fused_kernel<<<128, 384, SMEM_BYTES>>>(P);
}
```

```cpp
#include <cuda_runtime.h>
#include <cuda_bf16.h>
#include <cuda.h>
#include <stdint.h>

namespace {

typedef __nv_bfloat16 bf16;
constexpr int S_ = 2048, D_ = 1024, F_ = 3584;

constexpr uint32_t OFF_STG  = 163840;
constexpr uint32_t OFF_X    = 196608;
constexpr uint32_t OFF_BAR  = 229376;
constexpr uint32_t OFF_CS   = OFF_BAR + 512;
constexpr uint32_t OFF_B1   = OFF_CS + 1536;
constexpr uint32_t SMEM_BYTES = OFF_B1 + 896 + 128;
constexpr int F1 = 0, E1 = 4, F2 = 8, E2 = 13, F3 = 18, E3 = 22, F4 = 26, E4 = 32;
constexpr int JOB = 38;
constexpr int RD = 48;
constexpr int XF = 54, STD = 56, STAT = 58, FOLD = 59, CSJ = 61, HALO = 62;
constexpr int NB_BOTH = 1, NB_INIT = 2, NB_LEAD = 3, NB_WG0 = 4;

__host__ __device__ constexpr uint32_t slot1(int p) { return p * 40960; }
__host__ __device__ constexpr uint32_t slot2(int p) { return p * 32768; }
__host__ __device__ constexpr uint32_t slot3(int p) { return ((p + 2) & 3) * 49152; }
__host__ __device__ constexpr uint32_t slot4(int p) { return (p < 2 ? p + 4 : p - 2) * 32768; }

__device__ __align__(1024) uint8_t gXB[16 * 16 * 16384];
__device__ __align__(1024) uint8_t gOB[16 * 16 * 16384];
__device__ __align__(1024) uint8_t gHB[8 * 32 * 16384];
__device__ __align__(1024) uint8_t gUB[8 * 56 * 16384];
__device__ __align__(1024) uint2   gST[2][16][8][8][16];
__device__ __align__(1024) uint4   gHalo[2][16][8][12][32];
__device__ __align__(1024) uint32_t gAck[2][16][8][2][8];
__device__ __align__(1024) uint4   gCS[8][16][64];
__device__ __align__(1024) uint32_t gFlag[2][7][16][32];
__device__ uint32_t gEpoch;

struct Params {
  CUtensorMap x0, wqkv, wo, w1, w1h, w2;
  uint8_t* out;
  const bf16 *wqkv_p, *wo_p, *w1_p, *b1, *b2;
  uint32_t zero;
};

template <int TA, int TB, uint32_t IA, uint32_t IB, int O = 0, int LEN> __device__ __forceinline__ void wgmma_32(float (&d)[LEN], uint32_t da, uint32_t db) {
  asm volatile("{\n.reg .b64 da, db;\n.reg .b32 la, lb;\nadd.u32 la, %16, %20;\nadd.u32 lb, %17, %21;\nmov.b64 da, {la, 0x40000040};\nmov.b64 db, {lb, 0x40000040};\n"
  "wgmma.mma_async.sync.aligned.m64n32k16.f32.bf16.bf16 {"
  "%0, %1, %2, %3, %4, %5, %6, %7, %8, %9, %10, %11, %12, %13, %14, %15"
  "}, da, db, 1, 1, 1, %18, %19;\n}\n"
  : "+f"(d[O + 0]), "+f"(d[O + 1]), "+f"(d[O + 2]), "+f"(d[O + 3]), "+f"(d[O + 4]), "+f"(d[O + 5]), "+f"(d[O + 6]), "+f"(d[O + 7]),
    "+f"(d[O + 8]), "+f"(d[O + 9]), "+f"(d[O + 10]), "+f"(d[O + 11]), "+f"(d[O + 12]), "+f"(d[O + 13]), "+f"(d[O + 14]), "+f"(d[O + 15])
  : "r"(da), "r"(db), "n"(TA), "n"(TB), "n"(IA), "n"(IB));
}
template <int TA, int TB, uint32_t IA, uint32_t IB, int O = 0, int LEN> __device__ __forceinline__ void wgmma_128(float (&d)[LEN], uint32_t da, uint32_t db) {
  asm volatile("{\n.reg .b64 da, db;\n.reg .b32 la, lb;\nadd.u32 la, %64, %68;\nadd.u32 lb, %65, %69;\nmov.b64 da, {la, 0x40000040};\nmov.b64 db, {lb, 0x40000040};\n"
  "wgmma.mma_async.sync.aligned.m64n128k16.f32.bf16.bf16 {"
  "%0, %1, %2, %3, %4, %5, %6, %7, %8, %9, %10, %11, %12, %13, %14, %15, "
  "%16, %17, %18, %19, %20, %21, %22, %23, %24, %25, %26, %27, %28, %29, %30, %31, "
  "%32, %33, %34, %35, %36, %37, %38, %39, %40, %41, %42, %43, %44, %45, %46, %47, "
  "%48, %49, %50, %51, %52, %53, %54, %55, %56, %57, %58, %59, %60, %61, %62, %63"
  "}, da, db, 1, 1, 1, %66, %67;\n}\n"
  : "+f"(d[O + 0]), "+f"(d[O + 1]), "+f"(d[O + 2]), "+f"(d[O + 3]), "+f"(d[O + 4]), "+f"(d[O + 5]), "+f"(d[O + 6]), "+f"(d[O + 7]),
    "+f"(d[O + 8]), "+f"(d[O + 9]), "+f"(d[O + 10]), "+f"(d[O + 11]), "+f"(d[O + 12]), "+f"(d[O + 13]), "+f"(d[O + 14]), "+f"(d[O + 15]),
    "+f"(d[O + 16]), "+f"(d[O + 17]), "+f"(d[O + 18]), "+f"(d[O + 19]), "+f"(d[O + 20]), "+f"(d[O + 21]), "+f"(d[O + 22]), "+f"(d[O + 23]),
    "+f"(d[O + 24]), "+f"(d[O + 25]), "+f"(d[O + 26]), "+f"(d[O + 27]), "+f"(d[O + 28]), "+f"(d[O + 29]), "+f"(d[O + 30]), "+f"(d[O + 31]),
    "+f"(d[O + 32]), "+f"(d[O + 33]), "+f"(d[O + 34]), "+f"(d[O + 35]), "+f"(d[O + 36]), "+f"(d[O + 37]), "+f"(d[O + 38]), "+f"(d[O + 39]),
    "+f"(d[O + 40]), "+f"(d[O + 41]), "+f"(d[O + 42]), "+f"(d[O + 43]), "+f"(d[O + 44]), "+f"(d[O + 45]), "+f"(d[O + 46]), "+f"(d[O + 47]),
    "+f"(d[O + 48]), "+f"(d[O + 49]), "+f"(d[O + 50]), "+f"(d[O + 51]), "+f"(d[O + 52]), "+f"(d[O + 53]), "+f"(d[O + 54]), "+f"(d[O + 55]),
    "+f"(d[O + 56]), "+f"(d[O + 57]), "+f"(d[O + 58]), "+f"(d[O + 59]), "+f"(d[O + 60]), "+f"(d[O + 61]), "+f"(d[O + 62]), "+f"(d[O + 63])
  : "r"(da), "r"(db), "n"(TA), "n"(TB), "n"(IA), "n"(IB));
}
template <int TA, int TB, uint32_t IA, uint32_t IB, int O = 0, int LEN> __device__ __forceinline__ void wgmma_192(float (&d)[LEN], uint32_t da, uint32_t db) {
  asm volatile("{\n.reg .b64 da, db;\n.reg .b32 la, lb;\nadd.u32 la, %96, %100;\nadd.u32 lb, %97, %101;\nmov.b64 da, {la, 0x40000040};\nmov.b64 db, {lb, 0x40000040};\n"
  "wgmma.mma_async.sync.aligned.m64n192k16.f32.bf16.bf16 {"
  "%0, %1, %2, %3, %4, %5, %6, %7, %8, %9, %10, %11, %12, %13, %14, %15, "
  "%16, %17, %18, %19, %20, %21, %22, %23, %24, %25, %26, %27, %28, %29, %30, %31, "
  "%32, %33, %34, %35, %36, %37, %38, %39, %40, %41, %42, %43, %44, %45, %46, %47, "
  "%48, %49, %50, %51, %52, %53, %54, %55, %56, %57, %58, %59, %60, %61, %62, %63, "
  "%64, %65, %66, %67, %68, %69, %70, %71, %72, %73, %74, %75, %76, %77, %78, %79, "
  "%80, %81, %82, %83, %84, %85, %86, %87, %88, %89, %90, %91, %92, %93, %94, %95"
  "}, da, db, 1, 1, 1, %98, %99;\n}\n"
  : "+f"(d[O + 0]), "+f"(d[O + 1]), "+f"(d[O + 2]), "+f"(d[O + 3]), "+f"(d[O + 4]), "+f"(d[O + 5]), "+f"(d[O + 6]), "+f"(d[O + 7]),
    "+f"(d[O + 8]), "+f"(d[O + 9]), "+f"(d[O + 10]), "+f"(d[O + 11]), "+f"(d[O + 12]), "+f"(d[O + 13]), "+f"(d[O + 14]), "+f"(d[O + 15]),
    "+f"(d[O + 16]), "+f"(d[O + 17]), "+f"(d[O + 18]), "+f"(d[O + 19]), "+f"(d[O + 20]), "+f"(d[O + 21]), "+f"(d[O + 22]), "+f"(d[O + 23]),
    "+f"(d[O + 24]), "+f"(d[O + 25]), "+f"(d[O + 26]), "+f"(d[O + 27]), "+f"(d[O + 28]), "+f"(d[O + 29]), "+f"(d[O + 30]), "+f"(d[O + 31]),
    "+f"(d[O + 32]), "+f"(d[O + 33]), "+f"(d[O + 34]), "+f"(d[O + 35]), "+f"(d[O + 36]), "+f"(d[O + 37]), "+f"(d[O + 38]), "+f"(d[O + 39]),
    "+f"(d[O + 40]), "+f"(d[O + 41]), "+f"(d[O + 42]), "+f"(d[O + 43]), "+f"(d[O + 44]), "+f"(d[O + 45]), "+f"(d[O + 46]), "+f"(d[O + 47]),
    "+f"(d[O + 48]), "+f"(d[O + 49]), "+f"(d[O + 50]), "+f"(d[O + 51]), "+f"(d[O + 52]), "+f"(d[O + 53]), "+f"(d[O + 54]), "+f"(d[O + 55]),
    "+f"(d[O + 56]), "+f"(d[O + 57]), "+f"(d[O + 58]), "+f"(d[O + 59]), "+f"(d[O + 60]), "+f"(d[O + 61]), "+f"(d[O + 62]), "+f"(d[O + 63]),
    "+f"(d[O + 64]), "+f"(d[O + 65]), "+f"(d[O + 66]), "+f"(d[O + 67]), "+f"(d[O + 68]), "+f"(d[O + 69]), "+f"(d[O + 70]), "+f"(d[O + 71]),
    "+f"(d[O + 72]), "+f"(d[O + 73]), "+f"(d[O + 74]), "+f"(d[O + 75]), "+f"(d[O + 76]), "+f"(d[O + 77]), "+f"(d[O + 78]), "+f"(d[O + 79]),
    "+f"(d[O + 80]), "+f"(d[O + 81]), "+f"(d[O + 82]), "+f"(d[O + 83]), "+f"(d[O + 84]), "+f"(d[O + 85]), "+f"(d[O + 86]), "+f"(d[O + 87]),
    "+f"(d[O + 88]), "+f"(d[O + 89]), "+f"(d[O + 90]), "+f"(d[O + 91]), "+f"(d[O + 92]), "+f"(d[O + 93]), "+f"(d[O + 94]), "+f"(d[O + 95])
  : "r"(da), "r"(db), "n"(TA), "n"(TB), "n"(IA), "n"(IB));
}
template <int TA, int TB, uint32_t IA, uint32_t IB, int O = 0, int LEN> __device__ __forceinline__ void wgmma_192z(float (&d)[LEN], uint32_t da, uint32_t db) {
  asm volatile("{\n.reg .b64 da, db;\n.reg .b32 la, lb;\nadd.u32 la, %96, %100;\nadd.u32 lb, %97, %101;\nmov.b64 da, {la, 0x40000040};\nmov.b64 db, {lb, 0x40000040};\n"
  "wgmma.mma_async.sync.aligned.m64n192k16.f32.bf16.bf16 {"
  "%0, %1, %2, %3, %4, %5, %6, %7, %8, %9, %10, %11, %12, %13, %14, %15, "
  "%16, %17, %18, %19, %20, %21, %22, %23, %24, %25, %26, %27, %28, %29, %30, %31, "
  "%32, %33, %34, %35, %36, %37, %38, %39, %40, %41, %42, %43, %44, %45, %46, %47, "
  "%48, %49, %50, %51, %52, %53, %54, %55, %56, %57, %58, %59, %60, %61, %62, %63, "
  "%64, %65, %66, %67, %68, %69, %70, %71, %72, %73, %74, %75, %76, %77, %78, %79, "
  "%80, %81, %82, %83, %84, %85, %86, %87, %88, %89, %90, %91, %92, %93, %94, %95"
  "}, da, db, 0, 1, 1, %98, %99;\n}\n"
  : "=f"(d[O + 0]), "=f"(d[O + 1]), "=f"(d[O + 2]), "=f"(d[O + 3]), "=f"(d[O + 4]), "=f"(d[O + 5]), "=f"(d[O + 6]), "=f"(d[O + 7]),
    "=f"(d[O + 8]), "=f"(d[O + 9]), "=f"(d[O + 10]), "=f"(d[O + 11]), "=f"(d[O + 12]), "=f"(d[O + 13]), "=f"(d[O + 14]), "=f"(d[O + 15]),
    "=f"(d[O + 16]), "=f"(d[O + 17]), "=f"(d[O + 18]), "=f"(d[O + 19]), "=f"(d[O + 20]), "=f"(d[O + 21]), "=f"(d[O + 22]), "=f"(d[O + 23]),
    "=f"(d[O + 24]), "=f"(d[O + 25]), "=f"(d[O + 26]), "=f"(d[O + 27]), "=f"(d[O + 28]), "=f"(d[O + 29]), "=f"(d[O + 30]), "=f"(d[O + 31]),
    "=f"(d[O + 32]), "=f"(d[O + 33]), "=f"(d[O + 34]), "=f"(d[O + 35]), "=f"(d[O + 36]), "=f"(d[O + 37]), "=f"(d[O + 38]), "=f"(d[O + 39]),
    "=f"(d[O + 40]), "=f"(d[O + 41]), "=f"(d[O + 42]), "=f"(d[O + 43]), "=f"(d[O + 44]), "=f"(d[O + 45]), "=f"(d[O + 46]), "=f"(d[O + 47]),
    "=f"(d[O + 48]), "=f"(d[O + 49]), "=f"(d[O + 50]), "=f"(d[O + 51]), "=f"(d[O + 52]), "=f"(d[O + 53]), "=f"(d[O + 54]), "=f"(d[O + 55]),
    "=f"(d[O + 56]), "=f"(d[O + 57]), "=f"(d[O + 58]), "=f"(d[O + 59]), "=f"(d[O + 60]), "=f"(d[O + 61]), "=f"(d[O + 62]), "=f"(d[O + 63]),
    "=f"(d[O + 64]), "=f"(d[O + 65]), "=f"(d[O + 66]), "=f"(d[O + 67]), "=f"(d[O + 68]), "=f"(d[O + 69]), "=f"(d[O + 70]), "=f"(d[O + 71]),
    "=f"(d[O + 72]), "=f"(d[O + 73]), "=f"(d[O + 74]), "=f"(d[O + 75]), "=f"(d[O + 76]), "=f"(d[O + 77]), "=f"(d[O + 78]), "=f"(d[O + 79]),
    "=f"(d[O + 80]), "=f"(d[O + 81]), "=f"(d[O + 82]), "=f"(d[O + 83]), "=f"(d[O + 84]), "=f"(d[O + 85]), "=f"(d[O + 86]), "=f"(d[O + 87]),
    "=f"(d[O + 88]), "=f"(d[O + 89]), "=f"(d[O + 90]), "=f"(d[O + 91]), "=f"(d[O + 92]), "=f"(d[O + 93]), "=f"(d[O + 94]), "=f"(d[O + 95])
  : "r"(da), "r"(db), "n"(TA), "n"(TB), "n"(IA), "n"(IB));
}
template <int TA, int TB, uint32_t IA, uint32_t IB, int O = 0, int LEN> __device__ __forceinline__ void wgmma_224(float (&d)[LEN], uint32_t da, uint32_t db) {
  asm volatile("{\n.reg .b64 da, db;\n.reg .b32 la, lb;\nadd.u32 la, %112, %116;\nadd.u32 lb, %113, %117;\nmov.b64 da, {la, 0x40000040};\nmov.b64 db, {lb, 0x40000040};\n"
  "wgmma.mma_async.sync.aligned.m64n224k16.f32.bf16.bf16 {"
  "%0, %1, %2, %3, %4, %5, %6, %7, %8, %9, %10, %11, %12, %13, %14, %15, "
  "%16, %17, %18, %19, %20, %21, %22, %23, %24, %25, %26, %27, %28, %29, %30, %31, "
  "%32, %33, %34, %35, %36, %37, %38, %39, %40, %41, %42, %43, %44, %45, %46, %47, "
  "%48, %49, %50, %51, %52, %53, %54, %55, %56, %57, %58, %59, %60, %61, %62, %63, "
  "%64, %65, %66, %67, %68, %69, %70, %71, %72, %73, %74, %75, %76, %77, %78, %79, "
  "%80, %81, %82, %83, %84, %85, %86, %87, %88, %89, %90, %91, %92, %93, %94, %95, "
  "%96, %97, %98, %99, %100, %101, %102, %103, %104, %105, %106, %107, %108, %109, %110, %111"
  "}, da, db, 1, 1, 1, %114, %115;\n}\n"
  : "+f"(d[O + 0]), "+f"(d[O + 1]), "+f"(d[O + 2]), "+f"(d[O + 3]), "+f"(d[O + 4]), "+f"(d[O + 5]), "+f"(d[O + 6]), "+f"(d[O + 7]),
    "+f"(d[O + 8]), "+f"(d[O + 9]), "+f"(d[O + 10]), "+f"(d[O + 11]), "+f"(d[O + 12]), "+f"(d[O + 13]), "+f"(d[O + 14]), "+f"(d[O + 15]),
    "+f"(d[O + 16]), "+f"(d[O + 17]), "+f"(d[O + 18]), "+f"(d[O + 19]), "+f"(d[O + 20]), "+f"(d[O + 21]), "+f"(d[O + 22]), "+f"(d[O + 23]),
    "+f"(d[O + 24]), "+f"(d[O + 25]), "+f"(d[O + 26]), "+f"(d[O + 27]), "+f"(d[O + 28]), "+f"(d[O + 29]), "+f"(d[O + 30]), "+f"(d[O + 31]),
    "+f"(d[O + 32]), "+f"(d[O + 33]), "+f"(d[O + 34]), "+f"(d[O + 35]), "+f"(d[O + 36]), "+f"(d[O + 37]), "+f"(d[O + 38]), "+f"(d[O + 39]),
    "+f"(d[O + 40]), "+f"(d[O + 41]), "+f"(d[O + 42]), "+f"(d[O + 43]), "+f"(d[O + 44]), "+f"(d[O + 45]), "+f"(d[O + 46]), "+f"(d[O + 47]),
    "+f"(d[O + 48]), "+f"(d[O + 49]), "+f"(d[O + 50]), "+f"(d[O + 51]), "+f"(d[O + 52]), "+f"(d[O + 53]), "+f"(d[O + 54]), "+f"(d[O + 55]),
    "+f"(d[O + 56]), "+f"(d[O + 57]), "+f"(d[O + 58]), "+f"(d[O + 59]), "+f"(d[O + 60]), "+f"(d[O + 61]), "+f"(d[O + 62]), "+f"(d[O + 63]),
    "+f"(d[O + 64]), "+f"(d[O + 65]), "+f"(d[O + 66]), "+f"(d[O + 67]), "+f"(d[O + 68]), "+f"(d[O + 69]), "+f"(d[O + 70]), "+f"(d[O + 71]),
    "+f"(d[O + 72]), "+f"(d[O + 73]), "+f"(d[O + 74]), "+f"(d[O + 75]), "+f"(d[O + 76]), "+f"(d[O + 77]), "+f"(d[O + 78]), "+f"(d[O + 79]),
    "+f"(d[O + 80]), "+f"(d[O + 81]), "+f"(d[O + 82]), "+f"(d[O + 83]), "+f"(d[O + 84]), "+f"(d[O + 85]), "+f"(d[O + 86]), "+f"(d[O + 87]),
    "+f"(d[O + 88]), "+f"(d[O + 89]), "+f"(d[O + 90]), "+f"(d[O + 91]), "+f"(d[O + 92]), "+f"(d[O + 93]), "+f"(d[O + 94]), "+f"(d[O + 95]),
    "+f"(d[O + 96]), "+f"(d[O + 97]), "+f"(d[O + 98]), "+f"(d[O + 99]), "+f"(d[O + 100]), "+f"(d[O + 101]), "+f"(d[O + 102]), "+f"(d[O + 103]),
    "+f"(d[O + 104]), "+f"(d[O + 105]), "+f"(d[O + 106]), "+f"(d[O + 107]), "+f"(d[O + 108]), "+f"(d[O + 109]), "+f"(d[O + 110]), "+f"(d[O + 111])
  : "r"(da), "r"(db), "n"(TA), "n"(TB), "n"(IA), "n"(IB));
}
__device__ __forceinline__ void wgmma_rs_192(float (&d)[96], uint32_t a0, uint32_t a1, uint32_t a2, uint32_t a3, uint64_t db) {
  asm volatile("wgmma.mma_async.sync.aligned.m64n192k16.f32.bf16.bf16 {"
  "%0, %1, %2, %3, %4, %5, %6, %7, %8, %9, %10, %11, %12, %13, %14, %15, "
  "%16, %17, %18, %19, %20, %21, %22, %23, %24, %25, %26, %27, %28, %29, %30, %31, "
  "%32, %33, %34, %35, %36, %37, %38, %39, %40, %41, %42, %43, %44, %45, %46, %47, "
  "%48, %49, %50, %51, %52, %53, %54, %55, %56, %57, %58, %59, %60, %61, %62, %63, "
  "%64, %65, %66, %67, %68, %69, %70, %71, %72, %73, %74, %75, %76, %77, %78, %79, "
  "%80, %81, %82, %83, %84, %85, %86, %87, %88, %89, %90, %91, %92, %93, %94, %95"
  "}, {%96, %97, %98, %99}, %100, 1, 1, 1, 1;\n"
  : "+f"(d[0]), "+f"(d[1]), "+f"(d[2]), "+f"(d[3]), "+f"(d[4]), "+f"(d[5]), "+f"(d[6]), "+f"(d[7]),
    "+f"(d[8]), "+f"(d[9]), "+f"(d[10]), "+f"(d[11]), "+f"(d[12]), "+f"(d[13]), "+f"(d[14]), "+f"(d[15]),
    "+f"(d[16]), "+f"(d[17]), "+f"(d[18]), "+f"(d[19]), "+f"(d[20]), "+f"(d[21]), "+f"(d[22]), "+f"(d[23]),
    "+f"(d[24]), "+f"(d[25]), "+f"(d[26]), "+f"(d[27]), "+f"(d[28]), "+f"(d[29]), "+f"(d[30]), "+f"(d[31]),
    "+f"(d[32]), "+f"(d[33]), "+f"(d[34]), "+f"(d[35]), "+f"(d[36]), "+f"(d[37]), "+f"(d[38]), "+f"(d[39]),
    "+f"(d[40]), "+f"(d[41]), "+f"(d[42]), "+f"(d[43]), "+f"(d[44]), "+f"(d[45]), "+f"(d[46]), "+f"(d[47]),
    "+f"(d[48]), "+f"(d[49]), "+f"(d[50]), "+f"(d[51]), "+f"(d[52]), "+f"(d[53]), "+f"(d[54]), "+f"(d[55]),
    "+f"(d[56]), "+f"(d[57]), "+f"(d[58]), "+f"(d[59]), "+f"(d[60]), "+f"(d[61]), "+f"(d[62]), "+f"(d[63]),
    "+f"(d[64]), "+f"(d[65]), "+f"(d[66]), "+f"(d[67]), "+f"(d[68]), "+f"(d[69]), "+f"(d[70]), "+f"(d[71]),
    "+f"(d[72]), "+f"(d[73]), "+f"(d[74]), "+f"(d[75]), "+f"(d[76]), "+f"(d[77]), "+f"(d[78]), "+f"(d[79]),
    "+f"(d[80]), "+f"(d[81]), "+f"(d[82]), "+f"(d[83]), "+f"(d[84]), "+f"(d[85]), "+f"(d[86]), "+f"(d[87]),
    "+f"(d[88]), "+f"(d[89]), "+f"(d[90]), "+f"(d[91]), "+f"(d[92]), "+f"(d[93]), "+f"(d[94]), "+f"(d[95])
  : "r"(a0), "r"(a1), "r"(a2), "r"(a3), "l"(db));
}
__device__ __forceinline__ void wgmma_rs_224z(float (&d)[112], uint32_t a0, uint32_t a1, uint32_t a2, uint32_t a3, uint64_t db) {
  asm volatile("wgmma.mma_async.sync.aligned.m64n224k16.f32.bf16.bf16 {"
  "%0, %1, %2, %3, %4, %5, %6, %7, %8, %9, %10, %11, %12, %13, %14, %15, "
  "%16, %17, %18, %19, %20, %21, %22, %23, %24, %25, %26, %27, %28, %29, %30, %31, "
  "%32, %33, %34, %35, %36, %37, %38, %39, %40, %41, %42, %43, %44, %45, %46, %47, "
  "%48, %49, %50, %51, %52, %53, %54, %55, %56, %57, %58, %59, %60, %61, %62, %63, "
  "%64, %65, %66, %67, %68, %69, %70, %71, %72, %73, %74, %75, %76, %77, %78, %79, "
  "%80, %81, %82, %83, %84, %85, %86, %87, %88, %89, %90, %91, %92, %93, %94, %95, "
  "%96, %97, %98, %99, %100, %101, %102, %103, %104, %105, %106, %107, %108, %109, %110, %111"
  "}, {%112, %113, %114, %115}, %116, 0, 1, 1, 1;\n"
  : "=f"(d[0]), "=f"(d[1]), "=f"(d[2]), "=f"(d[3]), "=f"(d[4]), "=f"(d[5]), "=f"(d[6]), "=f"(d[7]),
    "=f"(d[8]), "=f"(d[9]), "=f"(d[10]), "=f"(d[11]), "=f"(d[12]), "=f"(d[13]), "=f"(d[14]), "=f"(d[15]),
    "=f"(d[16]), "=f"(d[17]), "=f"(d[18]), "=f"(d[19]), "=f"(d[20]), "=f"(d[21]), "=f"(d[22]), "=f"(d[23]),
    "=f"(d[24]), "=f"(d[25]), "=f"(d[26]), "=f"(d[27]), "=f"(d[28]), "=f"(d[29]), "=f"(d[30]), "=f"(d[31]),
    "=f"(d[32]), "=f"(d[33]), "=f"(d[34]), "=f"(d[35]), "=f"(d[36]), "=f"(d[37]), "=f"(d[38]), "=f"(d[39]),
    "=f"(d[40]), "=f"(d[41]), "=f"(d[42]), "=f"(d[43]), "=f"(d[44]), "=f"(d[45]), "=f"(d[46]), "=f"(d[47]),
    "=f"(d[48]), "=f"(d[49]), "=f"(d[50]), "=f"(d[51]), "=f"(d[52]), "=f"(d[53]), "=f"(d[54]), "=f"(d[55]),
    "=f"(d[56]), "=f"(d[57]), "=f"(d[58]), "=f"(d[59]), "=f"(d[60]), "=f"(d[61]), "=f"(d[62]), "=f"(d[63]),
    "=f"(d[64]), "=f"(d[65]), "=f"(d[66]), "=f"(d[67]), "=f"(d[68]), "=f"(d[69]), "=f"(d[70]), "=f"(d[71]),
    "=f"(d[72]), "=f"(d[73]), "=f"(d[74]), "=f"(d[75]), "=f"(d[76]), "=f"(d[77]), "=f"(d[78]), "=f"(d[79]),
    "=f"(d[80]), "=f"(d[81]), "=f"(d[82]), "=f"(d[83]), "=f"(d[84]), "=f"(d[85]), "=f"(d[86]), "=f"(d[87]),
    "=f"(d[88]), "=f"(d[89]), "=f"(d[90]), "=f"(d[91]), "=f"(d[92]), "=f"(d[93]), "=f"(d[94]), "=f"(d[95]),
    "=f"(d[96]), "=f"(d[97]), "=f"(d[98]), "=f"(d[99]), "=f"(d[100]), "=f"(d[101]), "=f"(d[102]), "=f"(d[103]),
    "=f"(d[104]), "=f"(d[105]), "=f"(d[106]), "=f"(d[107]), "=f"(d[108]), "=f"(d[109]), "=f"(d[110]), "=f"(d[111])
  : "r"(a0), "r"(a1), "r"(a2), "r"(a3), "l"(db));
}

__device__ __forceinline__ uint32_t smem_u32(const void* p) { return (uint32_t)__cvta_generic_to_shared(p); }
__device__ __forceinline__ void mbar_init(uint32_t bar, uint32_t cnt) { asm volatile("mbarrier.init.shared::cta.b64 [%0], %1;" ::"r"(bar), "r"(cnt) : "memory"); }
__device__ __forceinline__ void mbar_expect(uint32_t bar, uint32_t bytes) { asm volatile("mbarrier.arrive.expect_tx.shared::cta.b64 _, [%0], %1;" ::"r"(bar), "r"(bytes) : "memory"); }
__device__ __forceinline__ void mbar_arrive(uint32_t bar) { asm volatile("mbarrier.arrive.shared::cta.b64 _, [%0];" ::"r"(bar) : "memory"); }
__device__ __forceinline__ void mbar_arrive_cl(uint32_t cbar) { asm volatile("mbarrier.arrive.shared::cluster.b64 _, [%0];" ::"r"(cbar) : "memory"); }
__device__ __forceinline__ uint32_t mapa(uint32_t a, uint32_t cta) { uint32_t r; asm("mapa.shared::cluster.u32 %0, %1, %2;" : "=r"(r) : "r"(a), "r"(cta)); return r; }
__device__ __forceinline__ void mbar_wait(uint32_t bar, uint32_t parity) {
  asm volatile("{\n.reg .pred p;\n.reg .u32 n;\nmov.u32 n, 0;\n"
    "LAB_WAIT:\n"
    "mbarrier.try_wait.parity.shared::cta.b64 p, [%0], %1;\n"
    "@p bra LAB_DONE;\n"
    "add.u32 n, n, 1;\n"
    "setp.lt.u32 p, n, 2000000;\n"
    "@p bra LAB_WAIT;\n"
    "trap;\n"
    "LAB_DONE:\n}\n" ::"r"(bar), "r"(parity) : "memory");
}
constexpr uint32_t SPIN_MAX = 2000000;
__device__ __forceinline__ void tma2d(uint32_t dst, const CUtensorMap* m, uint32_t bar, int c0, int c1) {
  asm volatile("cp.async.bulk.tensor.2d.shared::cluster.global.mbarrier::complete_tx::bytes [%0], [%1, {%3, %4}], [%2];"
    ::"r"(dst), "l"(m), "r"(bar), "r"(c0), "r"(c1) : "memory");
}
__device__ __forceinline__ void tma2d_mc(uint32_t dst, const CUtensorMap* m, uint32_t bar, int c0, int c1) {
  asm volatile("cp.async.bulk.tensor.2d.shared::cluster.global.mbarrier::complete_tx::bytes.multicast::cluster [%0], [%1, {%3, %4}], [%2], %5;"
    ::"r"(dst), "l"(m), "r"(bar), "r"(c0), "r"(c1), "h"((uint16_t)3) : "memory");
}
__device__ __forceinline__ void tma3d(uint32_t dst, const CUtensorMap* m, uint32_t bar, int c0, int c1, int c2) {
  asm volatile("cp.async.bulk.tensor.3d.shared::cluster.global.mbarrier::complete_tx::bytes [%0], [%1, {%3, %4, %5}], [%2];"
    ::"r"(dst), "l"(m), "r"(bar), "r"(c0), "r"(c1), "r"(c2) : "memory");
}
__device__ __forceinline__ void tma3d_mc(uint32_t dst, const CUtensorMap* m, uint32_t bar, int c0, int c1, int c2) {
  asm volatile("cp.async.bulk.tensor.3d.shared::cluster.global.mbarrier::complete_tx::bytes.multicast::cluster [%0], [%1, {%3, %4, %5}], [%2], %6;"
    ::"r"(dst), "l"(m), "r"(bar), "r"(c0), "r"(c1), "r"(c2), "h"((uint16_t)3) : "memory");
}
__device__ __forceinline__ void bulk_ld(uint32_t dst, const void* src, uint32_t bytes, uint32_t bar) {
  asm volatile("cp.async.bulk.shared::cluster.global.mbarrier::complete_tx::bytes [%0], [%1], %2, [%3];" ::"r"(dst), "l"(src), "r"(bytes), "r"(bar) : "memory");
}
__device__ __forceinline__ void bulk_ld_mc(uint32_t dst, const void* src, uint32_t bytes, uint32_t bar) {
  asm volatile("cp.async.bulk.shared::cluster.global.mbarrier::complete_tx::bytes.multicast::cluster [%0], [%1], %2, [%3], %4;"
    ::"r"(dst), "l"(src), "r"(bytes), "r"(bar), "h"((uint16_t)3) : "memory");
}
__device__ __forceinline__ void bulk_st(void* dst, uint32_t src, uint32_t bytes) {
  asm volatile("cp.async.bulk.global.shared::cta.bulk_group [%0], [%1], %2;" ::"l"(dst), "r"(src), "r"(bytes) : "memory");
}
__device__ __forceinline__ void bulk_s2s(uint32_t cdst, uint32_t src, uint32_t bytes, uint32_t cbar) {
  asm volatile("cp.async.bulk.shared::cluster.shared::cta.mbarrier::complete_tx::bytes [%0], [%1], %2, [%3];" ::"r"(cdst), "r"(src), "r"(bytes), "r"(cbar) : "memory");
}
__device__ __forceinline__ void bulk_commit() { asm volatile("cp.async.bulk.commit_group;" ::: "memory"); }
__device__ __forceinline__ void bulk_wait0() { asm volatile("cp.async.bulk.wait_group 0;" ::: "memory"); }
__device__ __forceinline__ void fence_async_smem() { asm volatile("fence.proxy.async.shared::cta;" ::: "memory"); }
__device__ __forceinline__ void wg_fence() { asm volatile("wgmma.fence.sync.aligned;" ::: "memory"); }
__device__ __forceinline__ void wg_commit() { asm volatile("wgmma.commit_group.sync.aligned;" ::: "memory"); }
template <int N> __device__ __forceinline__ void wg_wait() { asm volatile("wgmma.wait_group.sync.aligned %0;" ::"n"(N) : "memory"); }
template <int R> __device__ __forceinline__ void reg_alloc() { asm volatile("setmaxnreg.inc.sync.aligned.u32 %0;" ::"n"(R)); }
template <int R> __device__ __forceinline__ void reg_dealloc() { asm volatile("setmaxnreg.dec.sync.aligned.u32 %0;" ::"n"(R)); }
__device__ __forceinline__ void cluster_bar() { asm volatile("barrier.cluster.arrive.relaxed;\nbarrier.cluster.wait;" ::: "memory"); }
template <int ID> __device__ __forceinline__ void nb_sync(int n) { asm volatile("barrier.sync %0, %1;" ::"n"(ID), "r"(n) : "memory"); }
template <int ID> __device__ __forceinline__ void nb_arrive(int n) { asm volatile("barrier.arrive %0, %1;" ::"n"(ID), "r"(n) : "memory"); }
__device__ __forceinline__ int fresh_tid() { int t; asm volatile("mov.u32 %0, %%tid.x;" : "=r"(t)); return t; }
__device__ __forceinline__ void sched_fence(uint32_t z) { asm volatile("{\n.reg .pred p;\nsetp.ne.u32 p, %0, 0;\nLAB_S:\n@p nanosleep.u32 0;\n@p bra LAB_S;\n}\n" ::"r"(z) : "memory"); }
__device__ __forceinline__ float rsq(float x) { float y; asm("rsqrt.approx.ftz.f32 %0, %1;" : "=f"(y) : "f"(x)); return y; }
__device__ __forceinline__ int opq(int v) { asm volatile("" : "+r"(v)); return v; }
template <int V> struct Int { static constexpr int value = V; };
struct True { static constexpr bool value = true; };
struct False { static constexpr bool value = false; };
template <int N> __device__ __forceinline__ void fence_regs(float (&d)[N]) {
#pragma unroll
  for (int i = 0; i < N; i++) asm volatile("" : "+f"(d[i])::"memory");
}
__host__ __device__ constexpr uint32_t DI(uint32_t off, uint32_t lbo) { return (off >> 4) + ((lbo >> 4) << 16); }
template <int K, int N, class F> __device__ __forceinline__ void static_for(F f) { if constexpr (K < N) { f(Int<K>{}); static_for<K + 1, N>(f); } }
__device__ __forceinline__ uint64_t mkdesc_vec(uint32_t addr, uint32_t sbo) { return (uint64_t)((addr & 0x3FFFF) >> 4) | ((uint64_t)(sbo >> 4) << 32); }
__device__ __forceinline__ void sts16(uint32_t a, uint32_t v) { asm volatile("st.shared.u16 [%0], %1;" ::"r"(a), "h"((uint16_t)v) : "memory"); }
__device__ __forceinline__ uint32_t pack2(float lo, float hi) { uint32_t r; asm("cvt.rn.bf16x2.f32 %0, %1, %2;" : "=r"(r) : "f"(hi), "f"(lo)); return r; }
__device__ __forceinline__ float bf_lo(uint32_t v) { return __uint_as_float(v << 16); }
__device__ __forceinline__ float bf_hi(uint32_t v) { return __uint_as_float(v & 0xffff0000u); }
__device__ __forceinline__ void stsm4(uint32_t a, uint32_t r0, uint32_t r1, uint32_t r2, uint32_t r3) {
  asm volatile("stmatrix.sync.aligned.m8n8.x4.shared.b16 [%0], {%1, %2, %3, %4};" ::"r"(a), "r"(r0), "r"(r1), "r"(r2), "r"(r3) : "memory");
}
__device__ __forceinline__ void stsm4t(uint32_t a, uint32_t r0, uint32_t r1, uint32_t r2, uint32_t r3) {
  asm volatile("stmatrix.sync.aligned.m8n8.x4.trans.shared.b16 [%0], {%1, %2, %3, %4};" ::"r"(a), "r"(r0), "r"(r1), "r"(r2), "r"(r3) : "memory");
}
__device__ __forceinline__ void ldsm4(uint32_t a, uint32_t& r0, uint32_t& r1, uint32_t& r2, uint32_t& r3) {
  asm volatile("ldmatrix.sync.aligned.m8n8.x4.shared.b16 {%0, %1, %2, %3}, [%4];" : "=r"(r0), "=r"(r1), "=r"(r2), "=r"(r3) : "r"(a) : "memory");
}
__device__ __forceinline__ void ldsm4t(uint32_t a, uint32_t& r0, uint32_t& r1, uint32_t& r2, uint32_t& r3) {
  asm volatile("ldmatrix.sync.aligned.m8n8.x4.trans.shared.b16 {%0, %1, %2, %3}, [%4];" : "=r"(r0), "=r"(r1), "=r"(r2), "=r"(r3) : "r"(a) : "memory");
}
__device__ __forceinline__ void mma16816(float (&c)[4], uint32_t a0, uint32_t a1, uint32_t a2, uint32_t a3, uint32_t b0, uint32_t b1) {
  asm volatile("mma.sync.aligned.m16n8k16.row.col.f32.bf16.bf16.f32 {%0, %1, %2, %3}, {%4, %5, %6, %7}, {%8, %9}, {%10, %11, %12, %13};"
    : "=f"(c[0]), "=f"(c[1]), "=f"(c[2]), "=f"(c[3]) : "r"(a0), "r"(a1), "r"(a2), "r"(a3), "r"(b0), "r"(b1), "f"(c[0]), "f"(c[1]), "f"(c[2]), "f"(c[3]));
}
__device__ __forceinline__ void sts128(uint32_t a, uint32_t r0, uint32_t r1, uint32_t r2, uint32_t r3) {
  asm volatile("st.shared.v4.b32 [%0], {%1, %2, %3, %4};" ::"r"(a), "r"(r0), "r"(r1), "r"(r2), "r"(r3) : "memory");
}
__device__ __forceinline__ void lds128(uint32_t a, uint32_t& r0, uint32_t& r1, uint32_t& r2, uint32_t& r3) {
  asm volatile("ld.shared.v4.b32 {%0, %1, %2, %3}, [%4];" : "=r"(r0), "=r"(r1), "=r"(r2), "=r"(r3) : "r"(a) : "memory");
}
__device__ __forceinline__ void sts64f(uint32_t a, float x, float y) { asm volatile("st.shared.v2.f32 [%0], {%1, %2};" ::"r"(a), "f"(x), "f"(y) : "memory"); }
__device__ __forceinline__ float lds32f(uint32_t a) { float v; asm volatile("ld.shared.f32 %0, [%1];" : "=f"(v) : "r"(a) : "memory"); return v; }
__device__ __forceinline__ void sts32f(uint32_t a, float x) { asm volatile("st.shared.f32 [%0], %1;" ::"r"(a), "f"(x) : "memory"); }
__device__ __forceinline__ void stat_st(uint2* p, float sum, float sq, uint32_t tag, bool on) {
  const float mean = sum * (1.f / 128), m2 = fmaxf(fmaf(-mean, sum, sq), 0.f);
  const uint32_t a = ((__float_as_uint(mean) + 8u) & ~15u) | (tag & 15u), b = ((__float_as_uint(m2) + 8u) & ~15u) | (tag & 15u);
  asm volatile("{\n.reg .b64 x;\n.reg .pred p;\nsetp.ne.u32 p, %3, 0;\nmov.b64 x, {%1, %2};\n@p st.relaxed.gpu.global.b64 [%0], x;\n}\n" ::"l"(p), "r"(a), "r"(b), "r"((uint32_t)on) : "memory");
}
__device__ __forceinline__ void stat_ld2(const uint2* p, uint32_t (&v)[4]) {
  asm volatile("{\n.reg .b64 x, y;\nld.relaxed.gpu.global.v2.b64 {x, y}, [%4];\nmov.b64 {%0, %1}, x;\nmov.b64 {%2, %3}, y;\n}\n"
    : "=r"(v[0]), "=r"(v[1]), "=r"(v[2]), "=r"(v[3]) : "l"(p) : "memory");
}
__device__ __forceinline__ float untag(uint32_t v) { return __uint_as_float(v & ~15u); }
__device__ __forceinline__ void ll_st3(uint4* p, uint32_t a, uint32_t b, uint32_t c, uint32_t tag) {
  asm volatile("{\n.reg .b64 x, y;\n.reg .b128 z;\nmov.b64 x, {%1, %2};\nmov.b64 y, {%3, %4};\nmov.b128 z, {x, y};\nst.relaxed.gpu.global.b128 [%0], z;\n}\n"
    ::"l"(p), "r"(a), "r"(b), "r"(c), "r"(tag) : "memory");
}
__device__ __forceinline__ uint32_t ll_ld3(const uint4* p, uint32_t& a, uint32_t& b, uint32_t& c, uint32_t tag) {
  uint32_t t;
  asm volatile("{\n.reg .b64 x, y;\n.reg .b128 z;\nld.relaxed.gpu.global.b128 z, [%4];\nmov.b128 {x, y}, z;\nmov.b64 {%0, %1}, x;\nmov.b64 {%2, %3}, y;\n}\n"
    : "=r"(a), "=r"(b), "=r"(c), "=r"(t) : "l"(p) : "memory");
  return t ^ tag;
}
__device__ __forceinline__ void halo_send(uint4* p, uint32_t a, const uint32_t (&tg)[6]) {
  asm volatile("{\n.reg .b64 x<6>, y<6>, w<2>;\n.reg .b32 c<4>;\n.reg .b128 z<6>;\n"
    "ld.shared.b64 w0, [%1+1536];\nld.shared.b64 w1, [%1+1792];\n"
    "ld.shared.b64 x0, [%1];\nld.shared.b64 x1, [%1+256];\nld.shared.b64 x2, [%1+512];\n"
    "ld.shared.b64 x3, [%1+768];\nld.shared.b64 x4, [%1+1024];\nld.shared.b64 x5, [%1+1280];\n"
    "mov.b64 {c0, c1}, w0;\nmov.b64 {c2, c3}, w1;\n"
    "mov.b64 y0, {c0, %2};\nmov.b64 y1, {c1, %3};\nmov.b64 y2, {c2, %4};\nmov.b64 y3, {c3, %5};\nmov.b64 y4, {%6, %6};\nmov.b64 y5, {%7, %7};\n"
    "mov.b128 z0, {x0, y0};\nmov.b128 z1, {x1, y1};\nmov.b128 z2, {x2, y2};\nmov.b128 z3, {x3, y3};\nmov.b128 z4, {x4, y4};\nmov.b128 z5, {x5, y5};\n"
    "st.relaxed.gpu.global.b128 [%0], z0;\nst.relaxed.gpu.global.b128 [%0+512], z1;\nst.relaxed.gpu.global.b128 [%0+1024], z2;\n"
    "st.relaxed.gpu.global.b128 [%0+1536], z3;\nst.relaxed.gpu.global.b128 [%0+2048], z4;\nst.relaxed.gpu.global.b128 [%0+2560], z5;\n}\n"
    ::"l"(p), "r"(a), "r"(tg[0]), "r"(tg[1]), "r"(tg[2]), "r"(tg[3]), "r"(tg[4]), "r"(tg[5]) : "memory");
}
template <int N> __device__ __forceinline__ void copy_out(uint8_t* dst, uint32_t src, int stride) {
  uint4 v[N];
#pragma unroll
  for (int k = 0; k < N; k++) lds128(src + k * stride, v[k].x, v[k].y, v[k].z, v[k].w);
#pragma unroll
  for (int k = 0; k < N; k++) asm volatile("st.global.v4.b32 [%0], {%1, %2, %3, %4};" ::"l"(dst + k * stride), "r"(v[k].x), "r"(v[k].y), "r"(v[k].z), "r"(v[k].w) : "memory");
}
__device__ __forceinline__ void warp_store(uint8_t* dst, uint32_t src, int bytes, uint32_t delay, uint32_t pace) {
  __nanosleep(delay);
#pragma unroll 1
  for (int o = 0; o < bytes; o += 2048) {
    if (pace) __nanosleep(pace);
    uint4 v[4];
#pragma unroll
    for (int k = 0; k < 4; k++) lds128(src + o + k * 512, v[k].x, v[k].y, v[k].z, v[k].w);
#pragma unroll
    for (int k = 0; k < 4; k++) asm volatile("st.global.v4.b32 [%0], {%1, %2, %3, %4};" ::"l"(dst + o + k * 512), "r"(v[k].x), "r"(v[k].y), "r"(v[k].z), "r"(v[k].w) : "memory");
  }
  __syncwarp();
}
__device__ __forceinline__ uint32_t clock32() { uint32_t t; asm volatile("mov.u32 %0, %%clock;" : "=r"(t)); return t; }
__device__ __forceinline__ void flag_set(uint32_t* p, uint32_t bit) { asm volatile("red.release.gpu.global.xor.b32 [%0], %1;" ::"l"(p), "r"(bit) : "memory"); }
__device__ __forceinline__ void flag_wait(const uint32_t* p, uint32_t inv, uint32_t need, uint32_t& ready) {
  if ((ready & need) == need) return;
  uint32_t n = 0;
  do {
    asm volatile("ld.relaxed.gpu.global.b32 %0, [%1];" : "=r"(ready) : "l"(p) : "memory");
    ready = __shfl_sync(0xffffffffu, ready, 0) ^ inv;
  } while ((ready & need) != need && ++n < SPIN_MAX);
  asm volatile("fence.acquire.gpu;\nfence.proxy.async.global;" ::: "memory");
}
__device__ __forceinline__ bool elect_one() {
  uint32_t p;
  asm volatile("{\n.reg .pred P;\nelect.sync _|P, 0xffffffff;\nselp.u32 %0, 1, 0, P;\n}\n" : "=r"(p));
  return p;
}
__device__ __forceinline__ float gelu_half(float hx) {
  const float y = hx * fmaf(hx * hx, 8.f * 0.0356774081f, 2.f * 0.7978845608f);
  float th;
  asm("tanh.approx.f32 %0, %1;" : "=f"(th) : "f"(y));
  return fmaf(hx, th, hx);
}
__device__ __forceinline__ float ex2(float x) { float y; asm("ex2.approx.ftz.f32 %0, %1;" : "=f"(y) : "f"(x)); return y; }

__device__ __forceinline__ void stat_combine(uint32_t am, uint32_t aq, uint32_t bm, uint32_t bq, float pv, float& mean, float& var) {
  const float d0 = untag(am) - pv, d1 = untag(bm) - pv;
  float s = d0 + d1, q = fmaf(fmaf(d0, d0, d1 * d1), 128.f, untag(aq) + untag(bq));
  s += __shfl_xor_sync(0xffffffffu, s, 8); q += __shfl_xor_sync(0xffffffffu, q, 8);
  s += __shfl_xor_sync(0xffffffffu, s, 16); q += __shfl_xor_sync(0xffffffffu, q, 16);
  s *= 0.125f;
  mean = pv + s;
  var = fmaxf(fmaf(-s, s, q * (1.f / D_)), 0.f);
}

__device__ __forceinline__ void attn_logits(const uint32_t* q0, const uint32_t* q1,
                                            const uint32_t* k0, const uint32_t* k1, const uint32_t* k2, const uint32_t* k3,
                                            float mk0, float mk1, float (&s)[4][4]) {
#pragma unroll
  for (int n = 0; n < 4; n++) {
    const uint32_t* k = n == 0 ? k0 : n == 1 ? k1 : n == 2 ? k2 : k3;
    s[n][0] = s[n][1] = n < 2 ? mk0 : 0.f; s[n][2] = s[n][3] = n < 2 ? mk1 : 0.f;
    mma16816(s[n], q0[0], q1[0], q0[1], q1[1], k[0], k[1]);
    mma16816(s[n], q0[2], q1[2], q0[3], q1[3], k[2], k[3]);
  }
}
__device__ __forceinline__ void attn_probs(const float (&s)[4][4], float sc0, float sc1, bool e, bool zneg, const uint32_t (&sel)[3],
                                           uint32_t (&pr)[6], float (&l)[2]) {
  float a0 = e ? s[1][1] : s[1][0];
  float b0 = zneg ? (e ? s[0][1] : s[0][0]) : (e ? s[2][1] : s[2][0]);
  float a1 = e ? s[2][3] : s[2][2];
  float b1 = zneg ? (e ? s[1][3] : s[1][2]) : (e ? s[3][3] : s[3][2]);
  float m0 = fmaxf(a0, b0), m1 = fmaxf(a1, b1);
  m0 = fmaxf(m0, __shfl_xor_sync(0xffffffffu, m0, 1)); m1 = fmaxf(m1, __shfl_xor_sync(0xffffffffu, m1, 1));
  m0 = fmaxf(m0, __shfl_xor_sync(0xffffffffu, m0, 2)); m1 = fmaxf(m1, __shfl_xor_sync(0xffffffffu, m1, 2));
  a0 = ex2((a0 - m0) * sc0); b0 = ex2((b0 - m0) * sc0); a1 = ex2((a1 - m1) * sc1); b1 = ex2((b1 - m1) * sc1);
  l[0] = a0 + b0; l[1] = a1 + b1;
  const uint32_t p0 = pack2(a0, b0), p1 = pack2(a1, b1);
#pragma unroll
  for (int k = 0; k < 3; k++) { pr[k] = __byte_perm(p0, 0u, sel[k]); pr[3 + k] = __byte_perm(p1, 0u, sel[k]); }
}
__device__ __forceinline__ void attn_pv(const uint32_t (&pr)[6], const uint32_t* vh, const uint32_t* v, float (&o)[4][4]) {
#pragma unroll
  for (int dt = 0; dt < 4; dt++) {
    o[dt][0] = o[dt][1] = o[dt][2] = o[dt][3] = 0.f;
    mma16816(o[dt], pr[0], 0u, pr[1], pr[3], vh[2 * dt], vh[2 * dt + 1]);
    mma16816(o[dt], pr[2], pr[4], 0u, pr[5], v[2 * dt], v[2 * dt + 1]);
  }
}

constexpr int FR = 1;
constexpr int XLD = 7;
constexpr int XST = 2;
constexpr int FA = 20;
constexpr int FO = 2;
constexpr int ATT = 25;
constexpr int COVER = 2;
constexpr int LEAD1 = 3;
constexpr int LEAD2 = 4;
constexpr int LEAD4 = 5;
constexpr int PD1 = 3;
constexpr int PD2 = 5;
constexpr int PD3 = 3;
constexpr int HALO_A_NS = 300;
constexpr int STAT_CLK = 150;
constexpr int H1D = 900;
constexpr int U0D = 300;
constexpr int X1D = 1200;
constexpr int PACE = 150;

__global__ void __cluster_dims__(2, 1, 1) __launch_bounds__(384, 1) fused_kernel(const __grid_constant__ Params P) {
  extern __shared__ __align__(1024) uint8_t smem_raw[];
  const uint32_t sb = smem_u32(smem_raw);
  const uint32_t bars = sb + OFF_BAR;
  const int tid = threadIdx.x;
  const int wu = __shfl_sync(0xffffffffu, tid >> 5, 0), wg = wu >> 2;
  const int r = blockIdx.x & 1, cl = blockIdx.x >> 1;
  int grp, slt;
  if (cl < 4) { grp = 0; slt = 4 + cl; }
  else if (cl < 36) { grp = (cl - 4) & 7; slt = (cl - 4) >> 3; }
  else { grp = 1 + (cl - 36) % 7; slt = 4 + (cl - 36) / 7; }
  const int m = grp, j = slt;
  const int i = 2 * m + r;
  auto BAR = [&](int k) { return bars + 8 * k; };

  auto kb1 = [&](int n) { const int h = n >= 9, t = n - 2 - 7 * h; return n < 2 ? 2 * j + n : 2 * (t == j ? 7 : t) + h; };
  auto first_round = [&](int u0, int u1) {
#pragma unroll 1
    for (int u = u0; u < u1; u++) {
      mbar_expect(BAR(F1 + u), 40960);
      tma2d(sb + slot1(u), &P.x0, BAR(F1 + u), u * 64, 128 * i);
      tma3d(sb + slot1(u) + 16384, &P.wqkv, BAR(F1 + u), 128 * j, u * 64, 0);
      tma3d(sb + slot1(u) + 28672, &P.wqkv, BAR(F1 + u), 128 * j, u * 64 + 32, 0);
    }
  };
  if (wu == 9) {
    if (elect_one()) asm volatile("prefetch.tensormap [%0];" ::"l"(&P.wqkv) : "memory");
    __syncwarp();
  } else if (wu == 8) {
    if (elect_one()) {
#pragma unroll
      for (int k = 0; k < 4; k++) mbar_init(BAR(F1 + k), 1);
      asm volatile("fence.mbarrier_init.release.cluster;" ::: "memory");
      fence_async_smem();
      first_round(0, FR);
    }
    __syncwarp();
  } else if (wu == 0) {
    if (elect_one()) {
#pragma unroll
      for (int k = E1; k < 64; k++) {
        int cnt = 1;
        if (k < F2 || (k >= E2 && k < F3) || (k >= E3 && k < F4) || (k >= E4 && k < JOB) || k == JOB + 2 || k == JOB + 3) cnt = 4;
        else if ((k >= JOB && k < RD) || k == CSJ) cnt = 8;
        else if (k == RD + 1 || k == STD || k == STAT) cnt = 2;
        mbar_init(BAR(k), cnt);
      }
      asm volatile("fence.mbarrier_init.release.cluster;" ::: "memory");
      fence_async_smem();
    }
    __syncwarp();
  }
  auto load_tag = [&]() { uint32_t t; asm volatile("ld.relaxed.gpu.global.u32 %0, [%1];" : "=r"(t) : "l"(&gEpoch) : "memory"); return t + 1; };
  if (wu == 8) nb_arrive<NB_INIT>(384); else nb_sync<NB_INIT>(384);
  asm volatile("barrier.cluster.arrive.relaxed;" ::: "memory");

  if (wg == 2) {
    reg_dealloc<40>();
    if (wu == 8) {
      if (elect_one()) first_round(FR, 4);
      __syncwarp();
    }
    asm volatile("barrier.cluster.wait;" ::: "memory");
    auto kb3 = [&](int n) { const int h = n >= 17, t = n - 3 - 14 * h; return n < 2 ? 2 * i + n : (n == 2 || n == 31) ? 2 * (i ^ 1) + h : 2 * ((2 * m + 2 + t) & 15) + h; };
    auto v1 = [&](int L, int u) { const int u0 = L ? 2 : 10; return (u >= u0 && u < 18) ? (u < u0 + 2 ? u - u0 + 16 : u - 2) : u; };
    auto kb2 = [&](int n) { return n < 8 ? 2 * n : n == 8 ? 2 * j + 1 : 2 * (n - 9 == j ? 7 : n - 9) + 1; };
    if (wu == 8) {
      const int lane = tid & 31;
      auto pf = [&](const bf16* p, bool on) { if (on) asm volatile("prefetch.global.L2 [%0];" ::"l"(p)); };
      auto k1 = [&](int L, int v) { return (L || v >= 16) ? kb1(v & 15) : v; };
      auto kb4f = [&](int n) {
        const bool own = n == 0 || n == 9 || n == 17;
        const int q = n - 10 - (n > 17), c = own ? n >> 3 : q / 15, t = q - 15 * c;
        const int ii = own ? i : t < 14 ? (2 * m + 2 + t) & 15 : i ^ 1;
        return (n >= 1 && n <= 8) ? 7 * ((m + n) & 7) + 3 : ((7 * ii + 1) >> 1) + c;
      };
      const uint32_t tab4 = kb4f(lane) | (kb4f(lane + 32) << 16);
      auto kb4 = [&](int n) { return (int)((__shfl_sync(0xffffffffu, tab4, n) >> ((n >> 1) & 16)) & 63); };
      const bf16* const q1 = P.wqkv_p + (4 * i + (lane & 3)) * 3072 + (lane >> 2) * 1024 + 128 * j;
      const bf16* const q2 = P.wo_p + (4 * i + (lane & 3)) * 1024 + (lane >> 2) * 64 + 128 * j;
      const bf16* const q3 = P.w1_p + (8 * j + (lane >> 2)) * 3584 + 64 * (7 * m + ((lane & 3) == 3 ? 3 : 4 * r + (lane & 3)));
      auto pf1 = [&](int L, int u) { const int v = v1(L, u); pf(q1 + k1(L, v) * (64 * 3072) + 64 * (v >> 4), lane < 12); };
      auto pf2 = [&](int n) { pf(q2 + kb2(n) * (64 * 1024), lane < 8); };
      auto pf3 = [&](int n) { pf(q3 + kb3(n) * (64 * 3584), true); };
#pragma unroll 1
      for (int u = 4; u < 4 + PD1; u++) pf1(0, u);
#pragma unroll 1
      for (int L = 0; L < 2; L++) {
#pragma unroll 1
        for (int u = L ? 0 : 4; u < 32; u++) {
          const int v = v1(L, u), p = u & 3;
          int c0 = 128 * j + 64 * (v >> 4), c1 = k1(L, v) * 64 + 32 * r; uint32_t dst = sb + slot1(p) + 16384 + r * 12288;
          asm volatile("" : "+r"(c0), "+r"(c1), "+r"(dst));
          if (L && u == 4) mbar_wait(BAR(RD + 5), 0);
          if (u >= 4) mbar_wait(BAR(E1 + p), ((u >> 2) - 1) & 1);
          else mbar_wait(BAR(E4 + (u == 3 ? 0 : u + 3)), u == 3);
          if (elect_one()) {
            mbar_expect(BAR(F1 + p), (v & 15) < 2 ? 24576 : 40960);
            tma3d_mc(dst, &P.wqkv, BAR(F1 + p), c0, c1, 0);
          }
          if (u + PD1 < 32) pf1(L, u + PD1);
          if (u + PD2 >= 32) pf2(u + PD2 - 32);
        }
        int p = 0; uint32_t par = L ? 0x1e : 0;
#pragma unroll 1
        for (int n = 0; n < 16; n++) {
          int c1 = kb2(n) * 64;
          asm volatile("" : "+r"(c1));
          if (n >= 5) { mbar_wait(BAR(E2 + p), (par >> p) & 1); par ^= 1u << p; }
          else if (n < 4) mbar_wait(BAR(E1 + n), 1);
          if (elect_one()) {
            mbar_expect(BAR(F2 + p), n == 8 ? 16384 : 32768);
            tma2d_mc(sb + slot2(p) + 16384 + r * 8192, &P.wo, BAR(F2 + p), 128 * j + 64 * r, c1);
          }
          if (++p == 5) p = 0;
          if (n + PD2 < 16) pf2(n + PD2);
          if (n + PD3 + 4 >= 16) pf3(n + PD3 + 4 - 16);
        }
#pragma unroll 1
        for (int u = 0; u < 32; u++) {
          const int n = u < 4 ? (0x2031 >> (4 * u)) & 3 : u, p = n & 3;
          int kb = kb3(n);
          asm volatile("" : "+r"(kb));
          if (n == 4) {
            mbar_wait(BAR(XF + 1), L ^ 1);
            const uint32_t rs = mapa(sb, r ^ 1);
            if (elect_one()) bulk_s2s(rs + slot3(2), sb + OFF_X, 16384, rs + OFF_BAR + 8 * (F3 + 2));
            mbar_wait(BAR(RD + 4), L);
          }
          if (n >= 4) mbar_wait(BAR(E3 + p), ((n >> 2) - 1) & 1);
          else if (n == 1) mbar_wait(BAR(STD + 1), L);
          else if (n == 3) mbar_wait(BAR(E2 + 2), L);
          else if (n == 0) mbar_wait(BAR(E2 + 4), L);
          else mbar_wait(BAR(E2 + 0), 1);
          if (elect_one()) {
            mbar_expect(BAR(F3 + p), n < 2 ? 32768 : 49152);
            tma3d(sb + slot3(p) + 16384, &P.w1, BAR(F3 + p), 0, kb * 64, 7 * m + 4 * r);
            tma3d(sb + slot3(p) + 40960, &P.w1h, BAR(F3 + p), 0, kb * 64, 14 * m + 6 + r);
          }
          if (u >= 4 && u + PD3 < 32) pf3(u + PD3);
        }
        auto g4w = [&](int n, int p, int kb) {
          if (elect_one()) {
            mbar_expect(BAR(F4 + p), (n == 0 || n == 9 || n == 17) ? 16384 : 32768);
            tma3d(sb + slot4(p), &P.w2, BAR(F4 + p), 0, kb * 64, 2 * i);
          }
        };
#pragma unroll 1
        for (int n = 0; n < 6; n++) {
          const int kb = kb4(n);
          if (n == 1) mbar_wait(BAR(RD + 3), L);
          if (n < 3) mbar_wait(BAR(E3 + n), 1);
          else if (n == 4) mbar_wait(BAR(E3 + 3), 1);
          g4w(n, n, kb);
        }
        p = 0; par = L ? 0x3c : 0;
#pragma unroll 1
        for (int n = 6; n < 56; n++) {
          const int kb = kb4(n);
          mbar_wait(BAR(E4 + p), (par >> p) & 1); par ^= 1u << p;
          g4w(n, p, kb);
          if (++p == 6) p = 0;
        }
        if (L == 0)
#pragma unroll 1
          for (int u = 0; u < PD1; u++) pf1(1, u);
      }
    } else if (wu == 9) {
      uint32_t inv = 0;
#define ADDR(d, s) uint32_t dst = (d); const uint8_t* src = (s); asm volatile("" : "+r"(dst), "+l"(src))
#pragma unroll 1
      for (int L = 0; L < 2; L++) {
        uint32_t ready = 0;
#pragma unroll 1
        for (int u = 4; u < 32; u++) {
          const int p = u & 3, v = v1(L, u), nn = v & 15, kb = (L || v >= 16) ? kb1(nn) : nn;
          if (L == 0 && (u == XLD || u == XLD + XST) && elect_one()) {
            const int h = u != XLD;
            mbar_expect(BAR(XF + h), 16384);
            tma2d(sb + OFF_X + h * 16384, &P.x0, BAR(XF + h), 128 * j + 64 * h, 128 * i);
          }
          if (nn < 2) continue;
          ADDR(sb + slot1(p), gXB + (i * 16 + kb) * 16384);
          if (L && u < 12) mbar_wait(BAR(F1 + p), u >> 3);
          if (u >= 4 + 4 * L) mbar_wait(BAR(E1 + p), ((u >> 2) - 1) & 1);
          if (L) {
            flag_wait(gFlag[0][0][i], inv, 1u << kb, ready);
            if (elect_one()) bulk_ld(dst, src, 16384, BAR(F1 + p));
          } else if (elect_one()) tma2d(sb + slot1(p), &P.x0, BAR(F1 + p), kb * 64, 128 * i);
        }
        ready = 0;
        if (L == 0) inv = (__shfl_sync(0xffffffffu, load_tag(), 0) & 1) - 1;
        int p = 0; uint32_t par = L ? 0x1e : 0;
#pragma unroll 1
        for (int n = 0; n < 16; n++) {
          const int hp = kb2(n);
          if (n == 8) { par ^= 8; p = 4; continue; }
          ADDR(sb + slot2(p), gOB + (i * 16 + hp) * 16384);
          if (n >= 5) { mbar_wait(BAR(E2 + p), (par >> p) & 1); par ^= 1u << p; }
          else if (n < 4) mbar_wait(BAR(E1 + n), 1);
          flag_wait(gFlag[L][1][i], inv, 1u << hp, ready);
          if (elect_one()) bulk_ld(dst, src, 16384, BAR(F2 + p));
          if (++p == 5) p = 0;
        }
        ready = 0;
        mbar_wait(BAR(E2 + 0), 1);
#pragma unroll 1
        for (int n = 3; n < 32; n++) {
          const int p = n & 3, kb = kb3(n);
          const int o = n != 31 ? r * 8192 : 0;
          ADDR(sb + slot3(p) + o, gHB + (j * 32 + kb) * 16384 + o);
          if (n > 3) mbar_wait(BAR(E3 + p), ((n >> 2) - 1) & 1);
          flag_wait(gFlag[L][2][j], inv, 1u << kb, ready);
          if (elect_one()) {
            if (n != 31) bulk_ld_mc(dst, src, 8192, BAR(F3 + p));
            else bulk_ld(dst, src, 16384, BAR(F3 + p));
          }
        }
        ready = 0; p = 1; par = L ? 0x3c : 0;
#pragma unroll 1
        for (int t = 0; t < 8; t++) {
          const int mm = (m + t + 1) & 7;
          ADDR(sb + slot4(p) + 16384 + r * 8192, gUB + (j * 56 + 48 + mm) * 16384 + r * 8192);
          if (t < 3) mbar_wait(BAR(E3 + 1 + t), 1);
          if (t >= 5) { mbar_wait(BAR(E4 + p), (par >> p) & 1); par ^= 1u << p; }
          flag_wait(gFlag[L][6][j], inv, 3u << (2 * mm), ready);
          if (elect_one()) bulk_ld_mc(dst, src, 8192, BAR(F4 + p));
          if (++p == 6) p = 0;
        }
#pragma unroll 1
        for (int c = 0; c < 3; c++) {
          ready = 0;
#pragma unroll 1
          for (int t = 0; t < 15; t++) {
            const int ii = t < 14 ? (2 * m + 2 + t) & 15 : i ^ 1;
            if (c == 0 && (t == 0 || t == 7)) { par ^= 1u << p; if (++p == 6) p = 0; }
            const int o = t < 14 ? r * 8192 : 0;
            ADDR(sb + slot4(p) + 16384 + o, gUB + (j * 56 + 16 * c + ii) * 16384 + o);
            mbar_wait(BAR(E4 + p), (par >> p) & 1); par ^= 1u << p;
            flag_wait(gFlag[L][3 + c][j], inv, 1u << ii, ready);
            if (elect_one()) {
              if (t < 14) bulk_ld_mc(dst, src, 8192, BAR(F4 + p));
              else bulk_ld(dst, src, 16384, BAR(F4 + p));
            }
            if (++p == 6) p = 0;
          }
        }
      }
    } else {
      const int h = wu - 10, i0 = i, j0 = j;
      {
      const uint32_t tag = load_tag();
      int lane = tid & 31, i = i0, j = j0;
#define FRESH asm volatile("" : "+r"(lane), "+r"(i), "+r"(j))
      auto signal = [&](int k) { if (lane == 0) mbar_arrive(BAR(k)); };
      auto publish = [&](uint32_t* f, int bit) { if (lane == 0) flag_set(f, 1u << bit); __syncwarp(); };
#pragma unroll 1
      for (int c = 32 * h + lane; c < 288; c += 64)
        sts16(sb + OFF_B1 + 2 * c, c >= 224 ? 0u : pack2(0.5f * __bfloat162float(P.b1[c < 192 ? 64 * (7 * m + 4 * r) + c : 64 * (7 * m + 3) + 32 * r + c - 192]), 0.f));
      if (h == 0) sts32f(sb + OFF_CS + 768 + 4 * lane, 0.f);
#pragma unroll 1
      for (int L = 0; L < 2; L++) {
        FRESH;
        if (L == 0) {
          mbar_wait(BAR(CSJ), 0);
          float c0 = 0.f, c1 = 0.f, c2 = 0.f;
          const uint32_t a = sb + OFF_STG + (32 * h + lane) * 4;
#pragma unroll 4
          for (int k = 0; k < 32; k++) { c0 += lds32f(a + k * 784); c1 += lds32f(a + k * 784 + 256); c2 += lds32f(a + k * 784 + 512); }
          ll_st3(&gCS[j][i][32 * h + lane], __float_as_uint(c0), __float_as_uint(c1), __float_as_uint(c2), tag);
          __nanosleep(500);
        }
        FRESH;
        if (L == 0) {
#pragma unroll 1
          for (int ab = 0; ab < 2; ab++) {
            float c0 = 0.f, c1 = 0.f, c2 = 0.f;
#pragma unroll 1
            for (int b4 = 0; b4 < 8; b4 += 4) {
              uint32_t a[4], b[4], c[4], n = 0, bad;
              do {
                bad = 0;
#pragma unroll
                for (int e = 0; e < 4; e++) bad |= ll_ld3(&gCS[j][2 * (b4 + e) + ab][32 * h + lane], a[e], b[e], c[e], tag);
              } while (bad && ++n < SPIN_MAX);
#pragma unroll
              for (int e = 0; e < 4; e++) { c0 += __uint_as_float(a[e]); c1 += __uint_as_float(b[e]); c2 += __uint_as_float(c[e]); }
            }
            const uint32_t a = sb + OFF_CS + ab * 768 + (4 * h + (lane >> 3)) * 32 + (lane & 7) * 2;
            const uint32_t h0 = pack2(c0, 0.f), h1 = pack2(c1, 0.f), h2 = pack2(c2, 0.f);
            sts16(a, h0); sts16(a + 256, h1); sts16(a + 512, h2);
            sts16(a + 16, pack2(c0 - bf_lo(h0), 0.f)); sts16(a + 272, pack2(c1 - bf_lo(h1), 0.f)); sts16(a + 528, pack2(c2 - bf_lo(h2), 0.f));
            fence_async_smem();
            __syncwarp();
            if (ab == 0) signal(STAT);
          }
        }
#pragma unroll 1
        for (int ab = 0; ab < 2; ab++) {
          FRESH;
          uint32_t v[18], tg[6];
          const uint32_t xs = sb + OFF_STG + h * 16384 + lane * 8;
          uint4* hp = &gHalo[L][i][j][6 * h][lane];
#pragma unroll
          for (int c = 0; c < 6; c++) { tg[c] = (2 * tag + ab) * 8 + c; asm volatile("" : "+r"(tg[c])); }
          asm volatile("" : "+l"(hp));
          mbar_wait(BAR(FOLD + h), ab);
          if (i < 15) {
            halo_send(hp, xs, tg);
          }
          if (i > 0) {
            if (!ab) __nanosleep(HALO_A_NS);
            uint32_t n = 0, bad;
            do {
              bad = 0;
#pragma unroll
              for (int c = 0; c < 6; c++) bad |= ll_ld3(hp + c * 32 - 8 * 12 * 32, v[3 * c], v[3 * c + 1], v[3 * c + 2], (2 * tag + ab) * 8);
            } while (bad > 7 && ++n < SPIN_MAX);
          } else {
#pragma unroll
            for (int c = 0; c < 18; c++) v[c] = 0u;
          }
#pragma unroll
          for (int c = 0; c < 6; c++) sts64f(xs + c * 256, __uint_as_float(v[3 * c]), __uint_as_float(v[3 * c + 1]));
          sts64f(xs + 1536, __uint_as_float(v[2]), __uint_as_float(v[5]));
          sts64f(xs + 1792, __uint_as_float(v[8]), __uint_as_float(v[11]));
          __syncwarp();
          signal(HALO + h);
          FRESH;
          if (ab == 0 && lane == 0) asm volatile("st.relaxed.gpu.global.u32 [%0], %1;" ::"l"(&gAck[L][i][j][h][0]), "r"(tag) : "memory");
          uint8_t* dst = gOB + (i * 16 + 2 * j + ab) * 16384;
          uint32_t* flag = gFlag[L][1][i];
          asm volatile("" : "+l"(dst), "+l"(flag));
          mbar_wait(BAR(JOB + ab), L);
          if (h == 0) {
            if (lane == 0) { bulk_st(dst, sb + OFF_STG, 16384); bulk_commit(); bulk_wait0(); }
            signal(STD + ab);
            publish(flag, 2 * j + ab);
          } else if (ab == 0) {
            if (i < 15 && lane < 2) {
              uint32_t t, n = 0;
              do { asm volatile("ld.relaxed.gpu.global.u32 %0, [%1];" : "=r"(t) : "l"(&gAck[L][i + 1][j][lane][0]) : "memory"); } while (t != tag && ++n < SPIN_MAX);
            }
            __syncwarp();
            signal(STD);
          }
        }
#pragma unroll 1
        for (int k = 0; k < 4 - L; k++) {
          FRESH;
          const int job = 2 * k + h;
          uint8_t* dst = k == 0 ? gHB + (j * 32 + 2 * i + 1) * 16384 : k == 3 ? gXB + (i * 16 + 2 * j + 1) * 16384 : gUB + (j * 56 + 16 * (job - 3) + i) * 16384;
          uint32_t* flag = k == 3 ? gFlag[0][0][i] : gFlag[L][(0x543622 >> (4 * job)) & 15][j];
          uint32_t bit = 1u << (k == 0 ? 2 * i + h : k == 3 ? 2 * j + h : i);
          asm volatile("" : "+l"(dst), "+l"(flag), "+r"(bit));
          mbar_wait(BAR(JOB + ((0x98654732 >> (4 * job)) & 15)), L);
          if ((0xba >> job) & 1) {
            if (job == 1) mbar_wait(BAR(RD + 4), L);
            if (job == 3) {
              __nanosleep(U0D);
              if (lane == 0) { bulk_st(dst, sb + OFF_X, 16384); bulk_commit(); bulk_wait0(); }
            } else warp_store(dst + lane * 16, sb + lane * 16 + OFF_X + (job == 5 ? 0 : 16384), 16384, job == 1 ? H1D : job == 7 ? X1D : 0, job == 7 ? 0 : PACE);
            if (job != 7) signal(RD + ((0x112000 >> (4 * job)) & 15));
          }
          if (lane == 0) flag_set(flag, bit);
          __syncwarp();
          if (h == 0 && k != 2) { signal(RD + (k == 3 ? 5 : 4 - k)); }
        }
      }
      if (blockIdx.x == 0 && h == 0 && lane == 0) asm volatile("st.relaxed.gpu.global.u32 [%0], %1;" ::"l"(&gEpoch), "r"(tag) : "memory");
      }
    }
    __syncwarp();
    cluster_bar();
  } else {
    reg_alloc<232>();
    asm volatile("barrier.cluster.wait;" ::: "memory");
    const uint32_t rbars = mapa(bars, tid & 1);
    const bool relp = (tid & 127) < 2;
    const uint32_t sd = (sb & 0x3FFFF) >> 4, sda = sd + wg * 512;
    uint32_t tag;
    asm volatile("ld.relaxed.gpu.global.u32 %0, [%1];" : "=r"(tag) : "l"(&gEpoch + (fresh_tid() >> 10)) : "memory");
    auto release = [&](int k) { if (relp) mbar_arrive_cl(rbars + 8 * k); };
    auto signal = [&](int k) { __syncwarp(); if ((fresh_tid() & 31) == 0) mbar_arrive(BAR(k)); };
#define GEOM const int t7 = fresh_tid() & 127, lane = t7 & 31, w = t7 >> 5, g = lane >> 2, q = lane & 3, \
                       lr = lane & 15, lt = lane >> 4, l7 = lane & 7; (void)w; (void)g; (void)q; (void)lr; (void)lt; (void)l7

#pragma unroll 1
    for (int L = 0; L < 2; L++) {
      float acca[96], accb[96], xa[64], acc3[112];
      float nmean0, nmean1, rstd0, rstd1;
      uint16_t b2a, b2b;
      uint2 *e2p, *e2s; uint8_t* e2g; uint32_t e2h;
      uint32_t Q[2][8], K[2][8], V[16];
      auto g1_issue = [&](float (&acc)[96], uint32_t a, uint32_t st, auto first) {
        const uint32_t da = sda + (a >> 4), db = sd + (st >> 4);
        wg_fence();
        static_for<0, 4>([&](auto kk) {
          constexpr uint32_t ia = DI(kk.value * 32, 16), ib = DI(16384 + (kk.value >> 1) * 12288 + (kk.value & 1) * 2048, 4096);
          if constexpr (first.value && kk.value == 0) wgmma_192z<0, 1, ia, ib>(acc, da, db); else wgmma_192<0, 1, ia, ib>(acc, da, db);
        });
        wg_commit();
      };
      auto g1_step = [&](float (&acc)[96], int u, bool rel, bool lead = false) {
        const int p = u & 3;
        mbar_wait(BAR(F1 + p), (u >> 2) & 1);
        g1_issue(acc, slot1(p), slot1(p), False{});
        if (lead) nb_arrive<NB_LEAD>(256);
        wg_wait<1>();
        if (rel) release(E1 + ((u - 1) & 3));
      };
      auto g1_loop = [&](float (&acc)[96], int u0, int u1, int urel) {
        int u = u0;
#pragma unroll 1
        do { g1_step(acc, u, u > urel); } while (++u < u1);
      };
      auto load_x = [&]() {
        GEOM;
#pragma unroll
        for (int t = 0; t < 16; t += 2) {
          uint32_t v0, v1, v2, v3;
          ldsm4(sb + OFF_X + (t >> 3) * 16384 + (16 * wu + lr) * 128 + ((((t & 7) + lt) ^ l7) << 4), v0, v1, v2, v3);
          xa[4 * t + 0] = bf_lo(v0); xa[4 * t + 1] = bf_hi(v0); xa[4 * t + 2] = bf_lo(v1); xa[4 * t + 3] = bf_hi(v1);
          xa[4 * t + 4] = bf_lo(v2); xa[4 * t + 5] = bf_hi(v2); xa[4 * t + 6] = bf_lo(v3); xa[4 * t + 7] = bf_hi(v3);
        }
      };
      auto stat_base = [&]() { return &gST[0][0][0][0][0] + ((L * 16 + opq(i)) * 8 + wu) * 128; };
      auto stat_slot = [&]() { const int lane = fresh_tid() & 31; return stat_base() + 16 * j + 2 * (lane >> 2) + (lane & 1); };
      auto stat_publish = [&](uint2* sp, float s0, float q0, float s2, float q2, uint32_t tg) {
        const int q = fresh_tid() & 3;
        const bool h1 = q & 1;
        float sm = (h1 ? s2 : s0) + __shfl_xor_sync(0xffffffffu, h1 ? s0 : s2, 1);
        float sq = (h1 ? q2 : q0) + __shfl_xor_sync(0xffffffffu, h1 ? q0 : q2, 1);
        sm += __shfl_xor_sync(0xffffffffu, sm, 2); sq += __shfl_xor_sync(0xffffffffu, sq, 2);
        stat_st(sp, sm, sq, tg, q < 2);
        return sm;
      };
      auto g1_stats = [&](int u0) {
        GEOM;
        const uint32_t xr = sb + OFF_X + (16 * wu + lr) * 128;
        float s0 = 0.f, q0 = 0.f, s2 = 0.f, q2 = 0.f;
        uint32_t v[8] = {0u, 0u, 0u, 0u, 0u, 0u, 0u, 0u};
#pragma unroll 1
        for (int k = 0; k < 5; k++) {
#pragma unroll
          for (int e = 0; e < 8; e += 2) {
            const float a = bf_lo(v[e]), b = bf_hi(v[e]), c = bf_lo(v[e + 1]), d = bf_hi(v[e + 1]);
            s0 += a + b; q0 = fmaf(a, a, fmaf(b, b, q0)); s2 += c + d; q2 = fmaf(c, c, fmaf(d, d, q2));
          }
          if (k == 4) break;
          const uint32_t o = ((2 * k + lt) ^ l7) << 4;
          ldsm4(xr + o, v[0], v[1], v[2], v[3]);
          ldsm4(xr + o + 16384, v[4], v[5], v[6], v[7]);
          g1_step(acca, u0 + k, true);
        }
        stat_publish(stat_slot(), s0, q0, s2, q2, 2 * (tag + 1));
      };
      uint32_t sv0[4], sv1[4];
      auto stat_src = [&]() { return stat_base() + 2 * (fresh_tid() & 31); };
      auto stat_fetch = [&](const uint2* sp) { stat_ld2(sp, sv0); stat_ld2(sp + 64, sv1); };
      auto stat_await = [&](auto src, uint32_t tg) {
#pragma unroll 1
        for (uint32_t n = 0; (((sv0[0] ^ tg) | (sv0[2] ^ tg) | (sv1[0] ^ tg) | (sv1[2] ^ tg)) & 15u) && n < SPIN_MAX; n++) stat_fetch(src());
        __syncwarp();
      };
      auto ln_stats = [&]() {
        GEOM;
        stat_await(stat_src, 2 * (tag + 1));
        float mean0, var0, mean1, var1;
        stat_combine(sv0[0], sv0[1], sv1[0], sv1[1], untag(__shfl_sync(0xffffffffu, sv0[0], l7)), mean0, var0);
        stat_combine(sv0[2], sv0[3], sv1[2], sv1[3], untag(__shfl_sync(0xffffffffu, sv0[2], l7)), mean1, var1);
        nmean0 = -__shfl_sync(0xffffffffu, mean0, g); rstd0 = rsq(__shfl_sync(0xffffffffu, var0, g) + 1e-5f);
        nmean1 = -__shfl_sync(0xffffffffu, mean1, g); rstd1 = rsq(__shfl_sync(0xffffffffu, var1, g) + 1e-5f);
      };
      auto center = [&](float (&acc)[96], int ab) {
        const bool q0 = (fresh_tid() & 3) == 0;
        const uint32_t h0 = pack2(nmean0, nmean0), h1 = pack2(nmean1, nmean1);
        const float l0 = nmean0 - bf_lo(h0), l1 = nmean1 - bf_lo(h1);
        const uint32_t a0 = q0 ? h0 : 0u, a1 = q0 ? h1 : 0u, a2 = q0 ? pack2(l0, l0) : 0u, a3 = q0 ? pack2(l1, l1) : 0u;
        wg_fence();
        wgmma_rs_192(acc, a0, a1, a2, a3, mkdesc_vec(sb + OFF_CS + ab * 768, 32));
      };
      auto frag = [&](float (&acc)[96], int t, uint32_t& p0, uint32_t& p1) {
        if (t >= 8) { p0 = pack2(acc[4 * t] * rstd0, acc[4 * t + 1] * rstd0); p1 = pack2(acc[4 * t + 2] * rstd1, acc[4 * t + 3] * rstd1); }
        else { p0 = pack2(acc[4 * t], acc[4 * t + 1]); p1 = pack2(acc[4 * t + 2], acc[4 * t + 3]); }
      };
      auto fold_v = [&](float (&acc)[96]) {
        GEOM;
        const uint32_t a = sb + OFF_STG + 16384 + ((wu + 1) & 7) * 2048 + lr * 128;
#pragma unroll
        for (int t = 0; t < 8; t += 2) {
          uint32_t p0, p1, p2, p3;
          frag(acc, 16 + t, p0, p1); frag(acc, 17 + t, p2, p3);
          stsm4(a + (((t + lt) ^ l7) << 4), p0, p1, p2, p3);
        }
        __syncwarp();
#pragma unroll
        for (int t = 0; t < 8; t += 2) ldsm4t(a + (((t + lt) ^ l7) << 4), V[2 * t], V[2 * t + 1], V[2 * t + 2], V[2 * t + 3]);
        if (wu == 7) signal(FOLD + 1);
      };
      auto fold_k = [&](float (&acc)[96]) {
        GEOM;
        const uint32_t a = sb + OFF_STG + ((wu + 1) & 7) * 2048 + lane * 16;
#pragma unroll
        for (int hh = 0; hh < 2; hh++) {
#pragma unroll
          for (int t = 4 * hh; t < 4 * hh + 4; t++) frag(acc, 8 + t, K[0][t], K[1][t]);
#pragma unroll
          for (int o = 0; o < 2; o++) sts128(a + (2 * o + hh) * 512, K[o][4 * hh], K[o][4 * hh + 1], K[o][4 * hh + 2], K[o][4 * hh + 3]);
        }
        if (wu == 7) signal(FOLD);
      };
      auto fold_q = [&](float (&acc)[96]) {
#pragma unroll
        for (int t = 0; t < 8; t++) frag(acc, t, Q[0][t], Q[1][t]);
      };
      auto attend = [&](int ab, auto drain, auto resume) {
        GEOM;
        nb_sync<NB_BOTH>(256);
        const uint32_t xa_ = sb + OFF_STG + wu * 2048 + lane * 16;
        if (wu == 0) mbar_wait(BAR(HALO), ab);
        uint32_t KH[2][8], VH[16];
#pragma unroll
        for (int c = 0; c < 4; c++)
          lds128(xa_ + c * 512, KH[c >> 1][4 * (c & 1)], KH[c >> 1][4 * (c & 1) + 1], KH[c >> 1][4 * (c & 1) + 2], KH[c >> 1][4 * (c & 1) + 3]);
        auto load_vh = [&]() {
          if (wu == 0) mbar_wait(BAR(HALO + 1), ab);
#pragma unroll
          for (int c = 0; c < 4; c++)
            ldsm4t(sb + OFF_STG + 16384 + wu * 2048 + lr * 128 + (((2 * c + lt) ^ l7) << 4), VH[4 * c], VH[4 * c + 1], VH[4 * c + 2], VH[4 * c + 3]);
        };
        if (!ab) load_vh();
        const bool e = g & 1, zneg = (g >> 1) < q, first = (i == 0) && (wu == 0);
        const float sc0 = rstd0 * (0.17677669530f * 1.4426950409f), sc1 = rstd1 * (0.17677669530f * 1.4426950409f);
        float mk0 = first ? __fdividef(-1.0e9f * 1.4426950409f, sc0) : 0.f, mk1 = first ? __fdividef(-1.0e9f * 1.4426950409f, sc1) : 0.f;
        const uint32_t sa = e ? 0x1044u : 0x4410u, sbb = e ? 0x3244u : 0x4432u;
        uint32_t sel[3] = {zneg ? sbb : 0x4444u, sa, zneg ? 0x4444u : sbb};
        uint32_t oa = sb + OFF_STG + (16 * wu + lr) * 128 + ((lt ^ l7) << 4);
        asm volatile("" : "+r"(sel[0]), "+r"(sel[1]), "+r"(sel[2]), "+r"(oa), "+f"(mk0), "+f"(mk1));
        drain();
        uint32_t pr[2][6];
        float l[2][2], sl[2][4][4];
#pragma unroll
        for (int hh = 0; hh < 2; hh++)
          attn_logits(&Q[0][4 * hh], &Q[1][4 * hh], &KH[0][4 * hh], &KH[1][4 * hh], &K[0][4 * hh], &K[1][4 * hh], mk0, mk1, sl[hh]);
        if (ab) load_vh();
#pragma unroll
        for (int hh = 0; hh < 2; hh++) attn_probs(sl[hh], sc0, sc1, e, zneg, sel, pr[hh], l[hh]);
        float o[2][4][4];
#pragma unroll
        for (int hh = 0; hh < 2; hh++) attn_pv(pr[hh], &VH[8 * hh], &V[8 * hh], o[hh]);
#pragma unroll
        for (int hh = 0; hh < 2; hh++) {
          float l0 = l[hh][0], l1 = l[hh][1];
          l0 += __shfl_xor_sync(0xffffffffu, l0, 1); l1 += __shfl_xor_sync(0xffffffffu, l1, 1);
          l0 += __shfl_xor_sync(0xffffffffu, l0, 2); l1 += __shfl_xor_sync(0xffffffffu, l1, 2);
          asm("rcp.approx.ftz.f32 %0, %0;" : "+f"(l0)); asm("rcp.approx.ftz.f32 %0, %0;" : "+f"(l1));
#pragma unroll
          for (int dt = 0; dt < 4; dt += 2)
            stsm4(oa ^ ((4 * hh + dt) << 4),
                  pack2(o[hh][dt][0] * l0, o[hh][dt][1] * l0), pack2(o[hh][dt][2] * l1, o[hh][dt][3] * l1),
                  pack2(o[hh][dt + 1][0] * l0, o[hh][dt + 1][1] * l0), pack2(o[hh][dt + 1][2] * l1, o[hh][dt + 1][3] * l1));
        }
        fence_async_smem();
        signal(JOB + ab);
        nb_sync<NB_BOTH>(256);
        resume();
      };

      mbar_wait(BAR(F1), 0);    g1_issue(acca, L ? OFF_X : slot1(0), slot1(0), True{});
      mbar_wait(BAR(F1 + 1), 0); g1_issue(acca, L ? OFF_X + 16384 : slot1(1), slot1(1), False{});
      wg_wait<1>(); release(E1 + 0);
      if (L == 0) {
        GEOM;
        const bf16* wp = P.wqkv_p + ((128 * opq(m) + 16 * wg + (t7 >> 3)) * 3072 + 128 * opq(j) + 64 * r + l7 * 8);
        const uint32_t ca = sb + OFF_STG + (16 * wg + (t7 >> 3)) * 784 + l7 * 32;
#pragma unroll 1
        for (int p = 0; p < 3; p++) {
          uint4 wv[4];
#pragma unroll
          for (int k = 0; k < 4; k++)
            asm volatile("ld.global.nc.v4.u32 {%0, %1, %2, %3}, [%4];" : "=r"(wv[k].x), "=r"(wv[k].y), "=r"(wv[k].z), "=r"(wv[k].w)
                         : "l"(wp + k * 32 * 3072 + p * 1024));
          g1_loop(acca, 2 + 3 * p, p < 2 ? 5 + 3 * p : 10, 0);
          float cs[8];
#pragma unroll
          for (int k = 0; k < 4; k++) {
            const uint4 v = wv[k];
            const float t[8] = {bf_lo(v.x), bf_hi(v.x), bf_lo(v.y), bf_hi(v.y), bf_lo(v.z), bf_hi(v.z), bf_lo(v.w), bf_hi(v.w)};
#pragma unroll
            for (int e = 0; e < 8; e++) cs[e] = k ? cs[e] + t[e] : t[e];
          }
          sts128(ca + p * 256, __float_as_uint(cs[0]), __float_as_uint(cs[1]), __float_as_uint(cs[2]), __float_as_uint(cs[3]));
          sts128(ca + p * 256 + 16, __float_as_uint(cs[4]), __float_as_uint(cs[5]), __float_as_uint(cs[6]), __float_as_uint(cs[7]));
        }
        signal(CSJ);
        mbar_wait(BAR(XF), 0); mbar_wait(BAR(XF + 1), 0);
      }
      {
        const int u0 = L ? 2 : 10;
        mbar_wait(BAR(F1 + 2), 0); g1_issue(accb, OFF_X, slot1(2), True{});
        wg_wait<1>(); release(E1 + 1);
        mbar_wait(BAR(F1 + 3), 0); g1_issue(accb, OFF_X + 16384, slot1(3), False{});
        wg_wait<1>(); release(E1 + 2);
        g1_stats(u0 + 2);
        g1_loop(acca, u0 + 6, 18, 0);
      }
      stat_fetch(stat_src());
      const int fa = FA + (wg ? 0 : FO);
      g1_loop(accb, 18, fa, 0);
      ln_stats();
      if (L == 0) mbar_wait(BAR(STAT), 0);
      center(acca, 0); wg_commit();
      wg_wait<0>(); release(E1 + ((fa - 1) & 3));
      fence_regs(acca);
      fold_k(acca); fold_v(acca); fold_q(acca);
      sched_fence(P.zero);
      g1_loop(accb, fa, ATT, fa);
      attend(0, [&]() { wg_wait<0>(); release(E1 + ((ATT - 1) & 3)); mbar_wait(BAR(F1 + (ATT & 3)), (ATT >> 2) & 1); },
             [&]() { g1_issue(accb, slot1(ATT & 3), slot1(ATT & 3), False{});
                     mbar_wait(BAR(F1 + ((ATT + 1) & 3)), ((ATT + 1) >> 2) & 1);
 g1_issue(accb, slot1((ATT + 1) & 3), slot1((ATT + 1) & 3), False{}); });
      wg_wait<1>(); release(E1 + (ATT & 3));
      load_x();
      fence_regs(xa);
      center(accb, 1);
#pragma unroll 1
      for (int u = ATT + 2; u < 32; u++) {
        const bool hold = u == 32 - LEAD1 && wg == 0;
        if (hold) { wg_wait<0>(); release(E1 + ((31 - LEAD1) & 3)); nb_sync<NB_LEAD>(256); }
        g1_step(accb, u, !hold, u == 31 && wg == 1);
      }
      mbar_wait(BAR(STD), L);
      wg_wait<0>(); release(E1 + 3);
      fence_regs(accb);
      fold_k(accb);
      sched_fence(P.zero);
      fold_v(accb);
      fold_q(accb);
      {
        auto g2_issue = [&](int p, bool own) {
          const uint32_t st = slot2(p);
          const uint32_t da = sda + ((own ? OFF_STG : st) >> 4), db = sd + (st >> 4);
          wg_fence();
          static_for<0, 4>([&](auto kk) { wgmma_128<0, 1, DI(kk.value * 32, 16), DI(16384 + kk.value * 2048, 8192)>(xa, da, db); });
          wg_commit();
        };
        uint32_t par = L ? 0x1e : 0;
        int p = 0, pp = 0;
        auto g2_loop = [&](int n0, int n1, int nrel) {
#pragma unroll 1
          for (int n = n0; n < n1; n++) {
            mbar_wait(BAR(F2 + p), (par >> p) & 1);
            par ^= 1u << p;
            g2_issue(p, n == 8);
            wg_wait<1>();
            if (n > nrel) release(E2 + pp);
            pp = p; if (++p == 5) p = 0;
          }
        };
        g2_loop(0, COVER, 0);
        attend(1, [&]() { wg_wait<0>(); release(E2 + COVER - 1); mbar_wait(BAR(F2 + COVER), (par >> COVER) & 1); },
               [&]() { g2_issue(COVER, false);
                       mbar_wait(BAR(F2 + COVER + 1), (par >> (COVER + 1)) & 1);
 g2_issue(COVER + 1, false); });
        wg_wait<1>(); release(E2 + COVER);
        par ^= 3u << COVER; pp = COVER + 1; p = (COVER + 2) % 5;
        {
          const bf16* bp = P.b2 + (128 * opq(i) + 16 * wu + ((fresh_tid() & 31) >> 2));
          asm volatile("ld.global.nc.u16 %0, [%1];" : "=h"(b2a) : "l"(bp));
          asm volatile("ld.global.nc.u16 %0, [%1];" : "=h"(b2b) : "l"(bp + 8));
        }
        {
          GEOM;
          e2p = stat_slot(); e2s = stat_src();
          e2g = gHB + (opq(j) * 32 + 2 * i) * 16384 + w * 2048 + lane * 16;
          e2h = sb + OFF_X + wg * 16384 + (16 * w + lr) * 128 + ((lt ^ l7) << 4);
          asm volatile("" : "+l"(e2p), "+l"(e2s), "+l"(e2g), "+r"(e2h));
        }
        g2_loop(COVER + 2, 16 - LEAD2, 0);
        if (wg == 1) { wg_wait<0>(); release(E2 + pp); nb_sync<NB_LEAD>(256); }
        static_for<16 - LEAD2, 16>([&](auto nn) {
          constexpr int n = nn.value, p = n % 5;
          mbar_wait(BAR(F2 + p), (n / 5 + (p ? L : 0)) & 1);
          wg_fence();
          static_for<0, 4>([&](auto kk) { wgmma_128<0, 1, DI(slot2(p) + kk.value * 32, 16), DI(slot2(p) + 16384 + kk.value * 2048, 8192)>(xa, sda, sd); });
          wg_commit();
          if (n == 15 && wg == 0) nb_arrive<NB_LEAD>(256);
          wg_wait<1>();
          if (n > 16 - LEAD2 || wg == 0) release(E2 + (n + 4) % 5);
        });
        wg_wait<0>();
        release(E2 + 0);
        fence_regs(xa);
      }
      {
        GEOM;
        const uint32_t tg = 2 * (tag + 1) + 1;
        float s0 = 0.f, s1 = 0.f, s2 = 0.f, s3 = 0.f, q0 = 0.f, q1 = 0.f, q2 = 0.f, q3 = 0.f;
#pragma unroll
        for (int t = 0; t < 16; t++) {
          s0 += xa[4 * t]; s1 += xa[4 * t + 1]; s2 += xa[4 * t + 2]; s3 += xa[4 * t + 3];
          q0 = fmaf(xa[4 * t], xa[4 * t], q0); q1 = fmaf(xa[4 * t + 1], xa[4 * t + 1], q1);
          q2 = fmaf(xa[4 * t + 2], xa[4 * t + 2], q2); q3 = fmaf(xa[4 * t + 3], xa[4 * t + 3], q3);
        }
        const float sm = stat_publish(e2p, s0 + s1, q0 + q1, s2 + s3, q2 + q3, tg);
        const uint32_t t0 = clock32();
        const float pv0 = __shfl_sync(0xffffffffu, sm, 4 * l7) * (1.f / 128), pv1 = __shfl_sync(0xffffffffu, sm, 4 * l7 + 1) * (1.f / 128);
        while (clock32() - t0 < STAT_CLK) {}
        stat_fetch(e2s);
        wg_fence();
        wgmma_rs_224z(acc3, q == 0 ? 0x3f80u : 0u, q == 0 ? 0x3f80u : 0u, 0u, 0u, mkdesc_vec(sb + OFF_B1, 16));
        wg_commit();
        stat_await([&]() { return e2s; }, tg);
        float r0, m0, r1, m1;
        {
          float mean0, var0, mean1, var1;
          stat_combine(sv0[0], sv0[1], sv1[0], sv1[1], pv0, mean0, var0); stat_combine(sv0[2], sv0[3], sv1[2], sv1[3], pv1, mean1, var1);
          mean0 = __shfl_sync(0xffffffffu, mean0, g); var0 = __shfl_sync(0xffffffffu, var0, g);
          mean1 = __shfl_sync(0xffffffffu, mean1, g); var1 = __shfl_sync(0xffffffffu, var1, g);
          r0 = 0.5f * rsq(fmaf(var0 + 1e-5f, 1e-5f, var0)); r1 = 0.5f * rsq(fmaf(var1 + 1e-5f, 1e-5f, var1));
          m0 = -mean0 * r0; m1 = -mean1 * r1;
        }
#pragma unroll
        for (int t = 0; t < 16; t += 2) {
          stsm4((e2h ^ ((t & 7) << 4)) + (t >> 3) * 8192,
                pack2(fmaf(xa[4 * t], r0, m0), fmaf(xa[4 * t + 1], r0, m0)), pack2(fmaf(xa[4 * t + 2], r1, m1), fmaf(xa[4 * t + 3], r1, m1)),
                pack2(fmaf(xa[4 * t + 4], r0, m0), fmaf(xa[4 * t + 5], r0, m0)), pack2(fmaf(xa[4 * t + 6], r1, m1), fmaf(xa[4 * t + 7], r1, m1)));
          if ((t & 7) == 6 && wg == 0) {
            __syncwarp();
            copy_out<4>(e2g + (t >> 3) * 8192, sb + OFF_X + (t >> 3) * 8192 + w * 2048 + lane * 16, 512);
          }
        }
        signal(JOB + 2 + wg);
        fence_async_smem();
        mbar_wait(BAR(F3 + 0), 0);
        if (wg == 0) { nb_sync<NB_WG0>(128); if (t7 == 0) mbar_arrive(BAR(XF + 1)); }
        else nb_sync<NB_BOTH>(256);
      }
      auto g3_issue = [&](uint32_t a, int p) {
        const uint32_t da = sda + (a >> 4), db = sd + (slot3(p) >> 4);
        wg_fence();
        static_for<0, 4>([&](auto kk) { wgmma_224<1, 1, DI(kk.value * 2048, 8192), DI(16384 + kk.value * 2048, 8192)>(acc3, da, db); });
        wg_commit();
      };
 g3_issue(OFF_X, 0);
      if (wg == 0) nb_sync<NB_BOTH>(256);
      mbar_wait(BAR(F3 + 1), 0); g3_issue(OFF_X + 16384, 1);
      sched_fence(P.zero);
      {
        const float c0 = __uint_as_float((uint32_t)b2a << 16), c1 = __uint_as_float((uint32_t)b2b << 16);
#pragma unroll
        for (int t = 0; t < 16; t++) { xa[4 * t] += c0; xa[4 * t + 1] += c0; xa[4 * t + 2] += c1; xa[4 * t + 3] += c1; }
        fence_regs(xa);
      }
      wg_wait<1>(); release(E3 + 0);
      auto g3_loop = [&](int n0, int n1, int nrel) {
#pragma unroll 1
        for (int n = n0; n < n1; n++) {
          const int p = n & 3;
          mbar_wait(BAR(F3 + p), (n >> 2) & 1);
          g3_issue(slot3(p), p);
          wg_wait<1>();
          if (n > nrel) release(E3 + ((n - 1) & 3));
        }
      };
      g3_loop(2, 29, 0);
      uint32_t ua;
      uint8_t* ug;
      {
        GEOM;
        ua = sb + OFF_X + wg * 8192 + (8 * lt + l7) * 128 + (((2 * w + ((lane >> 3) & 1)) ^ l7) << 4);
        ug = gUB + (opq(j) * 56 + 48 + m) * 16384 + r * 4096 + wg * 8192 + (lane >> 1) * 128 + (((2 * w + (lane & 1)) ^ ((lane >> 1) & 7)) << 4);
      }
      auto gelu8 = [&](int c, int k) {
        const int o = 32 * c + 8 * k;
        stsm4t(ua + (c & 1) * 16384 + k * 2048,
               pack2(gelu_half(acc3[o]), gelu_half(acc3[o + 1])), pack2(gelu_half(acc3[o + 2]), gelu_half(acc3[o + 3])),
               pack2(gelu_half(acc3[o + 4]), gelu_half(acc3[o + 5])), pack2(gelu_half(acc3[o + 6]), gelu_half(acc3[o + 7])));
      };
      {
        auto part = [&](auto p, auto half) {
          static_for<0, 4>([&](auto kk) {
            constexpr uint32_t o = slot3(p.value) + kk.value * 2048;
            if constexpr (half.value) wgmma_32<1, 1, DI(o, 8192), DI(o + 40960, 8192), 96>(acc3, sda, sd);
            else wgmma_192<1, 1, DI(o, 8192), DI(o + 16384, 8192), 0>(acc3, sda, sd);
          });
        };
        mbar_wait(BAR(RD), L);
        mbar_wait(BAR(F3 + 1), 1); mbar_wait(BAR(F3 + 2), 1);
        wg_wait<0>(); release(E3 + 0);
#pragma unroll
        for (int k = 0; k < 112; k++) { float t; asm volatile("mov.b32 %0, %1;" : "=f"(t) : "f"(acc3[k]) : "memory"); acc3[k] = t; }
        sched_fence(P.zero);
        wg_fence(); part(Int<1>{}, True{}); part(Int<2>{}, True{});
        mbar_wait(BAR(F3 + 3), 1); wg_fence(); part(Int<3>{}, True{}); wg_commit();
        part(Int<1>{}, False{}); wg_commit();
        wg_wait<1>();
#pragma unroll
        for (int k = 96; k < 112; k++) asm volatile("" : "+f"(acc3[k])::"memory");
        gelu8(3, 0); gelu8(3, 1);
        __syncwarp();
        copy_out<2>(ug, sb + OFF_X + 16384 + (uint32_t)((ug - gUB) & 0x2fff), 2048);
        signal(JOB + 7);
        sched_fence(P.zero);
        wg_fence(); part(Int<2>{}, False{}); wg_commit();
        wg_wait<1>(); release(E3 + 1);
        part(Int<3>{}, False{}); wg_commit();
        wg_wait<1>(); release(E3 + 2);
        wg_wait<0>(); release(E3 + 3);
      }
      fence_regs(acc3);
      auto g4_issue = [&](int p, uint32_t b) {
        const uint32_t da = sda + (slot4(p) >> 4), db = sd + (b >> 4);
        wg_fence();
        static_for<0, 4>([&](auto kk) { wgmma_128<1, 1, DI(kk.value * 2048, 8192), DI(kk.value * 2048, 8192)>(xa, da, db); });
        wg_commit();
      };
#pragma unroll
      for (int k = 0; k < 4; k++) gelu8(0, k);
      fence_async_smem();
      signal(JOB + 4);
      nb_sync<NB_BOTH>(256);
      static_for<0, 18>([&](auto nn) {
        constexpr int n = nn.value, p = n % 6;
        if (n == 9 || n == 17) mbar_wait(BAR(JOB + 4 + (n >> 3)), L);
        mbar_wait(BAR(F4 + p), (n / 6 + (p >= 2 ? L : 0)) & 1);
        wg_fence();
        static_for<0, 4>([&](auto kk) {
          wgmma_128<1, 1, DI(slot4(p) + kk.value * 2048, 8192), DI((n == 9 ? OFF_X + 16384 : n % 17 ? slot4(p) + 16384 : OFF_X) + kk.value * 2048, 8192)>(xa, sda, sd);
        });
        wg_commit();
        if (n) { wg_wait<1>(); release(E4 + (n + 5) % 6); }
        if (n == 8) mbar_wait(BAR(RD + 2), L);
        else if (n < 16 && !(n & 1)) sched_fence(P.zero);
        if constexpr (n < 16 && !(n & 1)) gelu8(1 + (n >> 3), (n >> 1) & 3);
        if ((n & 7) == 7) { fence_async_smem(); signal(JOB + 5 + (n >> 3)); }
      });
      {
        int p = 0, pp = 5;
        uint32_t par = L ? 0x03 : 0x3f;
        auto g4_loop = [&](int n0, int n1, int nrel) {
#pragma unroll 1
          for (int n = n0; n < n1; n++) {
            mbar_wait(BAR(F4 + p), (par >> p) & 1);
            par ^= 1u << p;
            g4_issue(p, slot4(p) + 16384);
            wg_wait<1>();
            if (n > nrel) release(E4 + pp);
            pp = p; if (++p == 6) p = 0;
          }
        };
        g4_loop(18, 56 - LEAD4, 0);
        if (wg == 1) { wg_wait<0>(); release(E4 + pp); nb_sync<NB_LEAD>(256); }
        static_for<56 - LEAD4, 56>([&](auto nn) {
          constexpr int n = nn.value, p = n % 6;
          mbar_wait(BAR(F4 + p), (n / 6 + (p >= 2 ? L : 0)) & 1);
          wg_fence();
          static_for<0, 4>([&](auto kk) { wgmma_128<1, 1, DI(slot4(p) + kk.value * 2048, 8192), DI(slot4(p) + 16384 + kk.value * 2048, 8192)>(xa, sda, sd); });
          wg_commit();
          if (n == 55 && wg == 0) nb_arrive<NB_LEAD>(256);
          wg_wait<1>();
          if (n > 56 - LEAD4 || wg == 0) release(E4 + (n + 5) % 6);
        });
      }
      uint32_t xs;
      uint8_t* xg;
      {
        GEOM;
        xs = sb + OFF_X + wu * 2048 + (lane >> 3) * 128 + ((L ? l7 ^ (lane >> 3) : l7) << 4);
        xg = L ? P.out + (128 * opq(i) + 16 * wu + (lane >> 3)) * 2048 + 256 * j + 16 * l7 : gXB + (opq(i) * 16 + 2 * j) * 16384 + wu * 2048 + lane * 16;
        asm volatile("" : "+r"(xs), "+l"(xg));
      }
      mbar_wait(BAR(RD + 1), L);
      wg_wait<0>();
      release(E4 + 1);
      fence_regs(xa);
      {
        GEOM;
#pragma unroll
        for (int t = 0; t < 16; t += 2) {
          stsm4(sb + OFF_X + (t >> 3) * 16384 + (16 * wu + lr) * 128 + ((((t & 7) + lt) ^ l7) << 4),
                pack2(xa[4 * t], xa[4 * t + 1]), pack2(xa[4 * t + 2], xa[4 * t + 3]),
                pack2(xa[4 * t + 4], xa[4 * t + 5]), pack2(xa[4 * t + 6], xa[4 * t + 7]));
          if ((t & 7) == 6 && (L || t == 6)) {
            __syncwarp();
            uint4 v[4];
#pragma unroll
            for (int k = 0; k < 4; k++) lds128((xs ^ (L ? (k & 1) << 6 : 0)) + k * 512 + (t >> 3) * 16384, v[k].x, v[k].y, v[k].z, v[k].w);
#pragma unroll
            for (int k = 0; k < 4; k++)
              asm volatile("st.global.v4.b32 [%0], {%1, %2, %3, %4};" ::"l"(xg + k * (L ? 8192 : 512) + (t >> 3) * 128), "r"(v[k].x), "r"(v[k].y), "r"(v[k].z), "r"(v[k].w) : "memory");
            if (L == 0) signal(JOB + 8);
          }
        }
        if (L) break;
        fence_async_smem();
        signal(JOB + 9);
        nb_sync<NB_BOTH>(256);
      }
    }
    cluster_bar();
  }
}

typedef CUresult (*EncodeFn)(CUtensorMap*, CUtensorMapDataType, cuuint32_t, void*, const cuuint64_t*, const cuuint64_t*, const cuuint32_t*,
                             const cuuint32_t*, CUtensorMapInterleave, CUtensorMapSwizzle, CUtensorMapL2promotion, CUtensorMapFloatOOBfill);

void make_map(EncodeFn enc, CUtensorMap* mp, const void* base, int rank, cuuint64_t d0, cuuint64_t d1, cuuint64_t d2, cuuint64_t s1, cuuint64_t s2,
              cuuint32_t b0, cuuint32_t b1, cuuint32_t b2) {
  cuuint64_t dims[3] = {d0, d1, d2}, strides[2] = {s1, s2};
  cuuint32_t box[3] = {b0, b1, b2}, es[3] = {1, 1, 1};
  CUresult res = enc(mp, CU_TENSOR_MAP_DATA_TYPE_BFLOAT16, rank, const_cast<void*>(base), dims, strides, box, es, CU_TENSOR_MAP_INTERLEAVE_NONE,
                     CU_TENSOR_MAP_SWIZZLE_128B, CU_TENSOR_MAP_L2_PROMOTION_L2_128B, CU_TENSOR_MAP_FLOAT_OOB_FILL_NONE);
  (void)res;
}

}

extern "C" void kernel_launch(void* const* d_in, const int* in_sizes, int n_in, void* d_out, int out_size) {
  (void)in_sizes; (void)n_in; (void)out_size;
  static EncodeFn enc = nullptr;
  if (!enc) {
    void* fn = nullptr;
    cudaDriverEntryPointQueryResult qr;
    cudaGetDriverEntryPoint("cuTensorMapEncodeTiled", &fn, cudaEnableDefault, &qr);
    enc = (EncodeFn)fn;
    cudaFuncSetAttribute(fused_kernel, cudaFuncAttributeMaxDynamicSharedMemorySize, SMEM_BYTES);
  }
  Params P;
  make_map(enc, &P.x0, d_in[0], 2, D_, S_, 1, D_ * 2, 0, 64, 128, 1);
  make_map(enc, &P.wqkv, d_in[1], 3, D_, D_, 3, 3 * D_ * 2, D_ * 2, 64, 32, 3);
  make_map(enc, &P.wo, d_in[2], 2, D_, D_, 1, D_ * 2, 0, 64, 64, 1);
  make_map(enc, &P.w1, d_in[4], 3, 64, S_, F_ / 64, F_ * 2, 128, 64, 64, 3);
  make_map(enc, &P.w1h, d_in[4], 3, 32, S_, F_ / 32, F_ * 2, 64, 64, 64, 1);
  make_map(enc, &P.w2, d_in[6], 3, 64, F_, S_ / 64, S_ * 2, 128, 64, 64, 2);
  P.out = (uint8_t*)d_out;
  P.wqkv_p = (const bf16*)d_in[1];
  P.wo_p = (const bf16*)d_in[2];
  P.w1_p = (const bf16*)d_in[4];
  P.b1 = (const bf16*)d_in[5];
  P.b2 = (const bf16*)d_in[7];
  P.zero = 0;
  fused_kernel<<<128, 384, SMEM_BYTES>>>(P);
}
```

```cpp
#include <cuda_runtime.h>
#include <cuda_bf16.h>
#include <cuda.h>
#include <stdint.h>

namespace {

typedef __nv_bfloat16 bf16;
constexpr int S_ = 2048, D_ = 1024, F_ = 3584;

constexpr uint32_t OFF_STG  = 163840;
constexpr uint32_t OFF_X    = 196608;
constexpr uint32_t OFF_BAR  = 229376;
constexpr uint32_t OFF_CS   = OFF_BAR + 512;
constexpr uint32_t OFF_B1   = OFF_CS + 1536;
constexpr uint32_t SMEM_BYTES = OFF_B1 + 896 + 128;
constexpr int F1 = 0, E1 = 4, F2 = 8, E2 = 13, F3 = 18, E3 = 22, F4 = 26, E4 = 32;
constexpr int JOB = 38;
constexpr int RD = 48;
constexpr int XF = 54, STD = 56, STAT = 58, FOLD = 59, CSJ = 61, HALO = 62;
constexpr int NB_BOTH = 1, NB_INIT = 2, NB_LEAD = 3, NB_WG0 = 4;

__host__ __device__ constexpr uint32_t slot1(int p) { return p * 40960; }
__host__ __device__ constexpr uint32_t slot2(int p) { return p * 32768; }
__host__ __device__ constexpr uint32_t slot3(int p) { return ((p + 2) & 3) * 49152; }
__host__ __device__ constexpr uint32_t slot4(int p) { return (p < 2 ? p + 4 : p - 2) * 32768; }

__device__ __align__(1024) uint8_t gXB[16 * 16 * 16384];
__device__ __align__(1024) uint8_t gOB[16 * 16 * 16384];
__device__ __align__(1024) uint8_t gHB[8 * 32 * 16384];
__device__ __align__(1024) uint8_t gUB[8 * 56 * 16384];
__device__ __align__(1024) uint2   gST[2][16][8][8][16];
__device__ __align__(1024) uint4   gHalo[2][16][8][12][32];
__device__ __align__(1024) uint32_t gAck[2][16][8][2][8];
__device__ __align__(1024) uint4   gCS[8][16][64];
__device__ __align__(1024) uint32_t gFlag[2][7][16][32];
__device__ uint32_t gEpoch;

struct Params {
  CUtensorMap x0, wqkv, wo, w1, w1h, w2;
  uint8_t* out;
  const bf16 *wo_p, *w1_p, *b1, *b2;
  uint32_t zero;
};

template <int TA, int TB, uint32_t IA, uint32_t IB, int O = 0, int LEN> __device__ __forceinline__ void wgmma_32(float (&d)[LEN], uint32_t da, uint32_t db) {
  asm volatile("{\n.reg .b64 da, db;\n.reg .b32 la, lb;\nadd.u32 la, %16, %20;\nadd.u32 lb, %17, %21;\nmov.b64 da, {la, 0x40000040};\nmov.b64 db, {lb, 0x40000040};\n"
  "wgmma.mma_async.sync.aligned.m64n32k16.f32.bf16.bf16 {"
  "%0, %1, %2, %3, %4, %5, %6, %7, %8, %9, %10, %11, %12, %13, %14, %15"
  "}, da, db, 1, 1, 1, %18, %19;\n}\n"
  : "+f"(d[O + 0]), "+f"(d[O + 1]), "+f"(d[O + 2]), "+f"(d[O + 3]), "+f"(d[O + 4]), "+f"(d[O + 5]), "+f"(d[O + 6]), "+f"(d[O + 7]),
    "+f"(d[O + 8]), "+f"(d[O + 9]), "+f"(d[O + 10]), "+f"(d[O + 11]), "+f"(d[O + 12]), "+f"(d[O + 13]), "+f"(d[O + 14]), "+f"(d[O + 15])
  : "r"(da), "r"(db), "n"(TA), "n"(TB), "n"(IA), "n"(IB));
}
template <int TA, int TB, uint32_t IA, uint32_t IB, int O = 0, int LEN> __device__ __forceinline__ void wgmma_128(float (&d)[LEN], uint32_t da, uint32_t db) {
  asm volatile("{\n.reg .b64 da, db;\n.reg .b32 la, lb;\nadd.u32 la, %64, %68;\nadd.u32 lb, %65, %69;\nmov.b64 da, {la, 0x40000040};\nmov.b64 db, {lb, 0x40000040};\n"
  "wgmma.mma_async.sync.aligned.m64n128k16.f32.bf16.bf16 {"
  "%0, %1, %2, %3, %4, %5, %6, %7, %8, %9, %10, %11, %12, %13, %14, %15, "
  "%16, %17, %18, %19, %20, %21, %22, %23, %24, %25, %26, %27, %28, %29, %30, %31, "
  "%32, %33, %34, %35, %36, %37, %38, %39, %40, %41, %42, %43, %44, %45, %46, %47, "
  "%48, %49, %50, %51, %52, %53, %54, %55, %56, %57, %58, %59, %60, %61, %62, %63"
  "}, da, db, 1, 1, 1, %66, %67;\n}\n"
  : "+f"(d[O + 0]), "+f"(d[O + 1]), "+f"(d[O + 2]), "+f"(d[O + 3]), "+f"(d[O + 4]), "+f"(d[O + 5]), "+f"(d[O + 6]), "+f"(d[O + 7]),
    "+f"(d[O + 8]), "+f"(d[O + 9]), "+f"(d[O + 10]), "+f"(d[O + 11]), "+f"(d[O + 12]), "+f"(d[O + 13]), "+f"(d[O + 14]), "+f"(d[O + 15]),
    "+f"(d[O + 16]), "+f"(d[O + 17]), "+f"(d[O + 18]), "+f"(d[O + 19]), "+f"(d[O + 20]), "+f"(d[O + 21]), "+f"(d[O + 22]), "+f"(d[O + 23]),
    "+f"(d[O + 24]), "+f"(d[O + 25]), "+f"(d[O + 26]), "+f"(d[O + 27]), "+f"(d[O + 28]), "+f"(d[O + 29]), "+f"(d[O + 30]), "+f"(d[O + 31]),
    "+f"(d[O + 32]), "+f"(d[O + 33]), "+f"(d[O + 34]), "+f"(d[O + 35]), "+f"(d[O + 36]), "+f"(d[O + 37]), "+f"(d[O + 38]), "+f"(d[O + 39]),
    "+f"(d[O + 40]), "+f"(d[O + 41]), "+f"(d[O + 42]), "+f"(d[O + 43]), "+f"(d[O + 44]), "+f"(d[O + 45]), "+f"(d[O + 46]), "+f"(d[O + 47]),
    "+f"(d[O + 48]), "+f"(d[O + 49]), "+f"(d[O + 50]), "+f"(d[O + 51]), "+f"(d[O + 52]), "+f"(d[O + 53]), "+f"(d[O + 54]), "+f"(d[O + 55]),
    "+f"(d[O + 56]), "+f"(d[O + 57]), "+f"(d[O + 58]), "+f"(d[O + 59]), "+f"(d[O + 60]), "+f"(d[O + 61]), "+f"(d[O + 62]), "+f"(d[O + 63])
  : "r"(da), "r"(db), "n"(TA), "n"(TB), "n"(IA), "n"(IB));
}
template <int TA, int TB, uint32_t IA, uint32_t IB, int O = 0, int LEN> __device__ __forceinline__ void wgmma_192(float (&d)[LEN], uint32_t da, uint32_t db) {
  asm volatile("{\n.reg .b64 da, db;\n.reg .b32 la, lb;\nadd.u32 la, %96, %100;\nadd.u32 lb, %97, %101;\nmov.b64 da, {la, 0x40000040};\nmov.b64 db, {lb, 0x40000040};\n"
  "wgmma.mma_async.sync.aligned.m64n192k16.f32.bf16.bf16 {"
  "%0, %1, %2, %3, %4, %5, %6, %7, %8, %9, %10, %11, %12, %13, %14, %15, "
  "%16, %17, %18, %19, %20, %21, %22, %23, %24, %25, %26, %27, %28, %29, %30, %31, "
  "%32, %33, %34, %35, %36, %37, %38, %39, %40, %41, %42, %43, %44, %45, %46, %47, "
  "%48, %49, %50, %51, %52, %53, %54, %55, %56, %57, %58, %59, %60, %61, %62, %63, "
  "%64, %65, %66, %67, %68, %69, %70, %71, %72, %73, %74, %75, %76, %77, %78, %79, "
  "%80, %81, %82, %83, %84, %85, %86, %87, %88, %89, %90, %91, %92, %93, %94, %95"
  "}, da, db, 1, 1, 1, %98, %99;\n}\n"
  : "+f"(d[O + 0]), "+f"(d[O + 1]), "+f"(d[O + 2]), "+f"(d[O + 3]), "+f"(d[O + 4]), "+f"(d[O + 5]), "+f"(d[O + 6]), "+f"(d[O + 7]),
    "+f"(d[O + 8]), "+f"(d[O + 9]), "+f"(d[O + 10]), "+f"(d[O + 11]), "+f"(d[O + 12]), "+f"(d[O + 13]), "+f"(d[O + 14]), "+f"(d[O + 15]),
    "+f"(d[O + 16]), "+f"(d[O + 17]), "+f"(d[O + 18]), "+f"(d[O + 19]), "+f"(d[O + 20]), "+f"(d[O + 21]), "+f"(d[O + 22]), "+f"(d[O + 23]),
    "+f"(d[O + 24]), "+f"(d[O + 25]), "+f"(d[O + 26]), "+f"(d[O + 27]), "+f"(d[O + 28]), "+f"(d[O + 29]), "+f"(d[O + 30]), "+f"(d[O + 31]),
    "+f"(d[O + 32]), "+f"(d[O + 33]), "+f"(d[O + 34]), "+f"(d[O + 35]), "+f"(d[O + 36]), "+f"(d[O + 37]), "+f"(d[O + 38]), "+f"(d[O + 39]),
    "+f"(d[O + 40]), "+f"(d[O + 41]), "+f"(d[O + 42]), "+f"(d[O + 43]), "+f"(d[O + 44]), "+f"(d[O + 45]), "+f"(d[O + 46]), "+f"(d[O + 47]),
    "+f"(d[O + 48]), "+f"(d[O + 49]), "+f"(d[O + 50]), "+f"(d[O + 51]), "+f"(d[O + 52]), "+f"(d[O + 53]), "+f"(d[O + 54]), "+f"(d[O + 55]),
    "+f"(d[O + 56]), "+f"(d[O + 57]), "+f"(d[O + 58]), "+f"(d[O + 59]), "+f"(d[O + 60]), "+f"(d[O + 61]), "+f"(d[O + 62]), "+f"(d[O + 63]),
    "+f"(d[O + 64]), "+f"(d[O + 65]), "+f"(d[O + 66]), "+f"(d[O + 67]), "+f"(d[O + 68]), "+f"(d[O + 69]), "+f"(d[O + 70]), "+f"(d[O + 71]),
    "+f"(d[O + 72]), "+f"(d[O + 73]), "+f"(d[O + 74]), "+f"(d[O + 75]), "+f"(d[O + 76]), "+f"(d[O + 77]), "+f"(d[O + 78]), "+f"(d[O + 79]),
    "+f"(d[O + 80]), "+f"(d[O + 81]), "+f"(d[O + 82]), "+f"(d[O + 83]), "+f"(d[O + 84]), "+f"(d[O + 85]), "+f"(d[O + 86]), "+f"(d[O + 87]),
    "+f"(d[O + 88]), "+f"(d[O + 89]), "+f"(d[O + 90]), "+f"(d[O + 91]), "+f"(d[O + 92]), "+f"(d[O + 93]), "+f"(d[O + 94]), "+f"(d[O + 95])
  : "r"(da), "r"(db), "n"(TA), "n"(TB), "n"(IA), "n"(IB));
}
template <int TA, int TB, uint32_t IA, uint32_t IB, int O = 0, int LEN> __device__ __forceinline__ void wgmma_192z(float (&d)[LEN], uint32_t da, uint32_t db) {
  asm volatile("{\n.reg .b64 da, db;\n.reg .b32 la, lb;\nadd.u32 la, %96, %100;\nadd.u32 lb, %97, %101;\nmov.b64 da, {la, 0x40000040};\nmov.b64 db, {lb, 0x40000040};\n"
  "wgmma.mma_async.sync.aligned.m64n192k16.f32.bf16.bf16 {"
  "%0, %1, %2, %3, %4, %5, %6, %7, %8, %9, %10, %11, %12, %13, %14, %15, "
  "%16, %17, %18, %19, %20, %21, %22, %23, %24, %25, %26, %27, %28, %29, %30, %31, "
  "%32, %33, %34, %35, %36, %37, %38, %39, %40, %41, %42, %43, %44, %45, %46, %47, "
  "%48, %49, %50, %51, %52, %53, %54, %55, %56, %57, %58, %59, %60, %61, %62, %63, "
  "%64, %65, %66, %67, %68, %69, %70, %71, %72, %73, %74, %75, %76, %77, %78, %79, "
  "%80, %81, %82, %83, %84, %85, %86, %87, %88, %89, %90, %91, %92, %93, %94, %95"
  "}, da, db, 0, 1, 1, %98, %99;\n}\n"
  : "=f"(d[O + 0]), "=f"(d[O + 1]), "=f"(d[O + 2]), "=f"(d[O + 3]), "=f"(d[O + 4]), "=f"(d[O + 5]), "=f"(d[O + 6]), "=f"(d[O + 7]),
    "=f"(d[O + 8]), "=f"(d[O + 9]), "=f"(d[O + 10]), "=f"(d[O + 11]), "=f"(d[O + 12]), "=f"(d[O + 13]), "=f"(d[O + 14]), "=f"(d[O + 15]),
    "=f"(d[O + 16]), "=f"(d[O + 17]), "=f"(d[O + 18]), "=f"(d[O + 19]), "=f"(d[O + 20]), "=f"(d[O + 21]), "=f"(d[O + 22]), "=f"(d[O + 23]),
    "=f"(d[O + 24]), "=f"(d[O + 25]), "=f"(d[O + 26]), "=f"(d[O + 27]), "=f"(d[O + 28]), "=f"(d[O + 29]), "=f"(d[O + 30]), "=f"(d[O + 31]),
    "=f"(d[O + 32]), "=f"(d[O + 33]), "=f"(d[O + 34]), "=f"(d[O + 35]), "=f"(d[O + 36]), "=f"(d[O + 37]), "=f"(d[O + 38]), "=f"(d[O + 39]),
    "=f"(d[O + 40]), "=f"(d[O + 41]), "=f"(d[O + 42]), "=f"(d[O + 43]), "=f"(d[O + 44]), "=f"(d[O + 45]), "=f"(d[O + 46]), "=f"(d[O + 47]),
    "=f"(d[O + 48]), "=f"(d[O + 49]), "=f"(d[O + 50]), "=f"(d[O + 51]), "=f"(d[O + 52]), "=f"(d[O + 53]), "=f"(d[O + 54]), "=f"(d[O + 55]),
    "=f"(d[O + 56]), "=f"(d[O + 57]), "=f"(d[O + 58]), "=f"(d[O + 59]), "=f"(d[O + 60]), "=f"(d[O + 61]), "=f"(d[O + 62]), "=f"(d[O + 63]),
    "=f"(d[O + 64]), "=f"(d[O + 65]), "=f"(d[O + 66]), "=f"(d[O + 67]), "=f"(d[O + 68]), "=f"(d[O + 69]), "=f"(d[O + 70]), "=f"(d[O + 71]),
    "=f"(d[O + 72]), "=f"(d[O + 73]), "=f"(d[O + 74]), "=f"(d[O + 75]), "=f"(d[O + 76]), "=f"(d[O + 77]), "=f"(d[O + 78]), "=f"(d[O + 79]),
    "=f"(d[O + 80]), "=f"(d[O + 81]), "=f"(d[O + 82]), "=f"(d[O + 83]), "=f"(d[O + 84]), "=f"(d[O + 85]), "=f"(d[O + 86]), "=f"(d[O + 87]),
    "=f"(d[O + 88]), "=f"(d[O + 89]), "=f"(d[O + 90]), "=f"(d[O + 91]), "=f"(d[O + 92]), "=f"(d[O + 93]), "=f"(d[O + 94]), "=f"(d[O + 95])
  : "r"(da), "r"(db), "n"(TA), "n"(TB), "n"(IA), "n"(IB));
}
template <int TA, int TB, uint32_t IA, uint32_t IB, int O = 0, int LEN> __device__ __forceinline__ void wgmma_224(float (&d)[LEN], uint32_t da, uint32_t db) {
  asm volatile("{\n.reg .b64 da, db;\n.reg .b32 la, lb;\nadd.u32 la, %112, %116;\nadd.u32 lb, %113, %117;\nmov.b64 da, {la, 0x40000040};\nmov.b64 db, {lb, 0x40000040};\n"
  "wgmma.mma_async.sync.aligned.m64n224k16.f32.bf16.bf16 {"
  "%0, %1, %2, %3, %4, %5, %6, %7, %8, %9, %10, %11, %12, %13, %14, %15, "
  "%16, %17, %18, %19, %20, %21, %22, %23, %24, %25, %26, %27, %28, %29, %30, %31, "
  "%32, %33, %34, %35, %36, %37, %38, %39, %40, %41, %42, %43, %44, %45, %46, %47, "
  "%48, %49, %50, %51, %52, %53, %54, %55, %56, %57, %58, %59, %60, %61, %62, %63, "
  "%64, %65, %66, %67, %68, %69, %70, %71, %72, %73, %74, %75, %76, %77, %78, %79, "
  "%80, %81, %82, %83, %84, %85, %86, %87, %88, %89, %90, %91, %92, %93, %94, %95, "
  "%96, %97, %98, %99, %100, %101, %102, %103, %104, %105, %106, %107, %108, %109, %110, %111"
  "}, da, db, 1, 1, 1, %114, %115;\n}\n"
  : "+f"(d[O + 0]), "+f"(d[O + 1]), "+f"(d[O + 2]), "+f"(d[O + 3]), "+f"(d[O + 4]), "+f"(d[O + 5]), "+f"(d[O + 6]), "+f"(d[O + 7]),
    "+f"(d[O + 8]), "+f"(d[O + 9]), "+f"(d[O + 10]), "+f"(d[O + 11]), "+f"(d[O + 12]), "+f"(d[O + 13]), "+f"(d[O + 14]), "+f"(d[O + 15]),
    "+f"(d[O + 16]), "+f"(d[O + 17]), "+f"(d[O + 18]), "+f"(d[O + 19]), "+f"(d[O + 20]), "+f"(d[O + 21]), "+f"(d[O + 22]), "+f"(d[O + 23]),
    "+f"(d[O + 24]), "+f"(d[O + 25]), "+f"(d[O + 26]), "+f"(d[O + 27]), "+f"(d[O + 28]), "+f"(d[O + 29]), "+f"(d[O + 30]), "+f"(d[O + 31]),
    "+f"(d[O + 32]), "+f"(d[O + 33]), "+f"(d[O + 34]), "+f"(d[O + 35]), "+f"(d[O + 36]), "+f"(d[O + 37]), "+f"(d[O + 38]), "+f"(d[O + 39]),
    "+f"(d[O + 40]), "+f"(d[O + 41]), "+f"(d[O + 42]), "+f"(d[O + 43]), "+f"(d[O + 44]), "+f"(d[O + 45]), "+f"(d[O + 46]), "+f"(d[O + 47]),
    "+f"(d[O + 48]), "+f"(d[O + 49]), "+f"(d[O + 50]), "+f"(d[O + 51]), "+f"(d[O + 52]), "+f"(d[O + 53]), "+f"(d[O + 54]), "+f"(d[O + 55]),
    "+f"(d[O + 56]), "+f"(d[O + 57]), "+f"(d[O + 58]), "+f"(d[O + 59]), "+f"(d[O + 60]), "+f"(d[O + 61]), "+f"(d[O + 62]), "+f"(d[O + 63]),
    "+f"(d[O + 64]), "+f"(d[O + 65]), "+f"(d[O + 66]), "+f"(d[O + 67]), "+f"(d[O + 68]), "+f"(d[O + 69]), "+f"(d[O + 70]), "+f"(d[O + 71]),
    "+f"(d[O + 72]), "+f"(d[O + 73]), "+f"(d[O + 74]), "+f"(d[O + 75]), "+f"(d[O + 76]), "+f"(d[O + 77]), "+f"(d[O + 78]), "+f"(d[O + 79]),
    "+f"(d[O + 80]), "+f"(d[O + 81]), "+f"(d[O + 82]), "+f"(d[O + 83]), "+f"(d[O + 84]), "+f"(d[O + 85]), "+f"(d[O + 86]), "+f"(d[O + 87]),
    "+f"(d[O + 88]), "+f"(d[O + 89]), "+f"(d[O + 90]), "+f"(d[O + 91]), "+f"(d[O + 92]), "+f"(d[O + 93]), "+f"(d[O + 94]), "+f"(d[O + 95]),
    "+f"(d[O + 96]), "+f"(d[O + 97]), "+f"(d[O + 98]), "+f"(d[O + 99]), "+f"(d[O + 100]), "+f"(d[O + 101]), "+f"(d[O + 102]), "+f"(d[O + 103]),
    "+f"(d[O + 104]), "+f"(d[O + 105]), "+f"(d[O + 106]), "+f"(d[O + 107]), "+f"(d[O + 108]), "+f"(d[O + 109]), "+f"(d[O + 110]), "+f"(d[O + 111])
  : "r"(da), "r"(db), "n"(TA), "n"(TB), "n"(IA), "n"(IB));
}
__device__ __forceinline__ void wgmma_rs_192(float (&d)[96], uint32_t a0, uint32_t a1, uint32_t a2, uint32_t a3, uint64_t db) {
  asm volatile("wgmma.mma_async.sync.aligned.m64n192k16.f32.bf16.bf16 {"
  "%0, %1, %2, %3, %4, %5, %6, %7, %8, %9, %10, %11, %12, %13, %14, %15, "
  "%16, %17, %18, %19, %20, %21, %22, %23, %24, %25, %26, %27, %28, %29, %30, %31, "
  "%32, %33, %34, %35, %36, %37, %38, %39, %40, %41, %42, %43, %44, %45, %46, %47, "
  "%48, %49, %50, %51, %52, %53, %54, %55, %56, %57, %58, %59, %60, %61, %62, %63, "
  "%64, %65, %66, %67, %68, %69, %70, %71, %72, %73, %74, %75, %76, %77, %78, %79, "
  "%80, %81, %82, %83, %84, %85, %86, %87, %88, %89, %90, %91, %92, %93, %94, %95"
  "}, {%96, %97, %98, %99}, %100, 1, 1, 1, 1;\n"
  : "+f"(d[0]), "+f"(d[1]), "+f"(d[2]), "+f"(d[3]), "+f"(d[4]), "+f"(d[5]), "+f"(d[6]), "+f"(d[7]),
    "+f"(d[8]), "+f"(d[9]), "+f"(d[10]), "+f"(d[11]), "+f"(d[12]), "+f"(d[13]), "+f"(d[14]), "+f"(d[15]),
    "+f"(d[16]), "+f"(d[17]), "+f"(d[18]), "+f"(d[19]), "+f"(d[20]), "+f"(d[21]), "+f"(d[22]), "+f"(d[23]),
    "+f"(d[24]), "+f"(d[25]), "+f"(d[26]), "+f"(d[27]), "+f"(d[28]), "+f"(d[29]), "+f"(d[30]), "+f"(d[31]),
    "+f"(d[32]), "+f"(d[33]), "+f"(d[34]), "+f"(d[35]), "+f"(d[36]), "+f"(d[37]), "+f"(d[38]), "+f"(d[39]),
    "+f"(d[40]), "+f"(d[41]), "+f"(d[42]), "+f"(d[43]), "+f"(d[44]), "+f"(d[45]), "+f"(d[46]), "+f"(d[47]),
    "+f"(d[48]), "+f"(d[49]), "+f"(d[50]), "+f"(d[51]), "+f"(d[52]), "+f"(d[53]), "+f"(d[54]), "+f"(d[55]),
    "+f"(d[56]), "+f"(d[57]), "+f"(d[58]), "+f"(d[59]), "+f"(d[60]), "+f"(d[61]), "+f"(d[62]), "+f"(d[63]),
    "+f"(d[64]), "+f"(d[65]), "+f"(d[66]), "+f"(d[67]), "+f"(d[68]), "+f"(d[69]), "+f"(d[70]), "+f"(d[71]),
    "+f"(d[72]), "+f"(d[73]), "+f"(d[74]), "+f"(d[75]), "+f"(d[76]), "+f"(d[77]), "+f"(d[78]), "+f"(d[79]),
    "+f"(d[80]), "+f"(d[81]), "+f"(d[82]), "+f"(d[83]), "+f"(d[84]), "+f"(d[85]), "+f"(d[86]), "+f"(d[87]),
    "+f"(d[88]), "+f"(d[89]), "+f"(d[90]), "+f"(d[91]), "+f"(d[92]), "+f"(d[93]), "+f"(d[94]), "+f"(d[95])
  : "r"(a0), "r"(a1), "r"(a2), "r"(a3), "l"(db));
}
__device__ __forceinline__ void wgmma_rs_224z(float (&d)[112], uint32_t a0, uint32_t a1, uint32_t a2, uint32_t a3, uint64_t db) {
  asm volatile("wgmma.mma_async.sync.aligned.m64n224k16.f32.bf16.bf16 {"
  "%0, %1, %2, %3, %4, %5, %6, %7, %8, %9, %10, %11, %12, %13, %14, %15, "
  "%16, %17, %18, %19, %20, %21, %22, %23, %24, %25, %26, %27, %28, %29, %30, %31, "
  "%32, %33, %34, %35, %36, %37, %38, %39, %40, %41, %42, %43, %44, %45, %46, %47, "
  "%48, %49, %50, %51, %52, %53, %54, %55, %56, %57, %58, %59, %60, %61, %62, %63, "
  "%64, %65, %66, %67, %68, %69, %70, %71, %72, %73, %74, %75, %76, %77, %78, %79, "
  "%80, %81, %82, %83, %84, %85, %86, %87, %88, %89, %90, %91, %92, %93, %94, %95, "
  "%96, %97, %98, %99, %100, %101, %102, %103, %104, %105, %106, %107, %108, %109, %110, %111"
  "}, {%112, %113, %114, %115}, %116, 0, 1, 1, 1;\n"
  : "=f"(d[0]), "=f"(d[1]), "=f"(d[2]), "=f"(d[3]), "=f"(d[4]), "=f"(d[5]), "=f"(d[6]), "=f"(d[7]),
    "=f"(d[8]), "=f"(d[9]), "=f"(d[10]), "=f"(d[11]), "=f"(d[12]), "=f"(d[13]), "=f"(d[14]), "=f"(d[15]),
    "=f"(d[16]), "=f"(d[17]), "=f"(d[18]), "=f"(d[19]), "=f"(d[20]), "=f"(d[21]), "=f"(d[22]), "=f"(d[23]),
    "=f"(d[24]), "=f"(d[25]), "=f"(d[26]), "=f"(d[27]), "=f"(d[28]), "=f"(d[29]), "=f"(d[30]), "=f"(d[31]),
    "=f"(d[32]), "=f"(d[33]), "=f"(d[34]), "=f"(d[35]), "=f"(d[36]), "=f"(d[37]), "=f"(d[38]), "=f"(d[39]),
    "=f"(d[40]), "=f"(d[41]), "=f"(d[42]), "=f"(d[43]), "=f"(d[44]), "=f"(d[45]), "=f"(d[46]), "=f"(d[47]),
    "=f"(d[48]), "=f"(d[49]), "=f"(d[50]), "=f"(d[51]), "=f"(d[52]), "=f"(d[53]), "=f"(d[54]), "=f"(d[55]),
    "=f"(d[56]), "=f"(d[57]), "=f"(d[58]), "=f"(d[59]), "=f"(d[60]), "=f"(d[61]), "=f"(d[62]), "=f"(d[63]),
    "=f"(d[64]), "=f"(d[65]), "=f"(d[66]), "=f"(d[67]), "=f"(d[68]), "=f"(d[69]), "=f"(d[70]), "=f"(d[71]),
    "=f"(d[72]), "=f"(d[73]), "=f"(d[74]), "=f"(d[75]), "=f"(d[76]), "=f"(d[77]), "=f"(d[78]), "=f"(d[79]),
    "=f"(d[80]), "=f"(d[81]), "=f"(d[82]), "=f"(d[83]), "=f"(d[84]), "=f"(d[85]), "=f"(d[86]), "=f"(d[87]),
    "=f"(d[88]), "=f"(d[89]), "=f"(d[90]), "=f"(d[91]), "=f"(d[92]), "=f"(d[93]), "=f"(d[94]), "=f"(d[95]),
    "=f"(d[96]), "=f"(d[97]), "=f"(d[98]), "=f"(d[99]), "=f"(d[100]), "=f"(d[101]), "=f"(d[102]), "=f"(d[103]),
    "=f"(d[104]), "=f"(d[105]), "=f"(d[106]), "=f"(d[107]), "=f"(d[108]), "=f"(d[109]), "=f"(d[110]), "=f"(d[111])
  : "r"(a0), "r"(a1), "r"(a2), "r"(a3), "l"(db));
}

__device__ __forceinline__ uint32_t smem_u32(const void* p) { return (uint32_t)__cvta_generic_to_shared(p); }
__device__ __forceinline__ void mbar_init(uint32_t bar, uint32_t cnt) { asm volatile("mbarrier.init.shared::cta.b64 [%0], %1;" ::"r"(bar), "r"(cnt) : "memory"); }
__device__ __forceinline__ void mbar_expect(uint32_t bar, uint32_t bytes) { asm volatile("mbarrier.arrive.expect_tx.shared::cta.b64 _, [%0], %1;" ::"r"(bar), "r"(bytes) : "memory"); }
__device__ __forceinline__ void mbar_arrive(uint32_t bar) { asm volatile("mbarrier.arrive.shared::cta.b64 _, [%0];" ::"r"(bar) : "memory"); }
__device__ __forceinline__ void mbar_arrive_cl(uint32_t cbar) { asm volatile("mbarrier.arrive.shared::cluster.b64 _, [%0];" ::"r"(cbar) : "memory"); }
__device__ __forceinline__ uint32_t mapa(uint32_t a, uint32_t cta) { uint32_t r; asm("mapa.shared::cluster.u32 %0, %1, %2;" : "=r"(r) : "r"(a), "r"(cta)); return r; }
__device__ __forceinline__ void mbar_wait(uint32_t bar, uint32_t parity) {
  asm volatile("{\n.reg .pred p;\n.reg .u32 n;\nmov.u32 n, 0;\n"
    "LAB_WAIT:\n"
    "mbarrier.try_wait.parity.shared::cta.b64 p, [%0], %1;\n"
    "@p bra LAB_DONE;\n"
    "add.u32 n, n, 1;\n"
    "setp.lt.u32 p, n, 2000000;\n"
    "@p bra LAB_WAIT;\n"
    "trap;\n"
    "LAB_DONE:\n}\n" ::"r"(bar), "r"(parity) : "memory");
}
constexpr uint32_t SPIN_MAX = 2000000;
__device__ __forceinline__ void tma2d(uint32_t dst, const CUtensorMap* m, uint32_t bar, int c0, int c1) {
  asm volatile("cp.async.bulk.tensor.2d.shared::cluster.global.mbarrier::complete_tx::bytes [%0], [%1, {%3, %4}], [%2];"
    ::"r"(dst), "l"(m), "r"(bar), "r"(c0), "r"(c1) : "memory");
}
__device__ __forceinline__ void tma2d_mc(uint32_t dst, const CUtensorMap* m, uint32_t bar, int c0, int c1) {
  asm volatile("cp.async.bulk.tensor.2d.shared::cluster.global.mbarrier::complete_tx::bytes.multicast::cluster [%0], [%1, {%3, %4}], [%2], %5;"
    ::"r"(dst), "l"(m), "r"(bar), "r"(c0), "r"(c1), "h"((uint16_t)3) : "memory");
}
__device__ __forceinline__ void tma3d(uint32_t dst, const CUtensorMap* m, uint32_t bar, int c0, int c1, int c2) {
  asm volatile("cp.async.bulk.tensor.3d.shared::cluster.global.mbarrier::complete_tx::bytes [%0], [%1, {%3, %4, %5}], [%2];"
    ::"r"(dst), "l"(m), "r"(bar), "r"(c0), "r"(c1), "r"(c2) : "memory");
}
__device__ __forceinline__ void tma3d_mc(uint32_t dst, const CUtensorMap* m, uint32_t bar, int c0, int c1, int c2) {
  asm volatile("cp.async.bulk.tensor.3d.shared::cluster.global.mbarrier::complete_tx::bytes.multicast::cluster [%0], [%1, {%3, %4, %5}], [%2], %6;"
    ::"r"(dst), "l"(m), "r"(bar), "r"(c0), "r"(c1), "r"(c2), "h"((uint16_t)3) : "memory");
}
__device__ __forceinline__ void bulk_ld(uint32_t dst, const void* src, uint32_t bytes, uint32_t bar) {
  asm volatile("cp.async.bulk.shared::cluster.global.mbarrier::complete_tx::bytes [%0], [%1], %2, [%3];" ::"r"(dst), "l"(src), "r"(bytes), "r"(bar) : "memory");
}
__device__ __forceinline__ void bulk_ld_mc(uint32_t dst, const void* src, uint32_t bytes, uint32_t bar) {
  asm volatile("cp.async.bulk.shared::cluster.global.mbarrier::complete_tx::bytes.multicast::cluster [%0], [%1], %2, [%3], %4;"
    ::"r"(dst), "l"(src), "r"(bytes), "r"(bar), "h"((uint16_t)3) : "memory");
}
__device__ __forceinline__ void bulk_st(void* dst, uint32_t src, uint32_t bytes) {
  asm volatile("cp.async.bulk.global.shared::cta.bulk_group [%0], [%1], %2;" ::"l"(dst), "r"(src), "r"(bytes) : "memory");
}
__device__ __forceinline__ void bulk_s2s(uint32_t cdst, uint32_t src, uint32_t bytes, uint32_t cbar) {
  asm volatile("cp.async.bulk.shared::cluster.shared::cta.mbarrier::complete_tx::bytes [%0], [%1], %2, [%3];" ::"r"(cdst), "r"(src), "r"(bytes), "r"(cbar) : "memory");
}
__device__ __forceinline__ void bulk_commit() { asm volatile("cp.async.bulk.commit_group;" ::: "memory"); }
__device__ __forceinline__ void bulk_wait0() { asm volatile("cp.async.bulk.wait_group 0;" ::: "memory"); }
__device__ __forceinline__ void fence_async_smem() { asm volatile("fence.proxy.async.shared::cta;" ::: "memory"); }
__device__ __forceinline__ void wg_fence() { asm volatile("wgmma.fence.sync.aligned;" ::: "memory"); }
__device__ __forceinline__ void wg_commit() { asm volatile("wgmma.commit_group.sync.aligned;" ::: "memory"); }
template <int N> __device__ __forceinline__ void wg_wait() { asm volatile("wgmma.wait_group.sync.aligned %0;" ::"n"(N) : "memory"); }
template <int R> __device__ __forceinline__ void reg_alloc() { asm volatile("setmaxnreg.inc.sync.aligned.u32 %0;" ::"n"(R)); }
template <int R> __device__ __forceinline__ void reg_dealloc() { asm volatile("setmaxnreg.dec.sync.aligned.u32 %0;" ::"n"(R)); }
__device__ __forceinline__ void cluster_bar() { asm volatile("barrier.cluster.arrive.relaxed;\nbarrier.cluster.wait;" ::: "memory"); }
template <int ID> __device__ __forceinline__ void nb_sync(int n) { asm volatile("barrier.sync %0, %1;" ::"n"(ID), "r"(n) : "memory"); }
template <int ID> __device__ __forceinline__ void nb_arrive(int n) { asm volatile("barrier.arrive %0, %1;" ::"n"(ID), "r"(n) : "memory"); }
__device__ __forceinline__ int fresh_tid() { int t; asm volatile("mov.u32 %0, %%tid.x;" : "=r"(t)); return t; }
__device__ __forceinline__ void sched_fence(uint32_t z) { asm volatile("{\n.reg .pred p;\nsetp.ne.u32 p, %0, 0;\nLAB_S:\n@p nanosleep.u32 0;\n@p bra LAB_S;\n}\n" ::"r"(z) : "memory"); }
__device__ __forceinline__ float rsq(float x) { float y; asm("rsqrt.approx.ftz.f32 %0, %1;" : "=f"(y) : "f"(x)); return y; }
__device__ __forceinline__ int opq(int v) { asm volatile("" : "+r"(v)); return v; }
template <int V> struct Int { static constexpr int value = V; };
struct True { static constexpr bool value = true; };
struct False { static constexpr bool value = false; };
template <int N> __device__ __forceinline__ void fence_regs(float (&d)[N]) {
#pragma unroll
  for (int i = 0; i < N; i++) asm volatile("" : "+f"(d[i])::"memory");
}
__host__ __device__ constexpr uint32_t DI(uint32_t off, uint32_t lbo) { return (off >> 4) + ((lbo >> 4) << 16); }
template <int K, int N, class F> __device__ __forceinline__ void static_for(F f) { if constexpr (K < N) { f(Int<K>{}); static_for<K + 1, N>(f); } }
__device__ __forceinline__ uint64_t mkdesc_vec(uint32_t addr, uint32_t sbo) { return (uint64_t)((addr & 0x3FFFF) >> 4) | ((uint64_t)(sbo >> 4) << 32); }
__device__ __forceinline__ void sts16(uint32_t a, uint32_t v) { asm volatile("st.shared.u16 [%0], %1;" ::"r"(a), "h"((uint16_t)v) : "memory"); }
__device__ __forceinline__ uint32_t pack2(float lo, float hi) { uint32_t r; asm("cvt.rn.bf16x2.f32 %0, %1, %2;" : "=r"(r) : "f"(hi), "f"(lo)); return r; }
__device__ __forceinline__ float bf_lo(uint32_t v) { return __uint_as_float(v << 16); }
__device__ __forceinline__ float bf_hi(uint32_t v) { return __uint_as_float(v & 0xffff0000u); }
__device__ __forceinline__ void stsm4(uint32_t a, uint32_t r0, uint32_t r1, uint32_t r2, uint32_t r3) {
  asm volatile("stmatrix.sync.aligned.m8n8.x4.shared.b16 [%0], {%1, %2, %3, %4};" ::"r"(a), "r"(r0), "r"(r1), "r"(r2), "r"(r3) : "memory");
}
__device__ __forceinline__ void stsm4t(uint32_t a, uint32_t r0, uint32_t r1, uint32_t r2, uint32_t r3) {
  asm volatile("stmatrix.sync.aligned.m8n8.x4.trans.shared.b16 [%0], {%1, %2, %3, %4};" ::"r"(a), "r"(r0), "r"(r1), "r"(r2), "r"(r3) : "memory");
}
__device__ __forceinline__ void ldsm4(uint32_t a, uint32_t& r0, uint32_t& r1, uint32_t& r2, uint32_t& r3) {
  asm volatile("ldmatrix.sync.aligned.m8n8.x4.shared.b16 {%0, %1, %2, %3}, [%4];" : "=r"(r0), "=r"(r1), "=r"(r2), "=r"(r3) : "r"(a) : "memory");
}
__device__ __forceinline__ void ldsm4t(uint32_t a, uint32_t& r0, uint32_t& r1, uint32_t& r2, uint32_t& r3) {
  asm volatile("ldmatrix.sync.aligned.m8n8.x4.trans.shared.b16 {%0, %1, %2, %3}, [%4];" : "=r"(r0), "=r"(r1), "=r"(r2), "=r"(r3) : "r"(a) : "memory");
}
__device__ __forceinline__ void mma16816(float (&c)[4], uint32_t a0, uint32_t a1, uint32_t a2, uint32_t a3, uint32_t b0, uint32_t b1) {
  asm volatile("mma.sync.aligned.m16n8k16.row.col.f32.bf16.bf16.f32 {%0, %1, %2, %3}, {%4, %5, %6, %7}, {%8, %9}, {%10, %11, %12, %13};"
    : "=f"(c[0]), "=f"(c[1]), "=f"(c[2]), "=f"(c[3]) : "r"(a0), "r"(a1), "r"(a2), "r"(a3), "r"(b0), "r"(b1), "f"(c[0]), "f"(c[1]), "f"(c[2]), "f"(c[3]));
}
__device__ __forceinline__ void sts128(uint32_t a, uint32_t r0, uint32_t r1, uint32_t r2, uint32_t r3) {
  asm volatile("st.shared.v4.b32 [%0], {%1, %2, %3, %4};" ::"r"(a), "r"(r0), "r"(r1), "r"(r2), "r"(r3) : "memory");
}
__device__ __forceinline__ void lds128(uint32_t a, uint32_t& r0, uint32_t& r1, uint32_t& r2, uint32_t& r3) {
  asm volatile("ld.shared.v4.b32 {%0, %1, %2, %3}, [%4];" : "=r"(r0), "=r"(r1), "=r"(r2), "=r"(r3) : "r"(a) : "memory");
}
__device__ __forceinline__ void sts64f(uint32_t a, float x, float y) { asm volatile("st.shared.v2.f32 [%0], {%1, %2};" ::"r"(a), "f"(x), "f"(y) : "memory"); }
__device__ __forceinline__ float lds32f(uint32_t a) { float v; asm volatile("ld.shared.f32 %0, [%1];" : "=f"(v) : "r"(a) : "memory"); return v; }
__device__ __forceinline__ void sts32f(uint32_t a, float x) { asm volatile("st.shared.f32 [%0], %1;" ::"r"(a), "f"(x) : "memory"); }
__device__ __forceinline__ void stat_st(uint2* p, float sum, float sq, uint32_t tag, bool on) {
  const float mean = sum * (1.f / 128), m2 = fmaxf(fmaf(-mean, sum, sq), 0.f);
  const uint32_t a = ((__float_as_uint(mean) + 8u) & ~15u) | (tag & 15u), b = ((__float_as_uint(m2) + 8u) & ~15u) | (tag & 15u);
  asm volatile("{\n.reg .b64 x;\n.reg .pred p;\nsetp.ne.u32 p, %3, 0;\nmov.b64 x, {%1, %2};\n@p st.relaxed.gpu.global.b64 [%0], x;\n}\n" ::"l"(p), "r"(a), "r"(b), "r"((uint32_t)on) : "memory");
}
__device__ __forceinline__ void stat_ld2(const uint2* p, uint32_t (&v)[4]) {
  asm volatile("{\n.reg .b64 x, y;\nld.relaxed.gpu.global.v2.b64 {x, y}, [%4];\nmov.b64 {%0, %1}, x;\nmov.b64 {%2, %3}, y;\n}\n"
    : "=r"(v[0]), "=r"(v[1]), "=r"(v[2]), "=r"(v[3]) : "l"(p) : "memory");
}
__device__ __forceinline__ float untag(uint32_t v) { return __uint_as_float(v & ~15u); }
__device__ __forceinline__ void ll_st3(uint4* p, uint32_t a, uint32_t b, uint32_t c, uint32_t tag) {
  asm volatile("{\n.reg .b64 x, y;\n.reg .b128 z;\nmov.b64 x, {%1, %2};\nmov.b64 y, {%3, %4};\nmov.b128 z, {x, y};\nst.relaxed.gpu.global.b128 [%0], z;\n}\n"
    ::"l"(p), "r"(a), "r"(b), "r"(c), "r"(tag) : "memory");
}
__device__ __forceinline__ uint32_t ll_ld3(const uint4* p, uint32_t& a, uint32_t& b, uint32_t& c, uint32_t tag) {
  uint32_t t;
  asm volatile("{\n.reg .b64 x, y;\n.reg .b128 z;\nld.relaxed.gpu.global.b128 z, [%4];\nmov.b128 {x, y}, z;\nmov.b64 {%0, %1}, x;\nmov.b64 {%2, %3}, y;\n}\n"
    : "=r"(a), "=r"(b), "=r"(c), "=r"(t) : "l"(p) : "memory");
  return t ^ tag;
}
__device__ __forceinline__ void halo_send(uint4* p, uint32_t a, const uint32_t (&tg)[6]) {
  asm volatile("{\n.reg .b64 x<6>, y<6>, w<2>;\n.reg .b32 c<4>;\n.reg .b128 z<6>;\n"
    "ld.shared.b64 w0, [%1+1536];\nld.shared.b64 w1, [%1+1792];\n"
    "ld.shared.b64 x0, [%1];\nld.shared.b64 x1, [%1+256];\nld.shared.b64 x2, [%1+512];\n"
    "ld.shared.b64 x3, [%1+768];\nld.shared.b64 x4, [%1+1024];\nld.shared.b64 x5, [%1+1280];\n"
    "mov.b64 {c0, c1}, w0;\nmov.b64 {c2, c3}, w1;\n"
    "mov.b64 y0, {c0, %2};\nmov.b64 y1, {c1, %3};\nmov.b64 y2, {c2, %4};\nmov.b64 y3, {c3, %5};\nmov.b64 y4, {%6, %6};\nmov.b64 y5, {%7, %7};\n"
    "mov.b128 z0, {x0, y0};\nmov.b128 z1, {x1, y1};\nmov.b128 z2, {x2, y2};\nmov.b128 z3, {x3, y3};\nmov.b128 z4, {x4, y4};\nmov.b128 z5, {x5, y5};\n"
    "st.relaxed.gpu.global.b128 [%0], z0;\nst.relaxed.gpu.global.b128 [%0+512], z1;\nst.relaxed.gpu.global.b128 [%0+1024], z2;\n"
    "st.relaxed.gpu.global.b128 [%0+1536], z3;\nst.relaxed.gpu.global.b128 [%0+2048], z4;\nst.relaxed.gpu.global.b128 [%0+2560], z5;\n}\n"
    ::"l"(p), "r"(a), "r"(tg[0]), "r"(tg[1]), "r"(tg[2]), "r"(tg[3]), "r"(tg[4]), "r"(tg[5]) : "memory");
}
template <int N> __device__ __forceinline__ void copy_out(uint8_t* dst, uint32_t src, int stride) {
  uint4 v[N];
#pragma unroll
  for (int k = 0; k < N; k++) lds128(src + k * stride, v[k].x, v[k].y, v[k].z, v[k].w);
#pragma unroll
  for (int k = 0; k < N; k++) asm volatile("st.global.v4.b32 [%0], {%1, %2, %3, %4};" ::"l"(dst + k * stride), "r"(v[k].x), "r"(v[k].y), "r"(v[k].z), "r"(v[k].w) : "memory");
}
__device__ __forceinline__ void warp_store(uint8_t* dst, uint32_t src, int bytes, uint32_t delay, uint32_t pace) {
  __nanosleep(delay);
#pragma unroll 1
  for (int o = 0; o < bytes; o += 2048) {
    if (pace) __nanosleep(pace);
    uint4 v[4];
#pragma unroll
    for (int k = 0; k < 4; k++) lds128(src + o + k * 512, v[k].x, v[k].y, v[k].z, v[k].w);
#pragma unroll
    for (int k = 0; k < 4; k++) asm volatile("st.global.v4.b32 [%0], {%1, %2, %3, %4};" ::"l"(dst + o + k * 512), "r"(v[k].x), "r"(v[k].y), "r"(v[k].z), "r"(v[k].w) : "memory");
  }
  __syncwarp();
}
__device__ __forceinline__ uint32_t clock32() { uint32_t t; asm volatile("mov.u32 %0, %%clock;" : "=r"(t)); return t; }
__device__ __forceinline__ void flag_set(uint32_t* p, uint32_t bit) { asm volatile("red.release.gpu.global.xor.b32 [%0], %1;" ::"l"(p), "r"(bit) : "memory"); }
__device__ __forceinline__ void flag_wait(const uint32_t* p, uint32_t inv, uint32_t need, uint32_t& ready) {
  if ((ready & need) == need) return;
  uint32_t n = 0;
  do {
    asm volatile("ld.relaxed.gpu.global.b32 %0, [%1];" : "=r"(ready) : "l"(p) : "memory");
    ready = __shfl_sync(0xffffffffu, ready, 0) ^ inv;
  } while ((ready & need) != need && ++n < SPIN_MAX);
  asm volatile("fence.acquire.gpu;\nfence.proxy.async.global;" ::: "memory");
}
__device__ __forceinline__ bool elect_one() {
  uint32_t p;
  asm volatile("{\n.reg .pred P;\nelect.sync _|P, 0xffffffff;\nselp.u32 %0, 1, 0, P;\n}\n" : "=r"(p));
  return p;
}
__device__ __forceinline__ float gelu_half(float hx) {
  const float y = hx * fmaf(hx * hx, 8.f * 0.0356774081f, 2.f * 0.7978845608f);
  float th;
  asm("tanh.approx.f32 %0, %1;" : "=f"(th) : "f"(y));
  return fmaf(hx, th, hx);
}
__device__ __forceinline__ float ex2(float x) { float y; asm("ex2.approx.ftz.f32 %0, %1;" : "=f"(y) : "f"(x)); return y; }

__device__ __forceinline__ void stat_combine(uint32_t am, uint32_t aq, uint32_t bm, uint32_t bq, float pv, float& mean, float& var) {
  const float d0 = untag(am) - pv, d1 = untag(bm) - pv;
  float s = d0 + d1, q = fmaf(fmaf(d0, d0, d1 * d1), 128.f, untag(aq) + untag(bq));
  s += __shfl_xor_sync(0xffffffffu, s, 8); q += __shfl_xor_sync(0xffffffffu, q, 8);
  s += __shfl_xor_sync(0xffffffffu, s, 16); q += __shfl_xor_sync(0xffffffffu, q, 16);
  s *= 0.125f;
  mean = pv + s;
  var = fmaxf(fmaf(-s, s, q * (1.f / D_)), 0.f);
}

__device__ __forceinline__ void attn_logits(const uint32_t* q0, const uint32_t* q1,
                                            const uint32_t* k0, const uint32_t* k1, const uint32_t* k2, const uint32_t* k3,
                                            float mk0, float mk1, float (&s)[4][4]) {
#pragma unroll
  for (int n = 0; n < 4; n++) {
    const uint32_t* k = n == 0 ? k0 : n == 1 ? k1 : n == 2 ? k2 : k3;
    s[n][0] = s[n][1] = n < 2 ? mk0 : 0.f; s[n][2] = s[n][3] = n < 2 ? mk1 : 0.f;
    mma16816(s[n], q0[0], q1[0], q0[1], q1[1], k[0], k[1]);
    mma16816(s[n], q0[2], q1[2], q0[3], q1[3], k[2], k[3]);
  }
}
__device__ __forceinline__ void attn_probs(const float (&s)[4][4], float sc0, float sc1, bool e, bool zneg, const uint32_t (&sel)[3],
                                           uint32_t (&pr)[6], float (&l)[2]) {
  float a0 = e ? s[1][1] : s[1][0];
  float b0 = zneg ? (e ? s[0][1] : s[0][0]) : (e ? s[2][1] : s[2][0]);
  float a1 = e ? s[2][3] : s[2][2];
  float b1 = zneg ? (e ? s[1][3] : s[1][2]) : (e ? s[3][3] : s[3][2]);
  float m0 = fmaxf(a0, b0), m1 = fmaxf(a1, b1);
  m0 = fmaxf(m0, __shfl_xor_sync(0xffffffffu, m0, 1)); m1 = fmaxf(m1, __shfl_xor_sync(0xffffffffu, m1, 1));
  m0 = fmaxf(m0, __shfl_xor_sync(0xffffffffu, m0, 2)); m1 = fmaxf(m1, __shfl_xor_sync(0xffffffffu, m1, 2));
  a0 = ex2((a0 - m0) * sc0); b0 = ex2((b0 - m0) * sc0); a1 = ex2((a1 - m1) * sc1); b1 = ex2((b1 - m1) * sc1);
  l[0] = a0 + b0; l[1] = a1 + b1;
  const uint32_t p0 = pack2(a0, b0), p1 = pack2(a1, b1);
#pragma unroll
  for (int k = 0; k < 3; k++) { pr[k] = __byte_perm(p0, 0u, sel[k]); pr[3 + k] = __byte_perm(p1, 0u, sel[k]); }
}
__device__ __forceinline__ void attn_pv(const uint32_t (&pr)[6], const uint32_t* vh, const uint32_t* v, float (&o)[4][4]) {
#pragma unroll
  for (int dt = 0; dt < 4; dt++) {
    o[dt][0] = o[dt][1] = o[dt][2] = o[dt][3] = 0.f;
    mma16816(o[dt], pr[0], 0u, pr[1], pr[3], vh[2 * dt], vh[2 * dt + 1]);
    mma16816(o[dt], pr[2], pr[4], 0u, pr[5], v[2 * dt], v[2 * dt + 1]);
  }
}

constexpr int CP0 = 1;
constexpr int FR = 2;
constexpr int XLD = 7;
constexpr int XST = 2;
constexpr int FA = 20;
constexpr int FO = 2;
constexpr int ATT = 25;
constexpr int COVER = 2;
constexpr int LEAD1 = 3;
constexpr int LEAD2 = 4;
constexpr int LEAD4 = 5;
constexpr int PD1 = 3;
constexpr int PD2 = 5;
constexpr int PD3 = 3;
constexpr int HALO_A_NS = 300;
constexpr int STAT_CLK = 150;
constexpr int H1D = 900;
constexpr int U0D = 300;
constexpr int X1D = 1200;
constexpr int PACE = 150;

__global__ void __cluster_dims__(2, 1, 1) __launch_bounds__(384, 1) fused_kernel(const bf16* __restrict__ x_p, const bf16* __restrict__ wqkv_p, const __grid_constant__ Params P) {
  extern __shared__ __align__(1024) uint8_t smem_raw[];
  const uint32_t sb = smem_u32(smem_raw);
  const uint32_t bars = sb + OFF_BAR;
  const int tid = threadIdx.x;
  const int wu = __shfl_sync(0xffffffffu, tid >> 5, 0), wg = wu >> 2;
  const int r = blockIdx.x & 1, cl = blockIdx.x >> 1;
  int grp, slt;
  if (cl < 4) { grp = 0; slt = 4 + cl; }
  else if (cl < 36) { grp = (cl - 4) & 7; slt = (cl - 4) >> 3; }
  else { grp = 1 + (cl - 36) % 7; slt = 4 + (cl - 36) / 7; }
  const int m = grp, j = slt;
  const int i = 2 * m + r;
  auto BAR = [&](int k) { return bars + 8 * k; };

  auto kb1 = [&](int n) { const int h = n >= 9, t = n - 2 - 7 * h; return n < 2 ? 2 * j + n : 2 * (t == j ? 7 : t) + h; };
  auto first_round = [&](int u0, int u1) {
#pragma unroll 1
    for (int u = u0; u < u1; u++) {
      mbar_expect(BAR(F1 + u), 40960);
      tma2d(sb + slot1(u), &P.x0, BAR(F1 + u), u * 64, 128 * i);
      tma3d(sb + slot1(u) + 16384, &P.wqkv, BAR(F1 + u), 128 * j, u * 64, 0);
      tma3d(sb + slot1(u) + 28672, &P.wqkv, BAR(F1 + u), 128 * j, u * 64 + 32, 0);
    }
  };
  if (CP0 && wu < 8) {
    const int row = tid >> 3, ch = tid & 7;
    const uint32_t d = sb + row * 128 + ((ch ^ (row & 7)) << 4);
    const bf16* xp = x_p + (128 * i + row) * 1024 + ch * 8;
    const bf16* wp = wqkv_p + row * 3072 + 128 * j + ch * 8;
#pragma unroll
    for (int k = 0; k < 10; k++)
      asm volatile("cp.async.cg.shared.global [%0], [%1], 16;" ::"r"(d + k * 4096), "l"(k < 4 ? xp + k * 32 * 1024 : wp + ((k - 4) / 3) * 32 * 3072 + ((k - 4) % 3) * 1024) : "memory");
  }
  if (wu == 9) {
    if (elect_one()) asm volatile("prefetch.tensormap [%0];" ::"l"(&P.wqkv) : "memory");
    __syncwarp();
  } else if (wu == 8) {
    if (elect_one()) {
#pragma unroll
      for (int k = 0; k < 4; k++) mbar_init(BAR(F1 + k), 1);
      asm volatile("fence.mbarrier_init.release.cluster;" ::: "memory");
      fence_async_smem();
      if (CP0) mbar_arrive(BAR(F1));
      first_round(CP0, FR);
    }
    __syncwarp();
  } else if (wu == 10) {
    if (elect_one()) {
#pragma unroll
      for (int k = E1; k < 64; k++) {
        int cnt = 1;
        if (k < F2 || (k >= E2 && k < F3) || (k >= E3 && k < F4) || (k >= E4 && k < JOB) || k == JOB + 2 || k == JOB + 3) cnt = 4;
        else if ((k >= JOB && k < RD) || k == CSJ) cnt = 8;
        else if (k == RD + 1 || k == STD || k == STAT) cnt = 2;
        mbar_init(BAR(k), cnt);
      }
      asm volatile("fence.mbarrier_init.release.cluster;" ::: "memory");
      fence_async_smem();
    }
    __syncwarp();
  }
  auto load_tag = [&]() { uint32_t t; asm volatile("ld.relaxed.gpu.global.u32 %0, [%1];" : "=r"(t) : "l"(&gEpoch) : "memory"); return t + 1; };
  if (wu == 8) nb_arrive<NB_INIT>(384); else nb_sync<NB_INIT>(384);
  asm volatile("barrier.cluster.arrive.relaxed;" ::: "memory");

  if (wg == 2) {
    reg_dealloc<40>();
    if (wu == 8) {
      if (elect_one()) first_round(FR, 4);
      __syncwarp();
    }
    asm volatile("barrier.cluster.wait;" ::: "memory");
    auto kb3 = [&](int n) { const int h = n >= 17, t = n - 3 - 14 * h; return n < 2 ? 2 * i + n : (n == 2 || n == 31) ? 2 * (i ^ 1) + h : 2 * ((2 * m + 2 + t) & 15) + h; };
    auto v1 = [&](int L, int u) { const int u0 = L ? 2 : 10; return (u >= u0 && u < 18) ? (u < u0 + 2 ? u - u0 + 16 : u - 2) : u; };
    auto kb2 = [&](int n) { return n < 8 ? 2 * n : n == 8 ? 2 * j + 1 : 2 * (n - 9 == j ? 7 : n - 9) + 1; };
    if (wu == 8) {
      const int lane = tid & 31;
      auto pf = [&](const bf16* p, bool on) { if (on) asm volatile("prefetch.global.L2 [%0];" ::"l"(p)); };
      auto k1 = [&](int L, int v) { return (L || v >= 16) ? kb1(v & 15) : v; };
      auto kb4f = [&](int n) {
        const bool own = n == 0 || n == 9 || n == 17;
        const int q = n - 10 - (n > 17), c = own ? n >> 3 : q / 15, t = q - 15 * c;
        const int ii = own ? i : t < 14 ? (2 * m + 2 + t) & 15 : i ^ 1;
        return (n >= 1 && n <= 8) ? 7 * ((m + n) & 7) + 3 : ((7 * ii + 1) >> 1) + c;
      };
      const uint32_t tab4 = kb4f(lane) | (kb4f(lane + 32) << 16);
      auto kb4 = [&](int n) { return (int)((__shfl_sync(0xffffffffu, tab4, n) >> ((n >> 1) & 16)) & 63); };
      const bf16* const q1 = wqkv_p + (4 * i + (lane & 3)) * 3072 + (lane >> 2) * 1024 + 128 * j;
      const bf16* const q2 = P.wo_p + (4 * i + (lane & 3)) * 1024 + (lane >> 2) * 64 + 128 * j;
      const bf16* const q3 = P.w1_p + (8 * j + (lane >> 2)) * 3584 + 64 * (7 * m + ((lane & 3) == 3 ? 3 : 4 * r + (lane & 3)));
      auto pf1 = [&](int L, int u) { const int v = v1(L, u); pf(q1 + k1(L, v) * (64 * 3072) + 64 * (v >> 4), lane < 12); };
      auto pf2 = [&](int n) { pf(q2 + kb2(n) * (64 * 1024), lane < 8); };
      auto pf3 = [&](int n) { pf(q3 + kb3(n) * (64 * 3584), true); };
#pragma unroll 1
      for (int u = 4; u < 4 + PD1; u++) pf1(0, u);
#pragma unroll 1
      for (int L = 0; L < 2; L++) {
#pragma unroll 1
        for (int u = L ? 0 : 4; u < 32; u++) {
          const int v = v1(L, u), p = u & 3;
          int c0 = 128 * j + 64 * (v >> 4), c1 = k1(L, v) * 64 + 32 * r; uint32_t dst = sb + slot1(p) + 16384 + r * 12288;
          asm volatile("" : "+r"(c0), "+r"(c1), "+r"(dst));
          if (L && u == 4) mbar_wait(BAR(RD + 5), 0);
          if (u >= 4) mbar_wait(BAR(E1 + p), ((u >> 2) - 1) & 1);
          else mbar_wait(BAR(E4 + (u == 3 ? 0 : u + 3)), u == 3);
          if (elect_one()) {
            mbar_expect(BAR(F1 + p), (v & 15) < 2 ? 24576 : 40960);
            tma3d_mc(dst, &P.wqkv, BAR(F1 + p), c0, c1, 0);
          }
          if (u + PD1 < 32) pf1(L, u + PD1);
          if (u + PD2 >= 32) pf2(u + PD2 - 32);
        }
        int p = 0; uint32_t par = L ? 0x1e : 0;
#pragma unroll 1
        for (int n = 0; n < 16; n++) {
          int c1 = kb2(n) * 64;
          asm volatile("" : "+r"(c1));
          if (n >= 5) { mbar_wait(BAR(E2 + p), (par >> p) & 1); par ^= 1u << p; }
          else if (n < 4) mbar_wait(BAR(E1 + n), 1);
          if (elect_one()) {
            mbar_expect(BAR(F2 + p), n == 8 ? 16384 : 32768);
            tma2d_mc(sb + slot2(p) + 16384 + r * 8192, &P.wo, BAR(F2 + p), 128 * j + 64 * r, c1);
          }
          if (++p == 5) p = 0;
          if (n + PD2 < 16) pf2(n + PD2);
          if (n + PD3 + 4 >= 16) pf3(n + PD3 + 4 - 16);
        }
#pragma unroll 1
        for (int u = 0; u < 32; u++) {
          const int n = u < 4 ? (0x2031 >> (4 * u)) & 3 : u, p = n & 3;
          int kb = kb3(n);
          asm volatile("" : "+r"(kb));
          if (n == 4) {
            mbar_wait(BAR(XF + 1), L ^ 1);
            const uint32_t rs = mapa(sb, r ^ 1);
            if (elect_one()) bulk_s2s(rs + slot3(2), sb + OFF_X, 16384, rs + OFF_BAR + 8 * (F3 + 2));
            mbar_wait(BAR(RD + 4), L);
          }
          if (n >= 4) mbar_wait(BAR(E3 + p), ((n >> 2) - 1) & 1);
          else if (n == 1) mbar_wait(BAR(STD + 1), L);
          else if (n == 3) mbar_wait(BAR(E2 + 2), L);
          else if (n == 0) mbar_wait(BAR(E2 + 4), L);
          else mbar_wait(BAR(E2 + 0), 1);
          if (elect_one()) {
            mbar_expect(BAR(F3 + p), n < 2 ? 32768 : 49152);
            tma3d(sb + slot3(p) + 16384, &P.w1, BAR(F3 + p), 0, kb * 64, 7 * m + 4 * r);
            tma3d(sb + slot3(p) + 40960, &P.w1h, BAR(F3 + p), 0, kb * 64, 14 * m + 6 + r);
          }
          if (u >= 4 && u + PD3 < 32) pf3(u + PD3);
        }
        auto g4w = [&](int n, int p, int kb) {
          if (elect_one()) {
            mbar_expect(BAR(F4 + p), (n == 0 || n == 9 || n == 17) ? 16384 : 32768);
            tma3d(sb + slot4(p), &P.w2, BAR(F4 + p), 0, kb * 64, 2 * i);
          }
        };
#pragma unroll 1
        for (int n = 0; n < 6; n++) {
          const int kb = kb4(n);
          if (n == 1) mbar_wait(BAR(RD + 3), L);
          if (n < 3) mbar_wait(BAR(E3 + n), 1);
          else if (n == 4) mbar_wait(BAR(E3 + 3), 1);
          g4w(n, n, kb);
        }
        p = 0; par = L ? 0x3c : 0;
#pragma unroll 1
        for (int n = 6; n < 56; n++) {
          const int kb = kb4(n);
          mbar_wait(BAR(E4 + p), (par >> p) & 1); par ^= 1u << p;
          g4w(n, p, kb);
          if (++p == 6) p = 0;
        }
        if (L == 0)
#pragma unroll 1
          for (int u = 0; u < PD1; u++) pf1(1, u);
      }
    } else if (wu == 9) {
      uint32_t inv = 0;
#define ADDR(d, s) uint32_t dst = (d); const uint8_t* src = (s); asm volatile("" : "+r"(dst), "+l"(src))
#pragma unroll 1
      for (int L = 0; L < 2; L++) {
        uint32_t ready = 0;
#pragma unroll 1
        for (int u = 4; u < 32; u++) {
          const int p = u & 3, v = v1(L, u), nn = v & 15, kb = (L || v >= 16) ? kb1(nn) : nn;
          if (L == 0 && (u == XLD || u == XLD + XST) && elect_one()) {
            const int h = u != XLD;
            mbar_expect(BAR(XF + h), 16384);
            tma2d(sb + OFF_X + h * 16384, &P.x0, BAR(XF + h), 128 * j + 64 * h, 128 * i);
          }
          if (nn < 2) continue;
          ADDR(sb + slot1(p), gXB + (i * 16 + kb) * 16384);
          if (L && u < 12) mbar_wait(BAR(F1 + p), u >> 3);
          if (u >= 4 + 4 * L) mbar_wait(BAR(E1 + p), ((u >> 2) - 1) & 1);
          if (L) {
            flag_wait(gFlag[0][0][i], inv, 1u << kb, ready);
            if (elect_one()) bulk_ld(dst, src, 16384, BAR(F1 + p));
          } else if (elect_one()) tma2d(sb + slot1(p), &P.x0, BAR(F1 + p), kb * 64, 128 * i);
        }
        ready = 0;
        if (L == 0) inv = (__shfl_sync(0xffffffffu, load_tag(), 0) & 1) - 1;
        int p = 0; uint32_t par = L ? 0x1e : 0;
#pragma unroll 1
        for (int n = 0; n < 16; n++) {
          const int hp = kb2(n);
          if (n == 8) { par ^= 8; p = 4; continue; }
          ADDR(sb + slot2(p), gOB + (i * 16 + hp) * 16384);
          if (n >= 5) { mbar_wait(BAR(E2 + p), (par >> p) & 1); par ^= 1u << p; }
          else if (n < 4) mbar_wait(BAR(E1 + n), 1);
          flag_wait(gFlag[L][1][i], inv, 1u << hp, ready);
          if (elect_one()) bulk_ld(dst, src, 16384, BAR(F2 + p));
          if (++p == 5) p = 0;
        }
        ready = 0;
        mbar_wait(BAR(E2 + 0), 1);
#pragma unroll 1
        for (int n = 3; n < 32; n++) {
          const int p = n & 3, kb = kb3(n);
          const int o = n != 31 ? r * 8192 : 0;
          ADDR(sb + slot3(p) + o, gHB + (j * 32 + kb) * 16384 + o);
          if (n > 3) mbar_wait(BAR(E3 + p), ((n >> 2) - 1) & 1);
          flag_wait(gFlag[L][2][j], inv, 1u << kb, ready);
          if (elect_one()) {
            if (n != 31) bulk_ld_mc(dst, src, 8192, BAR(F3 + p));
            else bulk_ld(dst, src, 16384, BAR(F3 + p));
          }
        }
        ready = 0; p = 1; par = L ? 0x3c : 0;
#pragma unroll 1
        for (int t = 0; t < 8; t++) {
          const int mm = (m + t + 1) & 7;
          ADDR(sb + slot4(p) + 16384 + r * 8192, gUB + (j * 56 + 48 + mm) * 16384 + r * 8192);
          if (t < 3) mbar_wait(BAR(E3 + 1 + t), 1);
          if (t >= 5) { mbar_wait(BAR(E4 + p), (par >> p) & 1); par ^= 1u << p; }
          flag_wait(gFlag[L][6][j], inv, 3u << (2 * mm), ready);
          if (elect_one()) bulk_ld_mc(dst, src, 8192, BAR(F4 + p));
          if (++p == 6) p = 0;
        }
#pragma unroll 1
        for (int c = 0; c < 3; c++) {
          ready = 0;
#pragma unroll 1
          for (int t = 0; t < 15; t++) {
            const int ii = t < 14 ? (2 * m + 2 + t) & 15 : i ^ 1;
            if (c == 0 && (t == 0 || t == 7)) { par ^= 1u << p; if (++p == 6) p = 0; }
            const int o = t < 14 ? r * 8192 : 0;
            ADDR(sb + slot4(p) + 16384 + o, gUB + (j * 56 + 16 * c + ii) * 16384 + o);
            mbar_wait(BAR(E4 + p), (par >> p) & 1); par ^= 1u << p;
            flag_wait(gFlag[L][3 + c][j], inv, 1u << ii, ready);
            if (elect_one()) {
              if (t < 14) bulk_ld_mc(dst, src, 8192, BAR(F4 + p));
              else bulk_ld(dst, src, 16384, BAR(F4 + p));
            }
            if (++p == 6) p = 0;
          }
        }
      }
    } else {
      const int h = wu - 10, i0 = i, j0 = j;
      {
      const uint32_t tag = load_tag();
      int lane = tid & 31, i = i0, j = j0;
#define FRESH asm volatile("" : "+r"(lane), "+r"(i), "+r"(j))
      auto signal = [&](int k) { if (lane == 0) mbar_arrive(BAR(k)); };
      auto publish = [&](uint32_t* f, int bit) { if (lane == 0) flag_set(f, 1u << bit); __syncwarp(); };
#pragma unroll 1
      for (int c = 32 * h + lane; c < 288; c += 64)
        sts16(sb + OFF_B1 + 2 * c, c >= 224 ? 0u : pack2(0.5f * __bfloat162float(P.b1[c < 192 ? 64 * (7 * m + 4 * r) + c : 64 * (7 * m + 3) + 32 * r + c - 192]), 0.f));
      if (h == 0) sts32f(sb + OFF_CS + 768 + 4 * lane, 0.f);
#pragma unroll 1
      for (int L = 0; L < 2; L++) {
        FRESH;
        if (L == 0) {
          mbar_wait(BAR(CSJ), 0);
          float c0 = 0.f, c1 = 0.f, c2 = 0.f;
          const uint32_t a = sb + OFF_STG + (32 * h + lane) * 4;
#pragma unroll 4
          for (int k = 0; k < 32; k++) { c0 += lds32f(a + k * 784); c1 += lds32f(a + k * 784 + 256); c2 += lds32f(a + k * 784 + 512); }
          ll_st3(&gCS[j][i][32 * h + lane], __float_as_uint(c0), __float_as_uint(c1), __float_as_uint(c2), tag);
          __nanosleep(500);
        }
        FRESH;
        if (L == 0) {
#pragma unroll 1
          for (int ab = 0; ab < 2; ab++) {
            float c0 = 0.f, c1 = 0.f, c2 = 0.f;
#pragma unroll 1
            for (int b4 = 0; b4 < 8; b4 += 4) {
              uint32_t a[4], b[4], c[4], n = 0, bad;
              do {
                bad = 0;
#pragma unroll
                for (int e = 0; e < 4; e++) bad |= ll_ld3(&gCS[j][2 * (b4 + e) + ab][32 * h + lane], a[e], b[e], c[e], tag);
              } while (bad && ++n < SPIN_MAX);
#pragma unroll
              for (int e = 0; e < 4; e++) { c0 += __uint_as_float(a[e]); c1 += __uint_as_float(b[e]); c2 += __uint_as_float(c[e]); }
            }
            const uint32_t a = sb + OFF_CS + ab * 768 + (4 * h + (lane >> 3)) * 32 + (lane & 7) * 2;
            const uint32_t h0 = pack2(c0, 0.f), h1 = pack2(c1, 0.f), h2 = pack2(c2, 0.f);
            sts16(a, h0); sts16(a + 256, h1); sts16(a + 512, h2);
            sts16(a + 16, pack2(c0 - bf_lo(h0), 0.f)); sts16(a + 272, pack2(c1 - bf_lo(h1), 0.f)); sts16(a + 528, pack2(c2 - bf_lo(h2), 0.f));
            fence_async_smem();
            __syncwarp();
            if (ab == 0) signal(STAT);
          }
        }
#pragma unroll 1
        for (int ab = 0; ab < 2; ab++) {
          FRESH;
          uint32_t v[18], tg[6];
          const uint32_t xs = sb + OFF_STG + h * 16384 + lane * 8;
          uint4* hp = &gHalo[L][i][j][6 * h][lane];
#pragma unroll
          for (int c = 0; c < 6; c++) { tg[c] = (2 * tag + ab) * 8 + c; asm volatile("" : "+r"(tg[c])); }
          asm volatile("" : "+l"(hp));
          mbar_wait(BAR(FOLD + h), ab);
          if (i < 15) {
            halo_send(hp, xs, tg);
          }
          if (i > 0) {
            if (!ab) __nanosleep(HALO_A_NS);
            uint32_t n = 0, bad;
            do {
              bad = 0;
#pragma unroll
              for (int c = 0; c < 6; c++) bad |= ll_ld3(hp + c * 32 - 8 * 12 * 32, v[3 * c], v[3 * c + 1], v[3 * c + 2], (2 * tag + ab) * 8);
            } while (bad > 7 && ++n < SPIN_MAX);
          } else {
#pragma unroll
            for (int c = 0; c < 18; c++) v[c] = 0u;
          }
#pragma unroll
          for (int c = 0; c < 6; c++) sts64f(xs + c * 256, __uint_as_float(v[3 * c]), __uint_as_float(v[3 * c + 1]));
          sts64f(xs + 1536, __uint_as_float(v[2]), __uint_as_float(v[5]));
          sts64f(xs + 1792, __uint_as_float(v[8]), __uint_as_float(v[11]));
          __syncwarp();
          signal(HALO + h);
          FRESH;
          if (ab == 0 && lane == 0) asm volatile("st.relaxed.gpu.global.u32 [%0], %1;" ::"l"(&gAck[L][i][j][h][0]), "r"(tag) : "memory");
          uint8_t* dst = gOB + (i * 16 + 2 * j + ab) * 16384;
          uint32_t* flag = gFlag[L][1][i];
          asm volatile("" : "+l"(dst), "+l"(flag));
          mbar_wait(BAR(JOB + ab), L);
          if (h == 0) {
            if (lane == 0) { bulk_st(dst, sb + OFF_STG, 16384); bulk_commit(); bulk_wait0(); }
            signal(STD + ab);
            publish(flag, 2 * j + ab);
          } else if (ab == 0) {
            if (i < 15 && lane < 2) {
              uint32_t t, n = 0;
              do { asm volatile("ld.relaxed.gpu.global.u32 %0, [%1];" : "=r"(t) : "l"(&gAck[L][i + 1][j][lane][0]) : "memory"); } while (t != tag && ++n < SPIN_MAX);
            }
            __syncwarp();
            signal(STD);
          }
        }
#pragma unroll 1
        for (int k = 0; k < 4 - L; k++) {
          FRESH;
          const int job = 2 * k + h;
          uint8_t* dst = k == 0 ? gHB + (j * 32 + 2 * i + 1) * 16384 : k == 3 ? gXB + (i * 16 + 2 * j + 1) * 16384 : gUB + (j * 56 + 16 * (job - 3) + i) * 16384;
          uint32_t* flag = k == 3 ? gFlag[0][0][i] : gFlag[L][(0x543622 >> (4 * job)) & 15][j];
          uint32_t bit = 1u << (k == 0 ? 2 * i + h : k == 3 ? 2 * j + h : i);
          asm volatile("" : "+l"(dst), "+l"(flag), "+r"(bit));
          mbar_wait(BAR(JOB + ((0x98654732 >> (4 * job)) & 15)), L);
          if ((0xba >> job) & 1) {
            if (job == 1) mbar_wait(BAR(RD + 4), L);
            if (job == 3) {
              __nanosleep(U0D);
              if (lane == 0) { bulk_st(dst, sb + OFF_X, 16384); bulk_commit(); bulk_wait0(); }
            } else warp_store(dst + lane * 16, sb + lane * 16 + OFF_X + (job == 5 ? 0 : 16384), 16384, job == 1 ? H1D : job == 7 ? X1D : 0, job == 7 ? 0 : PACE);
            if (job != 7) signal(RD + ((0x112000 >> (4 * job)) & 15));
          }
          if (lane == 0) flag_set(flag, bit);
          __syncwarp();
          if (h == 0 && k != 2) { signal(RD + (k == 3 ? 5 : 4 - k)); }
        }
      }
      if (blockIdx.x == 0 && h == 0 && lane == 0) asm volatile("st.relaxed.gpu.global.u32 [%0], %1;" ::"l"(&gEpoch), "r"(tag) : "memory");
      }
    }
    __syncwarp();
    cluster_bar();
  } else {
    reg_alloc<232>();
    asm volatile("barrier.cluster.wait;" ::: "memory");
    if (CP0) { asm volatile("cp.async.wait_all;" ::: "memory"); fence_async_smem(); nb_sync<NB_BOTH>(256); }
    const uint32_t rbars = mapa(bars, tid & 1);
    const bool relp = (tid & 127) < 2;
    const uint32_t sd = (sb & 0x3FFFF) >> 4, sda = sd + wg * 512;
    uint32_t tag = 0;
    auto release = [&](int k) { if (relp) mbar_arrive_cl(rbars + 8 * k); };
    auto signal = [&](int k) { __syncwarp(); if ((fresh_tid() & 31) == 0) mbar_arrive(BAR(k)); };
#define GEOM const int t7 = fresh_tid() & 127, lane = t7 & 31, w = t7 >> 5, g = lane >> 2, q = lane & 3, \
                       lr = lane & 15, lt = lane >> 4, l7 = lane & 7; (void)w; (void)g; (void)q; (void)lr; (void)lt; (void)l7

#pragma unroll 1
    for (int L = 0; L < 2; L++) {
      float acca[96], accb[96], xa[64], acc3[112];
      float nmean0, nmean1, rstd0, rstd1;
      uint16_t b2a, b2b;
      uint2 *e2p, *e2s; uint8_t* e2g; uint32_t e2h;
      uint32_t Q[2][8], K[2][8], V[16];
      auto g1_issue = [&](float (&acc)[96], uint32_t a, uint32_t st, auto first) {
        const uint32_t da = sda + (a >> 4), db = sd + (st >> 4);
        wg_fence();
        static_for<0, 4>([&](auto kk) {
          constexpr uint32_t ia = DI(kk.value * 32, 16), ib = DI(16384 + (kk.value >> 1) * 12288 + (kk.value & 1) * 2048, 4096);
          if constexpr (first.value && kk.value == 0) wgmma_192z<0, 1, ia, ib>(acc, da, db); else wgmma_192<0, 1, ia, ib>(acc, da, db);
        });
        wg_commit();
      };
      auto g1_step = [&](float (&acc)[96], int u, bool rel, bool lead = false) {
        const int p = u & 3;
        mbar_wait(BAR(F1 + p), (u >> 2) & 1);
        g1_issue(acc, slot1(p), slot1(p), False{});
        if (lead) nb_arrive<NB_LEAD>(256);
        wg_wait<1>();
        if (rel) release(E1 + ((u - 1) & 3));
      };
      auto g1_loop = [&](float (&acc)[96], int u0, int u1, int urel) {
        int u = u0;
#pragma unroll 1
        do { g1_step(acc, u, u > urel); } while (++u < u1);
      };
      auto load_x = [&]() {
        GEOM;
#pragma unroll
        for (int t = 0; t < 16; t += 2) {
          uint32_t v0, v1, v2, v3;
          ldsm4(sb + OFF_X + (t >> 3) * 16384 + (16 * wu + lr) * 128 + ((((t & 7) + lt) ^ l7) << 4), v0, v1, v2, v3);
          xa[4 * t + 0] = bf_lo(v0); xa[4 * t + 1] = bf_hi(v0); xa[4 * t + 2] = bf_lo(v1); xa[4 * t + 3] = bf_hi(v1);
          xa[4 * t + 4] = bf_lo(v2); xa[4 * t + 5] = bf_hi(v2); xa[4 * t + 6] = bf_lo(v3); xa[4 * t + 7] = bf_hi(v3);
        }
      };
      auto stat_base = [&]() { return &gST[0][0][0][0][0] + ((L * 16 + opq(i)) * 8 + wu) * 128; };
      auto stat_slot = [&]() { const int lane = fresh_tid() & 31; return stat_base() + 16 * j + 2 * (lane >> 2) + (lane & 1); };
      auto stat_publish = [&](uint2* sp, float s0, float q0, float s2, float q2, uint32_t tg) {
        const int q = fresh_tid() & 3;
        const bool h1 = q & 1;
        float sm = (h1 ? s2 : s0) + __shfl_xor_sync(0xffffffffu, h1 ? s0 : s2, 1);
        float sq = (h1 ? q2 : q0) + __shfl_xor_sync(0xffffffffu, h1 ? q0 : q2, 1);
        sm += __shfl_xor_sync(0xffffffffu, sm, 2); sq += __shfl_xor_sync(0xffffffffu, sq, 2);
        stat_st(sp, sm, sq, tg, q < 2);
        return sm;
      };
      auto g1_stats = [&](int u0) {
        GEOM;
        const uint32_t xr = sb + OFF_X + (16 * wu + lr) * 128;
        float s0 = 0.f, q0 = 0.f, s2 = 0.f, q2 = 0.f;
        uint32_t v[8] = {0u, 0u, 0u, 0u, 0u, 0u, 0u, 0u};
#pragma unroll 1
        for (int k = 0; k < 5; k++) {
#pragma unroll
          for (int e = 0; e < 8; e += 2) {
            const float a = bf_lo(v[e]), b = bf_hi(v[e]), c = bf_lo(v[e + 1]), d = bf_hi(v[e + 1]);
            s0 += a + b; q0 = fmaf(a, a, fmaf(b, b, q0)); s2 += c + d; q2 = fmaf(c, c, fmaf(d, d, q2));
          }
          if (k == 4) break;
          const uint32_t o = ((2 * k + lt) ^ l7) << 4;
          ldsm4(xr + o, v[0], v[1], v[2], v[3]);
          ldsm4(xr + o + 16384, v[4], v[5], v[6], v[7]);
          g1_step(acca, u0 + k, true);
        }
        stat_publish(stat_slot(), s0, q0, s2, q2, 2 * (tag + 1));
      };
      uint32_t sv0[4], sv1[4];
      auto stat_src = [&]() { return stat_base() + 2 * (fresh_tid() & 31); };
      auto stat_fetch = [&](const uint2* sp) { stat_ld2(sp, sv0); stat_ld2(sp + 64, sv1); };
      auto stat_await = [&](auto src, uint32_t tg) {
#pragma unroll 1
        for (uint32_t n = 0; (((sv0[0] ^ tg) | (sv0[2] ^ tg) | (sv1[0] ^ tg) | (sv1[2] ^ tg)) & 15u) && n < SPIN_MAX; n++) stat_fetch(src());
        __syncwarp();
      };
      auto ln_stats = [&]() {
        GEOM;
        stat_await(stat_src, 2 * (tag + 1));
        float mean0, var0, mean1, var1;
        stat_combine(sv0[0], sv0[1], sv1[0], sv1[1], untag(__shfl_sync(0xffffffffu, sv0[0], l7)), mean0, var0);
        stat_combine(sv0[2], sv0[3], sv1[2], sv1[3], untag(__shfl_sync(0xffffffffu, sv0[2], l7)), mean1, var1);
        nmean0 = -__shfl_sync(0xffffffffu, mean0, g); rstd0 = rsq(__shfl_sync(0xffffffffu, var0, g) + 1e-5f);
        nmean1 = -__shfl_sync(0xffffffffu, mean1, g); rstd1 = rsq(__shfl_sync(0xffffffffu, var1, g) + 1e-5f);
      };
      auto center = [&](float (&acc)[96], int ab) {
        const bool q0 = (fresh_tid() & 3) == 0;
        const uint32_t h0 = pack2(nmean0, nmean0), h1 = pack2(nmean1, nmean1);
        const float l0 = nmean0 - bf_lo(h0), l1 = nmean1 - bf_lo(h1);
        const uint32_t a0 = q0 ? h0 : 0u, a1 = q0 ? h1 : 0u, a2 = q0 ? pack2(l0, l0) : 0u, a3 = q0 ? pack2(l1, l1) : 0u;
        wg_fence();
        wgmma_rs_192(acc, a0, a1, a2, a3, mkdesc_vec(sb + OFF_CS + ab * 768, 32));
      };
      auto frag = [&](float (&acc)[96], int t, uint32_t& p0, uint32_t& p1) {
        if (t >= 8) { p0 = pack2(acc[4 * t] * rstd0, acc[4 * t + 1] * rstd0); p1 = pack2(acc[4 * t + 2] * rstd1, acc[4 * t + 3] * rstd1); }
        else { p0 = pack2(acc[4 * t], acc[4 * t + 1]); p1 = pack2(acc[4 * t + 2], acc[4 * t + 3]); }
      };
      auto fold_v = [&](float (&acc)[96]) {
        GEOM;
        const uint32_t a = sb + OFF_STG + 16384 + ((wu + 1) & 7) * 2048 + lr * 128;
#pragma unroll
        for (int t = 0; t < 8; t += 2) {
          uint32_t p0, p1, p2, p3;
          frag(acc, 16 + t, p0, p1); frag(acc, 17 + t, p2, p3);
          stsm4(a + (((t + lt) ^ l7) << 4), p0, p1, p2, p3);
        }
        __syncwarp();
#pragma unroll
        for (int t = 0; t < 8; t += 2) ldsm4t(a + (((t + lt) ^ l7) << 4), V[2 * t], V[2 * t + 1], V[2 * t + 2], V[2 * t + 3]);
        if (wu == 7) signal(FOLD + 1);
      };
      auto fold_k = [&](float (&acc)[96]) {
        GEOM;
        const uint32_t a = sb + OFF_STG + ((wu + 1) & 7) * 2048 + lane * 16;
#pragma unroll
        for (int hh = 0; hh < 2; hh++) {
#pragma unroll
          for (int t = 4 * hh; t < 4 * hh + 4; t++) frag(acc, 8 + t, K[0][t], K[1][t]);
#pragma unroll
          for (int o = 0; o < 2; o++) sts128(a + (2 * o + hh) * 512, K[o][4 * hh], K[o][4 * hh + 1], K[o][4 * hh + 2], K[o][4 * hh + 3]);
        }
        if (wu == 7) signal(FOLD);
      };
      auto fold_q = [&](float (&acc)[96]) {
#pragma unroll
        for (int t = 0; t < 8; t++) frag(acc, t, Q[0][t], Q[1][t]);
      };
      auto attend = [&](int ab, auto drain, auto resume) {
        GEOM;
        nb_sync<NB_BOTH>(256);
        const uint32_t xa_ = sb + OFF_STG + wu * 2048 + lane * 16;
        if (wu == 0) mbar_wait(BAR(HALO), ab);
        uint32_t KH[2][8], VH[16];
#pragma unroll
        for (int c = 0; c < 4; c++)
          lds128(xa_ + c * 512, KH[c >> 1][4 * (c & 1)], KH[c >> 1][4 * (c & 1) + 1], KH[c >> 1][4 * (c & 1) + 2], KH[c >> 1][4 * (c & 1) + 3]);
        auto load_vh = [&]() {
          if (wu == 0) mbar_wait(BAR(HALO + 1), ab);
#pragma unroll
          for (int c = 0; c < 4; c++)
            ldsm4t(sb + OFF_STG + 16384 + wu * 2048 + lr * 128 + (((2 * c + lt) ^ l7) << 4), VH[4 * c], VH[4 * c + 1], VH[4 * c + 2], VH[4 * c + 3]);
        };
        if (!ab) load_vh();
        const bool e = g & 1, zneg = (g >> 1) < q, first = (i == 0) && (wu == 0);
        const float sc0 = rstd0 * (0.17677669530f * 1.4426950409f), sc1 = rstd1 * (0.17677669530f * 1.4426950409f);
        float mk0 = first ? __fdividef(-1.0e9f * 1.4426950409f, sc0) : 0.f, mk1 = first ? __fdividef(-1.0e9f * 1.4426950409f, sc1) : 0.f;
        const uint32_t sa = e ? 0x1044u : 0x4410u, sbb = e ? 0x3244u : 0x4432u;
        uint32_t sel[3] = {zneg ? sbb : 0x4444u, sa, zneg ? 0x4444u : sbb};
        uint32_t oa = sb + OFF_STG + (16 * wu + lr) * 128 + ((lt ^ l7) << 4);
        asm volatile("" : "+r"(sel[0]), "+r"(sel[1]), "+r"(sel[2]), "+r"(oa), "+f"(mk0), "+f"(mk1));
        drain();
        uint32_t pr[2][6];
        float l[2][2], sl[2][4][4];
#pragma unroll
        for (int hh = 0; hh < 2; hh++)
          attn_logits(&Q[0][4 * hh], &Q[1][4 * hh], &KH[0][4 * hh], &KH[1][4 * hh], &K[0][4 * hh], &K[1][4 * hh], mk0, mk1, sl[hh]);
        if (ab) load_vh();
#pragma unroll
        for (int hh = 0; hh < 2; hh++) attn_probs(sl[hh], sc0, sc1, e, zneg, sel, pr[hh], l[hh]);
        float o[2][4][4];
#pragma unroll
        for (int hh = 0; hh < 2; hh++) attn_pv(pr[hh], &VH[8 * hh], &V[8 * hh], o[hh]);
#pragma unroll
        for (int hh = 0; hh < 2; hh++) {
          float l0 = l[hh][0], l1 = l[hh][1];
          l0 += __shfl_xor_sync(0xffffffffu, l0, 1); l1 += __shfl_xor_sync(0xffffffffu, l1, 1);
          l0 += __shfl_xor_sync(0xffffffffu, l0, 2); l1 += __shfl_xor_sync(0xffffffffu, l1, 2);
          asm("rcp.approx.ftz.f32 %0, %0;" : "+f"(l0)); asm("rcp.approx.ftz.f32 %0, %0;" : "+f"(l1));
#pragma unroll
          for (int dt = 0; dt < 4; dt += 2)
            stsm4(oa ^ ((4 * hh + dt) << 4),
                  pack2(o[hh][dt][0] * l0, o[hh][dt][1] * l0), pack2(o[hh][dt][2] * l1, o[hh][dt][3] * l1),
                  pack2(o[hh][dt + 1][0] * l0, o[hh][dt + 1][1] * l0), pack2(o[hh][dt + 1][2] * l1, o[hh][dt + 1][3] * l1));
        }
        fence_async_smem();
        signal(JOB + ab);
        nb_sync<NB_BOTH>(256);
        resume();
      };

      mbar_wait(BAR(F1), 0);    g1_issue(acca, L ? OFF_X : slot1(0), slot1(0), True{});
      mbar_wait(BAR(F1 + 1), 0); g1_issue(acca, L ? OFF_X + 16384 : slot1(1), slot1(1), False{});
      wg_wait<1>(); release(E1 + 0);
      if (L == 0) {
        asm volatile("ld.relaxed.gpu.global.u32 %0, [%1];" : "=r"(tag) : "l"(&gEpoch + (fresh_tid() >> 10)) : "memory");
        GEOM;
        const bf16* wp = wqkv_p + ((128 * opq(m) + 16 * wg + (t7 >> 3)) * 3072 + 128 * opq(j) + 64 * r + l7 * 8);
        const uint32_t ca = sb + OFF_STG + (16 * wg + (t7 >> 3)) * 784 + l7 * 32;
#pragma unroll 1
        for (int p = 0; p < 3; p++) {
          uint4 wv[4];
#pragma unroll
          for (int k = 0; k < 4; k++)
            asm volatile("ld.global.nc.v4.u32 {%0, %1, %2, %3}, [%4];" : "=r"(wv[k].x), "=r"(wv[k].y), "=r"(wv[k].z), "=r"(wv[k].w)
                         : "l"(wp + k * 32 * 3072 + p * 1024));
          g1_loop(acca, 2 + 3 * p, p < 2 ? 5 + 3 * p : 10, 0);
          float cs[8];
#pragma unroll
          for (int k = 0; k < 4; k++) {
            const uint4 v = wv[k];
            const float t[8] = {bf_lo(v.x), bf_hi(v.x), bf_lo(v.y), bf_hi(v.y), bf_lo(v.z), bf_hi(v.z), bf_lo(v.w), bf_hi(v.w)};
#pragma unroll
            for (int e = 0; e < 8; e++) cs[e] = k ? cs[e] + t[e] : t[e];
          }
          sts128(ca + p * 256, __float_as_uint(cs[0]), __float_as_uint(cs[1]), __float_as_uint(cs[2]), __float_as_uint(cs[3]));
          sts128(ca + p * 256 + 16, __float_as_uint(cs[4]), __float_as_uint(cs[5]), __float_as_uint(cs[6]), __float_as_uint(cs[7]));
        }
        signal(CSJ);
        mbar_wait(BAR(XF), 0); mbar_wait(BAR(XF + 1), 0);
      }
      {
        const int u0 = L ? 2 : 10;
        mbar_wait(BAR(F1 + 2), 0); g1_issue(accb, OFF_X, slot1(2), True{});
        wg_wait<1>(); release(E1 + 1);
        mbar_wait(BAR(F1 + 3), 0); g1_issue(accb, OFF_X + 16384, slot1(3), False{});
        wg_wait<1>(); release(E1 + 2);
        g1_stats(u0 + 2);
        g1_loop(acca, u0 + 6, 18, 0);
      }
      stat_fetch(stat_src());
      const int fa = FA + (wg ? 0 : FO);
      g1_loop(accb, 18, fa, 0);
      ln_stats();
      if (L == 0) mbar_wait(BAR(STAT), 0);
      center(acca, 0); wg_commit();
      wg_wait<0>(); release(E1 + ((fa - 1) & 3));
      fence_regs(acca);
      fold_k(acca); fold_v(acca); fold_q(acca);
      sched_fence(P.zero);
      g1_loop(accb, fa, ATT, fa);
      attend(0, [&]() { wg_wait<0>(); release(E1 + ((ATT - 1) & 3)); mbar_wait(BAR(F1 + (ATT & 3)), (ATT >> 2) & 1); },
             [&]() { g1_issue(accb, slot1(ATT & 3), slot1(ATT & 3), False{});
                     mbar_wait(BAR(F1 + ((ATT + 1) & 3)), ((ATT + 1) >> 2) & 1);
 g1_issue(accb, slot1((ATT + 1) & 3), slot1((ATT + 1) & 3), False{}); });
      wg_wait<1>(); release(E1 + (ATT & 3));
      load_x();
      fence_regs(xa);
      center(accb, 1);
#pragma unroll 1
      for (int u = ATT + 2; u < 32; u++) {
        const bool hold = u == 32 - LEAD1 && wg == 0;
        if (hold) { wg_wait<0>(); release(E1 + ((31 - LEAD1) & 3)); nb_sync<NB_LEAD>(256); }
        g1_step(accb, u, !hold, u == 31 && wg == 1);
      }
      mbar_wait(BAR(STD), L);
      wg_wait<0>(); release(E1 + 3);
      fence_regs(accb);
      fold_k(accb);
      sched_fence(P.zero);
      fold_v(accb);
      fold_q(accb);
      {
        auto g2_issue = [&](int p, bool own) {
          const uint32_t st = slot2(p);
          const uint32_t da = sda + ((own ? OFF_STG : st) >> 4), db = sd + (st >> 4);
          wg_fence();
          static_for<0, 4>([&](auto kk) { wgmma_128<0, 1, DI(kk.value * 32, 16), DI(16384 + kk.value * 2048, 8192)>(xa, da, db); });
          wg_commit();
        };
        uint32_t par = L ? 0x1e : 0;
        int p = 0, pp = 0;
        auto g2_loop = [&](int n0, int n1, int nrel) {
#pragma unroll 1
          for (int n = n0; n < n1; n++) {
            mbar_wait(BAR(F2 + p), (par >> p) & 1);
            par ^= 1u << p;
            g2_issue(p, n == 8);
            wg_wait<1>();
            if (n > nrel) release(E2 + pp);
            pp = p; if (++p == 5) p = 0;
          }
        };
        g2_loop(0, COVER, 0);
        attend(1, [&]() { wg_wait<0>(); release(E2 + COVER - 1); mbar_wait(BAR(F2 + COVER), (par >> COVER) & 1); },
               [&]() { g2_issue(COVER, false);
                       mbar_wait(BAR(F2 + COVER + 1), (par >> (COVER + 1)) & 1);
 g2_issue(COVER + 1, false); });
        wg_wait<1>(); release(E2 + COVER);
        par ^= 3u << COVER; pp = COVER + 1; p = (COVER + 2) % 5;
        {
          const bf16* bp = P.b2 + (128 * opq(i) + 16 * wu + ((fresh_tid() & 31) >> 2));
          asm volatile("ld.global.nc.u16 %0, [%1];" : "=h"(b2a) : "l"(bp));
          asm volatile("ld.global.nc.u16 %0, [%1];" : "=h"(b2b) : "l"(bp + 8));
        }
        {
          GEOM;
          e2p = stat_slot(); e2s = stat_src();
          e2g = gHB + (opq(j) * 32 + 2 * i) * 16384 + w * 2048 + lane * 16;
          e2h = sb + OFF_X + wg * 16384 + (16 * w + lr) * 128 + ((lt ^ l7) << 4);
          asm volatile("" : "+l"(e2p), "+l"(e2s), "+l"(e2g), "+r"(e2h));
        }
        g2_loop(COVER + 2, 16 - LEAD2, 0);
        if (wg == 1) { wg_wait<0>(); release(E2 + pp); nb_sync<NB_LEAD>(256); }
        static_for<16 - LEAD2, 16>([&](auto nn) {
          constexpr int n = nn.value, p = n % 5;
          mbar_wait(BAR(F2 + p), (n / 5 + (p ? L : 0)) & 1);
          wg_fence();
          static_for<0, 4>([&](auto kk) { wgmma_128<0, 1, DI(slot2(p) + kk.value * 32, 16), DI(slot2(p) + 16384 + kk.value * 2048, 8192)>(xa, sda, sd); });
          wg_commit();
          if (n == 15 && wg == 0) nb_arrive<NB_LEAD>(256);
          wg_wait<1>();
          if (n > 16 - LEAD2 || wg == 0) release(E2 + (n + 4) % 5);
        });
        wg_wait<0>();
        release(E2 + 0);
        fence_regs(xa);
      }
      {
        GEOM;
        const uint32_t tg = 2 * (tag + 1) + 1;
        float s0 = 0.f, s1 = 0.f, s2 = 0.f, s3 = 0.f, q0 = 0.f, q1 = 0.f, q2 = 0.f, q3 = 0.f;
#pragma unroll
        for (int t = 0; t < 16; t++) {
          s0 += xa[4 * t]; s1 += xa[4 * t + 1]; s2 += xa[4 * t + 2]; s3 += xa[4 * t + 3];
          q0 = fmaf(xa[4 * t], xa[4 * t], q0); q1 = fmaf(xa[4 * t + 1], xa[4 * t + 1], q1);
          q2 = fmaf(xa[4 * t + 2], xa[4 * t + 2], q2); q3 = fmaf(xa[4 * t + 3], xa[4 * t + 3], q3);
        }
        const float sm = stat_publish(e2p, s0 + s1, q0 + q1, s2 + s3, q2 + q3, tg);
        const uint32_t t0 = clock32();
        const float pv0 = __shfl_sync(0xffffffffu, sm, 4 * l7) * (1.f / 128), pv1 = __shfl_sync(0xffffffffu, sm, 4 * l7 + 1) * (1.f / 128);
        while (clock32() - t0 < STAT_CLK) {}
        stat_fetch(e2s);
        wg_fence();
        wgmma_rs_224z(acc3, q == 0 ? 0x3f80u : 0u, q == 0 ? 0x3f80u : 0u, 0u, 0u, mkdesc_vec(sb + OFF_B1, 16));
        wg_commit();
        stat_await([&]() { return e2s; }, tg);
        float r0, m0, r1, m1;
        {
          float mean0, var0, mean1, var1;
          stat_combine(sv0[0], sv0[1], sv1[0], sv1[1], pv0, mean0, var0); stat_combine(sv0[2], sv0[3], sv1[2], sv1[3], pv1, mean1, var1);
          mean0 = __shfl_sync(0xffffffffu, mean0, g); var0 = __shfl_sync(0xffffffffu, var0, g);
          mean1 = __shfl_sync(0xffffffffu, mean1, g); var1 = __shfl_sync(0xffffffffu, var1, g);
          r0 = 0.5f * rsq(fmaf(var0 + 1e-5f, 1e-5f, var0)); r1 = 0.5f * rsq(fmaf(var1 + 1e-5f, 1e-5f, var1));
          m0 = -mean0 * r0; m1 = -mean1 * r1;
        }
#pragma unroll
        for (int t = 0; t < 16; t += 2) {
          stsm4((e2h ^ ((t & 7) << 4)) + (t >> 3) * 8192,
                pack2(fmaf(xa[4 * t], r0, m0), fmaf(xa[4 * t + 1], r0, m0)), pack2(fmaf(xa[4 * t + 2], r1, m1), fmaf(xa[4 * t + 3], r1, m1)),
                pack2(fmaf(xa[4 * t + 4], r0, m0), fmaf(xa[4 * t + 5], r0, m0)), pack2(fmaf(xa[4 * t + 6], r1, m1), fmaf(xa[4 * t + 7], r1, m1)));
          if ((t & 7) == 6 && wg == 0) {
            __syncwarp();
            copy_out<4>(e2g + (t >> 3) * 8192, sb + OFF_X + (t >> 3) * 8192 + w * 2048 + lane * 16, 512);
          }
        }
        signal(JOB + 2 + wg);
        fence_async_smem();
        mbar_wait(BAR(F3 + 0), 0);
        if (wg == 0) { nb_sync<NB_WG0>(128); if (t7 == 0) mbar_arrive(BAR(XF + 1)); }
        else nb_sync<NB_BOTH>(256);
      }
      auto g3_issue = [&](uint32_t a, int p) {
        const uint32_t da = sda + (a >> 4), db = sd + (slot3(p) >> 4);
        wg_fence();
        static_for<0, 4>([&](auto kk) { wgmma_224<1, 1, DI(kk.value * 2048, 8192), DI(16384 + kk.value * 2048, 8192)>(acc3, da, db); });
        wg_commit();
      };
 g3_issue(OFF_X, 0);
      if (wg == 0) nb_sync<NB_BOTH>(256);
      mbar_wait(BAR(F3 + 1), 0); g3_issue(OFF_X + 16384, 1);
      sched_fence(P.zero);
      {
        const float c0 = __uint_as_float((uint32_t)b2a << 16), c1 = __uint_as_float((uint32_t)b2b << 16);
#pragma unroll
        for (int t = 0; t < 16; t++) { xa[4 * t] += c0; xa[4 * t + 1] += c0; xa[4 * t + 2] += c1; xa[4 * t + 3] += c1; }
        fence_regs(xa);
      }
      wg_wait<1>(); release(E3 + 0);
      auto g3_loop = [&](int n0, int n1, int nrel) {
#pragma unroll 1
        for (int n = n0; n < n1; n++) {
          const int p = n & 3;
          mbar_wait(BAR(F3 + p), (n >> 2) & 1);
          g3_issue(slot3(p), p);
          wg_wait<1>();
          if (n > nrel) release(E3 + ((n - 1) & 3));
        }
      };
      g3_loop(2, 29, 0);
      uint32_t ua;
      uint8_t* ug;
      {
        GEOM;
        ua = sb + OFF_X + wg * 8192 + (8 * lt + l7) * 128 + (((2 * w + ((lane >> 3) & 1)) ^ l7) << 4);
        ug = gUB + (opq(j) * 56 + 48 + m) * 16384 + r * 4096 + wg * 8192 + (lane >> 1) * 128 + (((2 * w + (lane & 1)) ^ ((lane >> 1) & 7)) << 4);
      }
      auto gelu8 = [&](int c, int k) {
        const int o = 32 * c + 8 * k;
        stsm4t(ua + (c & 1) * 16384 + k * 2048,
               pack2(gelu_half(acc3[o]), gelu_half(acc3[o + 1])), pack2(gelu_half(acc3[o + 2]), gelu_half(acc3[o + 3])),
               pack2(gelu_half(acc3[o + 4]), gelu_half(acc3[o + 5])), pack2(gelu_half(acc3[o + 6]), gelu_half(acc3[o + 7])));
      };
      {
        auto part = [&](auto p, auto half) {
          static_for<0, 4>([&](auto kk) {
            constexpr uint32_t o = slot3(p.value) + kk.value * 2048;
            if constexpr (half.value) wgmma_32<1, 1, DI(o, 8192), DI(o + 40960, 8192), 96>(acc3, sda, sd);
            else wgmma_192<1, 1, DI(o, 8192), DI(o + 16384, 8192), 0>(acc3, sda, sd);
          });
        };
        mbar_wait(BAR(RD), L);
        mbar_wait(BAR(F3 + 1), 1); mbar_wait(BAR(F3 + 2), 1);
        wg_wait<0>(); release(E3 + 0);
#pragma unroll
        for (int k = 0; k < 112; k++) { float t; asm volatile("mov.b32 %0, %1;" : "=f"(t) : "f"(acc3[k]) : "memory"); acc3[k] = t; }
        sched_fence(P.zero);
        wg_fence(); part(Int<1>{}, True{}); part(Int<2>{}, True{});
        mbar_wait(BAR(F3 + 3), 1); wg_fence(); part(Int<3>{}, True{}); wg_commit();
        part(Int<1>{}, False{}); wg_commit();
        wg_wait<1>();
#pragma unroll
        for (int k = 96; k < 112; k++) asm volatile("" : "+f"(acc3[k])::"memory");
        gelu8(3, 0); gelu8(3, 1);
        __syncwarp();
        copy_out<2>(ug, sb + OFF_X + 16384 + (uint32_t)((ug - gUB) & 0x2fff), 2048);
        signal(JOB + 7);
        sched_fence(P.zero);
        wg_fence(); part(Int<2>{}, False{}); wg_commit();
        wg_wait<1>(); release(E3 + 1);
        part(Int<3>{}, False{}); wg_commit();
        wg_wait<1>(); release(E3 + 2);
        wg_wait<0>(); release(E3 + 3);
      }
      fence_regs(acc3);
      auto g4_issue = [&](int p, uint32_t b) {
        const uint32_t da = sda + (slot4(p) >> 4), db = sd + (b >> 4);
        wg_fence();
        static_for<0, 4>([&](auto kk) { wgmma_128<1, 1, DI(kk.value * 2048, 8192), DI(kk.value * 2048, 8192)>(xa, da, db); });
        wg_commit();
      };
#pragma unroll
      for (int k = 0; k < 4; k++) gelu8(0, k);
      fence_async_smem();
      signal(JOB + 4);
      nb_sync<NB_BOTH>(256);
      static_for<0, 18>([&](auto nn) {
        constexpr int n = nn.value, p = n % 6;
        if (n == 9 || n == 17) mbar_wait(BAR(JOB + 4 + (n >> 3)), L);
        mbar_wait(BAR(F4 + p), (n / 6 + (p >= 2 ? L : 0)) & 1);
        wg_fence();
        static_for<0, 4>([&](auto kk) {
          wgmma_128<1, 1, DI(slot4(p) + kk.value * 2048, 8192), DI((n == 9 ? OFF_X + 16384 : n % 17 ? slot4(p) + 16384 : OFF_X) + kk.value * 2048, 8192)>(xa, sda, sd);
        });
        wg_commit();
        if (n) { wg_wait<1>(); release(E4 + (n + 5) % 6); }
        if (n == 8) mbar_wait(BAR(RD + 2), L);
        else if (n < 16 && !(n & 1)) sched_fence(P.zero);
        if constexpr (n < 16 && !(n & 1)) gelu8(1 + (n >> 3), (n >> 1) & 3);
        if ((n & 7) == 7) { fence_async_smem(); signal(JOB + 5 + (n >> 3)); }
      });
      {
        int p = 0, pp = 5;
        uint32_t par = L ? 0x03 : 0x3f;
        auto g4_loop = [&](int n0, int n1, int nrel) {
#pragma unroll 1
          for (int n = n0; n < n1; n++) {
            mbar_wait(BAR(F4 + p), (par >> p) & 1);
            par ^= 1u << p;
            g4_issue(p, slot4(p) + 16384);
            wg_wait<1>();
            if (n > nrel) release(E4 + pp);
            pp = p; if (++p == 6) p = 0;
          }
        };
        g4_loop(18, 56 - LEAD4, 0);
        if (wg == 1) { wg_wait<0>(); release(E4 + pp); nb_sync<NB_LEAD>(256); }
        static_for<56 - LEAD4, 56>([&](auto nn) {
          constexpr int n = nn.value, p = n % 6;
          mbar_wait(BAR(F4 + p), (n / 6 + (p >= 2 ? L : 0)) & 1);
          wg_fence();
          static_for<0, 4>([&](auto kk) { wgmma_128<1, 1, DI(slot4(p) + kk.value * 2048, 8192), DI(slot4(p) + 16384 + kk.value * 2048, 8192)>(xa, sda, sd); });
          wg_commit();
          if (n == 55 && wg == 0) nb_arrive<NB_LEAD>(256);
          wg_wait<1>();
          if (n > 56 - LEAD4 || wg == 0) release(E4 + (n + 5) % 6);
        });
      }
      uint32_t xs;
      uint8_t* xg;
      {
        GEOM;
        xs = sb + OFF_X + wu * 2048 + (lane >> 3) * 128 + ((L ? l7 ^ (lane >> 3) : l7) << 4);
        xg = L ? P.out + (128 * opq(i) + 16 * wu + (lane >> 3)) * 2048 + 256 * j + 16 * l7 : gXB + (opq(i) * 16 + 2 * j) * 16384 + wu * 2048 + lane * 16;
        asm volatile("" : "+r"(xs), "+l"(xg));
      }
      mbar_wait(BAR(RD + 1), L);
      wg_wait<0>();
      release(E4 + 1);
      fence_regs(xa);
      {
        GEOM;
#pragma unroll
        for (int t = 0; t < 16; t += 2) {
          stsm4(sb + OFF_X + (t >> 3) * 16384 + (16 * wu + lr) * 128 + ((((t & 7) + lt) ^ l7) << 4),
                pack2(xa[4 * t], xa[4 * t + 1]), pack2(xa[4 * t + 2], xa[4 * t + 3]),
                pack2(xa[4 * t + 4], xa[4 * t + 5]), pack2(xa[4 * t + 6], xa[4 * t + 7]));
          if ((t & 7) == 6 && (L || t == 6)) {
            __syncwarp();
            uint4 v[4];
#pragma unroll
            for (int k = 0; k < 4; k++) lds128((xs ^ (L ? (k & 1) << 6 : 0)) + k * 512 + (t >> 3) * 16384, v[k].x, v[k].y, v[k].z, v[k].w);
#pragma unroll
            for (int k = 0; k < 4; k++)
              asm volatile("st.global.v4.b32 [%0], {%1, %2, %3, %4};" ::"l"(xg + k * (L ? 8192 : 512) + (t >> 3) * 128), "r"(v[k].x), "r"(v[k].y), "r"(v[k].z), "r"(v[k].w) : "memory");
            if (L == 0) signal(JOB + 8);
          }
        }
        if (L) break;
        fence_async_smem();
        signal(JOB + 9);
        nb_sync<NB_BOTH>(256);
      }
    }
    cluster_bar();
  }
}

typedef CUresult (*EncodeFn)(CUtensorMap*, CUtensorMapDataType, cuuint32_t, void*, const cuuint64_t*, const cuuint64_t*, const cuuint32_t*,
                             const cuuint32_t*, CUtensorMapInterleave, CUtensorMapSwizzle, CUtensorMapL2promotion, CUtensorMapFloatOOBfill);

void make_map(EncodeFn enc, CUtensorMap* mp, const void* base, int rank, cuuint64_t d0, cuuint64_t d1, cuuint64_t d2, cuuint64_t s1, cuuint64_t s2,
              cuuint32_t b0, cuuint32_t b1, cuuint32_t b2) {
  cuuint64_t dims[3] = {d0, d1, d2}, strides[2] = {s1, s2};
  cuuint32_t box[3] = {b0, b1, b2}, es[3] = {1, 1, 1};
  CUresult res = enc(mp, CU_TENSOR_MAP_DATA_TYPE_BFLOAT16, rank, const_cast<void*>(base), dims, strides, box, es, CU_TENSOR_MAP_INTERLEAVE_NONE,
                     CU_TENSOR_MAP_SWIZZLE_128B, CU_TENSOR_MAP_L2_PROMOTION_L2_128B, CU_TENSOR_MAP_FLOAT_OOB_FILL_NONE);
  (void)res;
}

}

extern "C" void kernel_launch(void* const* d_in, const int* in_sizes, int n_in, void* d_out, int out_size) {
  (void)in_sizes; (void)n_in; (void)out_size;
  static EncodeFn enc = nullptr;
  if (!enc) {
    void* fn = nullptr;
    cudaDriverEntryPointQueryResult qr;
    cudaGetDriverEntryPoint("cuTensorMapEncodeTiled", &fn, cudaEnableDefault, &qr);
    enc = (EncodeFn)fn;
    cudaFuncSetAttribute(fused_kernel, cudaFuncAttributeMaxDynamicSharedMemorySize, SMEM_BYTES);
  }
  Params P;
  make_map(enc, &P.x0, d_in[0], 2, D_, S_, 1, D_ * 2, 0, 64, 128, 1);
  make_map(enc, &P.wqkv, d_in[1], 3, D_, D_, 3, 3 * D_ * 2, D_ * 2, 64, 32, 3);
  make_map(enc, &P.wo, d_in[2], 2, D_, D_, 1, D_ * 2, 0, 64, 64, 1);
  make_map(enc, &P.w1, d_in[4], 3, 64, S_, F_ / 64, F_ * 2, 128, 64, 64, 3);
  make_map(enc, &P.w1h, d_in[4], 3, 32, S_, F_ / 32, F_ * 2, 64, 64, 64, 1);
  make_map(enc, &P.w2, d_in[6], 3, 64, F_, S_ / 64, S_ * 2, 128, 64, 64, 2);
  P.out = (uint8_t*)d_out;
  P.wo_p = (const bf16*)d_in[2];
  P.w1_p = (const bf16*)d_in[4];
  P.b1 = (const bf16*)d_in[5];
  P.b2 = (const bf16*)d_in[7];
  P.zero = 0;
  fused_kernel<<<128, 384, SMEM_BYTES>>>((const bf16*)d_in[0], (const bf16*)d_in[1], P);
}
```

```cpp
#include <cuda_runtime.h>
#include <cuda_bf16.h>
#include <cuda.h>
#include <stdint.h>

namespace {

typedef __nv_bfloat16 bf16;
constexpr int S_ = 2048, D_ = 1024, F_ = 3584;

constexpr uint32_t OFF_STG  = 163840;
constexpr uint32_t OFF_X    = 196608;
constexpr uint32_t OFF_BAR  = 229376;
constexpr uint32_t OFF_CS   = OFF_BAR + 512;
constexpr uint32_t OFF_B1   = OFF_CS + 1536;
constexpr uint32_t SMEM_BYTES = OFF_B1 + 896 + 128;
constexpr int F1 = 0, E1 = 4, F2 = 8, E2 = 13, F3 = 18, E3 = 22, F4 = 26, E4 = 32;
constexpr int JOB = 38;
constexpr int RD = 48;
constexpr int XF = 54, STD = 56, STAT = 58, FOLD = 59, CSJ = 61, HALO = 62;
constexpr int NB_BOTH = 1, NB_INIT = 2, NB_LEAD = 3, NB_WG0 = 4;

__host__ __device__ constexpr uint32_t slot1(int p) { return p * 40960; }
__host__ __device__ constexpr uint32_t slot2(int p) { return p * 32768; }
__host__ __device__ constexpr uint32_t slot3(int p) { return ((p + 2) & 3) * 49152; }
__host__ __device__ constexpr uint32_t slot4(int p) { return (p < 2 ? p + 4 : p - 2) * 32768; }

__device__ __align__(1024) uint8_t gXB[16 * 16 * 16384];
__device__ __align__(1024) uint8_t gOB[16 * 16 * 16384];
__device__ __align__(1024) uint8_t gHB[8 * 32 * 16384];
__device__ __align__(1024) uint8_t gUB[8 * 56 * 16384];
__device__ __align__(1024) uint2   gST[2][16][8][8][16];
__device__ __align__(1024) uint4   gHalo[2][16][8][12][32];
__device__ __align__(1024) uint32_t gAck[2][16][8][2][8];
__device__ __align__(1024) uint4   gCS[8][16][64];
__device__ __align__(1024) uint32_t gFlag[2][7][16][32];
__device__ uint32_t gEpoch;

struct Params {
  CUtensorMap x0, wqkv, wo, w1, w1h, w2;
  uint8_t* out;
  const bf16 *wo_p, *w1_p, *b1, *b2;
  uint32_t zero;
};

template <int TA, int TB, uint32_t IA, uint32_t IB, int O = 0, int LEN> __device__ __forceinline__ void wgmma_32(float (&d)[LEN], uint32_t da, uint32_t db) {
  asm volatile("{\n.reg .b64 da, db;\n.reg .b32 la, lb;\nadd.u32 la, %16, %20;\nadd.u32 lb, %17, %21;\nmov.b64 da, {la, 0x40000040};\nmov.b64 db, {lb, 0x40000040};\n"
  "wgmma.mma_async.sync.aligned.m64n32k16.f32.bf16.bf16 {"
  "%0, %1, %2, %3, %4, %5, %6, %7, %8, %9, %10, %11, %12, %13, %14, %15"
  "}, da, db, 1, 1, 1, %18, %19;\n}\n"
  : "+f"(d[O + 0]), "+f"(d[O + 1]), "+f"(d[O + 2]), "+f"(d[O + 3]), "+f"(d[O + 4]), "+f"(d[O + 5]), "+f"(d[O + 6]), "+f"(d[O + 7]),
    "+f"(d[O + 8]), "+f"(d[O + 9]), "+f"(d[O + 10]), "+f"(d[O + 11]), "+f"(d[O + 12]), "+f"(d[O + 13]), "+f"(d[O + 14]), "+f"(d[O + 15])
  : "r"(da), "r"(db), "n"(TA), "n"(TB), "n"(IA), "n"(IB));
}
template <int TA, int TB, uint32_t IA, uint32_t IB, int O = 0, int LEN> __device__ __forceinline__ void wgmma_128(float (&d)[LEN], uint32_t da, uint32_t db) {
  asm volatile("{\n.reg .b64 da, db;\n.reg .b32 la, lb;\nadd.u32 la, %64, %68;\nadd.u32 lb, %65, %69;\nmov.b64 da, {la, 0x40000040};\nmov.b64 db, {lb, 0x40000040};\n"
  "wgmma.mma_async.sync.aligned.m64n128k16.f32.bf16.bf16 {"
  "%0, %1, %2, %3, %4, %5, %6, %7, %8, %9, %10, %11, %12, %13, %14, %15, "
  "%16, %17, %18, %19, %20, %21, %22, %23, %24, %25, %26, %27, %28, %29, %30, %31, "
  "%32, %33, %34, %35, %36, %37, %38, %39, %40, %41, %42, %43, %44, %45, %46, %47, "
  "%48, %49, %50, %51, %52, %53, %54, %55, %56, %57, %58, %59, %60, %61, %62, %63"
  "}, da, db, 1, 1, 1, %66, %67;\n}\n"
  : "+f"(d[O + 0]), "+f"(d[O + 1]), "+f"(d[O + 2]), "+f"(d[O + 3]), "+f"(d[O + 4]), "+f"(d[O + 5]), "+f"(d[O + 6]), "+f"(d[O + 7]),
    "+f"(d[O + 8]), "+f"(d[O + 9]), "+f"(d[O + 10]), "+f"(d[O + 11]), "+f"(d[O + 12]), "+f"(d[O + 13]), "+f"(d[O + 14]), "+f"(d[O + 15]),
    "+f"(d[O + 16]), "+f"(d[O + 17]), "+f"(d[O + 18]), "+f"(d[O + 19]), "+f"(d[O + 20]), "+f"(d[O + 21]), "+f"(d[O + 22]), "+f"(d[O + 23]),
    "+f"(d[O + 24]), "+f"(d[O + 25]), "+f"(d[O + 26]), "+f"(d[O + 27]), "+f"(d[O + 28]), "+f"(d[O + 29]), "+f"(d[O + 30]), "+f"(d[O + 31]),
    "+f"(d[O + 32]), "+f"(d[O + 33]), "+f"(d[O + 34]), "+f"(d[O + 35]), "+f"(d[O + 36]), "+f"(d[O + 37]), "+f"(d[O + 38]), "+f"(d[O + 39]),
    "+f"(d[O + 40]), "+f"(d[O + 41]), "+f"(d[O + 42]), "+f"(d[O + 43]), "+f"(d[O + 44]), "+f"(d[O + 45]), "+f"(d[O + 46]), "+f"(d[O + 47]),
    "+f"(d[O + 48]), "+f"(d[O + 49]), "+f"(d[O + 50]), "+f"(d[O + 51]), "+f"(d[O + 52]), "+f"(d[O + 53]), "+f"(d[O + 54]), "+f"(d[O + 55]),
    "+f"(d[O + 56]), "+f"(d[O + 57]), "+f"(d[O + 58]), "+f"(d[O + 59]), "+f"(d[O + 60]), "+f"(d[O + 61]), "+f"(d[O + 62]), "+f"(d[O + 63])
  : "r"(da), "r"(db), "n"(TA), "n"(TB), "n"(IA), "n"(IB));
}
template <int TA, int TB, uint32_t IA, uint32_t IB, int O = 0, int LEN> __device__ __forceinline__ void wgmma_192(float (&d)[LEN], uint32_t da, uint32_t db) {
  asm volatile("{\n.reg .b64 da, db;\n.reg .b32 la, lb;\nadd.u32 la, %96, %100;\nadd.u32 lb, %97, %101;\nmov.b64 da, {la, 0x40000040};\nmov.b64 db, {lb, 0x40000040};\n"
  "wgmma.mma_async.sync.aligned.m64n192k16.f32.bf16.bf16 {"
  "%0, %1, %2, %3, %4, %5, %6, %7, %8, %9, %10, %11, %12, %13, %14, %15, "
  "%16, %17, %18, %19, %20, %21, %22, %23, %24, %25, %26, %27, %28, %29, %30, %31, "
  "%32, %33, %34, %35, %36, %37, %38, %39, %40, %41, %42, %43, %44, %45, %46, %47, "
  "%48, %49, %50, %51, %52, %53, %54, %55, %56, %57, %58, %59, %60, %61, %62, %63, "
  "%64, %65, %66, %67, %68, %69, %70, %71, %72, %73, %74, %75, %76, %77, %78, %79, "
  "%80, %81, %82, %83, %84, %85, %86, %87, %88, %89, %90, %91, %92, %93, %94, %95"
  "}, da, db, 1, 1, 1, %98, %99;\n}\n"
  : "+f"(d[O + 0]), "+f"(d[O + 1]), "+f"(d[O + 2]), "+f"(d[O + 3]), "+f"(d[O + 4]), "+f"(d[O + 5]), "+f"(d[O + 6]), "+f"(d[O + 7]),
    "+f"(d[O + 8]), "+f"(d[O + 9]), "+f"(d[O + 10]), "+f"(d[O + 11]), "+f"(d[O + 12]), "+f"(d[O + 13]), "+f"(d[O + 14]), "+f"(d[O + 15]),
    "+f"(d[O + 16]), "+f"(d[O + 17]), "+f"(d[O + 18]), "+f"(d[O + 19]), "+f"(d[O + 20]), "+f"(d[O + 21]), "+f"(d[O + 22]), "+f"(d[O + 23]),
    "+f"(d[O + 24]), "+f"(d[O + 25]), "+f"(d[O + 26]), "+f"(d[O + 27]), "+f"(d[O + 28]), "+f"(d[O + 29]), "+f"(d[O + 30]), "+f"(d[O + 31]),
    "+f"(d[O + 32]), "+f"(d[O + 33]), "+f"(d[O + 34]), "+f"(d[O + 35]), "+f"(d[O + 36]), "+f"(d[O + 37]), "+f"(d[O + 38]), "+f"(d[O + 39]),
    "+f"(d[O + 40]), "+f"(d[O + 41]), "+f"(d[O + 42]), "+f"(d[O + 43]), "+f"(d[O + 44]), "+f"(d[O + 45]), "+f"(d[O + 46]), "+f"(d[O + 47]),
    "+f"(d[O + 48]), "+f"(d[O + 49]), "+f"(d[O + 50]), "+f"(d[O + 51]), "+f"(d[O + 52]), "+f"(d[O + 53]), "+f"(d[O + 54]), "+f"(d[O + 55]),
    "+f"(d[O + 56]), "+f"(d[O + 57]), "+f"(d[O + 58]), "+f"(d[O + 59]), "+f"(d[O + 60]), "+f"(d[O + 61]), "+f"(d[O + 62]), "+f"(d[O + 63]),
    "+f"(d[O + 64]), "+f"(d[O + 65]), "+f"(d[O + 66]), "+f"(d[O + 67]), "+f"(d[O + 68]), "+f"(d[O + 69]), "+f"(d[O + 70]), "+f"(d[O + 71]),
    "+f"(d[O + 72]), "+f"(d[O + 73]), "+f"(d[O + 74]), "+f"(d[O + 75]), "+f"(d[O + 76]), "+f"(d[O + 77]), "+f"(d[O + 78]), "+f"(d[O + 79]),
    "+f"(d[O + 80]), "+f"(d[O + 81]), "+f"(d[O + 82]), "+f"(d[O + 83]), "+f"(d[O + 84]), "+f"(d[O + 85]), "+f"(d[O + 86]), "+f"(d[O + 87]),
    "+f"(d[O + 88]), "+f"(d[O + 89]), "+f"(d[O + 90]), "+f"(d[O + 91]), "+f"(d[O + 92]), "+f"(d[O + 93]), "+f"(d[O + 94]), "+f"(d[O + 95])
  : "r"(da), "r"(db), "n"(TA), "n"(TB), "n"(IA), "n"(IB));
}
template <int TA, int TB, uint32_t IA, uint32_t IB, int O = 0, int LEN> __device__ __forceinline__ void wgmma_192z(float (&d)[LEN], uint32_t da, uint32_t db) {
  asm volatile("{\n.reg .b64 da, db;\n.reg .b32 la, lb;\nadd.u32 la, %96, %100;\nadd.u32 lb, %97, %101;\nmov.b64 da, {la, 0x40000040};\nmov.b64 db, {lb, 0x40000040};\n"
  "wgmma.mma_async.sync.aligned.m64n192k16.f32.bf16.bf16 {"
  "%0, %1, %2, %3, %4, %5, %6, %7, %8, %9, %10, %11, %12, %13, %14, %15, "
  "%16, %17, %18, %19, %20, %21, %22, %23, %24, %25, %26, %27, %28, %29, %30, %31, "
  "%32, %33, %34, %35, %36, %37, %38, %39, %40, %41, %42, %43, %44, %45, %46, %47, "
  "%48, %49, %50, %51, %52, %53, %54, %55, %56, %57, %58, %59, %60, %61, %62, %63, "
  "%64, %65, %66, %67, %68, %69, %70, %71, %72, %73, %74, %75, %76, %77, %78, %79, "
  "%80, %81, %82, %83, %84, %85, %86, %87, %88, %89, %90, %91, %92, %93, %94, %95"
  "}, da, db, 0, 1, 1, %98, %99;\n}\n"
  : "=f"(d[O + 0]), "=f"(d[O + 1]), "=f"(d[O + 2]), "=f"(d[O + 3]), "=f"(d[O + 4]), "=f"(d[O + 5]), "=f"(d[O + 6]), "=f"(d[O + 7]),
    "=f"(d[O + 8]), "=f"(d[O + 9]), "=f"(d[O + 10]), "=f"(d[O + 11]), "=f"(d[O + 12]), "=f"(d[O + 13]), "=f"(d[O + 14]), "=f"(d[O + 15]),
    "=f"(d[O + 16]), "=f"(d[O + 17]), "=f"(d[O + 18]), "=f"(d[O + 19]), "=f"(d[O + 20]), "=f"(d[O + 21]), "=f"(d[O + 22]), "=f"(d[O + 23]),
    "=f"(d[O + 24]), "=f"(d[O + 25]), "=f"(d[O + 26]), "=f"(d[O + 27]), "=f"(d[O + 28]), "=f"(d[O + 29]), "=f"(d[O + 30]), "=f"(d[O + 31]),
    "=f"(d[O + 32]), "=f"(d[O + 33]), "=f"(d[O + 34]), "=f"(d[O + 35]), "=f"(d[O + 36]), "=f"(d[O + 37]), "=f"(d[O + 38]), "=f"(d[O + 39]),
    "=f"(d[O + 40]), "=f"(d[O + 41]), "=f"(d[O + 42]), "=f"(d[O + 43]), "=f"(d[O + 44]), "=f"(d[O + 45]), "=f"(d[O + 46]), "=f"(d[O + 47]),
    "=f"(d[O + 48]), "=f"(d[O + 49]), "=f"(d[O + 50]), "=f"(d[O + 51]), "=f"(d[O + 52]), "=f"(d[O + 53]), "=f"(d[O + 54]), "=f"(d[O + 55]),
    "=f"(d[O + 56]), "=f"(d[O + 57]), "=f"(d[O + 58]), "=f"(d[O + 59]), "=f"(d[O + 60]), "=f"(d[O + 61]), "=f"(d[O + 62]), "=f"(d[O + 63]),
    "=f"(d[O + 64]), "=f"(d[O + 65]), "=f"(d[O + 66]), "=f"(d[O + 67]), "=f"(d[O + 68]), "=f"(d[O + 69]), "=f"(d[O + 70]), "=f"(d[O + 71]),
    "=f"(d[O + 72]), "=f"(d[O + 73]), "=f"(d[O + 74]), "=f"(d[O + 75]), "=f"(d[O + 76]), "=f"(d[O + 77]), "=f"(d[O + 78]), "=f"(d[O + 79]),
    "=f"(d[O + 80]), "=f"(d[O + 81]), "=f"(d[O + 82]), "=f"(d[O + 83]), "=f"(d[O + 84]), "=f"(d[O + 85]), "=f"(d[O + 86]), "=f"(d[O + 87]),
    "=f"(d[O + 88]), "=f"(d[O + 89]), "=f"(d[O + 90]), "=f"(d[O + 91]), "=f"(d[O + 92]), "=f"(d[O + 93]), "=f"(d[O + 94]), "=f"(d[O + 95])
  : "r"(da), "r"(db), "n"(TA), "n"(TB), "n"(IA), "n"(IB));
}
template <int TA, int TB, uint32_t IA, uint32_t IB, int O = 0, int LEN> __device__ __forceinline__ void wgmma_224(float (&d)[LEN], uint32_t da, uint32_t db) {
  asm volatile("{\n.reg .b64 da, db;\n.reg .b32 la, lb;\nadd.u32 la, %112, %116;\nadd.u32 lb, %113, %117;\nmov.b64 da, {la, 0x40000040};\nmov.b64 db, {lb, 0x40000040};\n"
  "wgmma.mma_async.sync.aligned.m64n224k16.f32.bf16.bf16 {"
  "%0, %1, %2, %3, %4, %5, %6, %7, %8, %9, %10, %11, %12, %13, %14, %15, "
  "%16, %17, %18, %19, %20, %21, %22, %23, %24, %25, %26, %27, %28, %29, %30, %31, "
  "%32, %33, %34, %35, %36, %37, %38, %39, %40, %41, %42, %43, %44, %45, %46, %47, "
  "%48, %49, %50, %51, %52, %53, %54, %55, %56, %57, %58, %59, %60, %61, %62, %63, "
  "%64, %65, %66, %67, %68, %69, %70, %71, %72, %73, %74, %75, %76, %77, %78, %79, "
  "%80, %81, %82, %83, %84, %85, %86, %87, %88, %89, %90, %91, %92, %93, %94, %95, "
  "%96, %97, %98, %99, %100, %101, %102, %103, %104, %105, %106, %107, %108, %109, %110, %111"
  "}, da, db, 1, 1, 1, %114, %115;\n}\n"
  : "+f"(d[O + 0]), "+f"(d[O + 1]), "+f"(d[O + 2]), "+f"(d[O + 3]), "+f"(d[O + 4]), "+f"(d[O + 5]), "+f"(d[O + 6]), "+f"(d[O + 7]),
    "+f"(d[O + 8]), "+f"(d[O + 9]), "+f"(d[O + 10]), "+f"(d[O + 11]), "+f"(d[O + 12]), "+f"(d[O + 13]), "+f"(d[O + 14]), "+f"(d[O + 15]),
    "+f"(d[O + 16]), "+f"(d[O + 17]), "+f"(d[O + 18]), "+f"(d[O + 19]), "+f"(d[O + 20]), "+f"(d[O + 21]), "+f"(d[O + 22]), "+f"(d[O + 23]),
    "+f"(d[O + 24]), "+f"(d[O + 25]), "+f"(d[O + 26]), "+f"(d[O + 27]), "+f"(d[O + 28]), "+f"(d[O + 29]), "+f"(d[O + 30]), "+f"(d[O + 31]),
    "+f"(d[O + 32]), "+f"(d[O + 33]), "+f"(d[O + 34]), "+f"(d[O + 35]), "+f"(d[O + 36]), "+f"(d[O + 37]), "+f"(d[O + 38]), "+f"(d[O + 39]),
    "+f"(d[O + 40]), "+f"(d[O + 41]), "+f"(d[O + 42]), "+f"(d[O + 43]), "+f"(d[O + 44]), "+f"(d[O + 45]), "+f"(d[O + 46]), "+f"(d[O + 47]),
    "+f"(d[O + 48]), "+f"(d[O + 49]), "+f"(d[O + 50]), "+f"(d[O + 51]), "+f"(d[O + 52]), "+f"(d[O + 53]), "+f"(d[O + 54]), "+f"(d[O + 55]),
    "+f"(d[O + 56]), "+f"(d[O + 57]), "+f"(d[O + 58]), "+f"(d[O + 59]), "+f"(d[O + 60]), "+f"(d[O + 61]), "+f"(d[O + 62]), "+f"(d[O + 63]),
    "+f"(d[O + 64]), "+f"(d[O + 65]), "+f"(d[O + 66]), "+f"(d[O + 67]), "+f"(d[O + 68]), "+f"(d[O + 69]), "+f"(d[O + 70]), "+f"(d[O + 71]),
    "+f"(d[O + 72]), "+f"(d[O + 73]), "+f"(d[O + 74]), "+f"(d[O + 75]), "+f"(d[O + 76]), "+f"(d[O + 77]), "+f"(d[O + 78]), "+f"(d[O + 79]),
    "+f"(d[O + 80]), "+f"(d[O + 81]), "+f"(d[O + 82]), "+f"(d[O + 83]), "+f"(d[O + 84]), "+f"(d[O + 85]), "+f"(d[O + 86]), "+f"(d[O + 87]),
    "+f"(d[O + 88]), "+f"(d[O + 89]), "+f"(d[O + 90]), "+f"(d[O + 91]), "+f"(d[O + 92]), "+f"(d[O + 93]), "+f"(d[O + 94]), "+f"(d[O + 95]),
    "+f"(d[O + 96]), "+f"(d[O + 97]), "+f"(d[O + 98]), "+f"(d[O + 99]), "+f"(d[O + 100]), "+f"(d[O + 101]), "+f"(d[O + 102]), "+f"(d[O + 103]),
    "+f"(d[O + 104]), "+f"(d[O + 105]), "+f"(d[O + 106]), "+f"(d[O + 107]), "+f"(d[O + 108]), "+f"(d[O + 109]), "+f"(d[O + 110]), "+f"(d[O + 111])
  : "r"(da), "r"(db), "n"(TA), "n"(TB), "n"(IA), "n"(IB));
}
__device__ __forceinline__ void wgmma_rs_192(float (&d)[96], uint32_t a0, uint32_t a1, uint32_t a2, uint32_t a3, uint64_t db) {
  asm volatile("wgmma.mma_async.sync.aligned.m64n192k16.f32.bf16.bf16 {"
  "%0, %1, %2, %3, %4, %5, %6, %7, %8, %9, %10, %11, %12, %13, %14, %15, "
  "%16, %17, %18, %19, %20, %21, %22, %23, %24, %25, %26, %27, %28, %29, %30, %31, "
  "%32, %33, %34, %35, %36, %37, %38, %39, %40, %41, %42, %43, %44, %45, %46, %47, "
  "%48, %49, %50, %51, %52, %53, %54, %55, %56, %57, %58, %59, %60, %61, %62, %63, "
  "%64, %65, %66, %67, %68, %69, %70, %71, %72, %73, %74, %75, %76, %77, %78, %79, "
  "%80, %81, %82, %83, %84, %85, %86, %87, %88, %89, %90, %91, %92, %93, %94, %95"
  "}, {%96, %97, %98, %99}, %100, 1, 1, 1, 1;\n"
  : "+f"(d[0]), "+f"(d[1]), "+f"(d[2]), "+f"(d[3]), "+f"(d[4]), "+f"(d[5]), "+f"(d[6]), "+f"(d[7]),
    "+f"(d[8]), "+f"(d[9]), "+f"(d[10]), "+f"(d[11]), "+f"(d[12]), "+f"(d[13]), "+f"(d[14]), "+f"(d[15]),
    "+f"(d[16]), "+f"(d[17]), "+f"(d[18]), "+f"(d[19]), "+f"(d[20]), "+f"(d[21]), "+f"(d[22]), "+f"(d[23]),
    "+f"(d[24]), "+f"(d[25]), "+f"(d[26]), "+f"(d[27]), "+f"(d[28]), "+f"(d[29]), "+f"(d[30]), "+f"(d[31]),
    "+f"(d[32]), "+f"(d[33]), "+f"(d[34]), "+f"(d[35]), "+f"(d[36]), "+f"(d[37]), "+f"(d[38]), "+f"(d[39]),
    "+f"(d[40]), "+f"(d[41]), "+f"(d[42]), "+f"(d[43]), "+f"(d[44]), "+f"(d[45]), "+f"(d[46]), "+f"(d[47]),
    "+f"(d[48]), "+f"(d[49]), "+f"(d[50]), "+f"(d[51]), "+f"(d[52]), "+f"(d[53]), "+f"(d[54]), "+f"(d[55]),
    "+f"(d[56]), "+f"(d[57]), "+f"(d[58]), "+f"(d[59]), "+f"(d[60]), "+f"(d[61]), "+f"(d[62]), "+f"(d[63]),
    "+f"(d[64]), "+f"(d[65]), "+f"(d[66]), "+f"(d[67]), "+f"(d[68]), "+f"(d[69]), "+f"(d[70]), "+f"(d[71]),
    "+f"(d[72]), "+f"(d[73]), "+f"(d[74]), "+f"(d[75]), "+f"(d[76]), "+f"(d[77]), "+f"(d[78]), "+f"(d[79]),
    "+f"(d[80]), "+f"(d[81]), "+f"(d[82]), "+f"(d[83]), "+f"(d[84]), "+f"(d[85]), "+f"(d[86]), "+f"(d[87]),
    "+f"(d[88]), "+f"(d[89]), "+f"(d[90]), "+f"(d[91]), "+f"(d[92]), "+f"(d[93]), "+f"(d[94]), "+f"(d[95])
  : "r"(a0), "r"(a1), "r"(a2), "r"(a3), "l"(db));
}
__device__ __forceinline__ void wgmma_rs_224z(float (&d)[112], uint32_t a0, uint32_t a1, uint32_t a2, uint32_t a3, uint64_t db) {
  asm volatile("wgmma.mma_async.sync.aligned.m64n224k16.f32.bf16.bf16 {"
  "%0, %1, %2, %3, %4, %5, %6, %7, %8, %9, %10, %11, %12, %13, %14, %15, "
  "%16, %17, %18, %19, %20, %21, %22, %23, %24, %25, %26, %27, %28, %29, %30, %31, "
  "%32, %33, %34, %35, %36, %37, %38, %39, %40, %41, %42, %43, %44, %45, %46, %47, "
  "%48, %49, %50, %51, %52, %53, %54, %55, %56, %57, %58, %59, %60, %61, %62, %63, "
  "%64, %65, %66, %67, %68, %69, %70, %71, %72, %73, %74, %75, %76, %77, %78, %79, "
  "%80, %81, %82, %83, %84, %85, %86, %87, %88, %89, %90, %91, %92, %93, %94, %95, "
  "%96, %97, %98, %99, %100, %101, %102, %103, %104, %105, %106, %107, %108, %109, %110, %111"
  "}, {%112, %113, %114, %115}, %116, 0, 1, 1, 1;\n"
  : "=f"(d[0]), "=f"(d[1]), "=f"(d[2]), "=f"(d[3]), "=f"(d[4]), "=f"(d[5]), "=f"(d[6]), "=f"(d[7]),
    "=f"(d[8]), "=f"(d[9]), "=f"(d[10]), "=f"(d[11]), "=f"(d[12]), "=f"(d[13]), "=f"(d[14]), "=f"(d[15]),
    "=f"(d[16]), "=f"(d[17]), "=f"(d[18]), "=f"(d[19]), "=f"(d[20]), "=f"(d[21]), "=f"(d[22]), "=f"(d[23]),
    "=f"(d[24]), "=f"(d[25]), "=f"(d[26]), "=f"(d[27]), "=f"(d[28]), "=f"(d[29]), "=f"(d[30]), "=f"(d[31]),
    "=f"(d[32]), "=f"(d[33]), "=f"(d[34]), "=f"(d[35]), "=f"(d[36]), "=f"(d[37]), "=f"(d[38]), "=f"(d[39]),
    "=f"(d[40]), "=f"(d[41]), "=f"(d[42]), "=f"(d[43]), "=f"(d[44]), "=f"(d[45]), "=f"(d[46]), "=f"(d[47]),
    "=f"(d[48]), "=f"(d[49]), "=f"(d[50]), "=f"(d[51]), "=f"(d[52]), "=f"(d[53]), "=f"(d[54]), "=f"(d[55]),
    "=f"(d[56]), "=f"(d[57]), "=f"(d[58]), "=f"(d[59]), "=f"(d[60]), "=f"(d[61]), "=f"(d[62]), "=f"(d[63]),
    "=f"(d[64]), "=f"(d[65]), "=f"(d[66]), "=f"(d[67]), "=f"(d[68]), "=f"(d[69]), "=f"(d[70]), "=f"(d[71]),
    "=f"(d[72]), "=f"(d[73]), "=f"(d[74]), "=f"(d[75]), "=f"(d[76]), "=f"(d[77]), "=f"(d[78]), "=f"(d[79]),
    "=f"(d[80]), "=f"(d[81]), "=f"(d[82]), "=f"(d[83]), "=f"(d[84]), "=f"(d[85]), "=f"(d[86]), "=f"(d[87]),
    "=f"(d[88]), "=f"(d[89]), "=f"(d[90]), "=f"(d[91]), "=f"(d[92]), "=f"(d[93]), "=f"(d[94]), "=f"(d[95]),
    "=f"(d[96]), "=f"(d[97]), "=f"(d[98]), "=f"(d[99]), "=f"(d[100]), "=f"(d[101]), "=f"(d[102]), "=f"(d[103]),
    "=f"(d[104]), "=f"(d[105]), "=f"(d[106]), "=f"(d[107]), "=f"(d[108]), "=f"(d[109]), "=f"(d[110]), "=f"(d[111])
  : "r"(a0), "r"(a1), "r"(a2), "r"(a3), "l"(db));
}

__device__ __forceinline__ uint32_t smem_u32(const void* p) { return (uint32_t)__cvta_generic_to_shared(p); }
__device__ __forceinline__ void mbar_init(uint32_t bar, uint32_t cnt) { asm volatile("mbarrier.init.shared::cta.b64 [%0], %1;" ::"r"(bar), "r"(cnt) : "memory"); }
__device__ __forceinline__ void mbar_expect(uint32_t bar, uint32_t bytes) { asm volatile("mbarrier.arrive.expect_tx.shared::cta.b64 _, [%0], %1;" ::"r"(bar), "r"(bytes) : "memory"); }
__device__ __forceinline__ void mbar_arrive(uint32_t bar) { asm volatile("mbarrier.arrive.shared::cta.b64 _, [%0];" ::"r"(bar) : "memory"); }
__device__ __forceinline__ void mbar_arrive_cl(uint32_t cbar) { asm volatile("mbarrier.arrive.shared::cluster.b64 _, [%0];" ::"r"(cbar) : "memory"); }
__device__ __forceinline__ uint32_t mapa(uint32_t a, uint32_t cta) { uint32_t r; asm("mapa.shared::cluster.u32 %0, %1, %2;" : "=r"(r) : "r"(a), "r"(cta)); return r; }
__device__ __forceinline__ void mbar_wait(uint32_t bar, uint32_t parity) {
  asm volatile("{\n.reg .pred p;\n.reg .u32 n;\nmov.u32 n, 0;\n"
    "LAB_WAIT:\n"
    "mbarrier.try_wait.parity.shared::cta.b64 p, [%0], %1;\n"
    "@p bra LAB_DONE;\n"
    "add.u32 n, n, 1;\n"
    "setp.lt.u32 p, n, 2000000;\n"
    "@p bra LAB_WAIT;\n"
    "trap;\n"
    "LAB_DONE:\n}\n" ::"r"(bar), "r"(parity) : "memory");
}
constexpr uint32_t SPIN_MAX = 2000000;
__device__ __forceinline__ void tma2d(uint32_t dst, const CUtensorMap* m, uint32_t bar, int c0, int c1) {
  asm volatile("cp.async.bulk.tensor.2d.shared::cluster.global.mbarrier::complete_tx::bytes [%0], [%1, {%3, %4}], [%2];"
    ::"r"(dst), "l"(m), "r"(bar), "r"(c0), "r"(c1) : "memory");
}
__device__ __forceinline__ void tma2d_mc(uint32_t dst, const CUtensorMap* m, uint32_t bar, int c0, int c1) {
  asm volatile("cp.async.bulk.tensor.2d.shared::cluster.global.mbarrier::complete_tx::bytes.multicast::cluster [%0], [%1, {%3, %4}], [%2], %5;"
    ::"r"(dst), "l"(m), "r"(bar), "r"(c0), "r"(c1), "h"((uint16_t)3) : "memory");
}
__device__ __forceinline__ void tma3d(uint32_t dst, const CUtensorMap* m, uint32_t bar, int c0, int c1, int c2) {
  asm volatile("cp.async.bulk.tensor.3d.shared::cluster.global.mbarrier::complete_tx::bytes [%0], [%1, {%3, %4, %5}], [%2];"
    ::"r"(dst), "l"(m), "r"(bar), "r"(c0), "r"(c1), "r"(c2) : "memory");
}
__device__ __forceinline__ void tma3d_mc(uint32_t dst, const CUtensorMap* m, uint32_t bar, int c0, int c1, int c2) {
  asm volatile("cp.async.bulk.tensor.3d.shared::cluster.global.mbarrier::complete_tx::bytes.multicast::cluster [%0], [%1, {%3, %4, %5}], [%2], %6;"
    ::"r"(dst), "l"(m), "r"(bar), "r"(c0), "r"(c1), "r"(c2), "h"((uint16_t)3) : "memory");
}
__device__ __forceinline__ void bulk_ld(uint32_t dst, const void* src, uint32_t bytes, uint32_t bar) {
  asm volatile("cp.async.bulk.shared::cluster.global.mbarrier::complete_tx::bytes [%0], [%1], %2, [%3];" ::"r"(dst), "l"(src), "r"(bytes), "r"(bar) : "memory");
}
__device__ __forceinline__ void bulk_ld_mc(uint32_t dst, const void* src, uint32_t bytes, uint32_t bar) {
  asm volatile("cp.async.bulk.shared::cluster.global.mbarrier::complete_tx::bytes.multicast::cluster [%0], [%1], %2, [%3], %4;"
    ::"r"(dst), "l"(src), "r"(bytes), "r"(bar), "h"((uint16_t)3) : "memory");
}
__device__ __forceinline__ void bulk_st(void* dst, uint32_t src, uint32_t bytes) {
  asm volatile("cp.async.bulk.global.shared::cta.bulk_group [%0], [%1], %2;" ::"l"(dst), "r"(src), "r"(bytes) : "memory");
}
__device__ __forceinline__ void bulk_s2s(uint32_t cdst, uint32_t src, uint32_t bytes, uint32_t cbar) {
  asm volatile("cp.async.bulk.shared::cluster.shared::cta.mbarrier::complete_tx::bytes [%0], [%1], %2, [%3];" ::"r"(cdst), "r"(src), "r"(bytes), "r"(cbar) : "memory");
}
__device__ __forceinline__ void bulk_commit() { asm volatile("cp.async.bulk.commit_group;" ::: "memory"); }
__device__ __forceinline__ void bulk_wait0() { asm volatile("cp.async.bulk.wait_group 0;" ::: "memory"); }
__device__ __forceinline__ void fence_async_smem() { asm volatile("fence.proxy.async.shared::cta;" ::: "memory"); }
__device__ __forceinline__ void wg_fence() { asm volatile("wgmma.fence.sync.aligned;" ::: "memory"); }
__device__ __forceinline__ void wg_commit() { asm volatile("wgmma.commit_group.sync.aligned;" ::: "memory"); }
template <int N> __device__ __forceinline__ void wg_wait() { asm volatile("wgmma.wait_group.sync.aligned %0;" ::"n"(N) : "memory"); }
template <int R> __device__ __forceinline__ void reg_alloc() { asm volatile("setmaxnreg.inc.sync.aligned.u32 %0;" ::"n"(R)); }
template <int R> __device__ __forceinline__ void reg_dealloc() { asm volatile("setmaxnreg.dec.sync.aligned.u32 %0;" ::"n"(R)); }
__device__ __forceinline__ void cluster_bar() { asm volatile("barrier.cluster.arrive.relaxed;\nbarrier.cluster.wait;" ::: "memory"); }
template <int ID> __device__ __forceinline__ void nb_sync(int n) { asm volatile("barrier.sync %0, %1;" ::"n"(ID), "r"(n) : "memory"); }
template <int ID> __device__ __forceinline__ void nb_arrive(int n) { asm volatile("barrier.arrive %0, %1;" ::"n"(ID), "r"(n) : "memory"); }
__device__ __forceinline__ int fresh_tid() { int t; asm volatile("mov.u32 %0, %%tid.x;" : "=r"(t)); return t; }
__device__ __forceinline__ void sched_fence(uint32_t z) { asm volatile("{\n.reg .pred p;\nsetp.ne.u32 p, %0, 0;\nLAB_S:\n@p nanosleep.u32 0;\n@p bra LAB_S;\n}\n" ::"r"(z) : "memory"); }
__device__ __forceinline__ float rsq(float x) { float y; asm("rsqrt.approx.ftz.f32 %0, %1;" : "=f"(y) : "f"(x)); return y; }
__device__ __forceinline__ int opq(int v) { asm volatile("" : "+r"(v)); return v; }
template <int V> struct Int { static constexpr int value = V; };
struct True { static constexpr bool value = true; };
struct False { static constexpr bool value = false; };
template <int N> __device__ __forceinline__ void fence_regs(float (&d)[N]) {
#pragma unroll
  for (int i = 0; i < N; i++) asm volatile("" : "+f"(d[i])::"memory");
}
__host__ __device__ constexpr uint32_t DI(uint32_t off, uint32_t lbo) { return (off >> 4) + ((lbo >> 4) << 16); }
template <int K, int N, class F> __device__ __forceinline__ void static_for(F f) { if constexpr (K < N) { f(Int<K>{}); static_for<K + 1, N>(f); } }
__device__ __forceinline__ uint64_t mkdesc_vec(uint32_t addr, uint32_t sbo) { return (uint64_t)((addr & 0x3FFFF) >> 4) | ((uint64_t)(sbo >> 4) << 32); }
__device__ __forceinline__ void sts16(uint32_t a, uint32_t v) { asm volatile("st.shared.u16 [%0], %1;" ::"r"(a), "h"((uint16_t)v) : "memory"); }
__device__ __forceinline__ uint32_t pack2(float lo, float hi) { uint32_t r; asm("cvt.rn.bf16x2.f32 %0, %1, %2;" : "=r"(r) : "f"(hi), "f"(lo)); return r; }
__device__ __forceinline__ float bf_lo(uint32_t v) { return __uint_as_float(v << 16); }
__device__ __forceinline__ float bf_hi(uint32_t v) { return __uint_as_float(v & 0xffff0000u); }
__device__ __forceinline__ void stsm4(uint32_t a, uint32_t r0, uint32_t r1, uint32_t r2, uint32_t r3) {
  asm volatile("stmatrix.sync.aligned.m8n8.x4.shared.b16 [%0], {%1, %2, %3, %4};" ::"r"(a), "r"(r0), "r"(r1), "r"(r2), "r"(r3) : "memory");
}
__device__ __forceinline__ void stsm4t(uint32_t a, uint32_t r0, uint32_t r1, uint32_t r2, uint32_t r3) {
  asm volatile("stmatrix.sync.aligned.m8n8.x4.trans.shared.b16 [%0], {%1, %2, %3, %4};" ::"r"(a), "r"(r0), "r"(r1), "r"(r2), "r"(r3) : "memory");
}
__device__ __forceinline__ void ldsm4(uint32_t a, uint32_t& r0, uint32_t& r1, uint32_t& r2, uint32_t& r3) {
  asm volatile("ldmatrix.sync.aligned.m8n8.x4.shared.b16 {%0, %1, %2, %3}, [%4];" : "=r"(r0), "=r"(r1), "=r"(r2), "=r"(r3) : "r"(a) : "memory");
}
__device__ __forceinline__ void ldsm4t(uint32_t a, uint32_t& r0, uint32_t& r1, uint32_t& r2, uint32_t& r3) {
  asm volatile("ldmatrix.sync.aligned.m8n8.x4.trans.shared.b16 {%0, %1, %2, %3}, [%4];" : "=r"(r0), "=r"(r1), "=r"(r2), "=r"(r3) : "r"(a) : "memory");
}
__device__ __forceinline__ void mma16816(float (&c)[4], uint32_t a0, uint32_t a1, uint32_t a2, uint32_t a3, uint32_t b0, uint32_t b1) {
  asm volatile("mma.sync.aligned.m16n8k16.row.col.f32.bf16.bf16.f32 {%0, %1, %2, %3}, {%4, %5, %6, %7}, {%8, %9}, {%10, %11, %12, %13};"
    : "=f"(c[0]), "=f"(c[1]), "=f"(c[2]), "=f"(c[3]) : "r"(a0), "r"(a1), "r"(a2), "r"(a3), "r"(b0), "r"(b1), "f"(c[0]), "f"(c[1]), "f"(c[2]), "f"(c[3]));
}
__device__ __forceinline__ void sts128(uint32_t a, uint32_t r0, uint32_t r1, uint32_t r2, uint32_t r3) {
  asm volatile("st.shared.v4.b32 [%0], {%1, %2, %3, %4};" ::"r"(a), "r"(r0), "r"(r1), "r"(r2), "r"(r3) : "memory");
}
__device__ __forceinline__ void lds128(uint32_t a, uint32_t& r0, uint32_t& r1, uint32_t& r2, uint32_t& r3) {
  asm volatile("ld.shared.v4.b32 {%0, %1, %2, %3}, [%4];" : "=r"(r0), "=r"(r1), "=r"(r2), "=r"(r3) : "r"(a) : "memory");
}
__device__ __forceinline__ void sts64f(uint32_t a, float x, float y) { asm volatile("st.shared.v2.f32 [%0], {%1, %2};" ::"r"(a), "f"(x), "f"(y) : "memory"); }
__device__ __forceinline__ float lds32f(uint32_t a) { float v; asm volatile("ld.shared.f32 %0, [%1];" : "=f"(v) : "r"(a) : "memory"); return v; }
__device__ __forceinline__ void sts32f(uint32_t a, float x) { asm volatile("st.shared.f32 [%0], %1;" ::"r"(a), "f"(x) : "memory"); }
__device__ __forceinline__ void stat_st(uint2* p, float sum, float sq, uint32_t tag, bool on) {
  const float mean = sum * (1.f / 128), m2 = fmaxf(fmaf(-mean, sum, sq), 0.f);
  const uint32_t a = ((__float_as_uint(mean) + 8u) & ~15u) | (tag & 15u), b = ((__float_as_uint(m2) + 8u) & ~15u) | (tag & 15u);
  asm volatile("{\n.reg .b64 x;\n.reg .pred p;\nsetp.ne.u32 p, %3, 0;\nmov.b64 x, {%1, %2};\n@p st.relaxed.gpu.global.b64 [%0], x;\n}\n" ::"l"(p), "r"(a), "r"(b), "r"((uint32_t)on) : "memory");
}
__device__ __forceinline__ void stat_ld2(const uint2* p, uint32_t (&v)[4]) {
  asm volatile("{\n.reg .b64 x, y;\nld.relaxed.gpu.global.v2.b64 {x, y}, [%4];\nmov.b64 {%0, %1}, x;\nmov.b64 {%2, %3}, y;\n}\n"
    : "=r"(v[0]), "=r"(v[1]), "=r"(v[2]), "=r"(v[3]) : "l"(p) : "memory");
}
__device__ __forceinline__ float untag(uint32_t v) { return __uint_as_float(v & ~15u); }
__device__ __forceinline__ void ll_st3(uint4* p, uint32_t a, uint32_t b, uint32_t c, uint32_t tag) {
  asm volatile("{\n.reg .b64 x, y;\n.reg .b128 z;\nmov.b64 x, {%1, %2};\nmov.b64 y, {%3, %4};\nmov.b128 z, {x, y};\nst.relaxed.gpu.global.b128 [%0], z;\n}\n"
    ::"l"(p), "r"(a), "r"(b), "r"(c), "r"(tag) : "memory");
}
__device__ __forceinline__ uint32_t ll_ld3(const uint4* p, uint32_t& a, uint32_t& b, uint32_t& c, uint32_t tag) {
  uint32_t t;
  asm volatile("{\n.reg .b64 x, y;\n.reg .b128 z;\nld.relaxed.gpu.global.b128 z, [%4];\nmov.b128 {x, y}, z;\nmov.b64 {%0, %1}, x;\nmov.b64 {%2, %3}, y;\n}\n"
    : "=r"(a), "=r"(b), "=r"(c), "=r"(t) : "l"(p) : "memory");
  return t ^ tag;
}
__device__ __forceinline__ void halo_send(uint4* p, uint32_t a, const uint32_t (&tg)[6]) {
  asm volatile("{\n.reg .b64 x<6>, y<6>, w<2>;\n.reg .b32 c<4>;\n.reg .b128 z<6>;\n"
    "ld.shared.b64 w0, [%1+1536];\nld.shared.b64 w1, [%1+1792];\n"
    "ld.shared.b64 x0, [%1];\nld.shared.b64 x1, [%1+256];\nld.shared.b64 x2, [%1+512];\n"
    "ld.shared.b64 x3, [%1+768];\nld.shared.b64 x4, [%1+1024];\nld.shared.b64 x5, [%1+1280];\n"
    "mov.b64 {c0, c1}, w0;\nmov.b64 {c2, c3}, w1;\n"
    "mov.b64 y0, {c0, %2};\nmov.b64 y1, {c1, %3};\nmov.b64 y2, {c2, %4};\nmov.b64 y3, {c3, %5};\nmov.b64 y4, {%6, %6};\nmov.b64 y5, {%7, %7};\n"
    "mov.b128 z0, {x0, y0};\nmov.b128 z1, {x1, y1};\nmov.b128 z2, {x2, y2};\nmov.b128 z3, {x3, y3};\nmov.b128 z4, {x4, y4};\nmov.b128 z5, {x5, y5};\n"
    "st.relaxed.gpu.global.b128 [%0], z0;\nst.relaxed.gpu.global.b128 [%0+512], z1;\nst.relaxed.gpu.global.b128 [%0+1024], z2;\n"
    "st.relaxed.gpu.global.b128 [%0+1536], z3;\nst.relaxed.gpu.global.b128 [%0+2048], z4;\nst.relaxed.gpu.global.b128 [%0+2560], z5;\n}\n"
    ::"l"(p), "r"(a), "r"(tg[0]), "r"(tg[1]), "r"(tg[2]), "r"(tg[3]), "r"(tg[4]), "r"(tg[5]) : "memory");
}
template <int N> __device__ __forceinline__ void copy_out(uint8_t* dst, uint32_t src, int stride) {
  uint4 v[N];
#pragma unroll
  for (int k = 0; k < N; k++) lds128(src + k * stride, v[k].x, v[k].y, v[k].z, v[k].w);
#pragma unroll
  for (int k = 0; k < N; k++) asm volatile("st.global.v4.b32 [%0], {%1, %2, %3, %4};" ::"l"(dst + k * stride), "r"(v[k].x), "r"(v[k].y), "r"(v[k].z), "r"(v[k].w) : "memory");
}
__device__ __forceinline__ void warp_store(uint8_t* dst, uint32_t src, int bytes, uint32_t delay, uint32_t pace) {
  __nanosleep(delay);
#pragma unroll 1
  for (int o = 0; o < bytes; o += 2048) {
    if (pace) __nanosleep(pace);
    uint4 v[4];
#pragma unroll
    for (int k = 0; k < 4; k++) lds128(src + o + k * 512, v[k].x, v[k].y, v[k].z, v[k].w);
#pragma unroll
    for (int k = 0; k < 4; k++) asm volatile("st.global.v4.b32 [%0], {%1, %2, %3, %4};" ::"l"(dst + o + k * 512), "r"(v[k].x), "r"(v[k].y), "r"(v[k].z), "r"(v[k].w) : "memory");
  }
  __syncwarp();
}
__device__ __forceinline__ uint32_t clock32() { uint32_t t; asm volatile("mov.u32 %0, %%clock;" : "=r"(t)); return t; }
__device__ __forceinline__ void flag_set(uint32_t* p, uint32_t bit) { asm volatile("red.release.gpu.global.xor.b32 [%0], %1;" ::"l"(p), "r"(bit) : "memory"); }
__device__ __forceinline__ void flag_wait(const uint32_t* p, uint32_t inv, uint32_t need, uint32_t& ready) {
  if ((ready & need) == need) return;
  uint32_t n = 0;
  do {
    asm volatile("ld.relaxed.gpu.global.b32 %0, [%1];" : "=r"(ready) : "l"(p) : "memory");
    ready = __shfl_sync(0xffffffffu, ready, 0) ^ inv;
  } while ((ready & need) != need && ++n < SPIN_MAX);
  asm volatile("fence.acquire.gpu;\nfence.proxy.async.global;" ::: "memory");
}
__device__ __forceinline__ bool elect_one() {
  uint32_t p;
  asm volatile("{\n.reg .pred P;\nelect.sync _|P, 0xffffffff;\nselp.u32 %0, 1, 0, P;\n}\n" : "=r"(p));
  return p;
}
__device__ __forceinline__ float gelu_half(float hx) {
  const float y = hx * fmaf(hx * hx, 8.f * 0.0356774081f, 2.f * 0.7978845608f);
  float th;
  asm("tanh.approx.f32 %0, %1;" : "=f"(th) : "f"(y));
  return fmaf(hx, th, hx);
}
__device__ __forceinline__ float ex2(float x) { float y; asm("ex2.approx.ftz.f32 %0, %1;" : "=f"(y) : "f"(x)); return y; }

__device__ __forceinline__ void stat_combine(uint32_t am, uint32_t aq, uint32_t bm, uint32_t bq, float pv, float& mean, float& var) {
  const float d0 = untag(am) - pv, d1 = untag(bm) - pv;
  float s = d0 + d1, q = fmaf(fmaf(d0, d0, d1 * d1), 128.f, untag(aq) + untag(bq));
  s += __shfl_xor_sync(0xffffffffu, s, 8); q += __shfl_xor_sync(0xffffffffu, q, 8);
  s += __shfl_xor_sync(0xffffffffu, s, 16); q += __shfl_xor_sync(0xffffffffu, q, 16);
  s *= 0.125f;
  mean = pv + s;
  var = fmaxf(fmaf(-s, s, q * (1.f / D_)), 0.f);
}

__device__ __forceinline__ void attn_logits(const uint32_t* q0, const uint32_t* q1,
                                            const uint32_t* k0, const uint32_t* k1, const uint32_t* k2, const uint32_t* k3,
                                            float mk0, float mk1, float (&s)[4][4]) {
#pragma unroll
  for (int n = 0; n < 4; n++) {
    const uint32_t* k = n == 0 ? k0 : n == 1 ? k1 : n == 2 ? k2 : k3;
    s[n][0] = s[n][1] = n < 2 ? mk0 : 0.f; s[n][2] = s[n][3] = n < 2 ? mk1 : 0.f;
    mma16816(s[n], q0[0], q1[0], q0[1], q1[1], k[0], k[1]);
    mma16816(s[n], q0[2], q1[2], q0[3], q1[3], k[2], k[3]);
  }
}
__device__ __forceinline__ void attn_probs(const float (&s)[4][4], float sc0, float sc1, bool e, bool zneg, const uint32_t (&sel)[3],
                                           uint32_t (&pr)[6], float (&l)[2]) {
  float a0 = e ? s[1][1] : s[1][0];
  float b0 = zneg ? (e ? s[0][1] : s[0][0]) : (e ? s[2][1] : s[2][0]);
  float a1 = e ? s[2][3] : s[2][2];
  float b1 = zneg ? (e ? s[1][3] : s[1][2]) : (e ? s[3][3] : s[3][2]);
  float m0 = fmaxf(a0, b0), m1 = fmaxf(a1, b1);
  m0 = fmaxf(m0, __shfl_xor_sync(0xffffffffu, m0, 1)); m1 = fmaxf(m1, __shfl_xor_sync(0xffffffffu, m1, 1));
  m0 = fmaxf(m0, __shfl_xor_sync(0xffffffffu, m0, 2)); m1 = fmaxf(m1, __shfl_xor_sync(0xffffffffu, m1, 2));
  a0 = ex2((a0 - m0) * sc0); b0 = ex2((b0 - m0) * sc0); a1 = ex2((a1 - m1) * sc1); b1 = ex2((b1 - m1) * sc1);
  l[0] = a0 + b0; l[1] = a1 + b1;
  const uint32_t p0 = pack2(a0, b0), p1 = pack2(a1, b1);
#pragma unroll
  for (int k = 0; k < 3; k++) { pr[k] = __byte_perm(p0, 0u, sel[k]); pr[3 + k] = __byte_perm(p1, 0u, sel[k]); }
}
__device__ __forceinline__ void attn_pv(const uint32_t (&pr)[6], const uint32_t* vh, const uint32_t* v, float (&o)[4][4]) {
#pragma unroll
  for (int dt = 0; dt < 4; dt++) {
    o[dt][0] = o[dt][1] = o[dt][2] = o[dt][3] = 0.f;
    mma16816(o[dt], pr[0], 0u, pr[1], pr[3], vh[2 * dt], vh[2 * dt + 1]);
    mma16816(o[dt], pr[2], pr[4], 0u, pr[5], v[2 * dt], v[2 * dt + 1]);
  }
}

constexpr int CP0 = 1;
constexpr int PFX = 1;
constexpr int FR = 2;
constexpr int XLD = 7;
constexpr int XST = 2;
constexpr int FA = 20;
constexpr int FO = 2;
constexpr int ATT = 25;
constexpr int COVER = 2;
constexpr int LEAD1 = 3;
constexpr int LEAD2 = 4;
constexpr int LEAD4 = 5;
constexpr int PD1 = 3;
constexpr int PD2 = 5;
constexpr int PD3 = 3;
constexpr int HALO_A_NS = 300;
constexpr int STAT_CLK = 150;
constexpr int H1D = 900;
constexpr int U0D = 300;
constexpr int X1D = 1200;
constexpr int PACE = 150;

__global__ void __cluster_dims__(2, 1, 1) __launch_bounds__(384, 1) fused_kernel(const bf16* __restrict__ x_p, const bf16* __restrict__ wqkv_p, const __grid_constant__ Params P) {
  extern __shared__ __align__(1024) uint8_t smem_raw[];
  const uint32_t sb = smem_u32(smem_raw);
  const uint32_t bars = sb + OFF_BAR;
  const int tid = threadIdx.x;
  const int wu = __shfl_sync(0xffffffffu, tid >> 5, 0), wg = wu >> 2;
  const int r = blockIdx.x & 1, cl = blockIdx.x >> 1;
  int grp, slt;
  if (cl < 4) { grp = 0; slt = 4 + cl; }
  else if (cl < 36) { grp = (cl - 4) & 7; slt = (cl - 4) >> 3; }
  else { grp = 1 + (cl - 36) % 7; slt = 4 + (cl - 36) / 7; }
  const int m = grp, j = slt;
  const int i = 2 * m + r;
  auto BAR = [&](int k) { return bars + 8 * k; };

  auto kb1 = [&](int n) { const int h = n >= 9, t = n - 2 - 7 * h; return n < 2 ? 2 * j + n : 2 * (t == j ? 7 : t) + h; };
  auto first_round = [&](int u0, int u1) {
#pragma unroll 1
    for (int u = u0; u < u1; u++) {
      mbar_expect(BAR(F1 + u), 40960);
      tma2d(sb + slot1(u), &P.x0, BAR(F1 + u), u * 64, 128 * i);
      tma3d(sb + slot1(u) + 16384, &P.wqkv, BAR(F1 + u), 128 * j, u * 64, 0);
      tma3d(sb + slot1(u) + 28672, &P.wqkv, BAR(F1 + u), 128 * j, u * 64 + 32, 0);
    }
  };
  if (CP0 && wu < 8) {
    const int row = tid >> 3, ch = tid & 7;
    const uint32_t d = sb + row * 128 + ((ch ^ (row & 7)) << 4);
    const bf16* xp = x_p + (128 * i + row) * 1024 + ch * 8;
    const bf16* wp = wqkv_p + row * 3072 + 128 * j + ch * 8;
#pragma unroll
    for (int k = 0; k < 10; k++)
      asm volatile("cp.async.cg.shared.global [%0], [%1], 16;" ::"r"(d + k * 4096), "l"(k < 4 ? xp + k * 32 * 1024 : wp + ((k - 4) / 3) * 32 * 3072 + ((k - 4) % 3) * 1024) : "memory");
  }
  if (wu == 9) {
    if (elect_one()) asm volatile("prefetch.tensormap [%0];" ::"l"(&P.wqkv) : "memory");
    __syncwarp();
  } else if (wu == 8) {
    if (elect_one()) {
#pragma unroll
      for (int k = 0; k < 4; k++) mbar_init(BAR(F1 + k), 1);
      asm volatile("fence.mbarrier_init.release.cluster;" ::: "memory");
      fence_async_smem();
      if (CP0) mbar_arrive(BAR(F1));
      first_round(CP0, FR);
    }
    __syncwarp();
  } else if (wu == 10) {
    if (elect_one()) {
#pragma unroll
      for (int k = E1; k < 64; k++) {
        int cnt = 1;
        if (k < F2 || (k >= E2 && k < F3) || (k >= E3 && k < F4) || (k >= E4 && k < JOB) || k == JOB + 2 || k == JOB + 3) cnt = 4;
        else if ((k >= JOB && k < RD) || k == CSJ) cnt = 8;
        else if (k == RD + 1 || k == STD || k == STAT) cnt = 2;
        mbar_init(BAR(k), cnt);
      }
      asm volatile("fence.mbarrier_init.release.cluster;" ::: "memory");
      fence_async_smem();
    }
    __syncwarp();
  }
  auto load_tag = [&]() { uint32_t t; asm volatile("ld.relaxed.gpu.global.u32 %0, [%1];" : "=r"(t) : "l"(&gEpoch) : "memory"); return t + 1; };
  if (wu == 8) nb_arrive<NB_INIT>(384); else nb_sync<NB_INIT>(384);
  asm volatile("barrier.cluster.arrive.relaxed;" ::: "memory");

  if (wg == 2) {
    reg_dealloc<40>();
    if (wu == 8) {
      if (elect_one()) first_round(FR, 4);
      __syncwarp();
    }
    asm volatile("barrier.cluster.wait;" ::: "memory");
    auto kb3 = [&](int n) { const int h = n >= 17, t = n - 3 - 14 * h; return n < 2 ? 2 * i + n : (n == 2 || n == 31) ? 2 * (i ^ 1) + h : 2 * ((2 * m + 2 + t) & 15) + h; };
    auto v1 = [&](int L, int u) { const int u0 = L ? 2 : 10; return (u >= u0 && u < 18) ? (u < u0 + 2 ? u - u0 + 16 : u - 2) : u; };
    auto kb2 = [&](int n) { return n < 8 ? 2 * n : n == 8 ? 2 * j + 1 : 2 * (n - 9 == j ? 7 : n - 9) + 1; };
    if (wu == 8) {
      const int lane = tid & 31;
      auto pf = [&](const bf16* p, bool on) { if (on) asm volatile("prefetch.global.L2 [%0];" ::"l"(p)); };
      auto k1 = [&](int L, int v) { return (L || v >= 16) ? kb1(v & 15) : v; };
      auto kb4f = [&](int n) {
        const bool own = n == 0 || n == 9 || n == 17;
        const int q = n - 10 - (n > 17), c = own ? n >> 3 : q / 15, t = q - 15 * c;
        const int ii = own ? i : t < 14 ? (2 * m + 2 + t) & 15 : i ^ 1;
        return (n >= 1 && n <= 8) ? 7 * ((m + n) & 7) + 3 : ((7 * ii + 1) >> 1) + c;
      };
      const uint32_t tab4 = kb4f(lane) | (kb4f(lane + 32) << 16);
      auto kb4 = [&](int n) { return (int)((__shfl_sync(0xffffffffu, tab4, n) >> ((n >> 1) & 16)) & 63); };
      const bf16* const q1 = wqkv_p + (4 * i + (lane & 3)) * 3072 + (lane >> 2) * 1024 + 128 * j;
      const bf16* const q2 = P.wo_p + (4 * i + (lane & 3)) * 1024 + (lane >> 2) * 64 + 128 * j;
      const bf16* const q3 = P.w1_p + (8 * j + (lane >> 2)) * 3584 + 64 * (7 * m + ((lane & 3) == 3 ? 3 : 4 * r + (lane & 3)));
      auto pf1 = [&](int L, int u) { const int v = v1(L, u); pf(q1 + k1(L, v) * (64 * 3072) + 64 * (v >> 4), lane < 12); };
      auto pfx = [&](int u) { pf(x_p + (128 * i + 16 * j + (lane & 15)) * 1024 + 64 * u, PFX && lane < 16); };
      auto pf2 = [&](int n) { pf(q2 + kb2(n) * (64 * 1024), lane < 8); };
      auto pf3 = [&](int n) { pf(q3 + kb3(n) * (64 * 3584), true); };
#pragma unroll 1
      for (int u = 4; u < 4 + PD1; u++) { pf1(0, u); pfx(u); }
#pragma unroll 1
      for (int L = 0; L < 2; L++) {
#pragma unroll 1
        for (int u = L ? 0 : 4; u < 32; u++) {
          const int v = v1(L, u), p = u & 3;
          int c0 = 128 * j + 64 * (v >> 4), c1 = k1(L, v) * 64 + 32 * r; uint32_t dst = sb + slot1(p) + 16384 + r * 12288;
          asm volatile("" : "+r"(c0), "+r"(c1), "+r"(dst));
          if (L && u == 4) mbar_wait(BAR(RD + 5), 0);
          if (u >= 4) mbar_wait(BAR(E1 + p), ((u >> 2) - 1) & 1);
          else mbar_wait(BAR(E4 + (u == 3 ? 0 : u + 3)), u == 3);
          if (elect_one()) {
            mbar_expect(BAR(F1 + p), (v & 15) < 2 ? 24576 : 40960);
            tma3d_mc(dst, &P.wqkv, BAR(F1 + p), c0, c1, 0);
          }
          if (u + PD1 < 32) pf1(L, u + PD1);
          if (L == 0 && u + PD1 < 10) pfx(u + PD1);
          if (u + PD2 >= 32) pf2(u + PD2 - 32);
        }
        int p = 0; uint32_t par = L ? 0x1e : 0;
#pragma unroll 1
        for (int n = 0; n < 16; n++) {
          int c1 = kb2(n) * 64;
          asm volatile("" : "+r"(c1));
          if (n >= 5) { mbar_wait(BAR(E2 + p), (par >> p) & 1); par ^= 1u << p; }
          else if (n < 4) mbar_wait(BAR(E1 + n), 1);
          if (elect_one()) {
            mbar_expect(BAR(F2 + p), n == 8 ? 16384 : 32768);
            tma2d_mc(sb + slot2(p) + 16384 + r * 8192, &P.wo, BAR(F2 + p), 128 * j + 64 * r, c1);
          }
          if (++p == 5) p = 0;
          if (n + PD2 < 16) pf2(n + PD2);
          if (n + PD3 + 4 >= 16) pf3(n + PD3 + 4 - 16);
        }
#pragma unroll 1
        for (int u = 0; u < 32; u++) {
          const int n = u < 4 ? (0x2031 >> (4 * u)) & 3 : u, p = n & 3;
          int kb = kb3(n);
          asm volatile("" : "+r"(kb));
          if (n == 4) {
            mbar_wait(BAR(XF + 1), L ^ 1);
            const uint32_t rs = mapa(sb, r ^ 1);
            if (elect_one()) bulk_s2s(rs + slot3(2), sb + OFF_X, 16384, rs + OFF_BAR + 8 * (F3 + 2));
            mbar_wait(BAR(RD + 4), L);
          }
          if (n >= 4) mbar_wait(BAR(E3 + p), ((n >> 2) - 1) & 1);
          else if (n == 1) mbar_wait(BAR(STD + 1), L);
          else if (n == 3) mbar_wait(BAR(E2 + 2), L);
          else if (n == 0) mbar_wait(BAR(E2 + 4), L);
          else mbar_wait(BAR(E2 + 0), 1);
          if (elect_one()) {
            mbar_expect(BAR(F3 + p), n < 2 ? 32768 : 49152);
            tma3d(sb + slot3(p) + 16384, &P.w1, BAR(F3 + p), 0, kb * 64, 7 * m + 4 * r);
            tma3d(sb + slot3(p) + 40960, &P.w1h, BAR(F3 + p), 0, kb * 64, 14 * m + 6 + r);
          }
          if (u >= 4 && u + PD3 < 32) pf3(u + PD3);
        }
        auto g4w = [&](int n, int p, int kb) {
          if (elect_one()) {
            mbar_expect(BAR(F4 + p), (n == 0 || n == 9 || n == 17) ? 16384 : 32768);
            tma3d(sb + slot4(p), &P.w2, BAR(F4 + p), 0, kb * 64, 2 * i);
          }
        };
#pragma unroll 1
        for (int n = 0; n < 6; n++) {
          const int kb = kb4(n);
          if (n == 1) mbar_wait(BAR(RD + 3), L);
          if (n < 3) mbar_wait(BAR(E3 + n), 1);
          else if (n == 4) mbar_wait(BAR(E3 + 3), 1);
          g4w(n, n, kb);
        }
        p = 0; par = L ? 0x3c : 0;
#pragma unroll 1
        for (int n = 6; n < 56; n++) {
          const int kb = kb4(n);
          mbar_wait(BAR(E4 + p), (par >> p) & 1); par ^= 1u << p;
          g4w(n, p, kb);
          if (++p == 6) p = 0;
        }
        if (L == 0)
#pragma unroll 1
          for (int u = 0; u < PD1; u++) pf1(1, u);
      }
    } else if (wu == 9) {
      uint32_t inv = 0;
#define ADDR(d, s) uint32_t dst = (d); const uint8_t* src = (s); asm volatile("" : "+r"(dst), "+l"(src))
#pragma unroll 1
      for (int L = 0; L < 2; L++) {
        uint32_t ready = 0;
#pragma unroll 1
        for (int u = 4; u < 32; u++) {
          const int p = u & 3, v = v1(L, u), nn = v & 15, kb = (L || v >= 16) ? kb1(nn) : nn;
          if (L == 0 && (u == XLD || u == XLD + XST) && elect_one()) {
            const int h = u != XLD;
            mbar_expect(BAR(XF + h), 16384);
            tma2d(sb + OFF_X + h * 16384, &P.x0, BAR(XF + h), 128 * j + 64 * h, 128 * i);
          }
          if (nn < 2) continue;
          ADDR(sb + slot1(p), gXB + (i * 16 + kb) * 16384);
          if (L && u < 12) mbar_wait(BAR(F1 + p), u >> 3);
          if (u >= 4 + 4 * L) mbar_wait(BAR(E1 + p), ((u >> 2) - 1) & 1);
          if (L) {
            flag_wait(gFlag[0][0][i], inv, 1u << kb, ready);
            if (elect_one()) bulk_ld(dst, src, 16384, BAR(F1 + p));
          } else if (elect_one()) tma2d(sb + slot1(p), &P.x0, BAR(F1 + p), kb * 64, 128 * i);
        }
        ready = 0;
        if (L == 0) inv = (__shfl_sync(0xffffffffu, load_tag(), 0) & 1) - 1;
        int p = 0; uint32_t par = L ? 0x1e : 0;
#pragma unroll 1
        for (int n = 0; n < 16; n++) {
          const int hp = kb2(n);
          if (n == 8) { par ^= 8; p = 4; continue; }
          ADDR(sb + slot2(p), gOB + (i * 16 + hp) * 16384);
          if (n >= 5) { mbar_wait(BAR(E2 + p), (par >> p) & 1); par ^= 1u << p; }
          else if (n < 4) mbar_wait(BAR(E1 + n), 1);
          flag_wait(gFlag[L][1][i], inv, 1u << hp, ready);
          if (elect_one()) bulk_ld(dst, src, 16384, BAR(F2 + p));
          if (++p == 5) p = 0;
        }
        ready = 0;
        mbar_wait(BAR(E2 + 0), 1);
#pragma unroll 1
        for (int n = 3; n < 32; n++) {
          const int p = n & 3, kb = kb3(n);
          const int o = n != 31 ? r * 8192 : 0;
          ADDR(sb + slot3(p) + o, gHB + (j * 32 + kb) * 16384 + o);
          if (n > 3) mbar_wait(BAR(E3 + p), ((n >> 2) - 1) & 1);
          flag_wait(gFlag[L][2][j], inv, 1u << kb, ready);
          if (elect_one()) {
            if (n != 31) bulk_ld_mc(dst, src, 8192, BAR(F3 + p));
            else bulk_ld(dst, src, 16384, BAR(F3 + p));
          }
        }
        ready = 0; p = 1; par = L ? 0x3c : 0;
#pragma unroll 1
        for (int t = 0; t < 8; t++) {
          const int mm = (m + t + 1) & 7;
          ADDR(sb + slot4(p) + 16384 + r * 8192, gUB + (j * 56 + 48 + mm) * 16384 + r * 8192);
          if (t < 3) mbar_wait(BAR(E3 + 1 + t), 1);
          if (t >= 5) { mbar_wait(BAR(E4 + p), (par >> p) & 1); par ^= 1u << p; }
          flag_wait(gFlag[L][6][j], inv, 3u << (2 * mm), ready);
          if (elect_one()) bulk_ld_mc(dst, src, 8192, BAR(F4 + p));
          if (++p == 6) p = 0;
        }
#pragma unroll 1
        for (int c = 0; c < 3; c++) {
          ready = 0;
#pragma unroll 1
          for (int t = 0; t < 15; t++) {
            const int ii = t < 14 ? (2 * m + 2 + t) & 15 : i ^ 1;
            if (c == 0 && (t == 0 || t == 7)) { par ^= 1u << p; if (++p == 6) p = 0; }
            const int o = t < 14 ? r * 8192 : 0;
            ADDR(sb + slot4(p) + 16384 + o, gUB + (j * 56 + 16 * c + ii) * 16384 + o);
            mbar_wait(BAR(E4 + p), (par >> p) & 1); par ^= 1u << p;
            flag_wait(gFlag[L][3 + c][j], inv, 1u << ii, ready);
            if (elect_one()) {
              if (t < 14) bulk_ld_mc(dst, src, 8192, BAR(F4 + p));
              else bulk_ld(dst, src, 16384, BAR(F4 + p));
            }
            if (++p == 6) p = 0;
          }
        }
      }
    } else {
      const int h = wu - 10, i0 = i, j0 = j;
      {
      const uint32_t tag = load_tag();
      int lane = tid & 31, i = i0, j = j0;
#define FRESH asm volatile("" : "+r"(lane), "+r"(i), "+r"(j))
      auto signal = [&](int k) { if (lane == 0) mbar_arrive(BAR(k)); };
      auto publish = [&](uint32_t* f, int bit) { if (lane == 0) flag_set(f, 1u << bit); __syncwarp(); };
#pragma unroll 1
      for (int c = 32 * h + lane; c < 288; c += 64)
        sts16(sb + OFF_B1 + 2 * c, c >= 224 ? 0u : pack2(0.5f * __bfloat162float(P.b1[c < 192 ? 64 * (7 * m + 4 * r) + c : 64 * (7 * m + 3) + 32 * r + c - 192]), 0.f));
      if (h == 0) sts32f(sb + OFF_CS + 768 + 4 * lane, 0.f);
#pragma unroll 1
      for (int L = 0; L < 2; L++) {
        FRESH;
        if (L == 0) {
          mbar_wait(BAR(CSJ), 0);
          float c0 = 0.f, c1 = 0.f, c2 = 0.f;
          const uint32_t a = sb + OFF_STG + (32 * h + lane) * 4;
#pragma unroll 4
          for (int k = 0; k < 32; k++) { c0 += lds32f(a + k * 784); c1 += lds32f(a + k * 784 + 256); c2 += lds32f(a + k * 784 + 512); }
          ll_st3(&gCS[j][i][32 * h + lane], __float_as_uint(c0), __float_as_uint(c1), __float_as_uint(c2), tag);
          __nanosleep(500);
        }
        FRESH;
        if (L == 0) {
#pragma unroll 1
          for (int ab = 0; ab < 2; ab++) {
            float c0 = 0.f, c1 = 0.f, c2 = 0.f;
#pragma unroll 1
            for (int b4 = 0; b4 < 8; b4 += 4) {
              uint32_t a[4], b[4], c[4], n = 0, bad;
              do {
                bad = 0;
#pragma unroll
                for (int e = 0; e < 4; e++) bad |= ll_ld3(&gCS[j][2 * (b4 + e) + ab][32 * h + lane], a[e], b[e], c[e], tag);
              } while (bad && ++n < SPIN_MAX);
#pragma unroll
              for (int e = 0; e < 4; e++) { c0 += __uint_as_float(a[e]); c1 += __uint_as_float(b[e]); c2 += __uint_as_float(c[e]); }
            }
            const uint32_t a = sb + OFF_CS + ab * 768 + (4 * h + (lane >> 3)) * 32 + (lane & 7) * 2;
            const uint32_t h0 = pack2(c0, 0.f), h1 = pack2(c1, 0.f), h2 = pack2(c2, 0.f);
            sts16(a, h0); sts16(a + 256, h1); sts16(a + 512, h2);
            sts16(a + 16, pack2(c0 - bf_lo(h0), 0.f)); sts16(a + 272, pack2(c1 - bf_lo(h1), 0.f)); sts16(a + 528, pack2(c2 - bf_lo(h2), 0.f));
            fence_async_smem();
            __syncwarp();
            if (ab == 0) signal(STAT);
          }
        }
#pragma unroll 1
        for (int ab = 0; ab < 2; ab++) {
          FRESH;
          uint32_t v[18], tg[6];
          const uint32_t xs = sb + OFF_STG + h * 16384 + lane * 8;
          uint4* hp = &gHalo[L][i][j][6 * h][lane];
#pragma unroll
          for (int c = 0; c < 6; c++) { tg[c] = (2 * tag + ab) * 8 + c; asm volatile("" : "+r"(tg[c])); }
          asm volatile("" : "+l"(hp));
          mbar_wait(BAR(FOLD + h), ab);
          if (i < 15) {
            halo_send(hp, xs, tg);
          }
          if (i > 0) {
            if (!ab) __nanosleep(HALO_A_NS);
            uint32_t n = 0, bad;
            do {
              bad = 0;
#pragma unroll
              for (int c = 0; c < 6; c++) bad |= ll_ld3(hp + c * 32 - 8 * 12 * 32, v[3 * c], v[3 * c + 1], v[3 * c + 2], (2 * tag + ab) * 8);
            } while (bad > 7 && ++n < SPIN_MAX);
          } else {
#pragma unroll
            for (int c = 0; c < 18; c++) v[c] = 0u;
          }
#pragma unroll
          for (int c = 0; c < 6; c++) sts64f(xs + c * 256, __uint_as_float(v[3 * c]), __uint_as_float(v[3 * c + 1]));
          sts64f(xs + 1536, __uint_as_float(v[2]), __uint_as_float(v[5]));
          sts64f(xs + 1792, __uint_as_float(v[8]), __uint_as_float(v[11]));
          __syncwarp();
          signal(HALO + h);
          FRESH;
          if (ab == 0 && lane == 0) asm volatile("st.relaxed.gpu.global.u32 [%0], %1;" ::"l"(&gAck[L][i][j][h][0]), "r"(tag) : "memory");
          uint8_t* dst = gOB + (i * 16 + 2 * j + ab) * 16384;
          uint32_t* flag = gFlag[L][1][i];
          asm volatile("" : "+l"(dst), "+l"(flag));
          mbar_wait(BAR(JOB + ab), L);
          if (h == 0) {
            if (lane == 0) { bulk_st(dst, sb + OFF_STG, 16384); bulk_commit(); bulk_wait0(); }
            signal(STD + ab);
            publish(flag, 2 * j + ab);
          } else if (ab == 0) {
            if (i < 15 && lane < 2) {
              uint32_t t, n = 0;
              do { asm volatile("ld.relaxed.gpu.global.u32 %0, [%1];" : "=r"(t) : "l"(&gAck[L][i + 1][j][lane][0]) : "memory"); } while (t != tag && ++n < SPIN_MAX);
            }
            __syncwarp();
            signal(STD);
          }
        }
#pragma unroll 1
        for (int k = 0; k < 4 - L; k++) {
          FRESH;
          const int job = 2 * k + h;
          uint8_t* dst = k == 0 ? gHB + (j * 32 + 2 * i + 1) * 16384 : k == 3 ? gXB + (i * 16 + 2 * j + 1) * 16384 : gUB + (j * 56 + 16 * (job - 3) + i) * 16384;
          uint32_t* flag = k == 3 ? gFlag[0][0][i] : gFlag[L][(0x543622 >> (4 * job)) & 15][j];
          uint32_t bit = 1u << (k == 0 ? 2 * i + h : k == 3 ? 2 * j + h : i);
          asm volatile("" : "+l"(dst), "+l"(flag), "+r"(bit));
          mbar_wait(BAR(JOB + ((0x98654732 >> (4 * job)) & 15)), L);
          if ((0xba >> job) & 1) {
            if (job == 1) mbar_wait(BAR(RD + 4), L);
            if (job == 3) {
              __nanosleep(U0D);
              if (lane == 0) { bulk_st(dst, sb + OFF_X, 16384); bulk_commit(); bulk_wait0(); }
            } else warp_store(dst + lane * 16, sb + lane * 16 + OFF_X + (job == 5 ? 0 : 16384), 16384, job == 1 ? H1D : job == 7 ? X1D : 0, job == 7 ? 0 : PACE);
            if (job != 7) signal(RD + ((0x112000 >> (4 * job)) & 15));
          }
          if (lane == 0) flag_set(flag, bit);
          __syncwarp();
          if (h == 0 && k != 2) { signal(RD + (k == 3 ? 5 : 4 - k)); }
        }
      }
      if (blockIdx.x == 0 && h == 0 && lane == 0) asm volatile("st.relaxed.gpu.global.u32 [%0], %1;" ::"l"(&gEpoch), "r"(tag) : "memory");
      }
    }
    __syncwarp();
    cluster_bar();
  } else {
    reg_alloc<232>();
    asm volatile("barrier.cluster.wait;" ::: "memory");
    if (CP0) { asm volatile("cp.async.wait_all;" ::: "memory"); fence_async_smem(); nb_sync<NB_BOTH>(256); }
    const uint32_t rbars = mapa(bars, tid & 1);
    const bool relp = (tid & 127) < 2;
    const uint32_t sd = (sb & 0x3FFFF) >> 4, sda = sd + wg * 512;
    uint32_t tag = 0;
    auto release = [&](int k) { if (relp) mbar_arrive_cl(rbars + 8 * k); };
    auto signal = [&](int k) { __syncwarp(); if ((fresh_tid() & 31) == 0) mbar_arrive(BAR(k)); };
#define GEOM const int t7 = fresh_tid() & 127, lane = t7 & 31, w = t7 >> 5, g = lane >> 2, q = lane & 3, \
                       lr = lane & 15, lt = lane >> 4, l7 = lane & 7; (void)w; (void)g; (void)q; (void)lr; (void)lt; (void)l7

#pragma unroll 1
    for (int L = 0; L < 2; L++) {
      float acca[96], accb[96], xa[64], acc3[112];
      float nmean0, nmean1, rstd0, rstd1;
      uint16_t b2a, b2b;
      uint2 *e2p, *e2s; uint8_t* e2g; uint32_t e2h;
      uint32_t Q[2][8], K[2][8], V[16];
      auto g1_issue = [&](float (&acc)[96], uint32_t a, uint32_t st, auto first) {
        const uint32_t da = sda + (a >> 4), db = sd + (st >> 4);
        wg_fence();
        static_for<0, 4>([&](auto kk) {
          constexpr uint32_t ia = DI(kk.value * 32, 16), ib = DI(16384 + (kk.value >> 1) * 12288 + (kk.value & 1) * 2048, 4096);
          if constexpr (first.value && kk.value == 0) wgmma_192z<0, 1, ia, ib>(acc, da, db); else wgmma_192<0, 1, ia, ib>(acc, da, db);
        });
        wg_commit();
      };
      auto g1_step = [&](float (&acc)[96], int u, bool rel, bool lead = false) {
        const int p = u & 3;
        mbar_wait(BAR(F1 + p), (u >> 2) & 1);
        g1_issue(acc, slot1(p), slot1(p), False{});
        if (lead) nb_arrive<NB_LEAD>(256);
        wg_wait<1>();
        if (rel) release(E1 + ((u - 1) & 3));
      };
      auto g1_loop = [&](float (&acc)[96], int u0, int u1, int urel) {
        int u = u0;
#pragma unroll 1
        do { g1_step(acc, u, u > urel); } while (++u < u1);
      };
      auto load_x = [&]() {
        GEOM;
#pragma unroll
        for (int t = 0; t < 16; t += 2) {
          uint32_t v0, v1, v2, v3;
          ldsm4(sb + OFF_X + (t >> 3) * 16384 + (16 * wu + lr) * 128 + ((((t & 7) + lt) ^ l7) << 4), v0, v1, v2, v3);
          xa[4 * t + 0] = bf_lo(v0); xa[4 * t + 1] = bf_hi(v0); xa[4 * t + 2] = bf_lo(v1); xa[4 * t + 3] = bf_hi(v1);
          xa[4 * t + 4] = bf_lo(v2); xa[4 * t + 5] = bf_hi(v2); xa[4 * t + 6] = bf_lo(v3); xa[4 * t + 7] = bf_hi(v3);
        }
      };
      auto stat_base = [&]() { return &gST[0][0][0][0][0] + ((L * 16 + opq(i)) * 8 + wu) * 128; };
      auto stat_slot = [&]() { const int lane = fresh_tid() & 31; return stat_base() + 16 * j + 2 * (lane >> 2) + (lane & 1); };
      auto stat_publish = [&](uint2* sp, float s0, float q0, float s2, float q2, uint32_t tg) {
        const int q = fresh_tid() & 3;
        const bool h1 = q & 1;
        float sm = (h1 ? s2 : s0) + __shfl_xor_sync(0xffffffffu, h1 ? s0 : s2, 1);
        float sq = (h1 ? q2 : q0) + __shfl_xor_sync(0xffffffffu, h1 ? q0 : q2, 1);
        sm += __shfl_xor_sync(0xffffffffu, sm, 2); sq += __shfl_xor_sync(0xffffffffu, sq, 2);
        stat_st(sp, sm, sq, tg, q < 2);
        return sm;
      };
      auto g1_stats = [&](int u0) {
        GEOM;
        const uint32_t xr = sb + OFF_X + (16 * wu + lr) * 128;
        float s0 = 0.f, q0 = 0.f, s2 = 0.f, q2 = 0.f;
        uint32_t v[8] = {0u, 0u, 0u, 0u, 0u, 0u, 0u, 0u};
#pragma unroll 1
        for (int k = 0; k < 5; k++) {
#pragma unroll
          for (int e = 0; e < 8; e += 2) {
            const float a = bf_lo(v[e]), b = bf_hi(v[e]), c = bf_lo(v[e + 1]), d = bf_hi(v[e + 1]);
            s0 += a + b; q0 = fmaf(a, a, fmaf(b, b, q0)); s2 += c + d; q2 = fmaf(c, c, fmaf(d, d, q2));
          }
          if (k == 4) break;
          const uint32_t o = ((2 * k + lt) ^ l7) << 4;
          ldsm4(xr + o, v[0], v[1], v[2], v[3]);
          ldsm4(xr + o + 16384, v[4], v[5], v[6], v[7]);
          g1_step(acca, u0 + k, true);
        }
        stat_publish(stat_slot(), s0, q0, s2, q2, 2 * (tag + 1));
      };
      uint32_t sv0[4], sv1[4];
      auto stat_src = [&]() { return stat_base() + 2 * (fresh_tid() & 31); };
      auto stat_fetch = [&](const uint2* sp) { stat_ld2(sp, sv0); stat_ld2(sp + 64, sv1); };
      auto stat_await = [&](auto src, uint32_t tg) {
#pragma unroll 1
        for (uint32_t n = 0; (((sv0[0] ^ tg) | (sv0[2] ^ tg) | (sv1[0] ^ tg) | (sv1[2] ^ tg)) & 15u) && n < SPIN_MAX; n++) stat_fetch(src());
        __syncwarp();
      };
      auto ln_stats = [&]() {
        GEOM;
        stat_await(stat_src, 2 * (tag + 1));
        float mean0, var0, mean1, var1;
        stat_combine(sv0[0], sv0[1], sv1[0], sv1[1], untag(__shfl_sync(0xffffffffu, sv0[0], l7)), mean0, var0);
        stat_combine(sv0[2], sv0[3], sv1[2], sv1[3], untag(__shfl_sync(0xffffffffu, sv0[2], l7)), mean1, var1);
        nmean0 = -__shfl_sync(0xffffffffu, mean0, g); rstd0 = rsq(__shfl_sync(0xffffffffu, var0, g) + 1e-5f);
        nmean1 = -__shfl_sync(0xffffffffu, mean1, g); rstd1 = rsq(__shfl_sync(0xffffffffu, var1, g) + 1e-5f);
      };
      auto center = [&](float (&acc)[96], int ab) {
        const bool q0 = (fresh_tid() & 3) == 0;
        const uint32_t h0 = pack2(nmean0, nmean0), h1 = pack2(nmean1, nmean1);
        const float l0 = nmean0 - bf_lo(h0), l1 = nmean1 - bf_lo(h1);
        const uint32_t a0 = q0 ? h0 : 0u, a1 = q0 ? h1 : 0u, a2 = q0 ? pack2(l0, l0) : 0u, a3 = q0 ? pack2(l1, l1) : 0u;
        wg_fence();
        wgmma_rs_192(acc, a0, a1, a2, a3, mkdesc_vec(sb + OFF_CS + ab * 768, 32));
      };
      auto frag = [&](float (&acc)[96], int t, uint32_t& p0, uint32_t& p1) {
        if (t >= 8) { p0 = pack2(acc[4 * t] * rstd0, acc[4 * t + 1] * rstd0); p1 = pack2(acc[4 * t + 2] * rstd1, acc[4 * t + 3] * rstd1); }
        else { p0 = pack2(acc[4 * t], acc[4 * t + 1]); p1 = pack2(acc[4 * t + 2], acc[4 * t + 3]); }
      };
      auto fold_v = [&](float (&acc)[96]) {
        GEOM;
        const uint32_t a = sb + OFF_STG + 16384 + ((wu + 1) & 7) * 2048 + lr * 128;
#pragma unroll
        for (int t = 0; t < 8; t += 2) {
          uint32_t p0, p1, p2, p3;
          frag(acc, 16 + t, p0, p1); frag(acc, 17 + t, p2, p3);
          stsm4(a + (((t + lt) ^ l7) << 4), p0, p1, p2, p3);
        }
        __syncwarp();
#pragma unroll
        for (int t = 0; t < 8; t += 2) ldsm4t(a + (((t + lt) ^ l7) << 4), V[2 * t], V[2 * t + 1], V[2 * t + 2], V[2 * t + 3]);
        if (wu == 7) signal(FOLD + 1);
      };
      auto fold_k = [&](float (&acc)[96]) {
        GEOM;
        const uint32_t a = sb + OFF_STG + ((wu + 1) & 7) * 2048 + lane * 16;
#pragma unroll
        for (int hh = 0; hh < 2; hh++) {
#pragma unroll
          for (int t = 4 * hh; t < 4 * hh + 4; t++) frag(acc, 8 + t, K[0][t], K[1][t]);
#pragma unroll
          for (int o = 0; o < 2; o++) sts128(a + (2 * o + hh) * 512, K[o][4 * hh], K[o][4 * hh + 1], K[o][4 * hh + 2], K[o][4 * hh + 3]);
        }
        if (wu == 7) signal(FOLD);
      };
      auto fold_q = [&](float (&acc)[96]) {
#pragma unroll
        for (int t = 0; t < 8; t++) frag(acc, t, Q[0][t], Q[1][t]);
      };
      auto attend = [&](int ab, auto drain, auto resume) {
        GEOM;
        nb_sync<NB_BOTH>(256);
        const uint32_t xa_ = sb + OFF_STG + wu * 2048 + lane * 16;
        if (wu == 0) mbar_wait(BAR(HALO), ab);
        uint32_t KH[2][8], VH[16];
#pragma unroll
        for (int c = 0; c < 4; c++)
          lds128(xa_ + c * 512, KH[c >> 1][4 * (c & 1)], KH[c >> 1][4 * (c & 1) + 1], KH[c >> 1][4 * (c & 1) + 2], KH[c >> 1][4 * (c & 1) + 3]);
        auto load_vh = [&]() {
          if (wu == 0) mbar_wait(BAR(HALO + 1), ab);
#pragma unroll
          for (int c = 0; c < 4; c++)
            ldsm4t(sb + OFF_STG + 16384 + wu * 2048 + lr * 128 + (((2 * c + lt) ^ l7) << 4), VH[4 * c], VH[4 * c + 1], VH[4 * c + 2], VH[4 * c + 3]);
        };
        if (!ab) load_vh();
        const bool e = g & 1, zneg = (g >> 1) < q, first = (i == 0) && (wu == 0);
        const float sc0 = rstd0 * (0.17677669530f * 1.4426950409f), sc1 = rstd1 * (0.17677669530f * 1.4426950409f);
        float mk0 = first ? __fdividef(-1.0e9f * 1.4426950409f, sc0) : 0.f, mk1 = first ? __fdividef(-1.0e9f * 1.4426950409f, sc1) : 0.f;
        const uint32_t sa = e ? 0x1044u : 0x4410u, sbb = e ? 0x3244u : 0x4432u;
        uint32_t sel[3] = {zneg ? sbb : 0x4444u, sa, zneg ? 0x4444u : sbb};
        uint32_t oa = sb + OFF_STG + (16 * wu + lr) * 128 + ((lt ^ l7) << 4);
        asm volatile("" : "+r"(sel[0]), "+r"(sel[1]), "+r"(sel[2]), "+r"(oa), "+f"(mk0), "+f"(mk1));
        drain();
        uint32_t pr[2][6];
        float l[2][2], sl[2][4][4];
#pragma unroll
        for (int hh = 0; hh < 2; hh++)
          attn_logits(&Q[0][4 * hh], &Q[1][4 * hh], &KH[0][4 * hh], &KH[1][4 * hh], &K[0][4 * hh], &K[1][4 * hh], mk0, mk1, sl[hh]);
        if (ab) load_vh();
#pragma unroll
        for (int hh = 0; hh < 2; hh++) attn_probs(sl[hh], sc0, sc1, e, zneg, sel, pr[hh], l[hh]);
        float o[2][4][4];
#pragma unroll
        for (int hh = 0; hh < 2; hh++) attn_pv(pr[hh], &VH[8 * hh], &V[8 * hh], o[hh]);
#pragma unroll
        for (int hh = 0; hh < 2; hh++) {
          float l0 = l[hh][0], l1 = l[hh][1];
          l0 += __shfl_xor_sync(0xffffffffu, l0, 1); l1 += __shfl_xor_sync(0xffffffffu, l1, 1);
          l0 += __shfl_xor_sync(0xffffffffu, l0, 2); l1 += __shfl_xor_sync(0xffffffffu, l1, 2);
          asm("rcp.approx.ftz.f32 %0, %0;" : "+f"(l0)); asm("rcp.approx.ftz.f32 %0, %0;" : "+f"(l1));
#pragma unroll
          for (int dt = 0; dt < 4; dt += 2)
            stsm4(oa ^ ((4 * hh + dt) << 4),
                  pack2(o[hh][dt][0] * l0, o[hh][dt][1] * l0), pack2(o[hh][dt][2] * l1, o[hh][dt][3] * l1),
                  pack2(o[hh][dt + 1][0] * l0, o[hh][dt + 1][1] * l0), pack2(o[hh][dt + 1][2] * l1, o[hh][dt + 1][3] * l1));
        }
        fence_async_smem();
        signal(JOB + ab);
        nb_sync<NB_BOTH>(256);
        resume();
      };

      mbar_wait(BAR(F1), 0);    g1_issue(acca, L ? OFF_X : slot1(0), slot1(0), True{});
      mbar_wait(BAR(F1 + 1), 0); g1_issue(acca, L ? OFF_X + 16384 : slot1(1), slot1(1), False{});
      wg_wait<1>(); release(E1 + 0);
      if (L == 0) {
        asm volatile("ld.relaxed.gpu.global.u32 %0, [%1];" : "=r"(tag) : "l"(&gEpoch + (fresh_tid() >> 10)) : "memory");
        GEOM;
        const bf16* wp = wqkv_p + ((128 * opq(m) + 16 * wg + (t7 >> 3)) * 3072 + 128 * opq(j) + 64 * r + l7 * 8);
        const uint32_t ca = sb + OFF_STG + (16 * wg + (t7 >> 3)) * 784 + l7 * 32;
#pragma unroll 1
        for (int p = 0; p < 3; p++) {
          uint4 wv[4];
#pragma unroll
          for (int k = 0; k < 4; k++)
            asm volatile("ld.global.nc.v4.u32 {%0, %1, %2, %3}, [%4];" : "=r"(wv[k].x), "=r"(wv[k].y), "=r"(wv[k].z), "=r"(wv[k].w)
                         : "l"(wp + k * 32 * 3072 + p * 1024));
          g1_loop(acca, 2 + 3 * p, p < 2 ? 5 + 3 * p : 10, 0);
          float cs[8];
#pragma unroll
          for (int k = 0; k < 4; k++) {
            const uint4 v = wv[k];
            const float t[8] = {bf_lo(v.x), bf_hi(v.x), bf_lo(v.y), bf_hi(v.y), bf_lo(v.z), bf_hi(v.z), bf_lo(v.w), bf_hi(v.w)};
#pragma unroll
            for (int e = 0; e < 8; e++) cs[e] = k ? cs[e] + t[e] : t[e];
          }
          sts128(ca + p * 256, __float_as_uint(cs[0]), __float_as_uint(cs[1]), __float_as_uint(cs[2]), __float_as_uint(cs[3]));
          sts128(ca + p * 256 + 16, __float_as_uint(cs[4]), __float_as_uint(cs[5]), __float_as_uint(cs[6]), __float_as_uint(cs[7]));
        }
        signal(CSJ);
        mbar_wait(BAR(XF), 0); mbar_wait(BAR(XF + 1), 0);
      }
      {
        const int u0 = L ? 2 : 10;
        mbar_wait(BAR(F1 + 2), 0); g1_issue(accb, OFF_X, slot1(2), True{});
        wg_wait<1>(); release(E1 + 1);
        mbar_wait(BAR(F1 + 3), 0); g1_issue(accb, OFF_X + 16384, slot1(3), False{});
        wg_wait<1>(); release(E1 + 2);
        g1_stats(u0 + 2);
        g1_loop(acca, u0 + 6, 18, 0);
      }
      stat_fetch(stat_src());
      const int fa = FA + (wg ? 0 : FO);
      g1_loop(accb, 18, fa, 0);
      ln_stats();
      if (L == 0) mbar_wait(BAR(STAT), 0);
      center(acca, 0); wg_commit();
      wg_wait<0>(); release(E1 + ((fa - 1) & 3));
      fence_regs(acca);
      fold_k(acca); fold_v(acca); fold_q(acca);
      sched_fence(P.zero);
      g1_loop(accb, fa, ATT, fa);
      attend(0, [&]() { wg_wait<0>(); release(E1 + ((ATT - 1) & 3)); mbar_wait(BAR(F1 + (ATT & 3)), (ATT >> 2) & 1); },
             [&]() { g1_issue(accb, slot1(ATT & 3), slot1(ATT & 3), False{});
                     mbar_wait(BAR(F1 + ((ATT + 1) & 3)), ((ATT + 1) >> 2) & 1);
 g1_issue(accb, slot1((ATT + 1) & 3), slot1((ATT + 1) & 3), False{}); });
      wg_wait<1>(); release(E1 + (ATT & 3));
      load_x();
      fence_regs(xa);
      center(accb, 1);
#pragma unroll 1
      for (int u = ATT + 2; u < 32; u++) {
        const bool hold = u == 32 - LEAD1 && wg == 0;
        if (hold) { wg_wait<0>(); release(E1 + ((31 - LEAD1) & 3)); nb_sync<NB_LEAD>(256); }
        g1_step(accb, u, !hold, u == 31 && wg == 1);
      }
      mbar_wait(BAR(STD), L);
      wg_wait<0>(); release(E1 + 3);
      fence_regs(accb);
      fold_k(accb);
      sched_fence(P.zero);
      fold_v(accb);
      fold_q(accb);
      {
        auto g2_issue = [&](int p, bool own) {
          const uint32_t st = slot2(p);
          const uint32_t da = sda + ((own ? OFF_STG : st) >> 4), db = sd + (st >> 4);
          wg_fence();
          static_for<0, 4>([&](auto kk) { wgmma_128<0, 1, DI(kk.value * 32, 16), DI(16384 + kk.value * 2048, 8192)>(xa, da, db); });
          wg_commit();
        };
        uint32_t par = L ? 0x1e : 0;
        int p = 0, pp = 0;
        auto g2_loop = [&](int n0, int n1, int nrel) {
#pragma unroll 1
          for (int n = n0; n < n1; n++) {
            mbar_wait(BAR(F2 + p), (par >> p) & 1);
            par ^= 1u << p;
            g2_issue(p, n == 8);
            wg_wait<1>();
            if (n > nrel) release(E2 + pp);
            pp = p; if (++p == 5) p = 0;
          }
        };
        g2_loop(0, COVER, 0);
        attend(1, [&]() { wg_wait<0>(); release(E2 + COVER - 1); mbar_wait(BAR(F2 + COVER), (par >> COVER) & 1); },
               [&]() { g2_issue(COVER, false);
                       mbar_wait(BAR(F2 + COVER + 1), (par >> (COVER + 1)) & 1);
 g2_issue(COVER + 1, false); });
        wg_wait<1>(); release(E2 + COVER);
        par ^= 3u << COVER; pp = COVER + 1; p = (COVER + 2) % 5;
        {
          const bf16* bp = P.b2 + (128 * opq(i) + 16 * wu + ((fresh_tid() & 31) >> 2));
          asm volatile("ld.global.nc.u16 %0, [%1];" : "=h"(b2a) : "l"(bp));
          asm volatile("ld.global.nc.u16 %0, [%1];" : "=h"(b2b) : "l"(bp + 8));
        }
        {
          GEOM;
          e2p = stat_slot(); e2s = stat_src();
          e2g = gHB + (opq(j) * 32 + 2 * i) * 16384 + w * 2048 + lane * 16;
          e2h = sb + OFF_X + wg * 16384 + (16 * w + lr) * 128 + ((lt ^ l7) << 4);
          asm volatile("" : "+l"(e2p), "+l"(e2s), "+l"(e2g), "+r"(e2h));
        }
        g2_loop(COVER + 2, 16 - LEAD2, 0);
        if (wg == 1) { wg_wait<0>(); release(E2 + pp); nb_sync<NB_LEAD>(256); }
        static_for<16 - LEAD2, 16>([&](auto nn) {
          constexpr int n = nn.value, p = n % 5;
          mbar_wait(BAR(F2 + p), (n / 5 + (p ? L : 0)) & 1);
          wg_fence();
          static_for<0, 4>([&](auto kk) { wgmma_128<0, 1, DI(slot2(p) + kk.value * 32, 16), DI(slot2(p) + 16384 + kk.value * 2048, 8192)>(xa, sda, sd); });
          wg_commit();
          if (n == 15 && wg == 0) nb_arrive<NB_LEAD>(256);
          wg_wait<1>();
          if (n > 16 - LEAD2 || wg == 0) release(E2 + (n + 4) % 5);
        });
        wg_wait<0>();
        release(E2 + 0);
        fence_regs(xa);
      }
      {
        GEOM;
        const uint32_t tg = 2 * (tag + 1) + 1;
        float s0 = 0.f, s1 = 0.f, s2 = 0.f, s3 = 0.f, q0 = 0.f, q1 = 0.f, q2 = 0.f, q3 = 0.f;
#pragma unroll
        for (int t = 0; t < 16; t++) {
          s0 += xa[4 * t]; s1 += xa[4 * t + 1]; s2 += xa[4 * t + 2]; s3 += xa[4 * t + 3];
          q0 = fmaf(xa[4 * t], xa[4 * t], q0); q1 = fmaf(xa[4 * t + 1], xa[4 * t + 1], q1);
          q2 = fmaf(xa[4 * t + 2], xa[4 * t + 2], q2); q3 = fmaf(xa[4 * t + 3], xa[4 * t + 3], q3);
        }
        const float sm = stat_publish(e2p, s0 + s1, q0 + q1, s2 + s3, q2 + q3, tg);
        const uint32_t t0 = clock32();
        const float pv0 = __shfl_sync(0xffffffffu, sm, 4 * l7) * (1.f / 128), pv1 = __shfl_sync(0xffffffffu, sm, 4 * l7 + 1) * (1.f / 128);
        while (clock32() - t0 < STAT_CLK) {}
        stat_fetch(e2s);
        wg_fence();
        wgmma_rs_224z(acc3, q == 0 ? 0x3f80u : 0u, q == 0 ? 0x3f80u : 0u, 0u, 0u, mkdesc_vec(sb + OFF_B1, 16));
        wg_commit();
        stat_await([&]() { return e2s; }, tg);
        float r0, m0, r1, m1;
        {
          float mean0, var0, mean1, var1;
          stat_combine(sv0[0], sv0[1], sv1[0], sv1[1], pv0, mean0, var0); stat_combine(sv0[2], sv0[3], sv1[2], sv1[3], pv1, mean1, var1);
          mean0 = __shfl_sync(0xffffffffu, mean0, g); var0 = __shfl_sync(0xffffffffu, var0, g);
          mean1 = __shfl_sync(0xffffffffu, mean1, g); var1 = __shfl_sync(0xffffffffu, var1, g);
          r0 = 0.5f * rsq(fmaf(var0 + 1e-5f, 1e-5f, var0)); r1 = 0.5f * rsq(fmaf(var1 + 1e-5f, 1e-5f, var1));
          m0 = -mean0 * r0; m1 = -mean1 * r1;
        }
#pragma unroll
        for (int t = 0; t < 16; t += 2) {
          stsm4((e2h ^ ((t & 7) << 4)) + (t >> 3) * 8192,
                pack2(fmaf(xa[4 * t], r0, m0), fmaf(xa[4 * t + 1], r0, m0)), pack2(fmaf(xa[4 * t + 2], r1, m1), fmaf(xa[4 * t + 3], r1, m1)),
                pack2(fmaf(xa[4 * t + 4], r0, m0), fmaf(xa[4 * t + 5], r0, m0)), pack2(fmaf(xa[4 * t + 6], r1, m1), fmaf(xa[4 * t + 7], r1, m1)));
          if ((t & 7) == 6 && wg == 0) {
            __syncwarp();
            copy_out<4>(e2g + (t >> 3) * 8192, sb + OFF_X + (t >> 3) * 8192 + w * 2048 + lane * 16, 512);
          }
        }
        signal(JOB + 2 + wg);
        fence_async_smem();
        mbar_wait(BAR(F3 + 0), 0);
        if (wg == 0) { nb_sync<NB_WG0>(128); if (t7 == 0) mbar_arrive(BAR(XF + 1)); }
        else nb_sync<NB_BOTH>(256);
      }
      auto g3_issue = [&](uint32_t a, int p) {
        const uint32_t da = sda + (a >> 4), db = sd + (slot3(p) >> 4);
        wg_fence();
        static_for<0, 4>([&](auto kk) { wgmma_224<1, 1, DI(kk.value * 2048, 8192), DI(16384 + kk.value * 2048, 8192)>(acc3, da, db); });
        wg_commit();
      };
 g3_issue(OFF_X, 0);
      if (wg == 0) nb_sync<NB_BOTH>(256);
      mbar_wait(BAR(F3 + 1), 0); g3_issue(OFF_X + 16384, 1);
      sched_fence(P.zero);
      {
        const float c0 = __uint_as_float((uint32_t)b2a << 16), c1 = __uint_as_float((uint32_t)b2b << 16);
#pragma unroll
        for (int t = 0; t < 16; t++) { xa[4 * t] += c0; xa[4 * t + 1] += c0; xa[4 * t + 2] += c1; xa[4 * t + 3] += c1; }
        fence_regs(xa);
      }
      wg_wait<1>(); release(E3 + 0);
      auto g3_loop = [&](int n0, int n1, int nrel) {
#pragma unroll 1
        for (int n = n0; n < n1; n++) {
          const int p = n & 3;
          mbar_wait(BAR(F3 + p), (n >> 2) & 1);
          g3_issue(slot3(p), p);
          wg_wait<1>();
          if (n > nrel) release(E3 + ((n - 1) & 3));
        }
      };
      g3_loop(2, 29, 0);
      uint32_t ua;
      uint8_t* ug;
      {
        GEOM;
        ua = sb + OFF_X + wg * 8192 + (8 * lt + l7) * 128 + (((2 * w + ((lane >> 3) & 1)) ^ l7) << 4);
        ug = gUB + (opq(j) * 56 + 48 + m) * 16384 + r * 4096 + wg * 8192 + (lane >> 1) * 128 + (((2 * w + (lane & 1)) ^ ((lane >> 1) & 7)) << 4);
      }
      auto gelu8 = [&](int c, int k) {
        const int o = 32 * c + 8 * k;
        stsm4t(ua + (c & 1) * 16384 + k * 2048,
               pack2(gelu_half(acc3[o]), gelu_half(acc3[o + 1])), pack2(gelu_half(acc3[o + 2]), gelu_half(acc3[o + 3])),
               pack2(gelu_half(acc3[o + 4]), gelu_half(acc3[o + 5])), pack2(gelu_half(acc3[o + 6]), gelu_half(acc3[o + 7])));
      };
      {
        auto part = [&](auto p, auto half) {
          static_for<0, 4>([&](auto kk) {
            constexpr uint32_t o = slot3(p.value) + kk.value * 2048;
            if constexpr (half.value) wgmma_32<1, 1, DI(o, 8192), DI(o + 40960, 8192), 96>(acc3, sda, sd);
            else wgmma_192<1, 1, DI(o, 8192), DI(o + 16384, 8192), 0>(acc3, sda, sd);
          });
        };
        mbar_wait(BAR(RD), L);
        mbar_wait(BAR(F3 + 1), 1); mbar_wait(BAR(F3 + 2), 1);
        wg_wait<0>(); release(E3 + 0);
#pragma unroll
        for (int k = 0; k < 112; k++) { float t; asm volatile("mov.b32 %0, %1;" : "=f"(t) : "f"(acc3[k]) : "memory"); acc3[k] = t; }
        sched_fence(P.zero);
        wg_fence(); part(Int<1>{}, True{}); part(Int<2>{}, True{});
        mbar_wait(BAR(F3 + 3), 1); wg_fence(); part(Int<3>{}, True{}); wg_commit();
        part(Int<1>{}, False{}); wg_commit();
        wg_wait<1>();
#pragma unroll
        for (int k = 96; k < 112; k++) asm volatile("" : "+f"(acc3[k])::"memory");
        gelu8(3, 0); gelu8(3, 1);
        __syncwarp();
        copy_out<2>(ug, sb + OFF_X + 16384 + (uint32_t)((ug - gUB) & 0x2fff), 2048);
        signal(JOB + 7);
        sched_fence(P.zero);
        wg_fence(); part(Int<2>{}, False{}); wg_commit();
        wg_wait<1>(); release(E3 + 1);
        part(Int<3>{}, False{}); wg_commit();
        wg_wait<1>(); release(E3 + 2);
        wg_wait<0>(); release(E3 + 3);
      }
      fence_regs(acc3);
      auto g4_issue = [&](int p, uint32_t b) {
        const uint32_t da = sda + (slot4(p) >> 4), db = sd + (b >> 4);
        wg_fence();
        static_for<0, 4>([&](auto kk) { wgmma_128<1, 1, DI(kk.value * 2048, 8192), DI(kk.value * 2048, 8192)>(xa, da, db); });
        wg_commit();
      };
#pragma unroll
      for (int k = 0; k < 4; k++) gelu8(0, k);
      fence_async_smem();
      signal(JOB + 4);
      nb_sync<NB_BOTH>(256);
      static_for<0, 18>([&](auto nn) {
        constexpr int n = nn.value, p = n % 6;
        if (n == 9 || n == 17) mbar_wait(BAR(JOB + 4 + (n >> 3)), L);
        mbar_wait(BAR(F4 + p), (n / 6 + (p >= 2 ? L : 0)) & 1);
        wg_fence();
        static_for<0, 4>([&](auto kk) {
          wgmma_128<1, 1, DI(slot4(p) + kk.value * 2048, 8192), DI((n == 9 ? OFF_X + 16384 : n % 17 ? slot4(p) + 16384 : OFF_X) + kk.value * 2048, 8192)>(xa, sda, sd);
        });
        wg_commit();
        if (n) { wg_wait<1>(); release(E4 + (n + 5) % 6); }
        if (n == 8) mbar_wait(BAR(RD + 2), L);
        else if (n < 16 && !(n & 1)) sched_fence(P.zero);
        if constexpr (n < 16 && !(n & 1)) gelu8(1 + (n >> 3), (n >> 1) & 3);
        if ((n & 7) == 7) { fence_async_smem(); signal(JOB + 5 + (n >> 3)); }
      });
      {
        int p = 0, pp = 5;
        uint32_t par = L ? 0x03 : 0x3f;
        auto g4_loop = [&](int n0, int n1, int nrel) {
#pragma unroll 1
          for (int n = n0; n < n1; n++) {
            mbar_wait(BAR(F4 + p), (par >> p) & 1);
            par ^= 1u << p;
            g4_issue(p, slot4(p) + 16384);
            wg_wait<1>();
            if (n > nrel) release(E4 + pp);
            pp = p; if (++p == 6) p = 0;
          }
        };
        g4_loop(18, 56 - LEAD4, 0);
        if (wg == 1) { wg_wait<0>(); release(E4 + pp); nb_sync<NB_LEAD>(256); }
        static_for<56 - LEAD4, 56>([&](auto nn) {
          constexpr int n = nn.value, p = n % 6;
          mbar_wait(BAR(F4 + p), (n / 6 + (p >= 2 ? L : 0)) & 1);
          wg_fence();
          static_for<0, 4>([&](auto kk) { wgmma_128<1, 1, DI(slot4(p) + kk.value * 2048, 8192), DI(slot4(p) + 16384 + kk.value * 2048, 8192)>(xa, sda, sd); });
          wg_commit();
          if (n == 55 && wg == 0) nb_arrive<NB_LEAD>(256);
          wg_wait<1>();
          if (n > 56 - LEAD4 || wg == 0) release(E4 + (n + 5) % 6);
        });
      }
      uint32_t xs;
      uint8_t* xg;
      {
        GEOM;
        xs = sb + OFF_X + wu * 2048 + (lane >> 3) * 128 + ((L ? l7 ^ (lane >> 3) : l7) << 4);
        xg = L ? P.out + (128 * opq(i) + 16 * wu + (lane >> 3)) * 2048 + 256 * j + 16 * l7 : gXB + (opq(i) * 16 + 2 * j) * 16384 + wu * 2048 + lane * 16;
        asm volatile("" : "+r"(xs), "+l"(xg));
      }
      mbar_wait(BAR(RD + 1), L);
      wg_wait<0>();
      release(E4 + 1);
      fence_regs(xa);
      {
        GEOM;
#pragma unroll
        for (int t = 0; t < 16; t += 2) {
          stsm4(sb + OFF_X + (t >> 3) * 16384 + (16 * wu + lr) * 128 + ((((t & 7) + lt) ^ l7) << 4),
                pack2(xa[4 * t], xa[4 * t + 1]), pack2(xa[4 * t + 2], xa[4 * t + 3]),
                pack2(xa[4 * t + 4], xa[4 * t + 5]), pack2(xa[4 * t + 6], xa[4 * t + 7]));
          if ((t & 7) == 6 && (L || t == 6)) {
            __syncwarp();
            uint4 v[4];
#pragma unroll
            for (int k = 0; k < 4; k++) lds128((xs ^ (L ? (k & 1) << 6 : 0)) + k * 512 + (t >> 3) * 16384, v[k].x, v[k].y, v[k].z, v[k].w);
#pragma unroll
            for (int k = 0; k < 4; k++)
              asm volatile("st.global.v4.b32 [%0], {%1, %2, %3, %4};" ::"l"(xg + k * (L ? 8192 : 512) + (t >> 3) * 128), "r"(v[k].x), "r"(v[k].y), "r"(v[k].z), "r"(v[k].w) : "memory");
            if (L == 0) signal(JOB + 8);
          }
        }
        if (L) break;
        fence_async_smem();
        signal(JOB + 9);
        nb_sync<NB_BOTH>(256);
      }
    }
    cluster_bar();
  }
}

typedef CUresult (*EncodeFn)(CUtensorMap*, CUtensorMapDataType, cuuint32_t, void*, const cuuint64_t*, const cuuint64_t*, const cuuint32_t*,
                             const cuuint32_t*, CUtensorMapInterleave, CUtensorMapSwizzle, CUtensorMapL2promotion, CUtensorMapFloatOOBfill);

void make_map(EncodeFn enc, CUtensorMap* mp, const void* base, int rank, cuuint64_t d0, cuuint64_t d1, cuuint64_t d2, cuuint64_t s1, cuuint64_t s2,
              cuuint32_t b0, cuuint32_t b1, cuuint32_t b2) {
  cuuint64_t dims[3] = {d0, d1, d2}, strides[2] = {s1, s2};
  cuuint32_t box[3] = {b0, b1, b2}, es[3] = {1, 1, 1};
  CUresult res = enc(mp, CU_TENSOR_MAP_DATA_TYPE_BFLOAT16, rank, const_cast<void*>(base), dims, strides, box, es, CU_TENSOR_MAP_INTERLEAVE_NONE,
                     CU_TENSOR_MAP_SWIZZLE_128B, CU_TENSOR_MAP_L2_PROMOTION_L2_128B, CU_TENSOR_MAP_FLOAT_OOB_FILL_NONE);
  (void)res;
}

}

extern "C" void kernel_launch(void* const* d_in, const int* in_sizes, int n_in, void* d_out, int out_size) {
  (void)in_sizes; (void)n_in; (void)out_size;
  static EncodeFn enc = nullptr;
  if (!enc) {
    void* fn = nullptr;
    cudaDriverEntryPointQueryResult qr;
    cudaGetDriverEntryPoint("cuTensorMapEncodeTiled", &fn, cudaEnableDefault, &qr);
    enc = (EncodeFn)fn;
    cudaFuncSetAttribute(fused_kernel, cudaFuncAttributeMaxDynamicSharedMemorySize, SMEM_BYTES);
  }
  Params P;
  make_map(enc, &P.x0, d_in[0], 2, D_, S_, 1, D_ * 2, 0, 64, 128, 1);
  make_map(enc, &P.wqkv, d_in[1], 3, D_, D_, 3, 3 * D_ * 2, D_ * 2, 64, 32, 3);
  make_map(enc, &P.wo, d_in[2], 2, D_, D_, 1, D_ * 2, 0, 64, 64, 1);
  make_map(enc, &P.w1, d_in[4], 3, 64, S_, F_ / 64, F_ * 2, 128, 64, 64, 3);
  make_map(enc, &P.w1h, d_in[4], 3, 32, S_, F_ / 32, F_ * 2, 64, 64, 64, 1);
  make_map(enc, &P.w2, d_in[6], 3, 64, F_, S_ / 64, S_ * 2, 128, 64, 64, 2);
  P.out = (uint8_t*)d_out;
  P.wo_p = (const bf16*)d_in[2];
  P.w1_p = (const bf16*)d_in[4];
  P.b1 = (const bf16*)d_in[5];
  P.b2 = (const bf16*)d_in[7];
  P.zero = 0;
  fused_kernel<<<128, 384, SMEM_BYTES>>>((const bf16*)d_in[0], (const bf16*)d_in[1], P);
}
```
